```python
import torch

def _softmax(x, axis=-1):
    return torch.softmax(x, dim=axis)

def _gelu(x):
    return torch.nn.functional.gelu(x, approximate='tanh')

def _silu(x):
    return torch.nn.functional.silu(x)

def _sigmoid(x):
    return torch.sigmoid(x)

def _layernorm(x, axis=-1, eps=1e-05):
    m = x.mean(dim=axis, keepdim=True)
    v = x.var(dim=axis, keepdim=True, unbiased=False)
    return (x - m) / torch.sqrt(v + eps)

def _scatter_add(tgt, idx, src, axis=0):
    return tgt.clone().index_add_(axis, idx, src)

def _segment_sum(src, seg, n):
    out = torch.zeros((n,) + src.shape[1:], dtype=src.dtype)
    return out.index_add_(0, seg, src)

def _pad(x, pw):
    flat = tuple((v for pair in reversed(pw) for v in pair))
    return torch.nn.functional.pad(x, flat)
kernel_name = 'interleave_layers__spectral_gfnet__memory_aug_recurrent_mem_tr__prompt'

def setup_inputs():

    _w = lambda a: (lambda t: t.to(torch.bfloat16) if t.is_floating_point() else t)(torch.as_tensor(a))

    def _A_setup():
        B, S, D = (1, 2048, 640)
        Df = D // 2 + 1
        return {'x': _w((lambda *s: torch.randn(*s, dtype=torch.bfloat16) * 0.05)(B, S, D)), 'w_r': _w((lambda *s: torch.randn(*s, dtype=torch.bfloat16) * 0.4)(S, Df) * 0.02), 'w_i': _w((lambda *s: torch.randn(*s, dtype=torch.bfloat16) * 0.4)(S, Df) * 0.02)}
    _A_in = _A_setup()

    def _B_setup():
        B, S, Dm = (1, 2048, 640)
        H, Dh = (32, 128)
        M, seg = (8, 32)
        seg = min(seg, S)
        S = S // seg * seg
        return {'x': _w((lambda *s: torch.randn(*s, dtype=torch.bfloat16) * 0.05)(B, S, Dm)), 'mem0': _w((lambda *s: torch.randn(*s, dtype=torch.bfloat16) * 0.2)(B, M, Dm)), 'Wq': _w((lambda *s: torch.randn(*s, dtype=torch.bfloat16) * 1.6)(Dm, H, Dh) * Dm ** (-0.5)), 'Wk': _w((lambda *s: torch.randn(*s, dtype=torch.bfloat16) * 1.6)(Dm, H, Dh) * Dm ** (-0.5)), 'Wv': _w((lambda *s: torch.randn(*s, dtype=torch.bfloat16) * 0.2)(Dm, H, Dh) * Dm ** (-0.5)), 'Wo': _w((lambda *s: torch.randn(*s, dtype=torch.bfloat16) * 0.2)(H, Dh, Dm) * (H * Dh) ** (-0.5)), 'seg_len': seg}
    _B_in = _B_setup()
    return {'A_x': _A_in['x'], 'A_w_r': _A_in['w_r'], 'A_w_i': _A_in['w_i'], 'B_x': _B_in['x'], 'B_mem0': _B_in['mem0'], 'B_Wq': _B_in['Wq'], 'B_Wk': _B_in['Wk'], 'B_Wv': _B_in['Wv'], 'B_Wo': _B_in['Wo'], 'B_seg_len': _B_in['seg_len']}

def reference(A_x, A_w_r, A_w_i, B_x, B_mem0, B_Wq, B_Wk, B_Wv, B_Wo, B_seg_len):

    def _A_ref(x, w_r, w_i):
        B, S, D = x.shape
        X = (lambda x, axes=(-2, -1): torch.fft.rfft2(x.float(), dim=axes))(x, axes=(-2, -1))
        W = w_r + 1j * w_i
        X = X * W
        y = (lambda x, s, axes=(-2, -1): torch.fft.irfft2(x, s=s, dim=axes).to(torch.bfloat16))(X, (S, D), axes=(-2, -1))
        return y

    def _B_ref(x, mem0, Wq, Wk, Wv, Wo, seg_len):
        B, S, Dm = x.shape
        H, Dh = (Wq.shape[1], Wq.shape[2])
        M = mem0.shape[1]
        scale = Dh ** (-0.5)
        n_seg = S // seg_len
        L = M + seg_len
        idx = torch.arange(L)
        mask = (idx[:, None] < M) | (idx[:, None] >= idx[None, :])
        mem = mem0
        outs = []
        for s in range(n_seg):
            xs = x[:, s * seg_len:(s + 1) * seg_len, :].clone()
            h = torch.concatenate([mem, xs], axis=1)
            q = torch.einsum('btd,dhe->bhte', h, Wq)
            k = torch.einsum('btd,dhe->bhte', h, Wk)
            v = torch.einsum('btd,dhe->bhte', h, Wv)
            scores = torch.einsum('bhqe,bhke->bhqk', q, k) * scale
            scores = torch.where(mask[None, None], scores, -1000000000.0)
            p = _softmax(scores, axis=-1)
            o = torch.einsum('bhqk,bhke->bhqe', p, v)
            o = torch.einsum('bhte,hed->btd', o, Wo)
            mem = o[:, :M, :].clone()
            outs.append(o[:, M:, :])
        return torch.concatenate(outs, axis=1)
    x = A_x
    x = x + _A_ref(_layernorm(x, axis=-1), A_w_r, A_w_i)
    x = x + _B_ref(_layernorm(x, axis=-1), B_mem0, B_Wq, B_Wk, B_Wv, B_Wo, B_seg_len)
    x = x + _A_ref(_layernorm(x, axis=-1), A_w_r, A_w_i)
    x = x + _B_ref(_layernorm(x, axis=-1), B_mem0, B_Wq, B_Wk, B_Wv, B_Wo, B_seg_len)
    return x
```

```cpp
#include <cuda_runtime.h>
#include <cuda_bf16.h>
#include <cuda_fp16.h>
#include <stdint.h>
#include <string.h>

namespace {

typedef __nv_bfloat16 bf16;
constexpr int S_ = 2048, D_ = 640, NSEG = 64;
constexpr int SPIN_LIM = 1 << 13;

__device__ float                  g_wmx[96];
__device__ __align__(1024) bf16   g_wot[4096 * 640];
__device__ __align__(16) float    g_co[1024];
__device__ __align__(256) uint2   g_stat[2 * 32 * 16 * 64];
__device__ float                  g_invM0;
__device__ __align__(16) float    g_wmax[128];
__device__ __align__(1024) char   g_redraw[65 * 32768];
constexpr int F_X = 2 * NSEG * 32, F_O = F_X + 2 * 128, NFLAG = F_O + 128, RING = 8;
constexpr int F_W = F_X + 66;
struct __align__(256) Flag { unsigned v; };
__device__ Flag                   g_flag[NFLAG];
__device__ Flag                   g_ready[1];
__device__ __align__(1024) char   g_item[RING * 32 * 32768];
__device__ __align__(1024) bf16   g_O[S_ * 4096];
__device__ __align__(1024) __half g_xn[S_ * D_];
__device__ __align__(1024) bf16   g_xa[S_ * D_];
__device__ __align__(1024) bf16   g_xb[S_ * D_];
__device__ __align__(1024) __half g_UT[D_ * S_];
__device__ __align__(1024) __half g_YT[D_ * S_];
__device__ __align__(1024) __half g_ctab[64 * 128 + 64 * 64];
__device__ __align__(1024) uint32_t g_Wf[321 * 2048];

#define TL(i)
#define TLN 0
#define TLL 1
#define CK(i)
__device__ __forceinline__ uint32_t smem_u32(const void* p) { return (uint32_t)__cvta_generic_to_shared(p); }
__device__ __forceinline__ uint32_t mapa(uint32_t a, uint32_t r) { uint32_t o; asm("mapa.shared::cluster.u32 %0,%1,%2;" : "=r"(o) : "r"(a), "r"(r)); return o; }
__device__ __forceinline__ void mbar_init(uint32_t a, int c) { asm volatile("mbarrier.init.shared::cta.b64 [%0],%1;" ::"r"(a), "r"(c) : "memory"); }
__device__ __forceinline__ void mbar_expect(uint32_t a, int bytes) { asm volatile("mbarrier.arrive.expect_tx.shared::cta.b64 _,[%0],%1;" ::"r"(a), "r"(bytes) : "memory"); }
__device__ __forceinline__ void mbar_arrive(uint32_t a) { asm volatile("mbarrier.arrive.shared::cta.b64 _,[%0];" ::"r"(a) : "memory"); }
__device__ __forceinline__ bool mbar_try(uint32_t a, uint32_t par) {
    uint32_t p;
    asm volatile("{.reg .pred q; mbarrier.try_wait.parity.shared::cta.b64 q,[%1],%2; selp.u32 %0,1,0,q;}" : "=r"(p) : "r"(a), "r"(par) : "memory");
    return p;
}
__device__ __forceinline__ void mbar_wait(uint32_t a, uint32_t par) {
    if (!mbar_try(a, par)) {
        int lim = 0;
        while (!mbar_try(a, par) && ++lim < SPIN_LIM) {}
    }
}
#define MW_HINT 20000
__device__ __forceinline__ void mbar_sleep(uint32_t a, uint32_t par) {
    asm volatile("{.reg .pred q; .reg .u32 n; mov.u32 n,0;\n"
                 "W_LOOP: mbarrier.try_wait.parity.shared::cta.b64 q,[%0],%1,%2; add.u32 n,n,1; setp.lt.and.u32 q,n,%3,!q; @q bra W_LOOP;}"
                 ::"r"(a), "r"(par), "n"(MW_HINT), "n"(SPIN_LIM) : "memory");
}
__device__ __forceinline__ void bar_arrive(int id, int n) { asm volatile("bar.arrive %0,%1;" ::"r"(id), "r"(n) : "memory"); }
__device__ __forceinline__ uint32_t clock32() { uint32_t c; asm volatile("mov.u32 %0,%%clock;" : "=r"(c)); return c; }
__device__ __forceinline__ uint32_t read_tid() { uint32_t v; asm volatile("mov.u32 %0,%%tid.x;" : "=r"(v)); return v; }
__device__ __forceinline__ void bar_sync(int id, int n) { asm volatile("bar.sync %0,%1;" ::"r"(id), "r"(n) : "memory"); }
__device__ __forceinline__ void fence_async_smem() { asm volatile("fence.proxy.async.shared::cta;" ::: "memory"); }
__device__ __forceinline__ void fence_async_glb() { asm volatile("fence.proxy.async.global;" ::: "memory"); }
__device__ __forceinline__ void cluster_sync_full() { asm volatile("barrier.cluster.arrive.aligned; barrier.cluster.wait.aligned;" ::: "memory"); }
__device__ __forceinline__ void bulk_g2s(uint32_t dst, const void* src, int bytes, uint32_t mb) {
    asm volatile("cp.async.bulk.shared::cluster.global.mbarrier::complete_tx::bytes [%0],[%1],%2,[%3];" ::"r"(dst), "l"(src), "r"(bytes), "r"(mb) : "memory");
}
__device__ __forceinline__ void bulk_g2s_last(uint32_t dst, const void* src, int bytes, uint32_t mb) {
    asm volatile("{.reg .b64 p; createpolicy.fractional.L2::evict_first.b64 p, 1.0;\n"
                 "cp.async.bulk.shared::cluster.global.mbarrier::complete_tx::bytes.L2::cache_hint [%0],[%1],%2,[%3],p;}"
                 ::"r"(dst), "l"(src), "r"(bytes), "r"(mb) : "memory");
}
__device__ __forceinline__ void bulk_s2s(uint32_t dst, uint32_t src, int bytes, uint32_t mb) {
    asm volatile("cp.async.bulk.shared::cluster.shared::cta.mbarrier::complete_tx::bytes [%0],[%1],%2,[%3];" ::"r"(dst), "r"(src), "r"(bytes), "r"(mb) : "memory");
}
__device__ __forceinline__ void bulk_s2g(void* dst, uint32_t src, int bytes) {
    asm volatile("cp.async.bulk.global.shared::cta.bulk_group [%0],[%1],%2;" ::"l"(dst), "r"(src), "r"(bytes) : "memory");
}
__device__ __forceinline__ void cp_async16(uint32_t dst, const void* src, uint32_t bytes = 16) {
    asm volatile("cp.async.cg.shared.global [%0],[%1],16,%2;" ::"r"(dst), "l"(src), "r"(bytes) : "memory");
}
__device__ __forceinline__ void cp_commit() { asm volatile("cp.async.commit_group;" ::: "memory"); }
template <int N> __device__ __forceinline__ void cp_wait() { asm volatile("cp.async.wait_group %0;" ::"n"(N) : "memory"); }
__device__ __forceinline__ void bulk_commit() { asm volatile("cp.async.bulk.commit_group;" ::: "memory"); }
__device__ __forceinline__ void bulk_wait0() { asm volatile("cp.async.bulk.wait_group 0;" ::: "memory"); }
__device__ __forceinline__ void ldsm4(uint32_t* r, uint32_t a) {
    asm volatile("ldmatrix.sync.aligned.m8n8.x4.shared.b16 {%0,%1,%2,%3},[%4];" : "=r"(r[0]), "=r"(r[1]), "=r"(r[2]), "=r"(r[3]) : "r"(a) : "memory");
}
__device__ __forceinline__ void ldsm4t(uint32_t* r, uint32_t a) {
    asm volatile("ldmatrix.sync.aligned.m8n8.x4.trans.shared.b16 {%0,%1,%2,%3},[%4];" : "=r"(r[0]), "=r"(r[1]), "=r"(r[2]), "=r"(r[3]) : "r"(a) : "memory");
}
__device__ __forceinline__ void stsm4(uint32_t a, uint32_t r0, uint32_t r1, uint32_t r2, uint32_t r3) {
    asm volatile("stmatrix.sync.aligned.m8n8.x4.shared.b16 [%0],{%1,%2,%3,%4};" ::"r"(a), "r"(r0), "r"(r1), "r"(r2), "r"(r3) : "memory");
}
__device__ __forceinline__ void stsm4t(uint32_t a, uint32_t r0, uint32_t r1, uint32_t r2, uint32_t r3) {
    asm volatile("stmatrix.sync.aligned.m8n8.x4.trans.shared.b16 [%0],{%1,%2,%3,%4};" ::"r"(a), "r"(r0), "r"(r1), "r"(r2), "r"(r3) : "memory");
}
__device__ __forceinline__ void lds128(uint32_t* r, uint32_t a) {
    asm volatile("ld.shared.v4.b32 {%0,%1,%2,%3},[%4];" : "=r"(r[0]), "=r"(r[1]), "=r"(r[2]), "=r"(r[3]) : "r"(a) : "memory");
}
__device__ __forceinline__ void lds64(uint32_t* r, uint32_t a) {
    asm volatile("ld.shared.v2.b32 {%0,%1},[%2];" : "=r"(r[0]), "=r"(r[1]) : "r"(a) : "memory");
}
__device__ __forceinline__ uint32_t lds32(uint32_t a) { uint32_t v; asm volatile("ld.shared.b32 %0,[%1];" : "=r"(v) : "r"(a) : "memory"); return v; }
__device__ __forceinline__ void sts128(uint32_t a, uint32_t r0, uint32_t r1, uint32_t r2, uint32_t r3) {
    asm volatile("st.shared.v4.b32 [%0],{%1,%2,%3,%4};" ::"r"(a), "r"(r0), "r"(r1), "r"(r2), "r"(r3) : "memory");
}
__device__ __forceinline__ void sts64(uint32_t a, uint32_t v0, uint32_t v1) { asm volatile("st.shared.v2.b32 [%0],{%1,%2};" ::"r"(a), "r"(v0), "r"(v1) : "memory"); }
[[maybe_unused]] __device__ __forceinline__ void sts32(uint32_t a, uint32_t v) { asm volatile("st.shared.b32 [%0],%1;" ::"r"(a), "r"(v) : "memory"); }
#define AU_(op) "{.reg .u32 t; add.u32 t,%4,%5; " op " {%0,%1,%2,%3},[t+%6];}"
template <int I> __device__ __forceinline__ void ldsm4_u(uint32_t* r, uint32_t a, uint32_t u) {
    asm volatile(AU_("ldmatrix.sync.aligned.m8n8.x4.shared.b16") : "=r"(r[0]), "=r"(r[1]), "=r"(r[2]), "=r"(r[3]) : "r"(a), "r"(u), "n"(I) : "memory");
}
template <int I> __device__ __forceinline__ void ldsm4t_u(uint32_t* r, uint32_t a, uint32_t u) {
    asm volatile(AU_("ldmatrix.sync.aligned.m8n8.x4.trans.shared.b16") : "=r"(r[0]), "=r"(r[1]), "=r"(r[2]), "=r"(r[3]) : "r"(a), "r"(u), "n"(I) : "memory");
}
template <int I> __device__ __forceinline__ void lds128_u(uint32_t* r, uint32_t a, uint32_t u) {
    asm volatile(AU_("ld.shared.v4.b32") : "=r"(r[0]), "=r"(r[1]), "=r"(r[2]), "=r"(r[3]) : "r"(a), "r"(u), "n"(I) : "memory");
}
template <int I> __device__ __forceinline__ void lds64_u(uint32_t* r, uint32_t a, uint32_t u) {
    asm volatile("{.reg .u32 t; add.u32 t,%2,%3; ld.shared.v2.b32 {%0,%1},[t+%4];}" : "=r"(r[0]), "=r"(r[1]) : "r"(a), "r"(u), "n"(I) : "memory");
}
template <int I> __device__ __forceinline__ uint32_t lds32_u(uint32_t a, uint32_t u) {
    uint32_t v;
    asm volatile("{.reg .u32 t; add.u32 t,%1,%2; ld.shared.b32 %0,[t+%3];}" : "=r"(v) : "r"(a), "r"(u), "n"(I) : "memory");
    return v;
}
template <int I> __device__ __forceinline__ void sts64_u(uint32_t a, uint32_t u, uint32_t v0, uint32_t v1) {
    asm volatile("{.reg .u32 t; add.u32 t,%0,%1; st.shared.v2.b32 [t+%2],{%3,%4};}" ::"r"(a), "r"(u), "n"(I), "r"(v0), "r"(v1) : "memory");
}
template <int I> __device__ __forceinline__ void sts32_u(uint32_t a, uint32_t u, uint32_t v) {
    asm volatile("{.reg .u32 t; add.u32 t,%0,%1; st.shared.b32 [t+%2],%3;}" ::"r"(a), "r"(u), "n"(I), "r"(v) : "memory");
}
template <int I> __device__ __forceinline__ void sts16_u(uint32_t a, uint32_t u, uint32_t v) {
    asm volatile("{.reg .u32 t; add.u32 t,%0,%1; st.shared.b16 [t+%2],%3;}" ::"r"(a), "r"(u), "n"(I), "h"((unsigned short)v) : "memory");
}
template <int I> __device__ __forceinline__ void sts128_u(uint32_t a, uint32_t u, uint32_t r0, uint32_t r1, uint32_t r2, uint32_t r3) {
    asm volatile("{.reg .u32 t; add.u32 t,%0,%1; st.shared.v4.b32 [t+%2],{%3,%4,%5,%6};}" ::"r"(a), "r"(u), "n"(I), "r"(r0), "r"(r1), "r"(r2), "r"(r3) : "memory");
}
template <int I> __device__ __forceinline__ void stsm4_u(uint32_t a, uint32_t u, uint32_t r0, uint32_t r1, uint32_t r2, uint32_t r3) {
    asm volatile("{.reg .u32 t; add.u32 t,%0,%1; stmatrix.sync.aligned.m8n8.x4.shared.b16 [t+%2],{%3,%4,%5,%6};}"
                 ::"r"(a), "r"(u), "n"(I), "r"(r0), "r"(r1), "r"(r2), "r"(r3) : "memory");
}
__device__ __forceinline__ void st_async2_x3(uint32_t a, uint32_t u, uint32_t mb, uint32_t v0, uint32_t v1) {
    asm volatile("{.reg .u32 t,x,y; add.u32 t,%0,%1;\n"
                 "mapa.shared::cluster.u32 x,t,0; mapa.shared::cluster.u32 y,%2,0; st.async.shared::cluster.mbarrier::complete_tx::bytes.v2.b32 [x],{%3,%4},[y];\n"
                 "mapa.shared::cluster.u32 x,t,1; mapa.shared::cluster.u32 y,%2,1; st.async.shared::cluster.mbarrier::complete_tx::bytes.v2.b32 [x],{%3,%4},[y];\n"
                 "mapa.shared::cluster.u32 x,t,2; mapa.shared::cluster.u32 y,%2,2; st.async.shared::cluster.mbarrier::complete_tx::bytes.v2.b32 [x],{%3,%4},[y];}"
                 ::"r"(a), "r"(u), "r"(mb), "r"(v0), "r"(v1) : "memory");
}
template <int V> struct IC { __host__ __device__ constexpr operator int() const { return V; } };
template <int N, class F> __device__ __forceinline__ void sfor(F f) {
    if constexpr (N > 0) { sfor<N - 1>(f); f(IC<N - 1>()); }
}
__device__ __forceinline__ void mma_f16(float* d, const uint32_t* a, uint32_t b0, uint32_t b1) {
    asm volatile("mma.sync.aligned.m16n8k16.row.col.f32.f16.f16.f32 {%0,%1,%2,%3},{%4,%5,%6,%7},{%8,%9},{%0,%1,%2,%3};"
                 : "+f"(d[0]), "+f"(d[1]), "+f"(d[2]), "+f"(d[3]) : "r"(a[0]), "r"(a[1]), "r"(a[2]), "r"(a[3]), "r"(b0), "r"(b1));
}
__device__ __forceinline__ void mma_bf(float* d, uint32_t a0, uint32_t a1, uint32_t a2, uint32_t a3, uint32_t b0, uint32_t b1) {
    asm volatile("mma.sync.aligned.m16n8k16.row.col.f32.bf16.bf16.f32 {%0,%1,%2,%3},{%4,%5,%6,%7},{%8,%9},{%0,%1,%2,%3};"
                 : "+f"(d[0]), "+f"(d[1]), "+f"(d[2]), "+f"(d[3]) : "r"(a0), "r"(a1), "r"(a2), "r"(a3), "r"(b0), "r"(b1));
}
__device__ __forceinline__ void mma_bf8(float* d, uint32_t a0, uint32_t a1, uint32_t b0) {
    asm volatile("mma.sync.aligned.m16n8k8.row.col.f32.bf16.bf16.f32 {%0,%1,%2,%3},{%4,%5},{%6},{%0,%1,%2,%3};"
                 : "+f"(d[0]), "+f"(d[1]), "+f"(d[2]), "+f"(d[3]) : "r"(a0), "r"(a1), "r"(b0));
}
__device__ __forceinline__ uint32_t pack_bf(float lo, float hi) { uint32_t r; asm("cvt.rn.bf16x2.f32 %0,%1,%2;" : "=r"(r) : "f"(hi), "f"(lo)); return r; }
__device__ __forceinline__ uint32_t pack_h(float lo, float hi) { uint32_t r; asm("cvt.rn.f16x2.f32 %0,%1,%2;" : "=r"(r) : "f"(hi), "f"(lo)); return r; }
__device__ __forceinline__ float bf_lo(uint32_t v) { return __uint_as_float(v << 16); }
__device__ __forceinline__ float bf_hi(uint32_t v) { return __uint_as_float(v & 0xffff0000u); }
__device__ __forceinline__ uint32_t bfma(uint32_t a, uint32_t b, uint32_t c) { uint32_t r; asm("fma.rn.bf16x2 %0,%1,%2,%3;" : "=r"(r) : "r"(a), "r"(b), "r"(c)); return r; }
__device__ __forceinline__ uint4 add_bf8(const uint4 x, const uint32_t* y, const uint32_t k = 0x3f803f80u) {
    return make_uint4(bfma(y[0], k, x.x), bfma(y[1], k, x.y), bfma(y[2], k, x.z), bfma(y[3], k, x.w));
}
__device__ __forceinline__ float ex2(float x) { float r; asm("ex2.approx.ftz.f32 %0,%1;" : "=f"(r) : "f"(x)); return r; }
__device__ __forceinline__ float rcp(float x) { float r; asm("rcp.approx.ftz.f32 %0,%1;" : "=f"(r) : "f"(x)); return r; }
__device__ __forceinline__ void wg_fence() { asm volatile("wgmma.fence.sync.aligned;" ::: "memory"); }
__device__ __forceinline__ void wg_commit() { asm volatile("wgmma.commit_group.sync.aligned;" ::: "memory"); }
template <int N> __device__ __forceinline__ void wg_wait() { asm volatile("wgmma.wait_group.sync.aligned %0;" ::"n"(N) : "memory"); }
__device__ __forceinline__ uint64_t mkdesc(uint32_t a, uint32_t lbo, uint32_t sbo, uint32_t sw) {
    return (uint64_t)((a & 0x3FFFF) >> 4) | ((uint64_t)(lbo >> 4) << 16) | ((uint64_t)(sbo >> 4) << 32) | ((uint64_t)sw << 62);
}
#define F4(d, i) "+f"(d[i]), "+f"(d[i + 1]), "+f"(d[i + 2]), "+f"(d[i + 3])
#define F8(d, i) F4(d, i), F4(d, i + 4)
#define F16(d, i) F8(d, i), F8(d, i + 8)
template <int OFF, int SC> __device__ __forceinline__ void wg_n32_x(float* d, const uint32_t* a, uint32_t lo) {
    asm volatile("{.reg .pred p; .reg .b32 l; .reg .b64 q; setp.ne.b32 p,%22,0; add.u32 l,%20,%21; mov.b64 q,{l,8};\n"
                 "wgmma.mma_async.sync.aligned.m64n32k16.f32.f16.f16 "
                 "{%0,%1,%2,%3,%4,%5,%6,%7,%8,%9,%10,%11,%12,%13,%14,%15},{%16,%17,%18,%19},q,p,1,1,0;}"
                 : F16(d, 0) : "r"(a[0]), "r"(a[1]), "r"(a[2]), "r"(a[3]), "r"(lo), "n"(OFF), "n"(SC));
}
__device__ __forceinline__ void wg_n128_rs(float* d, const uint32_t* a, uint64_t db, int sc) {
    asm volatile("{.reg .pred p; setp.ne.b32 p,%69,0; wgmma.mma_async.sync.aligned.m64n128k16.f32.f16.f16 "
                 "{%0,%1,%2,%3,%4,%5,%6,%7,%8,%9,%10,%11,%12,%13,%14,%15,%16,%17,%18,%19,%20,%21,%22,%23,%24,%25,%26,%27,%28,%29,%30,%31,"
                 "%32,%33,%34,%35,%36,%37,%38,%39,%40,%41,%42,%43,%44,%45,%46,%47,%48,%49,%50,%51,%52,%53,%54,%55,%56,%57,%58,%59,%60,%61,%62,%63},"
                 "{%64,%65,%66,%67},%68,p,1,1,0;}"
                 : F16(d, 0), F16(d, 16), F16(d, 32), F16(d, 48) : "r"(a[0]), "r"(a[1]), "r"(a[2]), "r"(a[3]), "l"(db), "r"(sc));
}
#define N80_REGS "{%0,%1,%2,%3,%4,%5,%6,%7,%8,%9,%10,%11,%12,%13,%14,%15,%16,%17,%18,%19,%20,%21,%22,%23,%24,%25,%26,%27,%28,%29,%30,%31,%32,%33,%34,%35,%36,%37,%38,%39}"
__device__ __forceinline__ void wg_n80_ss(float* d, uint64_t da, uint64_t db, int sc) {
    asm volatile("{.reg .pred p; setp.ne.b32 p,%42,0; wgmma.mma_async.sync.aligned.m64n80k16.f32.bf16.bf16 " N80_REGS ",%40,%41,p,1,1,0,0;}"
                 : F16(d, 0), F16(d, 16), F8(d, 32) : "l"(da), "l"(db), "r"(sc));
}
__device__ __forceinline__ void wg_n88_ss(float* d, uint64_t da, uint64_t db, int sc) {
    asm volatile("{.reg .pred p; setp.ne.b32 p,%46,0; wgmma.mma_async.sync.aligned.m64n88k16.f32.f16.f16 "
                 "{%0,%1,%2,%3,%4,%5,%6,%7,%8,%9,%10,%11,%12,%13,%14,%15,%16,%17,%18,%19,%20,%21,%22,%23,%24,%25,%26,%27,%28,%29,%30,%31,"
                 "%32,%33,%34,%35,%36,%37,%38,%39,%40,%41,%42,%43},%44,%45,p,1,1,0,0;}"
                 : F16(d, 0), F16(d, 16), F8(d, 32), F4(d, 40) : "l"(da), "l"(db), "r"(sc));
}
__device__ __forceinline__ void wg_n48_ss_ta(float* d, uint64_t da, uint64_t db, int sc) {
    asm volatile("{.reg .pred p; setp.ne.b32 p,%26,0; wgmma.mma_async.sync.aligned.m64n48k16.f32.f16.f16 "
                 "{%0,%1,%2,%3,%4,%5,%6,%7,%8,%9,%10,%11,%12,%13,%14,%15,%16,%17,%18,%19,%20,%21,%22,%23},%24,%25,p,1,1,1,0;}"
                 : F16(d, 0), F8(d, 16) : "l"(da), "l"(db), "r"(sc));
}
template <int TA> __device__ __forceinline__ void wg_n64_ss_tb(float* d, uint64_t da, uint64_t db, int sc) {
    asm volatile("{.reg .pred p; setp.ne.b32 p,%34,0; wgmma.mma_async.sync.aligned.m64n64k16.f32.f16.f16 "
                 "{%0,%1,%2,%3,%4,%5,%6,%7,%8,%9,%10,%11,%12,%13,%14,%15,%16,%17,%18,%19,%20,%21,%22,%23,%24,%25,%26,%27,%28,%29,%30,%31},"
                 "%32,%33,p,1,1,%35,1;}"
                 : F16(d, 0), F16(d, 16) : "l"(da), "l"(db), "r"(sc), "n"(TA));
}
__device__ __forceinline__ void pdl_wait() { asm volatile("griddepcontrol.wait;" ::: "memory"); }
__device__ __forceinline__ void pdl_go() { asm volatile("griddepcontrol.launch_dependents;" ::: "memory"); }
__device__ __forceinline__ float cos640(float p) {
    const float q = fmaf(p, 0.0015625f, 12582912.f) - 12582912.f;
    return __cosf(fmaf(q, -640.f, p) * 0.009817477042468103f);
}
__device__ __forceinline__ uint4 cos_row8(float p0, float step, float amp = 1.f) {
    float v[8];
    const float k = 2.f * cos640(step);
    v[0] = amp * cos640(p0); v[1] = amp * cos640(p0 + step);
#pragma unroll
    for (int i = 2; i < 8; i++) v[i] = fmaf(k, v[i - 1], -v[i - 2]);
    return make_uint4(pack_h(v[0], v[1]), pack_h(v[2], v[3]), pack_h(v[4], v[5]), pack_h(v[6], v[7]));
}
__device__ __forceinline__ float wfilter_max(int lane) {
    float m = fmaxf(fmaxf(g_wmax[lane], g_wmax[lane + 32]), fmaxf(g_wmax[lane + 64], g_wmax[lane + 96]));
    return __uint_as_float(__reduce_max_sync(~0u, __float_as_uint(m)));
}
__device__ __forceinline__ unsigned ld_acquire(const Flag* p) { unsigned v; asm volatile("ld.acquire.gpu.global.u32 %0,[%1];" : "=r"(v) : "l"(p) : "memory"); return v; }
#define POLL_NS 200
template <int NS = POLL_NS> __device__ __forceinline__ void wait_flag(const Flag* p, unsigned v) {
    if (ld_acquire(p) >= v) return;
    unsigned x;
    int lim = 0;
    do {
        __nanosleep(NS);
        asm volatile("ld.relaxed.gpu.global.u32 %0,[%1];" : "=r"(x) : "l"(p) : "memory");
    } while (x < v && ++lim < SPIN_LIM);
    ld_acquire(p);
}
__device__ __forceinline__ void prefetch_l2(const void* p, int bytes) { asm volatile("cp.async.bulk.prefetch.L2.global [%0],%1;" ::"l"(p), "r"(bytes) : "memory"); }
__device__ __forceinline__ void red_release(Flag* p) { asm volatile("red.release.gpu.global.add.u32 [%0],1;" ::"l"(p) : "memory"); }
__device__ __forceinline__ void red_relaxed(Flag* p) { asm volatile("red.relaxed.gpu.global.add.u32 [%0],1;" ::"l"(p) : "memory"); }
__device__ __forceinline__ void red_h8(void* p, uint32_t a, uint32_t b, uint32_t c, uint32_t d) {
    asm volatile("red.relaxed.gpu.global.add.noftz.v4.f16x2 [%0],{%1,%2,%3,%4};" ::"l"(p), "r"(a), "r"(b), "r"(c), "r"(d) : "memory");
}
__device__ __forceinline__ float pow2_scale(float bound, int top, float* inv) {
    int e = (int)((__float_as_uint(bound) >> 23) & 0xff) - 126;
    int k = top - e;
    k = max(-100, min(100, k));
    *inv = __uint_as_float((uint32_t)(127 - k) << 23);
    return __uint_as_float((uint32_t)(127 + k) << 23);
}
__device__ __forceinline__ char* red_base() { return (char*)(((uintptr_t)g_redraw + 32767) & ~(uintptr_t)32767); }

__device__ __forceinline__ void setup_a(char* sm, const int b, const bf16* __restrict__ wr, const bf16* __restrict__ wi) {
    const int tid = threadIdx.x, lane = tid & 31;
    const uint32_t sb = smem_u32(sm);
    auto row_byte = [&](int q) { return ((b >> 2) + 32 * ((q >> 1) * 8 + 2 * (b & 3) + (q & 1))) * 642; };
#pragma unroll 1
    for (int r = tid >> 5; r < 32; r += 8) {
        const char* src = (const char*)(r < 16 ? wr : wi) + (row_byte(r & 15) & ~15);
        cp_async16(sb + r * 672 + lane * 16, src + lane * 16);
        if (lane < 9) cp_async16(sb + r * 672 + 512 + lane * 16, src + 512 + lane * 16);
    }
    ((uint4*)g_stat)[b * 256 + tid] = make_uint4(0, 0, 0, 0);
    if (tid < 2 * (NFLAG / 128)) ((uint4*)(g_flag + b * (NFLAG / 128) + (tid >> 1)))[tid & 1] = make_uint4(0, 0, 0, 0);
    if (tid < 12) {
        const int i = b * 12 + tid;
        const int f = ((i >> 4) & 3) * 8 + (i & 7), im = (i >> 3) & 1, part = (i >> 8) & 1;
        ((uint4*)g_ctab)[i] = cos_row8((float)(i < 1024 ? (i >> 7) * 80 * (i & 63) + ((i & 64) ? 480 : 0) : ((i >> 6) & 3) * 160 * f + (im == part ? 0 : im ? 160 : 480)),
                                       (float)(i < 1024 ? 10 * (i & 63) : 20 * f));
    }
    asm volatile("cp.async.wait_all;" ::: "memory");
    __syncthreads();
    const int q0 = (tid & 3) * 4;
    const char* rp[4];
#pragma unroll
    for (int u = 0; u < 4; u++) rp[u] = sm + (q0 + u) * 672 + (row_byte(q0 + u) & 15);
    uint32_t mx = 0;
#pragma unroll 2
    for (int c = tid >> 2; c < 321; c += 64) {
        uint32_t v[4];
#pragma unroll
        for (int u = 0; u < 4; u++) {
            v[u] = ((const unsigned short*)rp[u])[c] | ((uint32_t)((const unsigned short*)(rp[u] + 16 * 672))[c] << 16);
            mx = __vmaxu2(mx, v[u] & 0x7fff7fffu);
        }
        ((uint4*)g_Wf)[(size_t)c * 512 + b * 4 + ((tid ^ (b >> 1)) & 3)] = make_uint4(v[0], v[1], v[2], v[3]);
    }
    mx = __reduce_max_sync(~0u, max(mx & 0xffffu, mx >> 16));
    __syncthreads();
    if (lane == 0) ((uint32_t*)sm)[tid >> 5] = mx;
    __syncthreads();
    if (tid < 32) {
        mx = __reduce_max_sync(~0u, ((uint32_t*)sm)[lane & 7]);
        if (tid == 0) g_wmax[b] = __uint_as_float(mx << 16);
    }
}
__device__ __forceinline__ void setup_b(const int b, const bf16* __restrict__ mem0) {
    const int tid = threadIdx.x;
    uint4* z = (uint4*)red_base();
    if (b < 3) {
        const int w = tid >> 5, lane = tid & 31, p = b * 2 + ((w >> 1) & 1), odd = w & 1;
        uint32_t mx = 0;
#pragma unroll 4
        for (int i = lane; i < 640; i += 32) {
            const uint4 u = ((const uint4*)mem0)[i];
            mx = __vmaxu2(__vmaxu2(mx, u.x & 0x7fff7fffu), __vmaxu2(__vmaxu2(u.y & 0x7fff7fffu, u.z & 0x7fff7fffu), u.w & 0x7fff7fffu));
        }
        float inv, v[7];
        const float sc = pow2_scale(__uint_as_float(__reduce_max_sync(~0u, max(mx & 0xffffu, mx >> 16)) << 16), 14, &inv);
        if (tid == 0) g_invM0 = inv;
#pragma unroll
        for (int j = 0; j < 7; j++) {
            const int r = p * 56 + (j < 6 ? odd * 32 + (j >> 1) * 8 : 24) + (lane >> 2), mr = 2 * (lane & 3) + (j < 6 ? (j & 1) : odd);
            v[j] = r < 320 ? __bfloat162float(mem0[mr * 640 + (w >> 2) * 320 + r]) * sc : 0.f;
        }
        const int off = w * 2048 + (lane >> 4) * 1024 + ((lane >> 3) & 1) * 256 + (lane & 7) * 16 + (b == 2 ? (w >> 1) * 4096 + 128 : b * 16384);
        const uint4 u = make_uint4(pack_h(v[0], v[1]), pack_h(v[2], v[3]), pack_h(v[4], v[5]), pack_h(v[6], 32.f));
        z[off >> 4] = u; z[65536 + (off >> 4)] = u;
    }
}

constexpr int SU_SMEM = 32 * 672;
__global__ void __launch_bounds__(256, 4) k_setup(const bf16* __restrict__ wr, const bf16* __restrict__ wi, const bf16* __restrict__ mem0) {
    extern __shared__ __align__(1024) char sm[];
    TL(0);
    setup_b(blockIdx.x, mem0);
    setup_a(sm, blockIdx.x, wr, wi);
    __syncthreads();
    if (threadIdx.x == 0) red_release(g_ready);
    TL(1);
}
__device__ __forceinline__ float weight_scale(int h, int ty, float* inv) { return pow2_scale(__ldcg(g_wmx + h * 3 + ty), 6, inv); }

#define STR_(x) #x
#define STR(x) STR_(x)
#define RF_U 1
constexpr int RF_A = 22 * 2816, RF_X = RF_A + 22 * 1024, RF_BAR = RF_X + 64 * 1344, RF_SMEM = RF_BAR + 64;
__global__ void __cluster_dims__(2, 1, 1) __launch_bounds__(256, 2)
k_rowf(const bf16* x, const int first, const bf16* Wq, const bf16* Wk, const bf16* Wv, const bf16* Wo) {
    extern __shared__ __align__(1024) char sm[];
    TL(first ? 2 : 16);
    const int tid = threadIdx.x, w = tid >> 5, lane = tid & 31, g = lane >> 2, t = lane & 3;
    if (blockIdx.x >= 128) { __nanosleep(2500); return; }
    const int a = blockIdx.x >> 2, gq = blockIdx.x & 3;
    const uint32_t sb = smem_u32(sm), mb = sb + RF_BAR + w * 8;
    if (lane == 0) {
        mbar_init(mb, 1);
        asm volatile("fence.mbarrier_init.release.cluster;" ::: "memory");
        mbar_expect(mb, 8 * 1280);
    }
    __syncwarp();
    asm volatile("barrier.cluster.arrive.relaxed.aligned;" ::: "memory");
#pragma unroll 1
    for (int ph = 0; ph < 2; ph++) {
        if (ph != first) {
            asm volatile("barrier.cluster.wait.aligned;" ::: "memory");
            pdl_wait();
            TL(first ? 3 : 17);
            if (lane < 4)
                asm volatile("cp.async.bulk.shared::cluster.global.mbarrier::complete_tx::bytes.multicast::cluster [%0],[%1],1280,[%2],%3;"
                             ::"r"(sb + RF_X + (w * 8 + (gq & 1) * 4 + lane) * 1344), "l"(x + (size_t)(a * 64 + w * 8 + (gq & 1) * 4 + lane) * 640), "r"(mb),
                             "h"((unsigned short)3) : "memory");
            __syncwarp();
            pdl_go();
        } else {
#pragma unroll 3
            for (int id = tid; id < 22 * 176; id += 256) {
                const int kg = id / 176, n = id - kg * 176;
                const float c = (float)(2 * n + (gq & 1));
                *(uint4*)(sm + id * 16) = cos_row8(fmaf((float)(kg * 8), c, (float)((gq & 2) * 80)), c, 0.03952847075210474f);
            }
        }
    }
    mbar_wait(mb, 0);
    const uint32_t row = sb + RF_X + (w * 8 + g) * 1344;
    float st[4][4] = {};
#pragma unroll 1
    for (int i = 0; i < 20; i += 4) {
        uint32_t u[4][4];
#pragma unroll
        for (int q = 0; q < 4; q++) lds128(u[q], row + (4 * (i + q) + t) * 16);
#pragma unroll
        for (int q = 0; q < 4; q++) {
            mma_bf(st[(q & 1) * 2], u[q][0], 0x3f803f80u, u[q][1], 0x3f803f80u, u[q][0], u[q][1]);
            mma_bf(st[(q & 1) * 2 + 1], u[q][2], 0x3f803f80u, u[q][3], 0x3f803f80u, u[q][2], u[q][3]);
        }
    }
#pragma unroll
    for (int q = 0; q < 4; q++) { st[0][q] += st[2][q]; st[1][q] += st[3][q]; }
    const float sq = __shfl_sync(~0u, (g & 1) ? st[0][1] + st[1][1] : st[0][0] + st[1][0], g * 4 + (g >> 1));
    const float mean = __shfl_sync(~0u, (g & 1) ? st[0][3] + st[1][3] : st[0][2] + st[1][2], g * 4 + (g >> 1)) * (1.f / 640.f);
    const float r = rsqrtf(fmaxf(fmaf(-mean, mean, sq * (1.f / 640.f)), 0.f) + 1e-5f), off = gq == 0 ? -4.f * mean * r : 0.f;
    const float r1 = (gq == 1 || gq == 2) ? -r : r, r2 = (gq & 1) ? -r : r, r3 = gq >= 2 ? -r : r;
    const uint32_t aa = sb + RF_A + w * 128 + g * 16;
    auto el = [&](int d) { unsigned short v; asm volatile("ld.shared.u16 %0,[%1];" : "=h"(v) : "r"(row + d * 2)); return __uint_as_float((uint32_t)v << 16); };
_Pragma(STR(unroll RF_U))
    for (int i = 0; i < 5; i++) {
        const int ch = t + 4 * i;
        uint32_t u[4][4];
        lds128(u[0], row + ch * 16); lds128(u[1], row + (39 - ch) * 16); lds128(u[2], row + (40 + ch) * 16); lds128(u[3], row + (79 - ch) * 16);
        const float nb0 = el(320 - 8 * ch), nb1 = el(ch ? 640 - 8 * ch : 0);
        float o[8];
#pragma unroll
        for (int q = 0; q < 8; q++) {
            const int m = (8 - q) >> 1;
            const float e0 = (q & 1) ? bf_hi(u[0][q >> 1]) : bf_lo(u[0][q >> 1]), e2 = (q & 1) ? bf_hi(u[2][q >> 1]) : bf_lo(u[2][q >> 1]);
            const float e1 = q == 0 ? nb0 : (q & 1) ? bf_hi(u[1][m & 3]) : bf_lo(u[1][m & 3]), e3 = q == 0 ? nb1 : (q & 1) ? bf_hi(u[3][m & 3]) : bf_lo(u[3][m & 3]);
            o[q] = fmaf(e3, r3, fmaf(e2, r2, fmaf(e1, r1, fmaf(e0, r, off))));
        }
        if (ch == 0) o[0] *= 0.5f;
        sts128(aa + ch * 1024, pack_h(o[0], o[1]), pack_h(o[2], o[3]), pack_h(o[4], o[5]), pack_h(o[6], o[7]));
    }
    if (t < 2) sts128(aa + (20 + t) * 1024, t == 0 ? pack_h(fmaf(el(480), r2, fmaf(el(160), r, 0.5f * off)), 0.f) : 0u, 0u, 0u, 0u);
    fence_async_smem();
    __syncthreads();
    const int wg = w >> 2;
    float acc[44];
    uint64_t da = mkdesc(sb + RF_A, 1024, 128, 0), db = mkdesc(sb + wg * 1408, 2816, 128, 0);
    wg_fence();
#pragma unroll 1
    for (int k = 0; k < 11; k++) { wg_n88_ss(acc, da, db, k); da += 128; db += 352; }
    wg_commit(); wg_wait<0>();
    const uint32_t stg = sb + RF_X + wg * 96 * 144;
#pragma unroll
    for (int j = 0; j < 12; j += 2) {
        const int m = lane >> 3, j1 = j < 10 ? j + 1 : j;
        stsm4t(stg + ((j + (m >> 1)) * 8 + (lane & 7)) * 144 + ((w & 3) * 16 + (m & 1) * 8) * 2, pack_h(acc[j * 4], acc[j * 4 + 1]),
               pack_h(acc[j * 4 + 2], acc[j * 4 + 3]), pack_h(acc[j1 * 4], acc[j1 * 4 + 1]), pack_h(acc[j1 * 4 + 2], acc[j1 * 4 + 3]));
    }
    bar_sync(1 + wg, 128);
#pragma unroll 3
    for (int rr = (tid & 127) >> 3; rr < 88; rr += 16) {
        const int ch = tid & 7, c = 2 * (wg * 88 + rr) + (gq & 1);
        if (c <= 320 - (gq >> 1) && (c | (gq ^ 2))) {
            uint32_t u[4];
            lds128(u, stg + rr * 144 + ch * 16);
            ((uint4*)g_UT)[((size_t)(c == 320 ? 1 : 2 * c + (gq >> 1)) * 32 + a) * 8 + (ch ^ (a & 7))] = make_uint4(u[0], u[1], u[2], u[3]);
        }
    }
    TL(first ? 4 : 18);
}

constexpr int GST = 4, GSTB = 32768 + 20480, GNC = 32;
constexpr int G_BAR = GST * GSTB + 3072;
#define GPACE 1100
#define GPACE2 650
__device__ __forceinline__ void oproj_load(const uint32_t sb, const int op, const int mb, const int nb, const int c0, const uint32_t pace) {
    const int by = op == 2 ? 20480 : 16384;
    const char* src = op == 2 ? (const char*)g_wot + (size_t)nb * GNC * 20480 : (const char*)g_O + (size_t)(2 * mb + op) * GNC * 16384;
    uint32_t t0 = clock32() - pace + op * (pace / 3);
#pragma unroll 1
    for (int c = c0; c < c0 + GNC; c++, src += by) {
        const int st = c % GST;
        if (c >= GST) mbar_wait(sb + G_BAR + (GST + st) * 8, ((c / GST) - 1) & 1);
        while (clock32() - t0 < pace) {}
        t0 = clock32();
        const int by_ = by;
        mbar_expect(sb + G_BAR + st * 8, by_);
        if (op == 2) bulk_g2s(sb + st * GSTB + 32768, src, by_, sb + G_BAR + st * 8);
        else bulk_g2s_last(sb + st * GSTB + op * 16384, src, by_, sb + G_BAR + st * 8);
    }
}
__device__ __forceinline__ void oproj_mma(const uint32_t sb, const int mb, const int nb, const int c0, const bf16* res, bf16* out) {
    const int w = threadIdx.x >> 5, lane = threadIdx.x & 31, wg = w >> 2;
    float acc[40];
    uint4 rv[5];
#pragma unroll 1
    for (int c = c0; c < c0 + GNC; c++) {
        const int st = c % GST;
        mbar_wait(sb + G_BAR + st * 8, (c / GST) & 1);
        const uint32_t d = sb + st * GSTB;
        wg_fence();
#pragma unroll
        for (int k = 0; k < 8; k++)
            wg_n80_ss(acc, mkdesc(d + wg * 16384 + k * 2048, 1024, 128, 0), mkdesc(d + 32768 + k * 2560, 1280, 128, 0), (c - c0) | k);
        wg_commit();
        if (c > c0) {
            wg_wait<1>();
            if (lane == 0) mbar_arrive(sb + G_BAR + (GST + (c - 1) % GST) * 8);
        }
    }
#pragma unroll
    for (int i = 0; i < 5; i++) {
        const int id = i * 32 + lane, r = id / 10;
        rv[i] = __ldcg((const uint4*)res + (size_t)(mb * 128 + w * 16 + r) * 80 + nb * 10 + id - r * 10);
    }
    wg_wait<0>();
    bar_sync(5, 256);
    const uint32_t stg = sb + (GST - 1) * GSTB + w * 16 * 176;
#pragma unroll
    for (int j = 0; j < 5; j++)
        stsm4(stg + (lane & 15) * 176 + (2 * j + (lane >> 4)) * 16, pack_bf(acc[j * 8], acc[j * 8 + 1]), pack_bf(acc[j * 8 + 2], acc[j * 8 + 3]),
              pack_bf(acc[j * 8 + 4], acc[j * 8 + 5]), pack_bf(acc[j * 8 + 6], acc[j * 8 + 7]));
    __syncwarp();
#pragma unroll
    for (int i = 0; i < 5; i++) {
        const int id = i * 32 + lane, r = id / 10, ch = id - r * 10;
        uint32_t y[4];
        lds128(y, stg + r * 176 + ch * 16);
        ((uint4*)out)[(size_t)(mb * 128 + w * 16 + r) * 80 + nb * 10 + ch] = add_bf8(rv[i], y);
    }
    fence_async_smem();
    __syncwarp();
    if (lane == 0) mbar_arrive(sb + G_BAR + (2 * GST - 1) * 8);
}

__global__ void __launch_bounds__(128, 4) k_col(const int first) {
    __shared__ __align__(1024) char sz[8192];
    __shared__ __align__(1024) char stab[24576];
    __shared__ __align__(1024) char swf[8192];
    __shared__ __align__(8) uint64_t bar[2];
    const int tid = threadIdx.x, wl = tid >> 5, lane = tid & 31, g = lane >> 2, t = lane & 3;
    const int c = blockIdx.x;
    TL(first ? 5 : 19);
    const bool realc = c == 0 || c == 320;
    const uint32_t z = smem_u32(sz), b2 = smem_u32(stab), a1 = b2 + 16384, wf = smem_u32(swf), mb = smem_u32(bar);
    if (tid == 0) { mbar_init(mb, 1); mbar_init(mb + 8, 1); fence_async_smem(); }
    if (realc) {
        for (int i = tid; i < 256; i += 128) sts128(z + 4096 + i * 16, 0, 0, 0, 0);
        fence_async_smem();
    }
    const int k1 = wl * 8 + g;
    float tc[16], ts[16];
#pragma unroll
    for (int j = 0; j < 16; j++) {
        const int p = ((j >> 1) * 8 + 2 * t + (j & 1)) * k1;
        __sincosf((float)(p - 1024) * 0.003067961575771282f, &ts[j], &tc[j]);
        ts[j] = -ts[j]; tc[j] = -tc[j];
    }
    if (first && tid == 32) { wait_flag<400>(g_ready, 128); fence_async_glb(); }
    __syncthreads();
    if (tid == 32) {
        mbar_expect(mb + 8, 24576 + 8192);
        bulk_g2s(b2, g_ctab, 24576, mb + 8);
        bulk_g2s(wf, g_Wf + (size_t)c * 2048, 8192, mb + 8);
    }
    float inv;
    const float wsc = pow2_scale(wfilter_max(lane), 0, &inv) * (realc ? 0.0625f : 0.125f);
    pdl_wait();
    TL(first ? 6 : 20);
    if (tid == 0) {
        const int by = realc ? 4096 : 8192;
        mbar_expect(mb, by);
        bulk_g2s_last(z, (const char*)g_UT + (size_t)(c == 320 ? 1 : 2 * c) * 4096, by, mb);
    }
    pdl_go();
    mbar_wait(mb + 8, 0);
    mbar_wait(mb, 0);
    float d[64];
    uint32_t a[4][4];
    wg_fence();
#pragma unroll
    for (int ks = 0; ks < 4; ks++) wg_n64_ss_tb<0>(d, mkdesc(a1 + ks * 2048, 1024, 128, 0), mkdesc(z + ks * 2048, 1024, 1024, 1), ks);
    wg_commit(); wg_wait<0>();
    const float r32 = 0.17677669529663687f;
#pragma unroll
    for (int j = 0; j < 8; j++) {
        float yr[2], yi[2];
#pragma unroll
        for (int e = 0; e < 2; e++) {
            const float re = d[j * 4 + e] * r32, im = d[j * 4 + 2 + e] * r32, cc = tc[j * 2 + e], ss = ts[j * 2 + e];
            yr[e] = re * cc + im * ss; yi[e] = im * cc - re * ss;
        }
        a[j >> 1][(j & 1) * 2] = pack_h(yr[0], yr[1]); a[j >> 1][(j & 1) * 2 + 1] = pack_h(yi[0], yi[1]);
    }
    wg_fence();
#pragma unroll
    for (int ks = 0; ks < 4; ks++) wg_n128_rs(d, a[ks], mkdesc(b2 + ks * 4096, 2048, 128, 0), ks);
    wg_commit(); wg_wait<0>();
#pragma unroll
    for (int q = 0; q < 4; q++) {
        uint32_t wv[4];
        lds128(wv, wf + tid * 64 + ((q ^ (tid >> 1)) & 3) * 16);
#pragma unroll
        for (int jj = 0; jj < 2; jj++) {
            const int j = 2 * q + jj;
            float yr[2], yi[2];
#pragma unroll
            for (int e = 0; e < 2; e++) {
                const float xr = d[j * 4 + e] + d[32 + j * 4 + 2 + e], xi = d[j * 4 + 2 + e] - d[32 + j * 4 + e];
                const float fr = bf_lo(wv[jj * 2 + e]) * wsc, fi = bf_hi(wv[jj * 2 + e]) * wsc;
                yr[e] = xr * fr - xi * fi; yi[e] = xr * fi + xi * fr;
            }
            a[q][jj * 2] = pack_h(yr[0], yr[1]); a[q][jj * 2 + 1] = pack_h(yi[0], yi[1]);
        }
    }
    wg_fence();
#pragma unroll
    for (int ks = 0; ks < 4; ks++) wg_n128_rs(d, a[ks], mkdesc(b2 + ks * 4096, 2048, 128, 0), ks);
    wg_commit(); wg_wait<0>();
#pragma unroll
    for (int j = 0; j < 8; j++) {
        float yr[2], yi[2];
#pragma unroll
        for (int e = 0; e < 2; e++) {
            const float vr = (d[j * 4 + e] - d[32 + j * 4 + 2 + e]) * 0.125f, vi = (d[j * 4 + 2 + e] + d[32 + j * 4 + e]) * 0.125f;
            const float cc = tc[j * 2 + e], ss = ts[j * 2 + e];
            yr[e] = vr * cc - vi * ss; yi[e] = vi * cc + vr * ss;
        }
        a[j >> 1][(j & 1) * 2] = pack_h(yr[0], yr[1]); a[j >> 1][(j & 1) * 2 + 1] = pack_h(yi[0], yi[1]);
    }
    __syncthreads();
    const int mm = lane >> 3, rr = lane & 7;
    const uint32_t rowo = (wl * 16 + (mm & 1) * 8 + rr) * 128;
#pragma unroll
    for (int q = 0; q < 4; q++) stsm4(z + rowo + (((2 * q + (mm >> 1)) ^ rr) << 4), a[q][0], a[q][1], a[q][2], a[q][3]);
    fence_async_smem();
    __syncthreads();
    wg_fence();
#pragma unroll
    for (int ks = 0; ks < 4; ks++) wg_n64_ss_tb<1>(d, mkdesc(a1 + ks * 256, 128, 1024, 0), mkdesc(z + ks * 2048, 1024, 1024, 1), ks);
    wg_commit(); wg_wait<0>();
#pragma unroll
    for (int q = 0; q < 4; q++)
        stsm4(wf + rowo + (((2 * q + (mm >> 1)) ^ rr) << 4), pack_h(d[q * 8] * r32, d[q * 8 + 1] * r32), pack_h(d[q * 8 + 2] * r32, d[q * 8 + 3] * r32),
              pack_h(d[q * 8 + 4] * r32, d[q * 8 + 5] * r32), pack_h(d[q * 8 + 6] * r32, d[q * 8 + 7] * r32));
    __syncwarp();
    if (!(realc && wl >= 2)) {
        const int kk = c == 320 ? 320 : (c & 1) * 160 + (c >> 1) + (wl >> 1) * 320;
#pragma unroll
        for (int i = 0; i < 4; i++) {
            const int r = wl * 16 + i * 4 + (lane >> 3), ch = lane & 7;
            uint32_t v[4];
            lds128(v, wf + r * 128 + ((ch ^ (r & 7)) << 4));
            ((uint4*)g_YT)[((size_t)(r & 31) * 640 + kk) * 8 + (ch ^ (kk & 7))] = make_uint4(v[0], v[1], v[2], v[3]);
        }
    }
    __syncthreads();
    if (tid == 0) red_release(g_flag + F_X + (first ? 0 : 128) + 65);
    TL(first ? 7 : 21);
}

constexpr int O_XS = 0;
constexpr int O_MS = 81920;
constexpr int O_QKP = O_MS + 10752;
constexpr int O_VM = O_QKP + 4096;
constexpr int O_SC = O_VM + 4096;
constexpr int O_OS = O_SC + 1536;
constexpr int O_XCH = O_OS + 2048;
constexpr int O_SUM = O_XCH + 8192;
constexpr int O_MX = O_SUM + 256;
constexpr int O_STG = O_MS + 65536 - 8192;
static_assert(O_STG - 16384 >= O_MX + 1024, "shared-memory map");
constexpr int O_WO = O_STG + 16384;
constexpr int O_SCL = O_WO + 65536;
constexpr int O_BAR = O_SCL + 64;
constexpr int B_XF = O_BAR, B_S = O_BAR + 16, B_GO = O_BAR + 24, B_VX = O_BAR + 32, B_STG = O_BAR + 48, B_FREE = O_BAR + 72;
constexpr int T_FA = O_BAR + 96, T_EA = T_FA + 32, T_FB = T_EA + 32, T_EB = T_FB + 56, T_RED = T_EB + 32;
constexpr int O_WMX = O_BAR + 512, B_W = O_BAR + 64;
constexpr int O_LAST = (O_WMX + 192 + 1023) / 1024 * 1024;
constexpr int CH_SMEM = O_LAST + 8192;
static_assert(O_WO == 19 * 8192, "weight staging");
__device__ __forceinline__ uint32_t tail_b(int c) { return c % 7 < 4 ? O_XS + (c % 7) * 20480 : O_WO + (c % 7 - 4) * 20480; }
constexpr int S_TX = 2 * 768 + 2048;

#define NPERM 1
#define NWO0 2
#define NWO1 6
#define XEARLY 0
#define RELAX 1
#define KVB 1
#define REL1 0
#define XLATE 0
#define TDELAY 800
#define WDEPTH 6
#define RDELAY 580

#define STAMP(i)

#define NTA 23
#define NTB 26
template <int LO, int HI>
__device__ __forceinline__ void tok_issue(const uint32_t (&A0)[20][4], const uint32_t (&A1)[20][4], float (&b0)[16], float (&b1)[16], uint32_t xd,
                                          const uint32_t zero) {
    if (LO == 0) wg_fence();
    sfor<HI - LO>([&](auto I) {
        constexpr int i = LO + I;
        if constexpr (i < 20) wg_n32_x<i * 64, i>(b0, A0[i], xd); else wg_n32_x<(i - 20) * 64, i - 20>(b1, A1[i - 20], xd + zero);
        if constexpr (i == 19 || i == NTB - 1 || i == 39) wg_commit();
    });
}
__device__ __forceinline__ void tok_give(const float (&b0)[16], const uint32_t L16, const uint32_t xch0) {
    wg_wait<1>();
    sfor<2>([&](auto I) {
        constexpr int i = I;
        sts128_u<i * 512>(L16, xch0, pack_h(b0[8 * i], b0[8 * i + 1]), pack_h(b0[8 * i + 2], b0[8 * i + 3]), pack_h(b0[8 * i + 4], b0[8 * i + 5]),
                          pack_h(b0[8 * i + 6], b0[8 * i + 7]));
    });
}
__device__ __forceinline__ void tok_finish(float (&b1)[16], const uint32_t (&e)[2][4], const uint32_t L16, const uint32_t dst, const uint32_t idn) {
#pragma unroll
    for (int j = 0; j < 4; j++)
        asm volatile("mma.sync.aligned.m16n8k8.row.col.f32.f16.f16.f32 {%0,%1,%2,%3},{%4,%5},{%6},{%0,%1,%2,%3};"
                     : F4(b1, 4 * j) : "r"(e[j >> 1][(j & 1) * 2]), "r"(e[j >> 1][(j & 1) * 2 + 1]), "r"(idn));
    stsm4_u<0>(L16, dst, pack_bf(b1[0], b1[1]), pack_bf(b1[2], b1[3]), pack_bf(b1[4], b1[5]), pack_bf(b1[6], b1[7]));
    stsm4_u<512>(L16, dst, pack_bf(b1[8], b1[9]), pack_bf(b1[10], b1[11]), pack_bf(b1[12], b1[13]), pack_bf(b1[14], b1[15]));
}
__device__ __forceinline__ uint32_t uni(uint32_t v) { return __shfl_sync(~0u, v, 0); }
__device__ __forceinline__ uint32_t badd(uint32_t a, uint32_t b) { uint32_t r; asm("add.rn.bf16x2 %0,%1,%2;" : "=r"(r) : "r"(a), "r"(b)); return r; }
__device__ __forceinline__ uint32_t bmax(uint32_t a, uint32_t b) { uint32_t r; asm("max.bf16x2 %0,%1,%2;" : "=r"(r) : "r"(a), "r"(b)); return r; }
__device__ __forceinline__ uint32_t babsmax(uint32_t a, uint32_t b) { uint32_t r; asm("max.xorsign.abs.bf16x2 %0,%1,%2;" : "=r"(r) : "r"(a), "r"(b)); return r; }
__device__ __forceinline__ uint32_t habsmax(uint32_t a, uint32_t b) { uint32_t r; asm("max.xorsign.abs.f16x2 %0,%1,%2;" : "=r"(r) : "r"(a), "r"(b)); return r; }

template <int NPF>
__device__ __forceinline__ float mem_out(const uint32_t sb, const uint32_t L16, const uint32_t L8, uint32_t (&wo)[16][4], const uint32_t woa,
                                         char* dst, const bool odd) {
    bar_sync(2, 352);
    float a[4][4];
#pragma unroll
    for (int i = 0; i < 4; i++) a[i][0] = a[i][1] = a[i][2] = a[i][3] = 0.f;
    uint32_t ob[4][4], sm_[2], sc[2];
    sfor<8>([&](auto I) {
        constexpr int i = I;
        if constexpr (!(i & 1)) ldsm4t_u<O_OS + (i >> 1) * 512>(ob[i >> 1], L16, sb);
        if constexpr (i >= NPF) { ldsm4t(wo[i], woa + i * 1024); ldsm4t(wo[8 + i], (woa ^ 32) + i * 1024); }
    });
    lds64_u<O_SUM>(sm_, L8 & 24, sb); lds64(sc, sb + O_SCL);
#pragma unroll
    for (int i = 0; i < 8; i++) {
        mma_bf(a[i & 1], wo[i][0], wo[i][1], wo[i][2], wo[i][3], ob[i >> 1][(i & 1) * 2], ob[i >> 1][(i & 1) * 2 + 1]);
        mma_bf(a[2 + (i & 1)], wo[8 + i][0], wo[8 + i][1], wo[8 + i][2], wo[8 + i][3], ob[i >> 1][(i & 1) * 2], ob[i >> 1][(i & 1) * 2 + 1]);
    }
    const float f0 = rcp(__uint_as_float(sm_[0])) * __uint_as_float(sc[0]), f1 = rcp(__uint_as_float(sm_[1])) * __uint_as_float(sc[0]);
    red_h8(dst, pack_h((a[0][0] + a[1][0]) * f0, (a[0][1] + a[1][1]) * f1), pack_h((a[0][2] + a[1][2]) * f0, (a[0][3] + a[1][3]) * f1),
           pack_h((a[2][0] + a[3][0]) * f0, (a[2][1] + a[3][1]) * f1), pack_h(odd ? (a[2][3] + a[3][3]) * f1 : (a[2][2] + a[3][2]) * f0, 1.f));
    return __uint_as_float(sc[1]);
}

__device__ __forceinline__ void chain_mma(const uint32_t sb, const int c, const int h, const int layer, const uint32_t zero, const bf16* __restrict__ Wq,
                                          const bf16* __restrict__ Wk, const bf16* __restrict__ Wv, const bf16* __restrict__ Wo,
                                          const bf16* res, bf16* out) {
    int tid = read_tid(), lane = tid & 31;
    const int w = __shfl_sync(~0u, tid >> 5, 0), wg = w >> 2;
    [[maybe_unused]] const int cta = h * 3 + c;
    uint32_t A0[20][4], A1[20][4];
    const int t0 = (w & 3) + wg * 4, t1 = t0 ^ 4;
    float sl;
    {
        const int tl = tid & 127, r = tl >> 3, ch = tl & 7;
        const size_t so = (size_t)(wg * 320 + r) * 4096 + h * 128 + ch * 8;
        const bf16 *wa = (c == 2 ? Wv : Wq + c * 64) + so, *wb = (c == 2 ? Wv + 64 : Wk + c * 64) + so;
        const uint32_t ring = sb + wg * 4096;
        const uint32_t dst = ring + r * 128 + ((ch ^ r) & 7) * 16;
        const uint32_t src = ring + ((lane & 7) + (lane >> 4) * 8) * 128 + ((((w & 3) * 2 + ((lane >> 3) & 1)) ^ lane) & 7) * 16;
        const int q4 = lane & 3, gr = (c * 2 + ((w >> 1) & 1)) * 56 + (q4 == 3 ? 24 : (w & 1) * 32 + q4 * 8);
        const bf16* wo_ = Wo + (size_t)(h * 128 + (lane >> 2)) * 640 + wg * 320 + min(gr, 312);
        const uint32_t wdst = sb + O_WO + w * 8192 + (lane >> 2) * 64 + ((q4 ^ (lane >> 3)) & 3) * 16;
        auto issue = [&](int i) {
            if (i < 20) {
                const uint32_t d = dst + (i < 19 ? i * 8192 : O_LAST);
                cp_async16(d, wa + (size_t)i * 65536); cp_async16(d + 2048, wb + (size_t)i * 65536);
                if (i < 16) cp_async16(wdst + i * 512, wo_ + i * 5120, gr < 320 ? 16 : 0);
            }
            cp_commit();
        };
#pragma unroll 1
        for (int i = 0; i < WDEPTH; i++) issue(i);
        asm volatile("barrier.cluster.arrive.relaxed.aligned;" ::: "memory");
        uint32_t ma = 0, mb = 0;
#pragma unroll 1
        for (int i = 0; i < 20; i++) {
            issue(i + WDEPTH);
            cp_wait<WDEPTH>();
            const uint32_t d = dst + (i < 19 ? i * 8192 : O_LAST);
            uint32_t u[8];
            lds128(u, d); lds128(u + 4, d + 2048);
            ma = babsmax(babsmax(ma, babsmax(u[0], u[1])), babsmax(u[2], u[3])); mb = babsmax(babsmax(mb, babsmax(u[4], u[5])), babsmax(u[6], u[7]));
        }
        ma = __reduce_max_sync(~0u, max(ma & 0x7fffu, (ma >> 16) & 0x7fffu)); mb = __reduce_max_sync(~0u, max(mb & 0x7fffu, (mb >> 16) & 0x7fffu));
        asm volatile("barrier.cluster.wait.aligned;" ::: "memory");
        if (lane < 3)
            asm volatile("st.async.shared::cluster.mbarrier::complete_tx::bytes.v2.b32 [%0],{%1,%2},[%3];"
                         ::"r"(mapa(sb + O_WMX + (c * 8 + w) * 8, lane)), "r"(ma), "r"(mb), "r"(mapa(sb + B_W, lane)) : "memory");
        if (layer == TLL) TL(49);
        mbar_wait(sb + B_W, 0);
        {
            uint32_t v[2];
            lds64(v, sb + O_WMX + (lane < 24 ? lane : 0) * 8);
            const bool mine = (lane >> 3) < 3 && ((lane >> 4) == 1) == (c == 2);
            ma = __reduce_max_sync(~0u, mine ? v[0] : 0u); mb = __reduce_max_sync(~0u, mine ? v[1] : 0u);
            if (c == 2) ma = mb = max(ma, mb);
        }
        const float fa = __uint_as_float(ma << 16), fb = __uint_as_float(mb << 16);
        if (tid == 0) {
            if (c != 1) g_wmx[h * 3 + c] = fa;
            if (c == 0) g_wmx[h * 3 + 1] = fb;
        }
        float ia, ib;
        const float sa = pow2_scale(fa, 6, &ia), sc_b = pow2_scale(fb, 6, &ib);
        sl = __uint_as_float(uni(__float_as_uint(ia * ib * (0.08838834764831845f * 1.4426950408889634f))));
        const uint32_t pa = pack_bf(sa, sa), pb = pack_bf(sc_b, sc_b);
        auto convert = [&](int lo) {
#pragma unroll 1
            for (int i = lo; i < lo + 10; i++) {
                const uint32_t d = dst + (i < 19 ? i * 8192 : O_LAST);
                uint32_t u[8];
                lds128(u, d); lds128(u + 4, d + 2048);
#pragma unroll
                for (int q = 0; q < 8; q++)
                    asm("{.reg .b32 m,l,u; mul.rn.bf16x2 m,%0,%1; shl.b32 l,m,16; and.b32 u,m,0xffff0000; cvt.rn.f16x2.f32 %0,u,l;}" : "+r"(u[q]) : "r"(q < 4 ? pa : pb));
                sts128(d, u[0], u[1], u[2], u[3]); sts128(d + 2048, u[4], u[5], u[6], u[7]);
            }
            bar_sync(6 + wg, 128);
        };
        const uint32_t s0 = src + wg * 2048, s1 = src + 2048 - wg * 2048;
        convert(0);
#pragma unroll
        for (int i = 0; i < 10; i++) { ldsm4t(A0[i], s0 + i * 8192); ldsm4t(A1[i], s1 + i * 8192); }
        if (layer == TLL) TL(50);
        convert(10);
#pragma unroll
        for (int i = 10; i < 20; i++) { ldsm4t(A0[i], s0 + (i < 19 ? i * 8192 : O_LAST)); ldsm4t(A1[i], s1 + (i < 19 ? i * 8192 : O_LAST)); }
        if (layer == TLL) TL(53);
        if (layer == 0) {
            uint32_t off[4];
            float cs[4] = {0.f, 0.f, 0.f, 0.f};
#pragma unroll
            for (int q = 0; q < 4; q++) {
                const int g_ = (c * 2 + ((w >> 1) & 1)) * 56 + (q == 3 ? 24 : (w & 1) * 32 + q * 8), col = wg * 320 + g_, nb = col / 80;
                off[q] = g_ < 320 && !(q == 3 && (w & 1)) ? ((nb * 512 + h * 16) * 10 + (col - nb * 80) / 8) * 32 + lane : ~0u;
            }
            const uint32_t ta = sb + O_WO + w * 8192 + (lane & 7) * 64 + (((lane >> 3) ^ (lane >> 1)) & 3) * 16;
#pragma unroll 2
            for (int i = 0; i < 16; i++) {
                uint32_t r[4];
                ldsm4t(r, ta + i * 512);
#pragma unroll
                for (int q = 0; q < 4; q++) {
                    if (off[q] != ~0u) ((uint32_t*)g_wot)[off[q] + i * 320] = r[q];
                    cs[q] += fabsf(bf_lo(r[q])) + fabsf(bf_hi(r[q]));
                }
            }
            float cm = 0.f;
#pragma unroll
            for (int q = 0; q < 4; q++) {
                cs[q] += __shfl_xor_sync(~0u, cs[q], 1); cs[q] += __shfl_xor_sync(~0u, cs[q], 2);
                cm = fmaxf(cm, cs[q]);
            }
            const uint32_t n1 = __reduce_max_sync(~0u, __float_as_uint(cm));
            if (lane == 0) g_co[h * 32 + c * 8 + w] = __uint_as_float(n1);
        }
        bar_sync(9, 256);
        if (tid == 0) red_release(g_flag + F_W + layer * 128);
        bar_sync(4, 288);
        asm volatile("barrier.cluster.arrive.relaxed.aligned;" ::: "memory");
    }
    const uint32_t idn = (lane >> 3) == (lane & 3) ? ((lane & 4) ? 0x3c000000u : 0x3c00u) : 0u;
    float invM = g_invM0;
    char* redp = red_base() + (size_t)layer * 32 * 32768 + w * 2048 + (lane >> 4) * 1024 + ((lane >> 3) & 1) * 256 + (lane & 7) * 16;
    const uint32_t ro2 = uni((w >> 1) * 4096 + 128), rown = uni(c == 2 ? ro2 : c * 16384);
    const uint32_t L16 = lane * 16, L8 = lane * 8, L4 = lane * 4;
    const uint32_t xch0 = uni(sb + O_XCH + t0 * 1024), xch1 = uni(sb + O_XCH + t1 * 1024);
    const uint32_t qo0 = uni(sb + O_QKP + (w & 3) * 1024 + (wg ? 768 : 0)), qp0 = uni(qo0 + (wg ? 128 : 256));
    const uint32_t qo1 = uni(sb + O_QKP + (w & 3) * 1024 + (wg ? 128 : 512)), qp1 = uni(qo1 + (wg ? 256 : 128));
    const uint32_t vo1 = uni(qo1 + (wg ? -128 : 256)), vp1 = uni(qp1 + (wg ? -128 : 256));
    const uint32_t msr = uni(sb + O_MS + wg * 5376);
    const uint32_t msw = uni(msr + ((w >> 1) & 1) * 896 + (w & 1) * 512), msh = uni(msr + ((w >> 1) & 1) * 896 + 384 + (w & 1) * 2);
    const uint32_t sco = uni(sb + O_SC + c * 768 + (w & 3) * 256);
    const uint32_t woa = sb + O_WO + w * 8192 + (lane >> 4) * 512 + (lane & 7) * 64 + (((lane >> 3) ^ (lane >> 1)) & 1) * 16 + ((lane >> 2) & 1) * 32;
    const uint32_t w512 = uni(sb + w * 512), w128 = uni(sb + w * 128);
    const bool scw = c < 2 && w >= 4 && w <= 6;
    uint32_t sn = uni(sb + O_STG + (c == 2 ? 8192 : 0) + t1 * 1024);
    uint32_t ka = uni(sb + (w == 6 ? O_QKP + 512 : O_STG + 4096 + (w & 1) * 512));
    uint32_t vs = uni(sb + O_VM + t1 * 256);
    uint32_t va = uni(sb + O_STG + 8192 + w * 2048), vr = uni(sb + O_VM + w * 512);
    const uint32_t sn2 = uni(2 * sn - 16384), ka2 = uni(2 * ka - (w == 6 ? 0 : 16384)), vs2 = uni(2 * vs + 2048), va2 = uni(2 * va - 16384),
                   vr2 = uni(2 * vr + 2048);
    uint32_t xd = uni((uint32_t)mkdesc(sb + O_XS + wg * 20480, 512, 128, 0));
    const uint32_t xd2 = uni(2 * xd + 2560);

    uint32_t wp[2 * NPERM + 1][4];
    sfor<NPERM>([&](auto I) { constexpr int i = I; ldsm4t(wp[2 * i], woa + i * 1024); ldsm4t(wp[2 * i + 1], (woa ^ 32) + i * 1024); });
    auto wo_fetch = [&](uint32_t (&wo)[16][4], auto I) {
        constexpr int i = I;
        if constexpr (i < NPERM) {
#pragma unroll
            for (int q = 0; q < 4; q++) { wo[i][q] = wp[2 * i][q]; wo[8 + i][q] = wp[2 * i + 1][q]; }
        } else { ldsm4t(wo[i], woa + i * 1024); ldsm4t(wo[8 + i], (woa ^ 32) + i * 1024); }
    };
    if (layer == TLL) TL(32);
    float b0[16], b1[16];
    mbar_wait(sb + B_XF, 0);
    if (layer == TLL) TL(33);
    tok_issue<0, NTB>(A0, A1, b0, b1, xd, zero);
    tok_give(b0, L16, xch0);
    tok_issue<NTB, 40>(A0, A1, b0, b1, xd, zero);
    bar_sync(4, 256);
    wg_wait<0>();
    {
        uint32_t e[2][4];
        lds128_u<0>(e[0], L16, xch1); lds128_u<512>(e[1], L16, xch1);
        tok_finish(b1, e, L16, sn, idn);
    }
    sn = sn2 - sn; xd = xd2 - xd;
    bar_sync(5, 288);
    asm volatile("barrier.cluster.wait.aligned;" ::: "memory");
    if (layer == TLL) TL(34);
    mbar_wait(sb + B_XF + 8, 0);
    if (layer == TLL) TL(35);
    tok_issue<0, NTA>(A0, A1, b0, b1, xd, zero);
    uint32_t tr = clock32() - RDELAY;

#pragma unroll 1
    for (int st = 0;; st++) {
        uint4 mv[3];
        asm volatile("{.reg .pred p; .reg .b32 t;\n"
                     "mov.b32 %0,0; mov.b32 %1,0; mov.b32 %2,0; mov.b32 %3,0; mov.b32 %4,0; mov.b32 %5,0; mov.b32 %6,0; mov.b32 %7,0;\n"
                     "mov.b32 %8,0; mov.b32 %9,0; mov.b32 %10,0; mov.b32 %11,0;\n"
                     "T_LOOP: mov.u32 t,%%clock; sub.u32 t,t,%14; setp.ge.u32 p,t,%15;\n"
                     "@p ld.relaxed.gpu.global.v4.u32 {%0,%1,%2,%3},[%12]; @p ld.relaxed.gpu.global.v4.u32 {%4,%5,%6,%7},[%12+16384];\n"
                     "@p ld.relaxed.gpu.global.v4.u32 {%8,%9,%10,%11},[%13];\n"
                     "@!p bra T_LOOP;}"
                     : "=r"(mv[0].x), "=r"(mv[0].y), "=r"(mv[0].z), "=r"(mv[0].w), "=r"(mv[1].x), "=r"(mv[1].y), "=r"(mv[1].z), "=r"(mv[1].w),
                       "=r"(mv[2].x), "=r"(mv[2].y), "=r"(mv[2].z), "=r"(mv[2].w)
                     : "l"(redp), "l"(redp + ro2), "r"(tr), "n"(RDELAY) : "memory");
        STAMP(10);
        tok_issue<NTA, NTB>(A0, A1, b0, b1, xd, zero);
        tok_give(b0, L16, xch0);
        tok_issue<NTB, 40>(A0, A1, b0, b1, xd, zero);
        xd = xd2 - xd;
        STAMP(9);
        if (zero >> 30) break;
        asm volatile("{.reg .pred p; .reg .b32 a,h,t,n; .reg .b16 l,u; .reg .b64 q;\n"
                     "add.u32 a,%12,%13; add.u32 h,%12,%14; mov.u32 n,0;\n"
                     "M_LOOP:\n .pragma \"nounroll\";\n"
                     "st.shared.b32 [a],%0; st.shared.b32 [a+128],%1; st.shared.b32 [a+256],%2; mov.b32 {l,u},%3; st.shared.b16 [h],l;\n"
                     "st.shared.b32 [a+1792],%4; st.shared.b32 [a+1920],%5; st.shared.b32 [a+2048],%6; mov.b32 {l,u},%7; st.shared.b16 [h+1792],l;\n"
                     "st.shared.b32 [a+3584],%8; st.shared.b32 [a+3712],%9; st.shared.b32 [a+3840],%10; mov.b32 {l,u},%11; st.shared.b16 [h+3584],l;\n"
                     "lop3.b32 t,%3,%7,0x50000000,0x7e; lop3.b32 t,t,%11,0x50000000,0xf6; setp.gt.u32 p,t,0xffff;\n"
                     "vote.sync.any.pred p,p,-1; add.u32 n,n,1; setp.lt.and.u32 p,n,%17,p; @!p bra M_DONE;\n"
                     "ld.relaxed.gpu.global.v4.u32 {%0,%1,%2,%3},[%15]; ld.relaxed.gpu.global.v4.u32 {%4,%5,%6,%7},[%15+16384];\n"
                     "cvt.u64.u32 q,%16; add.u64 q,q,%15; ld.relaxed.gpu.global.v4.u32 {%8,%9,%10,%11},[q];\n"
                     "bra M_LOOP;\n"
                     "M_DONE:}"
                     : "+r"(mv[0].x), "+r"(mv[0].y), "+r"(mv[0].z), "+r"(mv[0].w), "+r"(mv[1].x), "+r"(mv[1].y), "+r"(mv[1].z), "+r"(mv[1].w),
                       "+r"(mv[2].x), "+r"(mv[2].y), "+r"(mv[2].z), "+r"(mv[2].w)
                     : "r"(L4), "r"(msw), "r"(msh), "l"(redp), "r"(ro2), "n"(SPIN_LIM) : "memory");
        bar_sync(3, 256);
        STAMP(0);
        uint32_t e[2][4];
        float f1[4];
        {
            uint32_t b[10][4];
            float acc[4][4];
#pragma unroll
            for (int i = 0; i < 4; i++) acc[i][0] = acc[i][1] = acc[i][2] = acc[i][3] = 0.f;
            auto ld = [&](auto I) { constexpr int i = I; ldsm4t_u<i * 512>(b[i], L16, msr); };
            auto mm = [&](auto I) {
                constexpr int i = I;
                mma_f16(acc[0], A0[2 * i], b[i][0], b[i][1]); mma_f16(acc[2], A1[2 * i], b[i][0], b[i][1]);
                mma_f16(acc[1], A0[2 * i + 1], b[i][2], b[i][3]); mma_f16(acc[3], A1[2 * i + 1], b[i][2], b[i][3]);
            };
            ld(IC<0>()); ld(IC<1>()); ld(IC<2>()); ld(IC<3>());
            sts32_u<O_MX>(L4, w128,
                          habsmax(habsmax(habsmax(habsmax(mv[0].x, mv[0].y), habsmax(mv[0].z, mv[1].x)), habsmax(habsmax(mv[1].y, mv[1].z), mv[2].x)),
                                  habsmax(habsmax(mv[2].y, mv[2].z), habsmax(habsmax(mv[0].w, mv[1].w), mv[2].w) & 0xffffu)));
            wg_wait<0>();
            ld(IC<4>()); mm(IC<0>()); ld(IC<5>()); mm(IC<1>()); ld(IC<6>()); mm(IC<2>());
            ld(IC<7>()); mm(IC<3>()); ld(IC<8>()); mm(IC<4>()); ld(IC<9>()); mm(IC<5>());
            lds128_u<0>(e[0], L16, xch1); lds128_u<512>(e[1], L16, xch1);
            mm(IC<6>()); mm(IC<7>()); mm(IC<8>()); mm(IC<9>());
            const uint32_t u0 = pack_bf((acc[0][0] + acc[1][0]) * invM, (acc[0][1] + acc[1][1]) * invM);
            const uint32_t u1 = pack_bf((acc[0][2] + acc[1][2]) * invM, (acc[0][3] + acc[1][3]) * invM);
#pragma unroll
            for (int i = 0; i < 4; i++) f1[i] = (acc[2][i] + acc[3][i]) * invM;
            sts32_u<0>(L4, qo0, u0); sts32_u<0>(L4, qp0, u1); sts32_u<0>(L4, qo1, pack_bf(f1[0], f1[1])); sts32_u<0>(L4, qp1, pack_bf(f1[2], f1[3]));
        }
        STAMP(1);
        bar_sync(1, 320);
        if (__builtin_expect(scw, 1)) {
            float a[4][4];
#pragma unroll
            for (int i = 0; i < 4; i++) a[i][0] = a[i][1] = a[i][2] = a[i][3] = 0.f;
            uint32_t q[4][4], k[4][4];
            sfor<4>([&](auto I) {
                constexpr int i = I;
                ldsm4t_u<O_QKP + i * 1024>(q[i], L16, sb); ldsm4t_u<i * 1024>(k[i], L16, ka);
            });
#pragma unroll
            for (int i = 0; i < 4; i++) {
                mma_bf(a[i & 1], q[i][0], q[i][1], q[i][2], q[i][3], k[i][0], k[i][1]);
                mma_bf(a[2 + (i & 1)], q[i][0], q[i][1], q[i][2], q[i][3], k[i][2], k[i][3]);
            }
            const float mk = w == 6 ? 1.f : 0.f;
            const float x0 = (a[0][0] + a[0][2]) + (a[1][0] + a[1][2]), x1 = (a[0][1] + a[0][3]) + (a[1][1] + a[1][3]);
            const float y0 = (a[2][0] + a[2][2]) + (a[3][0] + a[3][2]), y1 = (a[2][1] + a[2][3]) + (a[3][1] + a[3][3]);
            st_async2_x3(L8, sco, sb + B_S, pack_bf(fmaf(y0, mk, x0) * sl, fmaf(y1, mk, x1) * sl), pack_bf(y0 * sl, y1 * sl));
        }
        if (c == 2) {
            const uint32_t x = lds32_u<0>(L4, vo1), y = lds32_u<0>(L4, vp1);
            st_async2_x3(L8, vs, sb + B_S, pack_bf(f1[0] + bf_lo(x), f1[1] + bf_hi(x)), pack_bf(f1[2] + bf_lo(y), f1[3] + bf_hi(y)));
        }
        STAMP(3);
        if (st == NSEG - 1) break;
        tok_finish(b1, e, L16, sn, idn);
        redp += (st & 1) ? 32768 - 512 : 512;
        if (wg == 0) {
            uint32_t wo[16][4], vx[2][2][4], vm[2][2];
            ldsm4_u<0>(vx[0][0], L16, va); ldsm4_u<512>(vx[0][1], L16, va); ldsm4_u<1024>(vx[1][0], L16, va); ldsm4_u<1536>(vx[1][1], L16, va);
            sfor<NWO0>([&](auto I) { wo_fetch(wo, I); });
            mbar_wait(sb + B_S, st & 1);
            STAMP(4);
            uint32_t s[5];
            {
                uint32_t p[2][5];
                sfor<2>([&](auto R) {
                    constexpr int r = R;
                    lds64_u<O_SC + r * 768>(p[r], L8, sb); lds64_u<O_SC + r * 768 + 256>(p[r] + 2, L8, sb); p[r][4] = lds32_u<O_SC + r * 768 + 512>(L8, sb);
                });
#pragma unroll
                for (int j = 0; j < 5; j++) s[j] = badd(p[0][j], p[1][j]);
            }
            lds64_u<0>(vm[0], L8, vr); lds64_u<256>(vm[1], L8, vr);
            uint32_t mm = bmax(bmax(bmax(s[0], s[1]), bmax(s[2], s[3])), s[4]);
            mm = bmax(bmax(mm, __shfl_xor_sync(~0u, mm, 1)), bmax(__shfl_xor_sync(~0u, mm, 2), __shfl_xor_sync(~0u, mm, 3)));
            const float m = fmaxf(bf_lo(mm), bf_hi(mm));
            float o0[4] = {0.f, 0.f, 0.f, 0.f}, o1[4] = {0.f, 0.f, 0.f, 0.f}, d[10];
#pragma unroll
            for (int j = 0; j < 5; j++) { d[2 * j] = bf_lo(s[j]) - m; d[2 * j + 1] = bf_hi(s[j]) - m; }
#pragma unroll
            for (int j = 0; j < 10; j++) d[(j + 8) % 10] = ex2(d[(j + 8) % 10]);
            float sum = ((d[8] + d[9]) + (d[0] + d[1])) + ((d[2] + d[3]) + (d[4] + d[5])) + (d[6] + d[7]);
            const uint32_t p4 = pack_bf(d[8], d[9]), p0 = pack_bf(d[0], d[1]), p1 = pack_bf(d[2], d[3]), p2 = pack_bf(d[4], d[5]), p3 = pack_bf(d[6], d[7]);
            mma_bf8(o0, vm[0][0], vm[0][1], p4);
            mma_bf8(o1, vm[1][0], vm[1][1], p4);
            mma_bf(o0, vx[0][0][0], vx[0][0][1], vx[0][0][2], vx[0][0][3], p0, p1);
            mma_bf(o1, vx[1][0][0], vx[1][0][1], vx[1][0][2], vx[1][0][3], p0, p1);
            mma_bf(o0, vx[0][1][0], vx[0][1][1], vx[0][1][2], vx[0][1][3], p2, p3);
            mma_bf(o1, vx[1][1][0], vx[1][1][1], vx[1][1][2], vx[1][1][3], p2, p3);
            sum += __shfl_xor_sync(~0u, sum, 1);
            sum += __shfl_xor_sync(~0u, sum, 2);
            sts32_u<O_OS>(L4, w512, pack_bf(o0[0], o0[1])); sts32_u<O_OS + 128>(L4, w512, pack_bf(o0[2], o0[3]));
            sts32_u<O_OS + 256>(L4, w512, pack_bf(o1[0], o1[1])); sts32_u<O_OS + 384>(L4, w512, pack_bf(o1[2], o1[3]));
            sts32_u<O_SUM>(lane & 28, sb, __float_as_uint(sum));
            STAMP(5);
            invM = mem_out<NWO0>(sb, L16, L8, wo, woa, redp + rown, w & 1);
            tr = clock32();
        } else {
            uint32_t wo[16][4];
            sfor<NWO1>([&](auto I) { wo_fetch(wo, I); });
            invM = mem_out<NWO1>(sb, L16, L8, wo, woa, redp + rown, w & 1);
            tr = clock32();
        }
        STAMP(7);
        tok_issue<0, NTA>(A0, A1, b0, b1, xd, zero);
        sn = sn2 - sn; ka = ka2 - ka; vs = vs2 - vs; va = va2 - va; vr = vr2 - vr;
        STAMP(8);
    }
    if (layer == TLL) TL(40);
    bar_arrive(8, 320);
    tid = read_tid(); lane = tid & 31;
    float acc[40];
    const int nc = c == 2 ? 10 : 11;
#pragma unroll 1
    for (int k = 0; k < nc; k++) {
        mbar_wait(sb + T_FB + (k % 7) * 8, k >= 7);
        mbar_wait(sb + T_FA + (k & 3) * 8, (k >> 2) & 1);
        if (layer == TLL && k == 0) TL(41);
        const uint64_t da = mkdesc(sb + O_MS + (k & 3) * 16384 + wg * 8192, 1024, 128, 0), db = mkdesc(sb + tail_b(k) + wg * 10240, 1280, 128, 0);
        wg_fence();
#pragma unroll
        for (int q = 0; q < 4; q++) wg_n80_ss(acc, da + q * 128, db + q * 160, k | q);
        wg_commit();
        if (k > 0) {
            wg_wait<1>();
            if (lane == 0) { mbar_arrive(sb + T_EA + ((k - 1) & 3) * 8); if (k <= 4) mbar_arrive(sb + T_EB + (k - 1) * 8); }
        }
    }
    if (layer == TLL) TL(52);
    const int mb = 28 + (h >> 3), nj = c == 2 ? 1 : 2;
    uint32_t rv[2][2];
    const size_t go = ((size_t)(mb * 64 + (w & 3) * 16 + (lane >> 2)) * 640 + (h & 7) * 80 + (wg * 5 + c * 2) * 8 + (lane & 3) * 2) >> 1;
#pragma unroll
    for (int u = 0; u < 4; u++) rv[u >> 1][u & 1] = (u >> 1) < nj ? __ldcg((const uint32_t*)res + go + (u >> 1) * 4 + (u & 1) * 2560) : 0u;
    wg_wait<0>();
    asm volatile("barrier.cluster.arrive.relaxed.aligned; barrier.cluster.wait.aligned;" ::: "memory");
    const uint32_t ra = sb + O_XS + tid * 16, rb = sb + O_MS + tid * 16;
#pragma unroll
    for (int j = 0; j < 5; j++) {
        const float* q = acc + 4 * j;
        sts128(rb + j * 4096, __float_as_uint(wg ? q[0] : q[20]), __float_as_uint(wg ? q[1] : q[21]), __float_as_uint(wg ? q[2] : q[22]), __float_as_uint(wg ? q[3] : q[23]));
    }
    bar_sync(4, 256);
#pragma unroll
    for (int j = 0; j < 5; j++) {
        const float* q = acc + 4 * j;
        uint32_t p[4];
        lds128(p, sb + O_MS + (tid ^ 128) * 16 + j * 4096);
        asm volatile("st.async.shared::cluster.mbarrier::complete_tx::bytes.v4.f32 [%0],{%1,%2,%3,%4},[%5];" ::"r"(mapa(ra + c * 8192 + (j & 1) * 4096, j >> 1)),
                     "f"((wg ? q[20] : q[0]) + __uint_as_float(p[0])), "f"((wg ? q[21] : q[1]) + __uint_as_float(p[1])),
                     "f"((wg ? q[22] : q[2]) + __uint_as_float(p[2])), "f"((wg ? q[23] : q[3]) + __uint_as_float(p[3])), "r"(mapa(sb + T_RED, j >> 1)) : "memory");
    }
    mbar_wait(sb + T_RED, 0);
#pragma unroll 1
    for (int u = 0; u < nj; u++) {
        uint32_t p[3][4];
#pragma unroll
        for (int q = 0; q < 3; q++) lds128(p[q], ra + q * 8192 + u * 4096);
        float y[4];
#pragma unroll
        for (int i = 0; i < 4; i++) y[i] = __uint_as_float(p[0][i]) + __uint_as_float(p[1][i]) + __uint_as_float(p[2][i]);
        ((uint32_t*)out)[go + u * 4] = bfma(pack_bf(y[0], y[1]), 0x3f803f80u, u ? rv[1][0] : rv[0][0]);
        ((uint32_t*)out)[go + u * 4 + 2560] = bfma(pack_bf(y[2], y[3]), 0x3f803f80u, u ? rv[1][1] : rv[0][1]);
    }
    TL(layer == 0 ? 15 : 29);
    asm volatile("barrier.cluster.arrive.relaxed.aligned; barrier.cluster.wait.aligned;" ::: "memory");
}

__device__ __forceinline__ void tail_load_b(const uint32_t sb, const int h, const int c, const int k) {
    mbar_expect(sb + T_FB + (k % 7) * 8, 20480);
    bulk_g2s(sb + tail_b(k), (const char*)g_wot + (size_t)((h & 7) * GNC + c * 11 + k) * 20480, 20480, sb + T_FB + (k % 7) * 8);
}
__device__ __forceinline__ void chain_aux(const uint32_t sb, const int c, const int h, const int layer, const int nact) {
    const int tid = read_tid(), w = __shfl_sync(~0u, tid >> 5, 0), lane = tid & 31;
    if (w == 8) {
        mbar_init(sb + O_BAR + lane * 8, lane == 3 || (lane >= 16 && lane < 20) || (lane >= 27 && lane < 31) ? 8 : 1);
        asm volatile("fence.mbarrier_init.release.cluster;" ::: "memory");
        fence_async_smem();
        __syncwarp();
    }
    {
        uint4* z = (uint4*)red_base() + layer * 65536;
#pragma unroll 1
        for (int i = blockIdx.x * 128 + tid - 256; i < 65536; i += 96 * 128)
            if (i >= 2048 || (i & 32)) z[i] = make_uint4(0, 0, 0, 0);
    }
    if (w == 8 && lane == 0) {
        mbar_expect(sb + B_S, S_TX);
        mbar_expect(sb + B_W, 192);
        mbar_expect(sb + T_RED, (c == 2 ? 1 : 2) * 3 * 4096);
        if (layer == 1) prefetch_l2(red_base() + 32 * 32768 + blockIdx.x * 1024, 1024);
        if (layer == 0) wait_flag<400>(g_ready, 128);
    }
    __syncwarp();
    cluster_sync_full();
    asm volatile("barrier.cluster.arrive.relaxed.aligned;" ::: "memory");
    pdl_wait();
    Flag* flag = g_flag + layer * NSEG * 32 + h;
    const Flag* xflag = g_flag + F_X + layer * 128;
    char* const it0 = g_item + (size_t)h * 32768;
    if (w == 8) {
#pragma unroll 1
        for (int n = 0; n < 3; n++) {
            wait_flag<100>(xflag + (n >> 1), 4);
            fence_async_glb();
            if (n == 0) { bar_sync(4, 288); fence_async_smem(); }
            if (lane == 0 && n < 2) {
                mbar_expect(sb + B_XF + n * 8, 40960);
                bulk_g2s(sb + O_XS + n * 40960, (const char*)g_xn + n * 40960, 40960, sb + B_XF + n * 8);
            }
            __syncwarp();
        }
#pragma unroll 1
        for (int n = 0; n < NSEG; n++) {
            const int np = n & 1;
            if (n == 0) { wait_flag<100>(g_flag + F_W + layer * 128, 96); bar_sync(5, 288); } else bar_sync(2, 352);
            if (n == 1) TL(12 + layer * 14);
            if (n == 63) TL(13 + layer * 14);
            if (lane == 0 && (n == NSEG - 1 || (XEARLY & 8))) mbar_arrive(sb + B_STG + np * 8);
            if (lane == 0 && n < NSEG - 1) {
                const uint32_t vs = sb + O_STG + 8192 - np * 16384, vb = sb + B_VX + np * 8;
                if (c == 2) {
                    fence_async_smem();
                    bulk_s2s(mapa(vs, 0), vs, 8192, mapa(vb, 0));
                    bulk_s2s(mapa(vs, 1), vs, 8192, mapa(vb, 1));
                } else mbar_expect(vb, 8192);
                if (n == 0) { mbar_expect(sb + B_XF, 40960); bulk_g2s(sb + O_XS, (const char*)g_xn + 2 * 40960, 40960, sb + B_XF); }
                if (n == h * 3 + c && !np && n + 6 < NSEG) prefetch_l2(red_base() + (size_t)(layer * 32 + (n >> 1) + 3) * 32768, 32768);
            }
            __syncwarp();
        }
    } else if (w == 11) {
        float cvo;
        {
            auto max8 = [&](const float* p) {
                const float4 u = ((const float4*)p)[0], v = ((const float4*)p)[1];
                return fmaxf(fmaxf(fmaxf(u.x, u.y), fmaxf(u.z, u.w)), fmaxf(fmaxf(v.x, v.y), fmaxf(v.z, v.w)));
            };
            wait_flag<300>(g_flag + F_W + layer * 128, 96);
            const float* pc = g_co + lane * 32;
            float a = 640.f * __ldcg(g_wmx + lane * 3 + 2), o = fmaxf(fmaxf(max8(pc), max8(pc + 8)), max8(pc + 16));
#pragma unroll 1
            for (int s = 16; s; s >>= 1) { a = fmaxf(a, __shfl_xor_sync(~0u, a, s)); o += __shfl_xor_sync(~0u, o, s); }
            cvo = a * o * 2.f;
        }
        float invM = g_invM0;
        float iv;
        weight_scale(h, 2, &iv);
        const uint32_t L16 = sb + lane * 16 + O_MX;
#pragma unroll 1
        for (int st = 0; st < NSEG; st++) {
            bar_sync(1, 320);
            if (st == NSEG - 1) break;
            if (!(XEARLY & 10) && lane == 0) mbar_arrive(sb + B_STG + (st & 1) * 8);
            uint32_t u[2][4];
            lds128(u[0], L16); lds128(u[1], L16 + 512);
            uint32_t mx = habsmax(habsmax(habsmax(u[0][0], u[0][1]), habsmax(u[0][2], u[0][3])), habsmax(habsmax(u[1][0], u[1][1]), habsmax(u[1][2], u[1][3])));
            mx = __reduce_max_sync(~0u, max(mx & 0x7fffu, (mx >> 16) & 0x7fffu));
            const float bound = fmaxf(__half2float(__ushort_as_half((unsigned short)mx)) * invM, 25.5f) * cvo;
            const float sc = pow2_scale(bound, 15, &invM);
            sts64(sb + O_SCL, __float_as_uint(sc * iv), __float_as_uint(invM));
            bar_arrive(2, 352);
        }
    } else if (w == 10) {
        if (lane == 0) {
#pragma unroll 1
            for (int n = 0; n < NSEG; n++) {
                mbar_sleep(sb + B_STG + (n & 1) * 8, (n >> 1) & 1);
                fence_async_smem();
                const uint32_t stg = sb + O_STG - (n & 1) * 16384;
                char* it = it0 + (size_t)(n % RING) * 32 * 32768;
                bulk_s2g(it + c * 8192, stg + (c == 2 ? 8192 : 0), 8192);
                bulk_commit();
                if (n + 1 >= RING && n + 1 < NSEG) wait_flag(flag - (RING - 1) * 32, REL1 ? 4 : 7);
                bulk_wait0();
                if (REL1) {
                    fence_async_glb();
                    mbar_arrive(sb + B_FREE + (n & 1) * 8);
                } else {
                    mbar_arrive(sb + B_FREE + (n & 1) * 8);
                    fence_async_glb();
                    if (RELAX & 1) red_relaxed(flag); else red_release(flag);
                }
                flag += 32;
            }
        }
    } else {
        const uint32_t L16 = sb + lane * 16;
        bool allx = false;
#pragma unroll 1
        for (int st = 0; st < NSEG; st++) {
            const int par = st & 1;
            char* it = it0 + (size_t)(st % RING) * 32 * 32768 + lane * 16;
            if (lane == 0 && !allx && st + 3 < NSEG) {
                allx = ld_acquire(xflag + 64) >= nact;
                if (!allx) wait_flag(xflag + ((st + 3) >> 1), 4);
                fence_async_glb();
            }
            __syncwarp();
            auto refill = [&] {
                if (lane == 0 && st + 3 < NSEG) {
                    mbar_expect(sb + B_XF + (par ^ 1) * 8, 40960);
                    bulk_g2s_last(sb + O_XS + (par ^ 1) * 40960, (const char*)g_xn + (size_t)(st + 3) * 40960, 40960, sb + B_XF + (par ^ 1) * 8);
                } else if (lane == 0 && st < NSEG - 1) {
                    tail_load_b(sb, h, c, (par ^ 1) * 2); tail_load_b(sb, h, c, (par ^ 1) * 2 + 1);
                }
                __syncwarp();
            };
            if (st < NSEG - 1 && c < 2) mbar_sleep(sb + B_VX + par * 8, (st >> 1) & 1);
            if (st < NSEG - 2) mbar_sleep(sb + B_XF + par * 8, ((st >> 1) + 1) & 1);
            bar_sync(1, 320);
            if (!(XEARLY & 1)) refill();
            char* const itb = it - lane * 16;
            if (lane == 0 && c < 2) {
                fence_async_smem();
#pragma unroll 1
                for (int i = 0; i < 4; i++) bulk_s2g(itb + 24576 + (c * 4 + i) * 512, sb + O_QKP + i * 1024 + 512, 512);
                bulk_commit();
                asm volatile("cp.async.bulk.wait_group.read 0;" ::: "memory");
            }
            __syncwarp();
            if (st < NSEG - 1) bar_arrive(2, 352);
            mbar_sleep(sb + B_S, par);
            __syncwarp();
            if (lane == 0) {
                if (st < NSEG - 1) mbar_expect(sb + B_S, S_TX);
                if (c == 2) { fence_async_smem(); bulk_s2g(itb + 28672, sb + O_VM + par * 2048, 2048); bulk_commit(); }
                if (st == NSEG - 1) asm volatile("cp.async.bulk.wait_group.read 0;" ::: "memory");
            }
            __syncwarp();
            if (st == NSEG - 1) bar_arrive(8, 320);
            if (lane == 0) { bulk_wait0(); fence_async_glb(); red_relaxed(flag); }
            __syncwarp();
            if (!REL1) mbar_sleep(sb + B_FREE + par * 8, (st >> 1) & 1);
            flag += 32;
            continue;
#pragma unroll 1
            for (int i = 0; i < (c < 2 ? 4 : 0); i += 2) {
                uint32_t v[8];
                lds128(v, L16 + O_QKP + i * 1024 + 512); lds128(v + 4, L16 + O_QKP + i * 1024 + 512 + 1024);
                *(uint4*)(it + 24576 + (c * 4 + i) * 512) = make_uint4(v[0], v[1], v[2], v[3]); *(uint4*)(it + 24576 + (c * 4 + i) * 512 + 512) = make_uint4(v[4], v[5], v[6], v[7]);
            }
            if (st < NSEG - 1) bar_arrive(2, 352);
            mbar_sleep(sb + B_S, par);
            __syncwarp();
            if (lane == 0 && st < NSEG - 1) mbar_expect(sb + B_S, S_TX);
#pragma unroll 1
            for (int i = 0; i < (c < 2 ? 0 : 4); i += 2) {
                uint32_t v[8];
                lds128(v, L16 + O_VM + par * 2048 + i * 512); lds128(v + 4, L16 + O_VM + par * 2048 + i * 512 + 512);
                *(uint4*)(it + 28672 + i * 512) = make_uint4(v[0], v[1], v[2], v[3]); *(uint4*)(it + 28672 + i * 512 + 512) = make_uint4(v[4], v[5], v[6], v[7]);
            }
            if (st == NSEG - 1) bar_arrive(8, 320);
            __syncwarp();
            if (REL1) mbar_sleep(sb + B_FREE + par * 8, (st >> 1) & 1);
            if (lane == 0) { if (RELAX & 2) red_relaxed(flag); else red_release(flag); }
            if (!REL1) mbar_sleep(sb + B_FREE + par * 8, (st >> 1) & 1);
            flag += 32;
        }
    }
    __syncwarp();
    const int nc = c == 2 ? 10 : 11;
    if (w == 10) {
        bar_sync(8, 320);
        if (lane == 0) {
            if (layer == 1 && blockIdx.x == 0) g_ready[0].v = 0;
            fence_async_smem();
            __nanosleep(TDELAY);
            wait_flag(xflag + 64, nact);
            wait_flag<50>(g_flag + F_O + layer * 32 + 28 + (h >> 3), 64);
            fence_async_glb();
#pragma unroll 1
            for (int k = 0; k < nc; k++) {
                if (k >= 4) mbar_sleep(sb + T_EA + (k & 3) * 8, ((k >> 2) - 1) & 1);
                mbar_expect(sb + T_FA + (k & 3) * 8, 16384);
                bulk_g2s_last(sb + O_MS + (k & 3) * 16384, (const char*)g_O + (size_t)((28 + (h >> 3)) * GNC + c * 11 + k) * 16384, 16384, sb + T_FA + (k & 3) * 8);
            }
        }
    } else if (w == 9 && lane == 0) {
        __nanosleep(TDELAY);
#pragma unroll 1
        for (int k = 4; k < nc; k++) {
            if (k >= 7) mbar_sleep(sb + T_EB + (k - 7) * 8, 0);
            tail_load_b(sb, h, c, k);
        }
    }
    __syncwarp();
    asm volatile("barrier.cluster.wait.aligned;" ::: "memory");
    asm volatile("barrier.cluster.arrive.relaxed.aligned; barrier.cluster.wait.aligned;" ::: "memory");
    asm volatile("barrier.cluster.arrive.relaxed.aligned; barrier.cluster.wait.aligned;" ::: "memory");
}

constexpr int RI_A = 0, RI_TAB = 81920, RI_STG = RI_TAB + 82 * 768;
constexpr int RI_RES = RI_STG + 25600, RI_ST = RI_RES + 2 * 64 * 336;
constexpr int HB_A = G_BAR + 64, HB_AFREE = HB_A + 32, HB_LN = HB_A + 40, HB_FULL = HB_A + 64, HB_DONE = HB_FULL + 48, HB_FREE = HB_DONE + 48;
constexpr int HP_SMEM = HB_FREE + 48;
static_assert(G_BAR >= RI_ST + 2048, "helper shared-memory map");
#define IDL 350
#define ITEM_NS 60
#define HORD 1
#define PFW_AT 19
#define PFW_NS 400
__device__ __forceinline__ void helper_aux(const uint32_t sb, const int j, const int nh, const int na, const int nbh, const int layer, const bf16* Wq,
                                           const bf16* Wk, const bf16* Wv, const bf16* Wo) {
    const int w = threadIdx.x >> 5, lane = threadIdx.x & 31, p = w - 8;
    if (lane == 0 && j < (nh & ~3)) {
        int n = 0;
        for (int a = j >> 2; a < 32; a += nh >> 2, n++) {
            if (n == 0) continue;
            mbar_wait(sb + HB_AFREE, (n - 1) & 1);
            mbar_expect(sb + HB_A + p * 8, 20480);
            bulk_g2s_last(sb + RI_A + p * 20480, (const char*)g_YT + (size_t)a * 81920 + p * 20480, 20480, sb + HB_A + p * 8);
            if (p == 0) { mbar_wait(sb + HB_LN, (n - 1) & 1); red_release(g_flag + F_X + layer * 128 + a - (nh >> 2)); }
        }
        if (p == 0) { mbar_wait(sb + HB_LN, (n - 1) & 1); red_release(g_flag + F_X + layer * 128 + (j >> 2) + (n - 1) * (nh >> 2)); }
    }
    __syncwarp();
    if (layer == 0 && w == 8 && lane == 0) wait_flag<400>(g_flag + F_W, 96);
    __syncwarp();
    bar_sync(3, 384);
    if (p == 3 && lane == 0 && j < (nh & ~3)) red_release(g_flag + F_X + layer * 128 + 64);
    fence_async_smem();
    Flag* oflag = g_flag + F_O + layer * 32;
    if (j < na) {
        int sl = p & 1, ph = 1;
        for (int idx = j + (p & 1) * na; idx < NSEG * 32 && p >= 2 && lane == 0; idx += 2 * na) {
            mbar_wait(sb + HB_DONE + sl * 8, ph ^ 1);
            mbar_arrive(sb + HB_FREE + sl * 8);
            red_release(oflag + (idx >> 6));
            atomicAdd(&g_flag[layer * NSEG * 32 + idx].v, 1u);
            sl += 2;
            if (sl >= 6) { sl -= 6; ph ^= 1; }
        }
        for (int idx = j + p * na; idx < NSEG * 32 && p < 2 && lane == 0; idx += 2 * na) {
            mbar_wait(sb + HB_FREE + sl * 8, ph);
            wait_flag<ITEM_NS>(g_flag + layer * NSEG * 32 + idx, REL1 ? 3 : 6);
            fence_async_glb();
            if (idx < (NSEG - 2) * 32) __nanosleep(IDL);
            mbar_expect(sb + HB_FULL + sl * 8, 30720);
            bulk_g2s(sb + sl * 30720, g_item + (size_t)(idx % (RING * 32)) * 32768, 30720, sb + HB_FULL + sl * 8);
            sl += 2;
            if (sl >= 6) { sl -= 6; ph ^= 1; }
        }
    } else if (lane == 0 && p == 3) {
        if (layer == 0) {
            wait_flag<1000>(oflag + PFW_AT, 64);
            const int np = nh - na;
#pragma unroll 1
            for (int i = j - na; i < 1280; i += np) {
                const bf16* W = i < 320 ? Wq : i < 640 ? Wk : i < 960 ? Wv : Wo;
                prefetch_l2((const char*)W + (size_t)(i % 320) * 16384, 16384);
                __nanosleep(PFW_NS);
            }
#pragma unroll 1
            for (int i = j - na; i < 205; i += np) {
                const char* p_ = i < 160 ? (const char*)g_Wf + i * 16384 : i < 165 ? (const char*)g_stat + (i - 144) * 16384
                               : i < 167 ? (const char*)g_ctab + (i - 165) * 8192 : (const char*)(g_flag + NFLAG) - (i - 166) * 16384;
                prefetch_l2(p_, 16384);
                __nanosleep(PFW_NS);
            }
        }
    } else if (lane == 0) {
        if (p == 2) wait_flag<500>(g_flag + F_X + layer * 128 + 64, nh & ~3);
        int c0 = 0;
        for (int mb = (j - na) >> 3; mb < nbh; mb += (nh - na) >> 3, c0 += GNC) {
            if (p < 2) wait_flag<300>(oflag + 2 * mb + p, 64);
            fence_async_glb();
            oproj_load(sb, p, mb, (j - na) & 7, c0, nh - na < 24 ? 0 : mb == nbh - 1 ? GPACE2 : GPACE);
        }
    }
}
__device__ __forceinline__ void helper_mma(char* sm, const int jh, const int nh, const int na, const int nbh, const int layer, const bf16* res, bf16* x,
                                           bf16* out) {
    const uint32_t sb = smem_u32(sm);
    const int tid = threadIdx.x, w = tid >> 5, lane = tid & 31, g = lane >> 2, t = lane & 3;
    const bool act = jh < (nh & ~3);
    const int j4 = jh & 3;
    const int fr = tid & 63, rg = w >> 1;
    auto chunk0 = [&](int u) { return u == 0 ? 5 * j4 : u == 1 ? 75 - 5 * j4 : u == 2 ? 40 + 5 * j4 : 35 - 5 * j4; };
    const int gr = tid / 20, gq_ = tid - gr * 20, go = gr * 80 + chunk0(gq_ / 5) + gq_ % 5;
    const uint32_t gs = sb + RI_RES + gr * 336 + gq_ * 16;
    auto residual = [&](int a, int n) {
#pragma unroll 1
        for (int r = 0; r < 64 - gr && tid < 240 && a < 32; r += 12) cp_async16(gs + (n & 1) * 21504 + r * 336, (const uint4*)res + (a * 64 + r) * 80 + go);
        cp_commit();
    };
    if (act) {
        if (tid < 240) {
            const int k0 = tid / 48, n = tid - k0 * 48;
            const float d = (float)(40 * j4 + n), amp = 2.f * 0.03952847075210474f;
#pragma unroll 4
            for (int u = 0; u < 16; u++)
                *(uint4*)(sm + RI_TAB + (tid + u * 240) * 16) = cos_row8(fmaf((float)((k0 + (u & 3) * 5) * 16 + ((u >> 2) & 1)), d, (float)((u & 8) * 20)), 2.f * d, amp);
            if (tid < 96) *(uint4*)(sm + RI_TAB + (3840 + tid) * 16) = make_uint4(k0 == 0 ? pack_h((n & 1) ? -amp : amp, 0.f) : 0u, 0, 0, 0);
        }
        fence_async_smem();
        residual(jh >> 2, 0);
    }
    bar_sync(1, 384);
    if (layer == TLL) TL(36);
    if (act) {
        const float4 wm = ((const float4*)g_wmax)[lane];
        const int wg = w >> 2;
        int n = 0;
#pragma unroll 1
        for (int a = jh >> 2; a < 32; a += nh >> 2, n++) {
            float acc[2][24];
            uint64_t da = mkdesc(sb + RI_A + wg * 40960, 1024, 1024, 1), db = mkdesc(sb + RI_TAB + wg * 30720, 768, 128, 0);
#pragma unroll
            for (int gq = 0; gq < 2; gq++) {
                mbar_wait(sb + HB_A + (wg * 2 + gq) * 8, n & 1);
                if (layer == TLL && n == TLN && gq == 0) TL(45);
                wg_fence();
#pragma unroll 5
                for (int k = 0; k < 10; k++) { wg_n48_ss_ta(acc[gq], da, db, k); da += 128; db += 96; }
                wg_commit();
            }
            if (wg == 0) {
                mbar_wait(sb + HB_A + 16, n & 1);
                wg_fence();
                wg_n48_ss_ta(acc[0], da, db + 20 * 96, 1);
                wg_commit();
            }
            float inv;
            pow2_scale(__uint_as_float(__reduce_max_sync(~0u, __float_as_uint(fmaxf(fmaxf(wm.x, wm.y), fmaxf(wm.z, wm.w))))), 0, &inv);
            const uint32_t ysc = pack_bf(inv, inv);
            wg_wait<0>();
            if (layer == TLL && n == TLN) TL(46);
            if (lane == 0) mbar_arrive(sb + HB_AFREE);
            const uint32_t ad = sb + RI_STG + ((w & 3) * 16 + (lane & 15)) * 400 + (lane >> 4) * 96 + wg * 192;
#pragma unroll
            for (int q = 0; q < 6; q++) {
                const float *e = acc[0] + q * 4, *o = acc[1] + q * 4;
                stsm4(ad + q * 16, pack_h(e[0] + o[0], e[1] + o[1]), pack_h(e[2] + o[2], e[3] + o[3]), pack_h(e[0] - o[0], e[1] - o[1]), pack_h(e[2] - o[2], e[3] - o[3]));
            }
            cp_wait<0>();
            bar_sync(4, 256);
            const uint32_t xa = sb + RI_RES + (n & 1) * 21504 + fr * 336 + rg * 80, sg = (rg & 1) ? 0xbc00bc00u : 0x3c003c00u;
            float sum = 0.f, sq = 0.f;
            uint32_t ya = sb + RI_STG + fr * 400 + (rg >> 1) * 96 + ((rg & 1) ? 64 : 0), carry;
            asm("fma.rn.f16x2 %0,%1,%2,%3;" : "=r"(carry) : "r"(lds32(ya + 208)), "r"(sg), "r"(lds32(ya + 16)));
#pragma unroll 1
            for (int ch = 0; ch < 5; ch++, ya += (rg & 1) ? -16 : 16) {
                uint32_t y[4], z[4], xr[4];
                lds128(y, ya); lds128(z, ya + 192); lds128(xr, xa + ch * 16);
#pragma unroll
                for (int q = 0; q < 4; q++) asm("fma.rn.f16x2 %0,%1,%2,%0;" : "+r"(y[q]) : "r"(z[q]), "r"(sg));
                if (rg & 1) {
                    const uint32_t y0 = y[0], y1 = y[1];
                    y[0] = __byte_perm(carry, y[3], 0x7610); y[1] = __byte_perm(y[3], y[2], 0x7610);
                    y[3] = __byte_perm(y1, y0, 0x7610); y[2] = __byte_perm(y[2], y1, 0x7610);
                    carry = y0;
                }
#pragma unroll
                for (int q = 0; q < 4; q++) {
                    const float2 yf = __half22float2(*(const __half2*)&y[q]);
                    xr[q] = bfma(pack_bf(yf.x, yf.y), ysc, xr[q]);
                    const float e = bf_lo(xr[q]), f = bf_hi(xr[q]);
                    sum += e + f; sq = fmaf(e, e, fmaf(f, f, sq));
                }
                sts128(xa + ch * 16, xr[0], xr[1], xr[2], xr[3]);
            }
            uint2* stat = g_stat + (size_t)(layer * 32 + a) * 1024 + rg * 64 + fr;
            asm volatile("st.relaxed.gpu.global.v2.u32 [%0],{%1,%2};" ::"l"(stat + j4 * 256), "r"(__float_as_uint(sum)), "r"(__float_as_uint(sq) | 0x80000000u) : "memory");
            if (layer == TLL && n == TLN) TL(47);
            uint32_t s0[3], s1[3];
            int lim = 0;
            do {
#pragma unroll
                for (int q = 0; q < 3; q++)
                    asm volatile("ld.relaxed.gpu.global.v2.u32 {%0,%1},[%2];" : "=r"(s0[q]), "=r"(s1[q]) : "l"(stat + ((j4 + 1 + q) & 3) * 256) : "memory");
            } while (__any_sync(~0u, (int)(s1[0] & s1[1] & s1[2]) >= 0) && ++lim < SPIN_LIM);
#pragma unroll
            for (int q = 0; q < 3; q++) { sum += __uint_as_float(s0[q]); sq -= __uint_as_float(s1[q]); }
            sts64(sb + RI_ST + tid * 8, __float_as_uint(sum), __float_as_uint(sq));
            bar_sync(4, 256);
            if (layer == TLL && n == TLN) TL(48);
#pragma unroll
            for (int q = 1; q < 4; q++) {
                uint32_t st2[2];
                lds64(st2, sb + RI_ST + ((tid + q * 64) & 255) * 8);
                sum += __uint_as_float(st2[0]); sq += __uint_as_float(st2[1]);
            }
            const float mean = sum * (1.f / 640.f), r = rsqrtf(fmaxf(fmaf(-mean, mean, sq * (1.f / 640.f)), 0.f) + 1e-5f), off = -mean * r;
            uint4* dst = (uint4*)g_xn + ((size_t)(2 * a + (w & 1)) * 80 + chunk0(rg)) * 32 + lane;
#pragma unroll
            for (int i = 0; i < 5; i++) {
                uint32_t u[4];
                lds128(u, xa + i * 16);
                dst[i * 32] = make_uint4(pack_h(fmaf(bf_lo(u[0]), r, off), fmaf(bf_hi(u[0]), r, off)), pack_h(fmaf(bf_lo(u[1]), r, off), fmaf(bf_hi(u[1]), r, off)),
                                         pack_h(fmaf(bf_lo(u[2]), r, off), fmaf(bf_hi(u[2]), r, off)), pack_h(fmaf(bf_lo(u[3]), r, off), fmaf(bf_hi(u[3]), r, off)));
            }
            __syncwarp();
            if (lane == 0) mbar_arrive(sb + HB_LN);
            if (layer == TLL) TL(37);
            if (layer == TLL && n == TLN) TL(44);
            residual(a + (nh >> 2), n + 1);
#pragma unroll 2
            for (int rr = 0; rr < 64 - gr && tid < 240; rr += 12) {
                uint32_t v[4];
                lds128(v, gs + (n & 1) * 21504 + rr * 336);
                ((uint4*)x)[(a * 64 + rr) * 80 + go] = make_uint4(v[0], v[1], v[2], v[3]);
            }
        }
    }
    bar_sync(3, 384);
    if (layer == TLL) TL(38);
    if (jh >= na) {
        int c0 = 0;
#pragma unroll 1
        for (int mb = (jh - na) >> 3; mb < nbh; mb += (nh - na) >> 3, c0 += GNC) oproj_mma(sb, mb, (jh - na) & 7, c0, x, out);
        if (layer == TLL) TL(42);
        return;
    }
    const int p = w >> 1, mi = w & 1;
    int slot = p, ph = 0;
    for (int idx = jh + p * na; idx < NSEG * 32; idx += 4 * na) {
        const uint32_t it = sb + slot * 30720 + lane * 16;
        float iq, ik, iv;
        weight_scale(idx & 31, 0, &iq); weight_scale(idx & 31, 1, &ik); weight_scale(idx & 31, 2, &iv);
        bar_sync(6 + p, 64);
        mbar_wait(sb + HB_DONE + slot * 8, ph ^ 1);
        mbar_wait(sb + HB_FULL + slot * 8, ph);
        if (layer == TLL && idx >= 63 * 32) TL(55);
        float s[6][4];
#pragma unroll
        for (int i = 0; i < 6; i++) s[i][0] = s[i][1] = s[i][2] = s[i][3] = 0.f;
#pragma unroll
        for (int e = 0; e < 8; e++) {
            uint32_t q[4], k[4];
            ldsm4t(q, it + (e >> 2) * 8192 + (e & 3) * 1024 + mi * 512);
            ldsm4t(k, it + 24576 + e * 512);
            mma_bf(s[4], q[0], q[2], q[1], q[3], k[0], k[1]);
            mma_bf(s[5], q[0], q[2], q[1], q[3], k[2], k[3]);
            ldsm4t(k, it + (e >> 2) * 8192 + 4096 + (e & 3) * 1024);
            mma_bf(s[0], q[0], q[2], q[1], q[3], k[0], k[1]);
            mma_bf(s[1], q[0], q[2], q[1], q[3], k[2], k[3]);
            if (mi) {
                ldsm4t(k, it + (e >> 2) * 8192 + 4096 + (e & 3) * 1024 + 512);
                mma_bf(s[2], q[0], q[2], q[1], q[3], k[0], k[1]);
                mma_bf(s[3], q[0], q[2], q[1], q[3], k[2], k[3]);
            }
        }
#pragma unroll
        for (int q = 0; q < 4; q++) s[4][q] += s[5][q];
        const int seg = idx >> 5, h = idx & 31;
        const float sl = iq * ik * (0.08838834764831845f * 1.4426950408889634f);
        float mx[2] = {-3.0e38f, -3.0e38f};
#pragma unroll
        for (int i = 0; i < 5; i++)
#pragma unroll
            for (int q = 0; q < 4; q++) {
                const bool ok = i == 4 || (i * 8 + 2 * t + (q & 1)) <= (mi * 16 + g + (q >> 1) * 8);
                s[i][q] = ok ? s[i][q] * sl : -1.0e9f * 1.4426950408889634f;
                mx[q >> 1] = fmaxf(mx[q >> 1], s[i][q]);
            }
        float sum[2] = {0.f, 0.f};
#pragma unroll
        for (int r = 0; r < 2; r++) {
            mx[r] = fmaxf(mx[r], __shfl_xor_sync(~0u, mx[r], 1));
            mx[r] = fmaxf(mx[r], __shfl_xor_sync(~0u, mx[r], 2));
        }
#pragma unroll
        for (int i = 0; i < 5; i++)
#pragma unroll
            for (int q = 0; q < 4; q++) { s[i][q] = ex2(s[i][q] - mx[q >> 1]); sum[q >> 1] += s[i][q]; }
#pragma unroll
        for (int r = 0; r < 2; r++) {
            sum[r] += __shfl_xor_sync(~0u, sum[r], 1);
            sum[r] += __shfl_xor_sync(~0u, sum[r], 2);
            sum[r] = iv * rcp(sum[r]);
        }
        uint32_t pp[5][2];
#pragma unroll
        for (int i = 0; i < 5; i++) { pp[i][0] = pack_bf(s[i][0] * sum[0], s[i][1] * sum[0]); pp[i][1] = pack_bf(s[i][2] * sum[1], s[i][3] * sum[1]); }
        uint32_t* o = (uint32_t*)g_O + (((size_t)(seg >> 1) * 512 + h * 16) * 8 + (seg & 1) * 4 + mi * 2) * 32 + lane;
#pragma unroll
        for (int e = 0; e < 8; e++) {
            float o0[4] = {0.f, 0.f, 0.f, 0.f}, o1[4] = {0.f, 0.f, 0.f, 0.f};
            uint32_t v[4];
            lds64(v, it - lane * 8 + 28672 + e * 256);
            mma_bf8(o0, pp[4][0], pp[4][1], v[0]);
            mma_bf8(o1, pp[4][0], pp[4][1], v[1]);
            ldsm4(v, it + 16384 + e * 1024);
            mma_bf(o0, pp[0][0], pp[0][1], pp[1][0], pp[1][1], v[0], v[2]);
            mma_bf(o1, pp[0][0], pp[0][1], pp[1][0], pp[1][1], v[1], v[3]);
            ldsm4(v, it + 16384 + e * 1024 + 512);
            mma_bf(o0, pp[2][0], pp[2][1], pp[3][0], pp[3][1], v[0], v[2]);
            mma_bf(o1, pp[2][0], pp[2][1], pp[3][0], pp[3][1], v[1], v[3]);
            o[(2 * e) * 256] = pack_bf(o0[0], o0[1]); o[(2 * e) * 256 + 32] = pack_bf(o0[2], o0[3]);
            o[(2 * e + 1) * 256] = pack_bf(o1[0], o1[1]); o[(2 * e + 1) * 256 + 32] = pack_bf(o1[2], o1[3]);
        }
        __syncwarp();
        if (lane == 0) mbar_arrive(sb + HB_DONE + slot * 8);
        slot += 4;
        if (slot >= 6) { slot -= 6; ph ^= 1; }
    }
    if (layer == TLL) TL(39);
}

__global__ void __cluster_dims__(3, 1, 1) __launch_bounds__(384, 1)
k_chain(const int layer, const int nact, const uint32_t zero, const bf16* __restrict__ Wq, const bf16* __restrict__ Wk, const bf16* __restrict__ Wv,
        const bf16* __restrict__ Wo, const bf16* res, bf16* out) {
    extern __shared__ __align__(1024) char sm[];
    const uint32_t sb = smem_u32(sm);
    const int b = blockIdx.x, h = b / 3, c = b - h * 3;
    pdl_go();
    if (threadIdx.x >= 256) {
        asm volatile("setmaxnreg.dec.sync.aligned.u32 24;");
        TL(11 + layer * 14);
        chain_aux(sb, c, h, layer, nact);
    } else {
        asm volatile("setmaxnreg.inc.sync.aligned.u32 240;");
        chain_mma(sb, c, h, layer, zero, Wq, Wk, Wv, Wo, res, out);
    }
}
__global__ void __launch_bounds__(384, 1) k_help(const bf16* res, bf16* x, bf16* out, const int layer, const int na, const int nbh, const int zero, const bf16* Wq,
                                                  const bf16* Wk, const bf16* Wv, const bf16* Wo) {
    extern __shared__ __align__(1024) char sm[];
    if (layer == TLL) TL(51);
    if (threadIdx.x >= 256) {
        const uint32_t sb = smem_u32(sm);
        const int p = (threadIdx.x >> 5) - 8, i = (threadIdx.x & 31) * 4 + p;
        if (i < 34) mbar_init(sb + G_BAR + i * 8, i < 4 ? 3 : i < 8 || i == 12 || i == 13 ? 8 : i >= 22 && i < 28 ? 2 : 1);
        fence_async_smem();
        wait_flag<100>(g_flag + F_X + layer * 128 + 65, 321);
        fence_async_glb();
        if (i == 8 + p && blockIdx.x < (gridDim.x & ~3)) {
            mbar_expect(sb + HB_A + p * 8, 20480);
            bulk_g2s(sb + RI_A + p * 20480, (const char*)g_YT + (size_t)(blockIdx.x >> 2) * 81920 + p * 20480, 20480, sb + HB_A + p * 8);
        }
        __syncwarp();
        bar_sync(2, 128);
        bar_arrive(1, 384);
    }
    if (threadIdx.x + zero >= 256) helper_aux(smem_u32(sm), blockIdx.x, gridDim.x, na, nbh, layer, Wq, Wk, Wv, Wo);
    else helper_mma(sm, blockIdx.x, gridDim.x, na, nbh, layer, res, x, out);
    __syncwarp();
    pdl_go();
    if (blockIdx.x == 0) pdl_wait();
}

#define COL_PAD 15872
template <class... P, class... A>
void launch_pdl(void (*k)(P...), int grid, int block, int smem, cudaStream_t st, A... args) {
    cudaLaunchConfig_t cfg = {};
    cfg.gridDim = dim3(grid); cfg.blockDim = dim3(block); cfg.dynamicSmemBytes = smem; cfg.stream = st;
    cudaLaunchAttribute at[1];
    at[0].id = cudaLaunchAttributeProgrammaticStreamSerialization; at[0].val.programmaticStreamSerializationAllowed = 1;
    cfg.attrs = at;
    cfg.numAttrs = 1;
    cudaLaunchKernelEx(&cfg, k, args...);
}

}

extern "C" void kernel_launch(void* const* d_in, const int* in_sizes, int n_in, void* d_out, int out_size) {
    const bf16* x = (const bf16*)d_in[0];
    const bf16* wr = (const bf16*)d_in[1];
    const bf16* wi = (const bf16*)d_in[2];
    const bf16* mem0 = (const bf16*)d_in[4];
    const bf16* Wq = (const bf16*)d_in[5];
    const bf16* Wk = (const bf16*)d_in[6];
    const bf16* Wv = (const bf16*)d_in[7];
    const bf16* Wo = (const bf16*)d_in[8];
    bf16* out = (bf16*)d_out;
    static int nhelp = 0;
    static bf16 *xa, *xb;
    static cudaStream_t s1;
    static cudaEvent_t ev_fork, ev_join;
    if (!nhelp) {
        cudaStreamCreateWithFlags(&s1, cudaStreamNonBlocking);
        cudaEventCreateWithFlags(&ev_fork, cudaEventDisableTiming);
        cudaEventCreateWithFlags(&ev_join, cudaEventDisableTiming);
        cudaFuncSetAttribute(k_setup, cudaFuncAttributeMaxDynamicSharedMemorySize, SU_SMEM);
        cudaFuncSetAttribute(k_rowf, cudaFuncAttributeMaxDynamicSharedMemorySize, RF_SMEM);
        cudaFuncSetAttribute(k_col, cudaFuncAttributeMaxDynamicSharedMemorySize, COL_PAD);
        cudaFuncSetAttribute(k_chain, cudaFuncAttributeMaxDynamicSharedMemorySize, CH_SMEM);
        cudaFuncSetAttribute(k_setup, cudaFuncAttributePreferredSharedMemoryCarveout, 100);
        cudaFuncSetAttribute(k_rowf, cudaFuncAttributePreferredSharedMemoryCarveout, 100);
        cudaFuncSetAttribute(k_col, cudaFuncAttributePreferredSharedMemoryCarveout, 100);
        cudaFuncSetAttribute(k_chain, cudaFuncAttributePreferredSharedMemoryCarveout, 100);
        cudaFuncSetAttribute(k_help, cudaFuncAttributeMaxDynamicSharedMemorySize, HP_SMEM);
        cudaFuncSetAttribute(k_help, cudaFuncAttributePreferredSharedMemoryCarveout, 100);
        int dev = 0, sms = 0;
        cudaGetDevice(&dev);
        cudaDeviceGetAttribute(&sms, cudaDevAttrMultiProcessorCount, dev);
        nhelp = sms - 96 < 12 ? 12 : sms - 96;
        cudaGetSymbolAddress((void**)&xa, g_xa);
        cudaGetSymbolAddress((void**)&xb, g_xb);
    }
    const int na = nhelp - (nhelp >= 36 ? 24 : nhelp >= 28 ? 16 : 8), nbh = 14;
    cudaStream_t s0 = cudaStreamPerThread;
    cudaEventRecord(ev_fork, s0);
    cudaStreamWaitEvent(s1, ev_fork, 0);
    k_rowf<<<(96 + nhelp) & ~1, 256, RF_SMEM, s0>>>(x, 1, Wq, Wk, Wv, Wo);
    k_setup<<<128, 256, SU_SMEM, s1>>>(wr, wi, mem0);
    cudaEventRecord(ev_join, s1);
#define NLAYER 2
    for (int l = 0; l < NLAYER; l++) {
        const bf16* xin = l == 0 ? x : xb;
        if (l == 1) launch_pdl(k_rowf, 128, 256, RF_SMEM, s0, xin, 0, Wq, Wk, Wv, Wo);
        launch_pdl(k_col, 321, 128, l == 0 ? 0 : COL_PAD, s0, (int)(l == 0));
        launch_pdl(k_chain, 96, 384, CH_SMEM, s0, l, nhelp & ~3, 0u, Wq, Wk, Wv, Wo, (const bf16*)xa, l == 0 ? xb : out);
        launch_pdl(k_help, nhelp, 384, HP_SMEM, s0, xin, xa, l == 0 ? xb : out, l, na, nbh, 0, Wq, Wk, Wv, Wo);
    }
    cudaStreamWaitEvent(s0, ev_join, 0);
}
```

```cpp
#include <cuda_runtime.h>
#include <cuda_bf16.h>
#include <cuda_fp16.h>
#include <stdint.h>
#include <string.h>

namespace {

typedef __nv_bfloat16 bf16;
constexpr int S_ = 2048, D_ = 640, NSEG = 64;
constexpr int SPIN_LIM = 1 << 13;

__device__ float                  g_wmx[96];
__device__ __align__(1024) bf16   g_wot[4096 * 640];
__device__ __align__(16) float    g_co[1024];
__device__ __align__(256) uint2   g_stat[2 * 32 * 16 * 64];
__device__ float                  g_invM0;
__device__ __align__(16) float    g_wmax[128];
__device__ __align__(1024) char   g_redraw[65 * 32768];
constexpr int F_X = 2 * NSEG * 32, F_O = F_X + 2 * 128, NFLAG = F_O + 128, RING = 8;
constexpr int F_W = F_X + 66;
struct __align__(256) Flag { unsigned v; };
__device__ Flag                   g_flag[NFLAG];
__device__ Flag                   g_ready[1];
__device__ __align__(1024) char   g_item[RING * 32 * 32768];
__device__ __align__(1024) bf16   g_O[S_ * 4096];
__device__ __align__(1024) __half g_xn[S_ * D_];
__device__ __align__(1024) bf16   g_xa[S_ * D_];
__device__ __align__(1024) bf16   g_xb[S_ * D_];
__device__ __align__(1024) __half g_UT[D_ * S_];
__device__ __align__(1024) __half g_YT[D_ * S_];
__device__ __align__(1024) __half g_ctab[64 * 128 + 64 * 64];
__device__ __align__(1024) uint32_t g_Wf[321 * 2048];

#define TL(i)
#define TLN 0
#define TLL 1
#define CK(i)
__device__ __forceinline__ uint32_t smem_u32(const void* p) { return (uint32_t)__cvta_generic_to_shared(p); }
__device__ __forceinline__ uint32_t mapa(uint32_t a, uint32_t r) { uint32_t o; asm("mapa.shared::cluster.u32 %0,%1,%2;" : "=r"(o) : "r"(a), "r"(r)); return o; }
__device__ __forceinline__ void mbar_init(uint32_t a, int c) { asm volatile("mbarrier.init.shared::cta.b64 [%0],%1;" ::"r"(a), "r"(c) : "memory"); }
__device__ __forceinline__ void mbar_expect(uint32_t a, int bytes) { asm volatile("mbarrier.arrive.expect_tx.shared::cta.b64 _,[%0],%1;" ::"r"(a), "r"(bytes) : "memory"); }
__device__ __forceinline__ void mbar_arrive(uint32_t a) { asm volatile("mbarrier.arrive.shared::cta.b64 _,[%0];" ::"r"(a) : "memory"); }
__device__ __forceinline__ bool mbar_try(uint32_t a, uint32_t par) {
    uint32_t p;
    asm volatile("{.reg .pred q; mbarrier.try_wait.parity.shared::cta.b64 q,[%1],%2; selp.u32 %0,1,0,q;}" : "=r"(p) : "r"(a), "r"(par) : "memory");
    return p;
}
__device__ __forceinline__ void mbar_wait(uint32_t a, uint32_t par) {
    if (!mbar_try(a, par)) {
        int lim = 0;
        while (!mbar_try(a, par) && ++lim < SPIN_LIM) {}
    }
}
#define MW_HINT 20000
__device__ __forceinline__ void mbar_sleep(uint32_t a, uint32_t par) {
    asm volatile("{.reg .pred q; .reg .u32 n; mov.u32 n,0;\n"
                 "W_LOOP: mbarrier.try_wait.parity.shared::cta.b64 q,[%0],%1,%2; add.u32 n,n,1; setp.lt.and.u32 q,n,%3,!q; @q bra W_LOOP;}"
                 ::"r"(a), "r"(par), "n"(MW_HINT), "n"(SPIN_LIM) : "memory");
}
__device__ __forceinline__ void bar_arrive(int id, int n) { asm volatile("bar.arrive %0,%1;" ::"r"(id), "r"(n) : "memory"); }
__device__ __forceinline__ uint32_t clock32() { uint32_t c; asm volatile("mov.u32 %0,%%clock;" : "=r"(c)); return c; }
__device__ __forceinline__ uint32_t read_tid() { uint32_t v; asm volatile("mov.u32 %0,%%tid.x;" : "=r"(v)); return v; }
__device__ __forceinline__ void bar_sync(int id, int n) { asm volatile("bar.sync %0,%1;" ::"r"(id), "r"(n) : "memory"); }
__device__ __forceinline__ void fence_async_smem() { asm volatile("fence.proxy.async.shared::cta;" ::: "memory"); }
__device__ __forceinline__ void fence_async_glb() { asm volatile("fence.proxy.async.global;" ::: "memory"); }
__device__ __forceinline__ void cluster_sync_full() { asm volatile("barrier.cluster.arrive.aligned; barrier.cluster.wait.aligned;" ::: "memory"); }
__device__ __forceinline__ void bulk_g2s(uint32_t dst, const void* src, int bytes, uint32_t mb) {
    asm volatile("cp.async.bulk.shared::cluster.global.mbarrier::complete_tx::bytes [%0],[%1],%2,[%3];" ::"r"(dst), "l"(src), "r"(bytes), "r"(mb) : "memory");
}
__device__ __forceinline__ void bulk_g2s_last(uint32_t dst, const void* src, int bytes, uint32_t mb) {
    asm volatile("{.reg .b64 p; createpolicy.fractional.L2::evict_first.b64 p, 1.0;\n"
                 "cp.async.bulk.shared::cluster.global.mbarrier::complete_tx::bytes.L2::cache_hint [%0],[%1],%2,[%3],p;}"
                 ::"r"(dst), "l"(src), "r"(bytes), "r"(mb) : "memory");
}
__device__ __forceinline__ void bulk_s2s(uint32_t dst, uint32_t src, int bytes, uint32_t mb) {
    asm volatile("cp.async.bulk.shared::cluster.shared::cta.mbarrier::complete_tx::bytes [%0],[%1],%2,[%3];" ::"r"(dst), "r"(src), "r"(bytes), "r"(mb) : "memory");
}
__device__ __forceinline__ void bulk_s2g(void* dst, uint32_t src, int bytes) {
    asm volatile("cp.async.bulk.global.shared::cta.bulk_group [%0],[%1],%2;" ::"l"(dst), "r"(src), "r"(bytes) : "memory");
}
__device__ __forceinline__ void cp_async16(uint32_t dst, const void* src, uint32_t bytes = 16) {
    asm volatile("cp.async.cg.shared.global [%0],[%1],16,%2;" ::"r"(dst), "l"(src), "r"(bytes) : "memory");
}
__device__ __forceinline__ void cp_commit() { asm volatile("cp.async.commit_group;" ::: "memory"); }
template <int N> __device__ __forceinline__ void cp_wait() { asm volatile("cp.async.wait_group %0;" ::"n"(N) : "memory"); }
__device__ __forceinline__ void bulk_commit() { asm volatile("cp.async.bulk.commit_group;" ::: "memory"); }
__device__ __forceinline__ void bulk_wait0() { asm volatile("cp.async.bulk.wait_group 0;" ::: "memory"); }
__device__ __forceinline__ void ldsm4(uint32_t* r, uint32_t a) {
    asm volatile("ldmatrix.sync.aligned.m8n8.x4.shared.b16 {%0,%1,%2,%3},[%4];" : "=r"(r[0]), "=r"(r[1]), "=r"(r[2]), "=r"(r[3]) : "r"(a) : "memory");
}
__device__ __forceinline__ void ldsm4t(uint32_t* r, uint32_t a) {
    asm volatile("ldmatrix.sync.aligned.m8n8.x4.trans.shared.b16 {%0,%1,%2,%3},[%4];" : "=r"(r[0]), "=r"(r[1]), "=r"(r[2]), "=r"(r[3]) : "r"(a) : "memory");
}
__device__ __forceinline__ void stsm4(uint32_t a, uint32_t r0, uint32_t r1, uint32_t r2, uint32_t r3) {
    asm volatile("stmatrix.sync.aligned.m8n8.x4.shared.b16 [%0],{%1,%2,%3,%4};" ::"r"(a), "r"(r0), "r"(r1), "r"(r2), "r"(r3) : "memory");
}
__device__ __forceinline__ void stsm4t(uint32_t a, uint32_t r0, uint32_t r1, uint32_t r2, uint32_t r3) {
    asm volatile("stmatrix.sync.aligned.m8n8.x4.trans.shared.b16 [%0],{%1,%2,%3,%4};" ::"r"(a), "r"(r0), "r"(r1), "r"(r2), "r"(r3) : "memory");
}
__device__ __forceinline__ void lds128(uint32_t* r, uint32_t a) {
    asm volatile("ld.shared.v4.b32 {%0,%1,%2,%3},[%4];" : "=r"(r[0]), "=r"(r[1]), "=r"(r[2]), "=r"(r[3]) : "r"(a) : "memory");
}
__device__ __forceinline__ void lds64(uint32_t* r, uint32_t a) {
    asm volatile("ld.shared.v2.b32 {%0,%1},[%2];" : "=r"(r[0]), "=r"(r[1]) : "r"(a) : "memory");
}
__device__ __forceinline__ uint32_t lds32(uint32_t a) { uint32_t v; asm volatile("ld.shared.b32 %0,[%1];" : "=r"(v) : "r"(a) : "memory"); return v; }
__device__ __forceinline__ void sts128(uint32_t a, uint32_t r0, uint32_t r1, uint32_t r2, uint32_t r3) {
    asm volatile("st.shared.v4.b32 [%0],{%1,%2,%3,%4};" ::"r"(a), "r"(r0), "r"(r1), "r"(r2), "r"(r3) : "memory");
}
__device__ __forceinline__ void sts64(uint32_t a, uint32_t v0, uint32_t v1) { asm volatile("st.shared.v2.b32 [%0],{%1,%2};" ::"r"(a), "r"(v0), "r"(v1) : "memory"); }
[[maybe_unused]] __device__ __forceinline__ void sts32(uint32_t a, uint32_t v) { asm volatile("st.shared.b32 [%0],%1;" ::"r"(a), "r"(v) : "memory"); }
#define AU_(op) "{.reg .u32 t; add.u32 t,%4,%5; " op " {%0,%1,%2,%3},[t+%6];}"
template <int I> __device__ __forceinline__ void ldsm4_u(uint32_t* r, uint32_t a, uint32_t u) {
    asm volatile(AU_("ldmatrix.sync.aligned.m8n8.x4.shared.b16") : "=r"(r[0]), "=r"(r[1]), "=r"(r[2]), "=r"(r[3]) : "r"(a), "r"(u), "n"(I) : "memory");
}
template <int I> __device__ __forceinline__ void ldsm4t_u(uint32_t* r, uint32_t a, uint32_t u) {
    asm volatile(AU_("ldmatrix.sync.aligned.m8n8.x4.trans.shared.b16") : "=r"(r[0]), "=r"(r[1]), "=r"(r[2]), "=r"(r[3]) : "r"(a), "r"(u), "n"(I) : "memory");
}
template <int I> __device__ __forceinline__ void lds128_u(uint32_t* r, uint32_t a, uint32_t u) {
    asm volatile(AU_("ld.shared.v4.b32") : "=r"(r[0]), "=r"(r[1]), "=r"(r[2]), "=r"(r[3]) : "r"(a), "r"(u), "n"(I) : "memory");
}
template <int I> __device__ __forceinline__ void lds64_u(uint32_t* r, uint32_t a, uint32_t u) {
    asm volatile("{.reg .u32 t; add.u32 t,%2,%3; ld.shared.v2.b32 {%0,%1},[t+%4];}" : "=r"(r[0]), "=r"(r[1]) : "r"(a), "r"(u), "n"(I) : "memory");
}
template <int I> __device__ __forceinline__ uint32_t lds32_u(uint32_t a, uint32_t u) {
    uint32_t v;
    asm volatile("{.reg .u32 t; add.u32 t,%1,%2; ld.shared.b32 %0,[t+%3];}" : "=r"(v) : "r"(a), "r"(u), "n"(I) : "memory");
    return v;
}
template <int I> __device__ __forceinline__ void sts64_u(uint32_t a, uint32_t u, uint32_t v0, uint32_t v1) {
    asm volatile("{.reg .u32 t; add.u32 t,%0,%1; st.shared.v2.b32 [t+%2],{%3,%4};}" ::"r"(a), "r"(u), "n"(I), "r"(v0), "r"(v1) : "memory");
}
template <int I> __device__ __forceinline__ void sts32_u(uint32_t a, uint32_t u, uint32_t v) {
    asm volatile("{.reg .u32 t; add.u32 t,%0,%1; st.shared.b32 [t+%2],%3;}" ::"r"(a), "r"(u), "n"(I), "r"(v) : "memory");
}
template <int I> __device__ __forceinline__ void sts16_u(uint32_t a, uint32_t u, uint32_t v) {
    asm volatile("{.reg .u32 t; add.u32 t,%0,%1; st.shared.b16 [t+%2],%3;}" ::"r"(a), "r"(u), "n"(I), "h"((unsigned short)v) : "memory");
}
template <int I> __device__ __forceinline__ void sts128_u(uint32_t a, uint32_t u, uint32_t r0, uint32_t r1, uint32_t r2, uint32_t r3) {
    asm volatile("{.reg .u32 t; add.u32 t,%0,%1; st.shared.v4.b32 [t+%2],{%3,%4,%5,%6};}" ::"r"(a), "r"(u), "n"(I), "r"(r0), "r"(r1), "r"(r2), "r"(r3) : "memory");
}
template <int I> __device__ __forceinline__ void stsm4_u(uint32_t a, uint32_t u, uint32_t r0, uint32_t r1, uint32_t r2, uint32_t r3) {
    asm volatile("{.reg .u32 t; add.u32 t,%0,%1; stmatrix.sync.aligned.m8n8.x4.shared.b16 [t+%2],{%3,%4,%5,%6};}"
                 ::"r"(a), "r"(u), "n"(I), "r"(r0), "r"(r1), "r"(r2), "r"(r3) : "memory");
}
__device__ __forceinline__ void st_async2_x3(uint32_t a, uint32_t u, uint32_t mb, uint32_t v0, uint32_t v1) {
    asm volatile("{.reg .u32 t,x,y; add.u32 t,%0,%1;\n"
                 "mapa.shared::cluster.u32 x,t,0; mapa.shared::cluster.u32 y,%2,0; st.async.shared::cluster.mbarrier::complete_tx::bytes.v2.b32 [x],{%3,%4},[y];\n"
                 "mapa.shared::cluster.u32 x,t,1; mapa.shared::cluster.u32 y,%2,1; st.async.shared::cluster.mbarrier::complete_tx::bytes.v2.b32 [x],{%3,%4},[y];\n"
                 "mapa.shared::cluster.u32 x,t,2; mapa.shared::cluster.u32 y,%2,2; st.async.shared::cluster.mbarrier::complete_tx::bytes.v2.b32 [x],{%3,%4},[y];}"
                 ::"r"(a), "r"(u), "r"(mb), "r"(v0), "r"(v1) : "memory");
}
template <int V> struct IC { __host__ __device__ constexpr operator int() const { return V; } };
template <int N, class F> __device__ __forceinline__ void sfor(F f) {
    if constexpr (N > 0) { sfor<N - 1>(f); f(IC<N - 1>()); }
}
__device__ __forceinline__ void mma_f16(float* d, const uint32_t* a, uint32_t b0, uint32_t b1) {
    asm volatile("mma.sync.aligned.m16n8k16.row.col.f32.f16.f16.f32 {%0,%1,%2,%3},{%4,%5,%6,%7},{%8,%9},{%0,%1,%2,%3};"
                 : "+f"(d[0]), "+f"(d[1]), "+f"(d[2]), "+f"(d[3]) : "r"(a[0]), "r"(a[1]), "r"(a[2]), "r"(a[3]), "r"(b0), "r"(b1));
}
__device__ __forceinline__ void mma_bf(float* d, uint32_t a0, uint32_t a1, uint32_t a2, uint32_t a3, uint32_t b0, uint32_t b1) {
    asm volatile("mma.sync.aligned.m16n8k16.row.col.f32.bf16.bf16.f32 {%0,%1,%2,%3},{%4,%5,%6,%7},{%8,%9},{%0,%1,%2,%3};"
                 : "+f"(d[0]), "+f"(d[1]), "+f"(d[2]), "+f"(d[3]) : "r"(a0), "r"(a1), "r"(a2), "r"(a3), "r"(b0), "r"(b1));
}
__device__ __forceinline__ void mma_bf8(float* d, uint32_t a0, uint32_t a1, uint32_t b0) {
    asm volatile("mma.sync.aligned.m16n8k8.row.col.f32.bf16.bf16.f32 {%0,%1,%2,%3},{%4,%5},{%6},{%0,%1,%2,%3};"
                 : "+f"(d[0]), "+f"(d[1]), "+f"(d[2]), "+f"(d[3]) : "r"(a0), "r"(a1), "r"(b0));
}
__device__ __forceinline__ uint32_t pack_bf(float lo, float hi) { uint32_t r; asm("cvt.rn.bf16x2.f32 %0,%1,%2;" : "=r"(r) : "f"(hi), "f"(lo)); return r; }
__device__ __forceinline__ uint32_t pack_h(float lo, float hi) { uint32_t r; asm("cvt.rn.f16x2.f32 %0,%1,%2;" : "=r"(r) : "f"(hi), "f"(lo)); return r; }
__device__ __forceinline__ float bf_lo(uint32_t v) { return __uint_as_float(v << 16); }
__device__ __forceinline__ float bf_hi(uint32_t v) { return __uint_as_float(v & 0xffff0000u); }
__device__ __forceinline__ uint32_t bfma(uint32_t a, uint32_t b, uint32_t c) { uint32_t r; asm("fma.rn.bf16x2 %0,%1,%2,%3;" : "=r"(r) : "r"(a), "r"(b), "r"(c)); return r; }
__device__ __forceinline__ uint4 add_bf8(const uint4 x, const uint32_t* y, const uint32_t k = 0x3f803f80u) {
    return make_uint4(bfma(y[0], k, x.x), bfma(y[1], k, x.y), bfma(y[2], k, x.z), bfma(y[3], k, x.w));
}
__device__ __forceinline__ float ex2(float x) { float r; asm("ex2.approx.ftz.f32 %0,%1;" : "=f"(r) : "f"(x)); return r; }
__device__ __forceinline__ float rcp(float x) { float r; asm("rcp.approx.ftz.f32 %0,%1;" : "=f"(r) : "f"(x)); return r; }
__device__ __forceinline__ void wg_fence() { asm volatile("wgmma.fence.sync.aligned;" ::: "memory"); }
__device__ __forceinline__ void wg_commit() { asm volatile("wgmma.commit_group.sync.aligned;" ::: "memory"); }
template <int N> __device__ __forceinline__ void wg_wait() { asm volatile("wgmma.wait_group.sync.aligned %0;" ::"n"(N) : "memory"); }
__device__ __forceinline__ uint64_t mkdesc(uint32_t a, uint32_t lbo, uint32_t sbo, uint32_t sw) {
    return (uint64_t)((a & 0x3FFFF) >> 4) | ((uint64_t)(lbo >> 4) << 16) | ((uint64_t)(sbo >> 4) << 32) | ((uint64_t)sw << 62);
}
#define F4(d, i) "+f"(d[i]), "+f"(d[i + 1]), "+f"(d[i + 2]), "+f"(d[i + 3])
#define F8(d, i) F4(d, i), F4(d, i + 4)
#define F16(d, i) F8(d, i), F8(d, i + 8)
template <int OFF, int SC> __device__ __forceinline__ void wg_n32_x(float* d, const uint32_t* a, uint32_t lo) {
    asm volatile("{.reg .pred p; .reg .b32 l; .reg .b64 q; setp.ne.b32 p,%22,0; add.u32 l,%20,%21; mov.b64 q,{l,8};\n"
                 "wgmma.mma_async.sync.aligned.m64n32k16.f32.f16.f16 "
                 "{%0,%1,%2,%3,%4,%5,%6,%7,%8,%9,%10,%11,%12,%13,%14,%15},{%16,%17,%18,%19},q,p,1,1,0;}"
                 : F16(d, 0) : "r"(a[0]), "r"(a[1]), "r"(a[2]), "r"(a[3]), "r"(lo), "n"(OFF), "n"(SC));
}
__device__ __forceinline__ void wg_n128_rs(float* d, const uint32_t* a, uint64_t db, int sc) {
    asm volatile("{.reg .pred p; setp.ne.b32 p,%69,0; wgmma.mma_async.sync.aligned.m64n128k16.f32.f16.f16 "
                 "{%0,%1,%2,%3,%4,%5,%6,%7,%8,%9,%10,%11,%12,%13,%14,%15,%16,%17,%18,%19,%20,%21,%22,%23,%24,%25,%26,%27,%28,%29,%30,%31,"
                 "%32,%33,%34,%35,%36,%37,%38,%39,%40,%41,%42,%43,%44,%45,%46,%47,%48,%49,%50,%51,%52,%53,%54,%55,%56,%57,%58,%59,%60,%61,%62,%63},"
                 "{%64,%65,%66,%67},%68,p,1,1,0;}"
                 : F16(d, 0), F16(d, 16), F16(d, 32), F16(d, 48) : "r"(a[0]), "r"(a[1]), "r"(a[2]), "r"(a[3]), "l"(db), "r"(sc));
}
#define N80_REGS "{%0,%1,%2,%3,%4,%5,%6,%7,%8,%9,%10,%11,%12,%13,%14,%15,%16,%17,%18,%19,%20,%21,%22,%23,%24,%25,%26,%27,%28,%29,%30,%31,%32,%33,%34,%35,%36,%37,%38,%39}"
__device__ __forceinline__ void wg_n80_ss(float* d, uint64_t da, uint64_t db, int sc) {
    asm volatile("{.reg .pred p; setp.ne.b32 p,%42,0; wgmma.mma_async.sync.aligned.m64n80k16.f32.bf16.bf16 " N80_REGS ",%40,%41,p,1,1,0,0;}"
                 : F16(d, 0), F16(d, 16), F8(d, 32) : "l"(da), "l"(db), "r"(sc));
}
__device__ __forceinline__ void wg_n88_ss(float* d, uint64_t da, uint64_t db, int sc) {
    asm volatile("{.reg .pred p; setp.ne.b32 p,%46,0; wgmma.mma_async.sync.aligned.m64n88k16.f32.f16.f16 "
                 "{%0,%1,%2,%3,%4,%5,%6,%7,%8,%9,%10,%11,%12,%13,%14,%15,%16,%17,%18,%19,%20,%21,%22,%23,%24,%25,%26,%27,%28,%29,%30,%31,"
                 "%32,%33,%34,%35,%36,%37,%38,%39,%40,%41,%42,%43},%44,%45,p,1,1,0,0;}"
                 : F16(d, 0), F16(d, 16), F8(d, 32), F4(d, 40) : "l"(da), "l"(db), "r"(sc));
}
__device__ __forceinline__ void wg_n48_ss_ta(float* d, uint64_t da, uint64_t db, int sc) {
    asm volatile("{.reg .pred p; setp.ne.b32 p,%26,0; wgmma.mma_async.sync.aligned.m64n48k16.f32.f16.f16 "
                 "{%0,%1,%2,%3,%4,%5,%6,%7,%8,%9,%10,%11,%12,%13,%14,%15,%16,%17,%18,%19,%20,%21,%22,%23},%24,%25,p,1,1,1,0;}"
                 : F16(d, 0), F8(d, 16) : "l"(da), "l"(db), "r"(sc));
}
template <int TA> __device__ __forceinline__ void wg_n64_ss_tb(float* d, uint64_t da, uint64_t db, int sc) {
    asm volatile("{.reg .pred p; setp.ne.b32 p,%34,0; wgmma.mma_async.sync.aligned.m64n64k16.f32.f16.f16 "
                 "{%0,%1,%2,%3,%4,%5,%6,%7,%8,%9,%10,%11,%12,%13,%14,%15,%16,%17,%18,%19,%20,%21,%22,%23,%24,%25,%26,%27,%28,%29,%30,%31},"
                 "%32,%33,p,1,1,%35,1;}"
                 : F16(d, 0), F16(d, 16) : "l"(da), "l"(db), "r"(sc), "n"(TA));
}
__device__ __forceinline__ void pdl_wait() { asm volatile("griddepcontrol.wait;" ::: "memory"); }
__device__ __forceinline__ void pdl_go() { asm volatile("griddepcontrol.launch_dependents;" ::: "memory"); }
__device__ __forceinline__ float cos640(float p) {
    const float q = fmaf(p, 0.0015625f, 12582912.f) - 12582912.f;
    return __cosf(fmaf(q, -640.f, p) * 0.009817477042468103f);
}
__device__ __forceinline__ uint4 cos_row8(float p0, float step, float amp = 1.f) {
    float v[8];
    const float k = 2.f * cos640(step);
    v[0] = amp * cos640(p0); v[1] = amp * cos640(p0 + step);
#pragma unroll
    for (int i = 2; i < 8; i++) v[i] = fmaf(k, v[i - 1], -v[i - 2]);
    return make_uint4(pack_h(v[0], v[1]), pack_h(v[2], v[3]), pack_h(v[4], v[5]), pack_h(v[6], v[7]));
}
__device__ __forceinline__ float wfilter_max(int lane) {
    float m = fmaxf(fmaxf(g_wmax[lane], g_wmax[lane + 32]), fmaxf(g_wmax[lane + 64], g_wmax[lane + 96]));
    return __uint_as_float(__reduce_max_sync(~0u, __float_as_uint(m)));
}
__device__ __forceinline__ unsigned ld_acquire(const Flag* p) { unsigned v; asm volatile("ld.acquire.gpu.global.u32 %0,[%1];" : "=r"(v) : "l"(p) : "memory"); return v; }
#define POLL_NS 200
template <int NS = POLL_NS> __device__ __forceinline__ void wait_flag(const Flag* p, unsigned v) {
    if (ld_acquire(p) >= v) return;
    unsigned x;
    int lim = 0;
    do {
        __nanosleep(NS);
        asm volatile("ld.relaxed.gpu.global.u32 %0,[%1];" : "=r"(x) : "l"(p) : "memory");
    } while (x < v && ++lim < SPIN_LIM);
    ld_acquire(p);
}
__device__ __forceinline__ void prefetch_l2(const void* p, int bytes) { asm volatile("cp.async.bulk.prefetch.L2.global [%0],%1;" ::"l"(p), "r"(bytes) : "memory"); }
__device__ __forceinline__ void red_release(Flag* p) { asm volatile("red.release.gpu.global.add.u32 [%0],1;" ::"l"(p) : "memory"); }
__device__ __forceinline__ void red_relaxed(Flag* p) { asm volatile("red.relaxed.gpu.global.add.u32 [%0],1;" ::"l"(p) : "memory"); }
__device__ __forceinline__ void red_h8(void* p, uint32_t a, uint32_t b, uint32_t c, uint32_t d) {
    asm volatile("red.relaxed.gpu.global.add.noftz.v4.f16x2 [%0],{%1,%2,%3,%4};" ::"l"(p), "r"(a), "r"(b), "r"(c), "r"(d) : "memory");
}
__device__ __forceinline__ float pow2_scale(float bound, int top, float* inv) {
    int e = (int)((__float_as_uint(bound) >> 23) & 0xff) - 126;
    int k = top - e;
    k = max(-100, min(100, k));
    *inv = __uint_as_float((uint32_t)(127 - k) << 23);
    return __uint_as_float((uint32_t)(127 + k) << 23);
}
__device__ __forceinline__ char* red_base() { return (char*)(((uintptr_t)g_redraw + 32767) & ~(uintptr_t)32767); }

__device__ __forceinline__ void setup_a(char* sm, const int b, const bf16* __restrict__ wr, const bf16* __restrict__ wi) {
    const int tid = threadIdx.x, lane = tid & 31;
    const uint32_t sb = smem_u32(sm);
    auto row_byte = [&](int q) { return ((b >> 2) + 32 * ((q >> 1) * 8 + 2 * (b & 3) + (q & 1))) * 642; };
#pragma unroll 1
    for (int r = tid >> 5; r < 32; r += 8) {
        const char* src = (const char*)(r < 16 ? wr : wi) + (row_byte(r & 15) & ~15);
        cp_async16(sb + r * 672 + lane * 16, src + lane * 16);
        if (lane < 9) cp_async16(sb + r * 672 + 512 + lane * 16, src + 512 + lane * 16);
    }
    ((uint4*)g_stat)[b * 256 + tid] = make_uint4(0, 0, 0, 0);
    if (tid < 2 * (NFLAG / 128)) ((uint4*)(g_flag + b * (NFLAG / 128) + (tid >> 1)))[tid & 1] = make_uint4(0, 0, 0, 0);
    if (tid < 12) {
        const int i = b * 12 + tid;
        const int f = ((i >> 4) & 3) * 8 + (i & 7), im = (i >> 3) & 1, part = (i >> 8) & 1;
        ((uint4*)g_ctab)[i] = cos_row8((float)(i < 1024 ? (i >> 7) * 80 * (i & 63) + ((i & 64) ? 480 : 0) : ((i >> 6) & 3) * 160 * f + (im == part ? 0 : im ? 160 : 480)),
                                       (float)(i < 1024 ? 10 * (i & 63) : 20 * f));
    }
    asm volatile("cp.async.wait_all;" ::: "memory");
    __syncthreads();
    const int q0 = (tid & 3) * 4;
    const char* rp[4];
#pragma unroll
    for (int u = 0; u < 4; u++) rp[u] = sm + (q0 + u) * 672 + (row_byte(q0 + u) & 15);
    uint32_t mx = 0;
#pragma unroll 2
    for (int c = tid >> 2; c < 321; c += 64) {
        uint32_t v[4];
#pragma unroll
        for (int u = 0; u < 4; u++) {
            v[u] = ((const unsigned short*)rp[u])[c] | ((uint32_t)((const unsigned short*)(rp[u] + 16 * 672))[c] << 16);
            mx = __vmaxu2(mx, v[u] & 0x7fff7fffu);
        }
        ((uint4*)g_Wf)[(size_t)c * 512 + b * 4 + ((tid ^ (b >> 1)) & 3)] = make_uint4(v[0], v[1], v[2], v[3]);
    }
    mx = __reduce_max_sync(~0u, max(mx & 0xffffu, mx >> 16));
    __syncthreads();
    if (lane == 0) ((uint32_t*)sm)[tid >> 5] = mx;
    __syncthreads();
    if (tid < 32) {
        mx = __reduce_max_sync(~0u, ((uint32_t*)sm)[lane & 7]);
        if (tid == 0) g_wmax[b] = __uint_as_float(mx << 16);
    }
}
__device__ __forceinline__ void setup_b(const int b, const bf16* __restrict__ mem0) {
    const int tid = threadIdx.x;
    uint4* z = (uint4*)red_base();
    if (b < 3) {
        const int w = tid >> 5, lane = tid & 31, p = b * 2 + ((w >> 1) & 1), odd = w & 1;
        uint32_t mx = 0;
#pragma unroll 4
        for (int i = lane; i < 640; i += 32) {
            const uint4 u = ((const uint4*)mem0)[i];
            mx = __vmaxu2(__vmaxu2(mx, u.x & 0x7fff7fffu), __vmaxu2(__vmaxu2(u.y & 0x7fff7fffu, u.z & 0x7fff7fffu), u.w & 0x7fff7fffu));
        }
        float inv, v[7];
        const float sc = pow2_scale(__uint_as_float(__reduce_max_sync(~0u, max(mx & 0xffffu, mx >> 16)) << 16), 14, &inv);
        if (tid == 0) g_invM0 = inv;
#pragma unroll
        for (int j = 0; j < 7; j++) {
            const int r = p * 56 + (j < 6 ? odd * 32 + (j >> 1) * 8 : 24) + (lane >> 2), mr = 2 * (lane & 3) + (j < 6 ? (j & 1) : odd);
            v[j] = r < 320 ? __bfloat162float(mem0[mr * 640 + (w >> 2) * 320 + r]) * sc : 0.f;
        }
        const int off = w * 2048 + (lane >> 4) * 1024 + ((lane >> 3) & 1) * 256 + (lane & 7) * 16 + (b == 2 ? (w >> 1) * 4096 + 128 : b * 16384);
        const uint4 u = make_uint4(pack_h(v[0], v[1]), pack_h(v[2], v[3]), pack_h(v[4], v[5]), pack_h(v[6], 32.f));
        z[off >> 4] = u; z[65536 + (off >> 4)] = u;
    }
}

constexpr int SU_SMEM = 32 * 672;
__global__ void __launch_bounds__(256, 4) k_setup(const bf16* __restrict__ wr, const bf16* __restrict__ wi, const bf16* __restrict__ mem0) {
    extern __shared__ __align__(1024) char sm[];
    TL(0);
    setup_b(blockIdx.x, mem0);
    setup_a(sm, blockIdx.x, wr, wi);
    __syncthreads();
    if (threadIdx.x == 0) red_release(g_ready);
    TL(1);
}
__device__ __forceinline__ float weight_scale(int h, int ty, float* inv) { return pow2_scale(__ldcg(g_wmx + h * 3 + ty), 6, inv); }

#define STR_(x) #x
#define STR(x) STR_(x)
#define RF_U 1
constexpr int RF_A = 22 * 2816, RF_X = RF_A + 22 * 1024, RF_BAR = RF_X + 64 * 1344, RF_SMEM = RF_BAR + 64;
__global__ void __cluster_dims__(2, 1, 1) __launch_bounds__(256, 2)
k_rowf(const bf16* x, const int first, const bf16* Wq, const bf16* Wk, const bf16* Wv, const bf16* Wo) {
    extern __shared__ __align__(1024) char sm[];
    TL(first ? 2 : 16);
    const int tid = threadIdx.x, w = tid >> 5, lane = tid & 31, g = lane >> 2, t = lane & 3;
    if (blockIdx.x >= 128) { __nanosleep(2500); return; }
    const int a = blockIdx.x >> 2, gq = blockIdx.x & 3;
    const uint32_t sb = smem_u32(sm), mb = sb + RF_BAR + w * 8;
    if (lane == 0) {
        mbar_init(mb, 1);
        asm volatile("fence.mbarrier_init.release.cluster;" ::: "memory");
        mbar_expect(mb, 8 * 1280);
    }
    __syncwarp();
    asm volatile("barrier.cluster.arrive.relaxed.aligned;" ::: "memory");
#pragma unroll 1
    for (int ph = 0; ph < 2; ph++) {
        if (ph != first) {
            asm volatile("barrier.cluster.wait.aligned;" ::: "memory");
            pdl_wait();
            TL(first ? 3 : 17);
            if (lane < 4)
                asm volatile("cp.async.bulk.shared::cluster.global.mbarrier::complete_tx::bytes.multicast::cluster [%0],[%1],1280,[%2],%3;"
                             ::"r"(sb + RF_X + (w * 8 + (gq & 1) * 4 + lane) * 1344), "l"(x + (size_t)(a * 64 + w * 8 + (gq & 1) * 4 + lane) * 640), "r"(mb),
                             "h"((unsigned short)3) : "memory");
            __syncwarp();
            pdl_go();
        } else {
#pragma unroll 3
            for (int id = tid; id < 22 * 176; id += 256) {
                const int kg = id / 176, n = id - kg * 176;
                const float c = (float)(2 * n + (gq & 1));
                *(uint4*)(sm + id * 16) = cos_row8(fmaf((float)(kg * 8), c, (float)((gq & 2) * 80)), c, 0.03952847075210474f);
            }
        }
    }
    mbar_wait(mb, 0);
    const uint32_t row = sb + RF_X + (w * 8 + g) * 1344;
    float st[4][4] = {};
#pragma unroll 1
    for (int i = 0; i < 20; i += 4) {
        uint32_t u[4][4];
#pragma unroll
        for (int q = 0; q < 4; q++) lds128(u[q], row + (4 * (i + q) + t) * 16);
#pragma unroll
        for (int q = 0; q < 4; q++) {
            mma_bf(st[(q & 1) * 2], u[q][0], 0x3f803f80u, u[q][1], 0x3f803f80u, u[q][0], u[q][1]);
            mma_bf(st[(q & 1) * 2 + 1], u[q][2], 0x3f803f80u, u[q][3], 0x3f803f80u, u[q][2], u[q][3]);
        }
    }
#pragma unroll
    for (int q = 0; q < 4; q++) { st[0][q] += st[2][q]; st[1][q] += st[3][q]; }
    const float sq = __shfl_sync(~0u, (g & 1) ? st[0][1] + st[1][1] : st[0][0] + st[1][0], g * 4 + (g >> 1));
    const float mean = __shfl_sync(~0u, (g & 1) ? st[0][3] + st[1][3] : st[0][2] + st[1][2], g * 4 + (g >> 1)) * (1.f / 640.f);
    const float r = rsqrtf(fmaxf(fmaf(-mean, mean, sq * (1.f / 640.f)), 0.f) + 1e-5f), off = gq == 0 ? -4.f * mean * r : 0.f;
    const float r1 = (gq == 1 || gq == 2) ? -r : r, r2 = (gq & 1) ? -r : r, r3 = gq >= 2 ? -r : r;
    const uint32_t aa = sb + RF_A + w * 128 + g * 16;
    auto el = [&](int d) { unsigned short v; asm volatile("ld.shared.u16 %0,[%1];" : "=h"(v) : "r"(row + d * 2)); return __uint_as_float((uint32_t)v << 16); };
_Pragma(STR(unroll RF_U))
    for (int i = 0; i < 5; i++) {
        const int ch = t + 4 * i;
        uint32_t u[4][4];
        lds128(u[0], row + ch * 16); lds128(u[1], row + (39 - ch) * 16); lds128(u[2], row + (40 + ch) * 16); lds128(u[3], row + (79 - ch) * 16);
        const float nb0 = el(320 - 8 * ch), nb1 = el(ch ? 640 - 8 * ch : 0);
        float o[8];
#pragma unroll
        for (int q = 0; q < 8; q++) {
            const int m = (8 - q) >> 1;
            const float e0 = (q & 1) ? bf_hi(u[0][q >> 1]) : bf_lo(u[0][q >> 1]), e2 = (q & 1) ? bf_hi(u[2][q >> 1]) : bf_lo(u[2][q >> 1]);
            const float e1 = q == 0 ? nb0 : (q & 1) ? bf_hi(u[1][m & 3]) : bf_lo(u[1][m & 3]), e3 = q == 0 ? nb1 : (q & 1) ? bf_hi(u[3][m & 3]) : bf_lo(u[3][m & 3]);
            o[q] = fmaf(e3, r3, fmaf(e2, r2, fmaf(e1, r1, fmaf(e0, r, off))));
        }
        if (ch == 0) o[0] *= 0.5f;
        sts128(aa + ch * 1024, pack_h(o[0], o[1]), pack_h(o[2], o[3]), pack_h(o[4], o[5]), pack_h(o[6], o[7]));
    }
    if (t < 2) sts128(aa + (20 + t) * 1024, t == 0 ? pack_h(fmaf(el(480), r2, fmaf(el(160), r, 0.5f * off)), 0.f) : 0u, 0u, 0u, 0u);
    fence_async_smem();
    __syncthreads();
    const int wg = w >> 2;
    float acc[44];
    uint64_t da = mkdesc(sb + RF_A, 1024, 128, 0), db = mkdesc(sb + wg * 1408, 2816, 128, 0);
    wg_fence();
#pragma unroll 1
    for (int k = 0; k < 11; k++) { wg_n88_ss(acc, da, db, k); da += 128; db += 352; }
    wg_commit(); wg_wait<0>();
    const uint32_t stg = sb + RF_X + wg * 96 * 144;
#pragma unroll
    for (int j = 0; j < 12; j += 2) {
        const int m = lane >> 3, j1 = j < 10 ? j + 1 : j;
        stsm4t(stg + ((j + (m >> 1)) * 8 + (lane & 7)) * 144 + ((w & 3) * 16 + (m & 1) * 8) * 2, pack_h(acc[j * 4], acc[j * 4 + 1]),
               pack_h(acc[j * 4 + 2], acc[j * 4 + 3]), pack_h(acc[j1 * 4], acc[j1 * 4 + 1]), pack_h(acc[j1 * 4 + 2], acc[j1 * 4 + 3]));
    }
    bar_sync(1 + wg, 128);
#pragma unroll 3
    for (int rr = (tid & 127) >> 3; rr < 88; rr += 16) {
        const int ch = tid & 7, c = 2 * (wg * 88 + rr) + (gq & 1);
        if (c <= 320 - (gq >> 1) && (c | (gq ^ 2))) {
            uint32_t u[4];
            lds128(u, stg + rr * 144 + ch * 16);
            ((uint4*)g_UT)[((size_t)(c == 320 ? 1 : 2 * c + (gq >> 1)) * 32 + a) * 8 + (ch ^ (a & 7))] = make_uint4(u[0], u[1], u[2], u[3]);
        }
    }
    TL(first ? 4 : 18);
}

constexpr int GST = 4, GSTB = 32768 + 20480, GNC = 32;
constexpr int G_BAR = GST * GSTB + 3072;
#define GPACE 1100
#define GPACE2 650
__device__ __forceinline__ void oproj_load(const uint32_t sb, const int op, const int mb, const int nb, const int c0, const uint32_t pace) {
    const int by = op == 2 ? 20480 : 16384;
    const char* src = op == 2 ? (const char*)g_wot + (size_t)nb * GNC * 20480 : (const char*)g_O + (size_t)(2 * mb + op) * GNC * 16384;
    uint32_t t0 = clock32() - pace + op * (pace / 3);
#pragma unroll 1
    for (int c = c0; c < c0 + GNC; c++, src += by) {
        const int st = c % GST;
        if (c >= GST) mbar_wait(sb + G_BAR + (GST + st) * 8, ((c / GST) - 1) & 1);
        while (clock32() - t0 < pace) {}
        t0 = clock32();
        const int by_ = by;
        mbar_expect(sb + G_BAR + st * 8, by_);
        if (op == 2) bulk_g2s(sb + st * GSTB + 32768, src, by_, sb + G_BAR + st * 8);
        else bulk_g2s_last(sb + st * GSTB + op * 16384, src, by_, sb + G_BAR + st * 8);
    }
}
__device__ __forceinline__ void oproj_mma(const uint32_t sb, const int mb, const int nb, const int c0, const bf16* res, bf16* out) {
    const int w = threadIdx.x >> 5, lane = threadIdx.x & 31, wg = w >> 2;
    float acc[40];
    uint4 rv[5];
#pragma unroll 1
    for (int c = c0; c < c0 + GNC; c++) {
        const int st = c % GST;
        mbar_wait(sb + G_BAR + st * 8, (c / GST) & 1);
        const uint32_t d = sb + st * GSTB;
        wg_fence();
#pragma unroll
        for (int k = 0; k < 8; k++)
            wg_n80_ss(acc, mkdesc(d + wg * 16384 + k * 2048, 1024, 128, 0), mkdesc(d + 32768 + k * 2560, 1280, 128, 0), (c - c0) | k);
        wg_commit();
        if (c > c0) {
            wg_wait<1>();
            if (lane == 0) mbar_arrive(sb + G_BAR + (GST + (c - 1) % GST) * 8);
        }
    }
#pragma unroll
    for (int i = 0; i < 5; i++) {
        const int id = i * 32 + lane, r = id / 10;
        rv[i] = __ldcg((const uint4*)res + (size_t)(mb * 128 + w * 16 + r) * 80 + nb * 10 + id - r * 10);
    }
    wg_wait<0>();
    bar_sync(5, 256);
    const uint32_t stg = sb + (GST - 1) * GSTB + w * 16 * 176;
#pragma unroll
    for (int j = 0; j < 5; j++)
        stsm4(stg + (lane & 15) * 176 + (2 * j + (lane >> 4)) * 16, pack_bf(acc[j * 8], acc[j * 8 + 1]), pack_bf(acc[j * 8 + 2], acc[j * 8 + 3]),
              pack_bf(acc[j * 8 + 4], acc[j * 8 + 5]), pack_bf(acc[j * 8 + 6], acc[j * 8 + 7]));
    __syncwarp();
#pragma unroll
    for (int i = 0; i < 5; i++) {
        const int id = i * 32 + lane, r = id / 10, ch = id - r * 10;
        uint32_t y[4];
        lds128(y, stg + r * 176 + ch * 16);
        ((uint4*)out)[(size_t)(mb * 128 + w * 16 + r) * 80 + nb * 10 + ch] = add_bf8(rv[i], y);
    }
    fence_async_smem();
    __syncwarp();
    if (lane == 0) mbar_arrive(sb + G_BAR + (2 * GST - 1) * 8);
}

__global__ void __launch_bounds__(128, 4) k_col(const int first) {
    __shared__ __align__(1024) char sz[8192];
    __shared__ __align__(1024) char stab[24576];
    __shared__ __align__(1024) char swf[8192];
    __shared__ __align__(8) uint64_t bar[2];
    const int tid = threadIdx.x, wl = tid >> 5, lane = tid & 31, g = lane >> 2, t = lane & 3;
    const int c = blockIdx.x;
    TL(first ? 5 : 19);
    const bool realc = c == 0 || c == 320;
    const uint32_t z = smem_u32(sz), b2 = smem_u32(stab), a1 = b2 + 16384, wf = smem_u32(swf), mb = smem_u32(bar);
    if (tid == 0) { mbar_init(mb, 1); mbar_init(mb + 8, 1); fence_async_smem(); }
    if (realc) {
        for (int i = tid; i < 256; i += 128) sts128(z + 4096 + i * 16, 0, 0, 0, 0);
        fence_async_smem();
    }
    const int k1 = wl * 8 + g;
    float tc[16], ts[16];
#pragma unroll
    for (int j = 0; j < 16; j++) {
        const int p = ((j >> 1) * 8 + 2 * t + (j & 1)) * k1;
        __sincosf((float)(p - 1024) * 0.003067961575771282f, &ts[j], &tc[j]);
        ts[j] = -ts[j]; tc[j] = -tc[j];
    }
    if (first && tid == 32) { wait_flag<400>(g_ready, 128); fence_async_glb(); }
    __syncthreads();
    if (tid == 32) {
        mbar_expect(mb + 8, 24576 + 8192);
        bulk_g2s(b2, g_ctab, 24576, mb + 8);
        bulk_g2s(wf, g_Wf + (size_t)c * 2048, 8192, mb + 8);
    }
    float inv;
    const float wsc = pow2_scale(wfilter_max(lane), 0, &inv) * (realc ? 0.0625f : 0.125f);
    pdl_wait();
    TL(first ? 6 : 20);
    if (tid == 0) {
        const int by = realc ? 4096 : 8192;
        mbar_expect(mb, by);
        bulk_g2s_last(z, (const char*)g_UT + (size_t)(c == 320 ? 1 : 2 * c) * 4096, by, mb);
    }
    pdl_go();
    mbar_wait(mb + 8, 0);
    mbar_wait(mb, 0);
    float d[64];
    uint32_t a[4][4];
    wg_fence();
#pragma unroll
    for (int ks = 0; ks < 4; ks++) wg_n64_ss_tb<0>(d, mkdesc(a1 + ks * 2048, 1024, 128, 0), mkdesc(z + ks * 2048, 1024, 1024, 1), ks);
    wg_commit(); wg_wait<0>();
    const float r32 = 0.17677669529663687f;
#pragma unroll
    for (int j = 0; j < 8; j++) {
        float yr[2], yi[2];
#pragma unroll
        for (int e = 0; e < 2; e++) {
            const float re = d[j * 4 + e] * r32, im = d[j * 4 + 2 + e] * r32, cc = tc[j * 2 + e], ss = ts[j * 2 + e];
            yr[e] = re * cc + im * ss; yi[e] = im * cc - re * ss;
        }
        a[j >> 1][(j & 1) * 2] = pack_h(yr[0], yr[1]); a[j >> 1][(j & 1) * 2 + 1] = pack_h(yi[0], yi[1]);
    }
    wg_fence();
#pragma unroll
    for (int ks = 0; ks < 4; ks++) wg_n128_rs(d, a[ks], mkdesc(b2 + ks * 4096, 2048, 128, 0), ks);
    wg_commit(); wg_wait<0>();
#pragma unroll
    for (int q = 0; q < 4; q++) {
        uint32_t wv[4];
        lds128(wv, wf + tid * 64 + ((q ^ (tid >> 1)) & 3) * 16);
#pragma unroll
        for (int jj = 0; jj < 2; jj++) {
            const int j = 2 * q + jj;
            float yr[2], yi[2];
#pragma unroll
            for (int e = 0; e < 2; e++) {
                const float xr = d[j * 4 + e] + d[32 + j * 4 + 2 + e], xi = d[j * 4 + 2 + e] - d[32 + j * 4 + e];
                const float fr = bf_lo(wv[jj * 2 + e]) * wsc, fi = bf_hi(wv[jj * 2 + e]) * wsc;
                yr[e] = xr * fr - xi * fi; yi[e] = xr * fi + xi * fr;
            }
            a[q][jj * 2] = pack_h(yr[0], yr[1]); a[q][jj * 2 + 1] = pack_h(yi[0], yi[1]);
        }
    }
    wg_fence();
#pragma unroll
    for (int ks = 0; ks < 4; ks++) wg_n128_rs(d, a[ks], mkdesc(b2 + ks * 4096, 2048, 128, 0), ks);
    wg_commit(); wg_wait<0>();
#pragma unroll
    for (int j = 0; j < 8; j++) {
        float yr[2], yi[2];
#pragma unroll
        for (int e = 0; e < 2; e++) {
            const float vr = (d[j * 4 + e] - d[32 + j * 4 + 2 + e]) * 0.125f, vi = (d[j * 4 + 2 + e] + d[32 + j * 4 + e]) * 0.125f;
            const float cc = tc[j * 2 + e], ss = ts[j * 2 + e];
            yr[e] = vr * cc - vi * ss; yi[e] = vi * cc + vr * ss;
        }
        a[j >> 1][(j & 1) * 2] = pack_h(yr[0], yr[1]); a[j >> 1][(j & 1) * 2 + 1] = pack_h(yi[0], yi[1]);
    }
    __syncthreads();
    const int mm = lane >> 3, rr = lane & 7;
    const uint32_t rowo = (wl * 16 + (mm & 1) * 8 + rr) * 128;
#pragma unroll
    for (int q = 0; q < 4; q++) stsm4(z + rowo + (((2 * q + (mm >> 1)) ^ rr) << 4), a[q][0], a[q][1], a[q][2], a[q][3]);
    fence_async_smem();
    __syncthreads();
    wg_fence();
#pragma unroll
    for (int ks = 0; ks < 4; ks++) wg_n64_ss_tb<1>(d, mkdesc(a1 + ks * 256, 128, 1024, 0), mkdesc(z + ks * 2048, 1024, 1024, 1), ks);
    wg_commit(); wg_wait<0>();
#pragma unroll
    for (int q = 0; q < 4; q++)
        stsm4(wf + rowo + (((2 * q + (mm >> 1)) ^ rr) << 4), pack_h(d[q * 8] * r32, d[q * 8 + 1] * r32), pack_h(d[q * 8 + 2] * r32, d[q * 8 + 3] * r32),
              pack_h(d[q * 8 + 4] * r32, d[q * 8 + 5] * r32), pack_h(d[q * 8 + 6] * r32, d[q * 8 + 7] * r32));
    __syncwarp();
    if (!(realc && wl >= 2)) {
        const int kk = c == 320 ? 320 : (c & 1) * 160 + (c >> 1) + (wl >> 1) * 320;
#pragma unroll
        for (int i = 0; i < 4; i++) {
            const int r = wl * 16 + i * 4 + (lane >> 3), ch = lane & 7;
            uint32_t v[4];
            lds128(v, wf + r * 128 + ((ch ^ (r & 7)) << 4));
            ((uint4*)g_YT)[((size_t)(r & 31) * 640 + kk) * 8 + (ch ^ (kk & 7))] = make_uint4(v[0], v[1], v[2], v[3]);
        }
    }
    __syncthreads();
    if (tid == 0) red_release(g_flag + F_X + (first ? 0 : 128) + 65);
    TL(first ? 7 : 21);
}

constexpr int O_XS = 0;
constexpr int O_MS = 81920;
constexpr int O_QKP = O_MS + 10752;
constexpr int O_VM = O_QKP + 4096;
constexpr int O_SC = O_VM + 4096;
constexpr int O_OS = O_SC + 1536;
constexpr int O_XCH = O_OS + 2048;
constexpr int O_SUM = O_XCH + 8192;
constexpr int O_MX = O_SUM + 256;
constexpr int O_STG = O_MS + 65536 - 8192;
static_assert(O_STG - 16384 >= O_MX + 1024, "shared-memory map");
constexpr int O_WO = O_STG + 16384;
constexpr int O_SCL = O_WO + 65536;
constexpr int O_BAR = O_SCL + 64;
constexpr int B_XF = O_BAR, B_S = O_BAR + 16, B_GO = O_BAR + 24, B_VX = O_BAR + 32, B_STG = O_BAR + 48, B_FREE = O_BAR + 72;
constexpr int T_FA = O_BAR + 96, T_EA = T_FA + 32, T_FB = T_EA + 32, T_EB = T_FB + 56, T_RED = T_EB + 32;
constexpr int O_WMX = O_BAR + 512, B_W = O_BAR + 64;
constexpr int O_LAST = (O_WMX + 192 + 1023) / 1024 * 1024;
constexpr int CH_SMEM = O_LAST + 8192;
static_assert(O_WO == 19 * 8192, "weight staging");
__device__ __forceinline__ uint32_t tail_b(int c) { return c % 7 < 4 ? O_XS + (c % 7) * 20480 : O_WO + (c % 7 - 4) * 20480; }
constexpr int S_TX = 2 * 768 + 2048;

#define NPERM 1
#define NWO0 2
#define NWO1 6
#define XEARLY 0
#define RELAX 1
#define VEARLY 0
#define VLATE 0
#define KVB 1
#define REL1 0
#define XLATE 0
#define TDELAY 800
#define WDEPTH 6
#define RDELAY 580

#define STAMP(i)

#define NTA 23
#define NTB 26
template <int LO, int HI>
__device__ __forceinline__ void tok_issue(const uint32_t (&A0)[20][4], const uint32_t (&A1)[20][4], float (&b0)[16], float (&b1)[16], uint32_t xd,
                                          const uint32_t zero) {
    if (LO == 0) wg_fence();
    sfor<HI - LO>([&](auto I) {
        constexpr int i = LO + I;
        if constexpr (i < 20) wg_n32_x<i * 64, i>(b0, A0[i], xd); else wg_n32_x<(i - 20) * 64, i - 20>(b1, A1[i - 20], xd + zero);
        if constexpr (i == 19 || i == NTB - 1 || i == 39) wg_commit();
    });
}
__device__ __forceinline__ void tok_give(const float (&b0)[16], const uint32_t L16, const uint32_t xch0) {
    wg_wait<1>();
    sfor<2>([&](auto I) {
        constexpr int i = I;
        sts128_u<i * 512>(L16, xch0, pack_h(b0[8 * i], b0[8 * i + 1]), pack_h(b0[8 * i + 2], b0[8 * i + 3]), pack_h(b0[8 * i + 4], b0[8 * i + 5]),
                          pack_h(b0[8 * i + 6], b0[8 * i + 7]));
    });
}
__device__ __forceinline__ void tok_finish(float (&b1)[16], const uint32_t (&e)[2][4], const uint32_t L16, const uint32_t dst, const uint32_t idn) {
#pragma unroll
    for (int j = 0; j < 4; j++)
        asm volatile("mma.sync.aligned.m16n8k8.row.col.f32.f16.f16.f32 {%0,%1,%2,%3},{%4,%5},{%6},{%0,%1,%2,%3};"
                     : F4(b1, 4 * j) : "r"(e[j >> 1][(j & 1) * 2]), "r"(e[j >> 1][(j & 1) * 2 + 1]), "r"(idn));
    stsm4_u<0>(L16, dst, pack_bf(b1[0], b1[1]), pack_bf(b1[2], b1[3]), pack_bf(b1[4], b1[5]), pack_bf(b1[6], b1[7]));
    stsm4_u<512>(L16, dst, pack_bf(b1[8], b1[9]), pack_bf(b1[10], b1[11]), pack_bf(b1[12], b1[13]), pack_bf(b1[14], b1[15]));
}
__device__ __forceinline__ uint32_t uni(uint32_t v) { return __shfl_sync(~0u, v, 0); }
__device__ __forceinline__ uint32_t badd(uint32_t a, uint32_t b) { uint32_t r; asm("add.rn.bf16x2 %0,%1,%2;" : "=r"(r) : "r"(a), "r"(b)); return r; }
__device__ __forceinline__ uint32_t bmax(uint32_t a, uint32_t b) { uint32_t r; asm("max.bf16x2 %0,%1,%2;" : "=r"(r) : "r"(a), "r"(b)); return r; }
__device__ __forceinline__ uint32_t babsmax(uint32_t a, uint32_t b) { uint32_t r; asm("max.xorsign.abs.bf16x2 %0,%1,%2;" : "=r"(r) : "r"(a), "r"(b)); return r; }
__device__ __forceinline__ uint32_t habsmax(uint32_t a, uint32_t b) { uint32_t r; asm("max.xorsign.abs.f16x2 %0,%1,%2;" : "=r"(r) : "r"(a), "r"(b)); return r; }

template <int NPF>
__device__ __forceinline__ float mem_out(const uint32_t sb, const uint32_t L16, const uint32_t L8, uint32_t (&wo)[16][4], const uint32_t woa,
                                         char* dst, const bool odd) {
    bar_sync(2, 352);
    float a[4][4];
#pragma unroll
    for (int i = 0; i < 4; i++) a[i][0] = a[i][1] = a[i][2] = a[i][3] = 0.f;
    uint32_t ob[4][4], sm_[2], sc[2];
    sfor<8>([&](auto I) {
        constexpr int i = I;
        if constexpr (!(i & 1)) ldsm4t_u<O_OS + (i >> 1) * 512>(ob[i >> 1], L16, sb);
        if constexpr (i >= NPF) { ldsm4t(wo[i], woa + i * 1024); ldsm4t(wo[8 + i], (woa ^ 32) + i * 1024); }
    });
    lds64_u<O_SUM>(sm_, L8 & 24, sb); lds64(sc, sb + O_SCL);
#pragma unroll
    for (int i = 0; i < 8; i++) {
        mma_bf(a[i & 1], wo[i][0], wo[i][1], wo[i][2], wo[i][3], ob[i >> 1][(i & 1) * 2], ob[i >> 1][(i & 1) * 2 + 1]);
        mma_bf(a[2 + (i & 1)], wo[8 + i][0], wo[8 + i][1], wo[8 + i][2], wo[8 + i][3], ob[i >> 1][(i & 1) * 2], ob[i >> 1][(i & 1) * 2 + 1]);
    }
    const float f0 = rcp(__uint_as_float(sm_[0])) * __uint_as_float(sc[0]), f1 = rcp(__uint_as_float(sm_[1])) * __uint_as_float(sc[0]);
    red_h8(dst, pack_h((a[0][0] + a[1][0]) * f0, (a[0][1] + a[1][1]) * f1), pack_h((a[0][2] + a[1][2]) * f0, (a[0][3] + a[1][3]) * f1),
           pack_h((a[2][0] + a[3][0]) * f0, (a[2][1] + a[3][1]) * f1), pack_h(odd ? (a[2][3] + a[3][3]) * f1 : (a[2][2] + a[3][2]) * f0, 1.f));
    return __uint_as_float(sc[1]);
}

__device__ __forceinline__ void chain_mma(const uint32_t sb, const int c, const int h, const int layer, const uint32_t zero, const bf16* __restrict__ Wq,
                                          const bf16* __restrict__ Wk, const bf16* __restrict__ Wv, const bf16* __restrict__ Wo,
                                          const bf16* res, bf16* out) {
    int tid = read_tid(), lane = tid & 31;
    const int w = __shfl_sync(~0u, tid >> 5, 0), wg = w >> 2;
    [[maybe_unused]] const int cta = h * 3 + c;
    uint32_t A0[20][4], A1[20][4];
    const int t0 = (w & 3) + wg * 4, t1 = t0 ^ 4;
    float sl;
    {
        const int tl = tid & 127, r = tl >> 3, ch = tl & 7;
        const size_t so = (size_t)(wg * 320 + r) * 4096 + h * 128 + ch * 8;
        const bf16 *wa = (c == 2 ? Wv : Wq + c * 64) + so, *wb = (c == 2 ? Wv + 64 : Wk + c * 64) + so;
        const uint32_t ring = sb + wg * 4096;
        const uint32_t dst = ring + r * 128 + ((ch ^ r) & 7) * 16;
        const uint32_t src = ring + ((lane & 7) + (lane >> 4) * 8) * 128 + ((((w & 3) * 2 + ((lane >> 3) & 1)) ^ lane) & 7) * 16;
        const int q4 = lane & 3, gr = (c * 2 + ((w >> 1) & 1)) * 56 + (q4 == 3 ? 24 : (w & 1) * 32 + q4 * 8);
        const bf16* wo_ = Wo + (size_t)(h * 128 + (lane >> 2)) * 640 + wg * 320 + min(gr, 312);
        const uint32_t wdst = sb + O_WO + w * 8192 + (lane >> 2) * 64 + ((q4 ^ (lane >> 3)) & 3) * 16;
        auto issue = [&](int i) {
            if (i < 20) {
                const uint32_t d = dst + (i < 19 ? i * 8192 : O_LAST);
                cp_async16(d, wa + (size_t)i * 65536); cp_async16(d + 2048, wb + (size_t)i * 65536);
                if (i < 16) cp_async16(wdst + i * 512, wo_ + i * 5120, gr < 320 ? 16 : 0);
            }
            cp_commit();
        };
#pragma unroll 1
        for (int i = 0; i < WDEPTH; i++) issue(i);
        asm volatile("barrier.cluster.arrive.relaxed.aligned;" ::: "memory");
        float fa, fb;
        if (layer == 0) {
            uint32_t ma = 0, mb = 0;
#pragma unroll 1
            for (int i = 0; i < 20; i++) {
                issue(i + WDEPTH);
                cp_wait<WDEPTH>();
                const uint32_t d = dst + (i < 19 ? i * 8192 : O_LAST);
                uint32_t u[8];
                lds128(u, d); lds128(u + 4, d + 2048);
                ma = babsmax(babsmax(ma, babsmax(u[0], u[1])), babsmax(u[2], u[3])); mb = babsmax(babsmax(mb, babsmax(u[4], u[5])), babsmax(u[6], u[7]));
            }
            ma = __reduce_max_sync(~0u, max(ma & 0x7fffu, (ma >> 16) & 0x7fffu)); mb = __reduce_max_sync(~0u, max(mb & 0x7fffu, (mb >> 16) & 0x7fffu));
            asm volatile("barrier.cluster.wait.aligned;" ::: "memory");
            if (lane < 3)
                asm volatile("st.async.shared::cluster.mbarrier::complete_tx::bytes.v2.b32 [%0],{%1,%2},[%3];"
                             ::"r"(mapa(sb + O_WMX + (c * 8 + w) * 8, lane)), "r"(ma), "r"(mb), "r"(mapa(sb + B_W, lane)) : "memory");
            mbar_wait(sb + B_W, 0);
            uint32_t v[2];
            lds64(v, sb + O_WMX + (lane < 24 ? lane : 0) * 8);
            const bool mine = (lane >> 3) < 3 && ((lane >> 4) == 1) == (c == 2);
            ma = __reduce_max_sync(~0u, mine ? v[0] : 0u); mb = __reduce_max_sync(~0u, mine ? v[1] : 0u);
            if (c == 2) ma = mb = max(ma, mb);
            fa = __uint_as_float(ma << 16); fb = __uint_as_float(mb << 16);
            if (tid == 0) {
                if (c != 1) g_wmx[h * 3 + c] = fa;
                if (c == 0) g_wmx[h * 3 + 1] = fb;
            }
        } else {
            fa = __ldcg(g_wmx + h * 3 + (c == 2 ? 2 : 0)); fb = __ldcg(g_wmx + h * 3 + (c == 2 ? 2 : 1));
            asm volatile("barrier.cluster.wait.aligned;" ::: "memory");
        }
        if (layer == TLL) TL(49);
        float ia, ib;
        const float sa = pow2_scale(fa, 6, &ia), sc_b = pow2_scale(fb, 6, &ib);
        sl = __uint_as_float(uni(__float_as_uint(ia * ib * (0.08838834764831845f * 1.4426950408889634f))));
        const uint32_t pa = pack_bf(sa, sa), pb = pack_bf(sc_b, sc_b);
        const int ahead = layer == 0 ? 20 : WDEPTH;
        auto convert = [&](int lo) {
#pragma unroll 1
            for (int i = lo; i < lo + 10; i++) {
                issue(i + ahead);
                cp_wait<WDEPTH>();
                const uint32_t d = dst + (i < 19 ? i * 8192 : O_LAST);
                uint32_t u[8];
                lds128(u, d); lds128(u + 4, d + 2048);
#pragma unroll
                for (int q = 0; q < 8; q++)
                    asm("{.reg .b32 m,l,u; mul.rn.bf16x2 m,%0,%1; shl.b32 l,m,16; and.b32 u,m,0xffff0000; cvt.rn.f16x2.f32 %0,u,l;}" : "+r"(u[q]) : "r"(q < 4 ? pa : pb));
                sts128(d, u[0], u[1], u[2], u[3]); sts128(d + 2048, u[4], u[5], u[6], u[7]);
            }
            bar_sync(6 + wg, 128);
        };
        const uint32_t s0 = src + wg * 2048, s1 = src + 2048 - wg * 2048;
        convert(0);
#pragma unroll
        for (int i = 0; i < 10; i++) { ldsm4t(A0[i], s0 + i * 8192); ldsm4t(A1[i], s1 + i * 8192); }
        if (layer == TLL) TL(50);
        convert(10);
#pragma unroll
        for (int i = 10; i < 20; i++) { ldsm4t(A0[i], s0 + (i < 19 ? i * 8192 : O_LAST)); ldsm4t(A1[i], s1 + (i < 19 ? i * 8192 : O_LAST)); }
        if (layer == TLL) TL(53);
        if (layer == 0) {
            uint32_t off[4];
            float cs[4] = {0.f, 0.f, 0.f, 0.f};
#pragma unroll
            for (int q = 0; q < 4; q++) {
                const int g_ = (c * 2 + ((w >> 1) & 1)) * 56 + (q == 3 ? 24 : (w & 1) * 32 + q * 8), col = wg * 320 + g_, nb = col / 80;
                off[q] = g_ < 320 && !(q == 3 && (w & 1)) ? ((nb * 512 + h * 16) * 10 + (col - nb * 80) / 8) * 32 + lane : ~0u;
            }
            const uint32_t ta = sb + O_WO + w * 8192 + (lane & 7) * 64 + (((lane >> 3) ^ (lane >> 1)) & 3) * 16;
#pragma unroll 2
            for (int i = 0; i < 16; i++) {
                uint32_t r[4];
                ldsm4t(r, ta + i * 512);
#pragma unroll
                for (int q = 0; q < 4; q++) {
                    if (off[q] != ~0u) ((uint32_t*)g_wot)[off[q] + i * 320] = r[q];
                    cs[q] += fabsf(bf_lo(r[q])) + fabsf(bf_hi(r[q]));
                }
            }
            float cm = 0.f;
#pragma unroll
            for (int q = 0; q < 4; q++) {
                cs[q] += __shfl_xor_sync(~0u, cs[q], 1); cs[q] += __shfl_xor_sync(~0u, cs[q], 2);
                cm = fmaxf(cm, cs[q]);
            }
            const uint32_t n1 = __reduce_max_sync(~0u, __float_as_uint(cm));
            if (lane == 0) g_co[h * 32 + c * 8 + w] = __uint_as_float(n1);
        }
        bar_sync(9, 256);
        if (tid == 0) red_release(g_flag + F_W + layer * 128);
        bar_sync(4, 288);
        asm volatile("barrier.cluster.arrive.relaxed.aligned;" ::: "memory");
    }
    const uint32_t idn = (lane >> 3) == (lane & 3) ? ((lane & 4) ? 0x3c000000u : 0x3c00u) : 0u;
    float invM = g_invM0;
    char* redp = red_base() + (size_t)layer * 32 * 32768 + w * 2048 + (lane >> 4) * 1024 + ((lane >> 3) & 1) * 256 + (lane & 7) * 16;
    const uint32_t ro2 = uni((w >> 1) * 4096 + 128), rown = uni(c == 2 ? ro2 : c * 16384);
    const uint32_t L16 = lane * 16, L8 = lane * 8, L4 = lane * 4;
    const uint32_t xch0 = uni(sb + O_XCH + t0 * 1024), xch1 = uni(sb + O_XCH + t1 * 1024);
    const uint32_t qo0 = uni(sb + O_QKP + (w & 3) * 1024 + (wg ? 768 : 0)), qp0 = uni(qo0 + (wg ? 128 : 256));
    const uint32_t qo1 = uni(sb + O_QKP + (w & 3) * 1024 + (wg ? 128 : 512)), qp1 = uni(qo1 + (wg ? 256 : 128));
    const uint32_t vo1 = uni(qo1 + (wg ? -128 : 256)), vp1 = uni(qp1 + (wg ? -128 : 256));
    const uint32_t msr = uni(sb + O_MS + wg * 5376);
    const uint32_t msw = uni(msr + ((w >> 1) & 1) * 896 + (w & 1) * 512), msh = uni(msr + ((w >> 1) & 1) * 896 + 384 + (w & 1) * 2);
    const uint32_t sco = uni(sb + O_SC + c * 768 + (w & 3) * 256);
    const uint32_t woa = sb + O_WO + w * 8192 + (lane >> 4) * 512 + (lane & 7) * 64 + (((lane >> 3) ^ (lane >> 1)) & 1) * 16 + ((lane >> 2) & 1) * 32;
    const uint32_t w512 = uni(sb + w * 512), w128 = uni(sb + w * 128);
    const bool scw = c < 2 && w >= 4 && w <= 6;
    uint32_t sn = uni(sb + O_STG + (c == 2 ? 8192 : 0) + t1 * 1024);
    uint32_t ka = uni(sb + (w == 6 ? O_QKP + 512 : O_STG + 4096 + (w & 1) * 512));
    uint32_t vs = uni(sb + O_VM + t1 * 256);
    uint32_t va = uni(sb + O_STG + 8192 + w * 2048), vr = uni(sb + O_VM + w * 512);
    const uint32_t sn2 = uni(2 * sn - 16384), ka2 = uni(2 * ka - (w == 6 ? 0 : 16384)), vs2 = uni(2 * vs + 2048), va2 = uni(2 * va - 16384),
                   vr2 = uni(2 * vr + 2048);
    uint32_t xd = uni((uint32_t)mkdesc(sb + O_XS + wg * 20480, 512, 128, 0));
    const uint32_t xd2 = uni(2 * xd + 2560);

    uint32_t wp[2 * NPERM + 1][4];
    sfor<NPERM>([&](auto I) { constexpr int i = I; ldsm4t(wp[2 * i], woa + i * 1024); ldsm4t(wp[2 * i + 1], (woa ^ 32) + i * 1024); });
    auto wo_fetch = [&](uint32_t (&wo)[16][4], auto I) {
        constexpr int i = I;
        if constexpr (i < NPERM) {
#pragma unroll
            for (int q = 0; q < 4; q++) { wo[i][q] = wp[2 * i][q]; wo[8 + i][q] = wp[2 * i + 1][q]; }
        } else { ldsm4t(wo[i], woa + i * 1024); ldsm4t(wo[8 + i], (woa ^ 32) + i * 1024); }
    };
    if (layer == TLL) TL(32);
    float b0[16], b1[16];
    mbar_wait(sb + B_XF, 0);
    if (layer == TLL) TL(33);
    tok_issue<0, NTB>(A0, A1, b0, b1, xd, zero);
    tok_give(b0, L16, xch0);
    tok_issue<NTB, 40>(A0, A1, b0, b1, xd, zero);
    bar_sync(4, 256);
    wg_wait<0>();
    {
        uint32_t e[2][4];
        lds128_u<0>(e[0], L16, xch1); lds128_u<512>(e[1], L16, xch1);
        tok_finish(b1, e, L16, sn, idn);
    }
    sn = sn2 - sn; xd = xd2 - xd;
    bar_sync(5, 288);
    asm volatile("barrier.cluster.wait.aligned;" ::: "memory");
    if (layer == TLL) TL(34);
    mbar_wait(sb + B_XF + 8, 0);
    if (layer == TLL) TL(35);
    tok_issue<0, NTA>(A0, A1, b0, b1, xd, zero);
    uint32_t tr = clock32() - RDELAY;

#pragma unroll 1
    for (int st = 0;; st++) {
        uint4 mv[3];
        asm volatile("{.reg .pred p; .reg .b32 t;\n"
                     "mov.b32 %0,0; mov.b32 %1,0; mov.b32 %2,0; mov.b32 %3,0; mov.b32 %4,0; mov.b32 %5,0; mov.b32 %6,0; mov.b32 %7,0;\n"
                     "mov.b32 %8,0; mov.b32 %9,0; mov.b32 %10,0; mov.b32 %11,0;\n"
                     "T_LOOP: mov.u32 t,%%clock; sub.u32 t,t,%14; setp.ge.u32 p,t,%15;\n"
                     "@p ld.relaxed.gpu.global.v4.u32 {%0,%1,%2,%3},[%12]; @p ld.relaxed.gpu.global.v4.u32 {%4,%5,%6,%7},[%12+16384];\n"
                     "@p ld.relaxed.gpu.global.v4.u32 {%8,%9,%10,%11},[%13];\n"
                     "@!p bra T_LOOP;}"
                     : "=r"(mv[0].x), "=r"(mv[0].y), "=r"(mv[0].z), "=r"(mv[0].w), "=r"(mv[1].x), "=r"(mv[1].y), "=r"(mv[1].z), "=r"(mv[1].w),
                       "=r"(mv[2].x), "=r"(mv[2].y), "=r"(mv[2].z), "=r"(mv[2].w)
                     : "l"(redp), "l"(redp + ro2), "r"(tr), "n"(RDELAY) : "memory");
        STAMP(10);
        tok_issue<NTA, NTB>(A0, A1, b0, b1, xd, zero);
        tok_give(b0, L16, xch0);
        tok_issue<NTB, 40>(A0, A1, b0, b1, xd, zero);
        xd = xd2 - xd;
        STAMP(9);
        if (zero >> 30) break;
        asm volatile("{.reg .pred p; .reg .b32 a,h,t,n; .reg .b16 l,u; .reg .b64 q;\n"
                     "add.u32 a,%12,%13; add.u32 h,%12,%14; mov.u32 n,0;\n"
                     "M_LOOP:\n .pragma \"nounroll\";\n"
                     "st.shared.b32 [a],%0; st.shared.b32 [a+128],%1; st.shared.b32 [a+256],%2; mov.b32 {l,u},%3; st.shared.b16 [h],l;\n"
                     "st.shared.b32 [a+1792],%4; st.shared.b32 [a+1920],%5; st.shared.b32 [a+2048],%6; mov.b32 {l,u},%7; st.shared.b16 [h+1792],l;\n"
                     "st.shared.b32 [a+3584],%8; st.shared.b32 [a+3712],%9; st.shared.b32 [a+3840],%10; mov.b32 {l,u},%11; st.shared.b16 [h+3584],l;\n"
                     "lop3.b32 t,%3,%7,0x50000000,0x7e; lop3.b32 t,t,%11,0x50000000,0xf6; setp.gt.u32 p,t,0xffff;\n"
                     "vote.sync.any.pred p,p,-1; add.u32 n,n,1; setp.lt.and.u32 p,n,%17,p; @!p bra M_DONE;\n"
                     "ld.relaxed.gpu.global.v4.u32 {%0,%1,%2,%3},[%15]; ld.relaxed.gpu.global.v4.u32 {%4,%5,%6,%7},[%15+16384];\n"
                     "cvt.u64.u32 q,%16; add.u64 q,q,%15; ld.relaxed.gpu.global.v4.u32 {%8,%9,%10,%11},[q];\n"
                     "bra M_LOOP;\n"
                     "M_DONE:}"
                     : "+r"(mv[0].x), "+r"(mv[0].y), "+r"(mv[0].z), "+r"(mv[0].w), "+r"(mv[1].x), "+r"(mv[1].y), "+r"(mv[1].z), "+r"(mv[1].w),
                       "+r"(mv[2].x), "+r"(mv[2].y), "+r"(mv[2].z), "+r"(mv[2].w)
                     : "r"(L4), "r"(msw), "r"(msh), "l"(redp), "r"(ro2), "n"(SPIN_LIM) : "memory");
        bar_sync(3, 256);
        STAMP(0);
        uint32_t e[2][4];
        float f1[4];
        {
            uint32_t b[10][4];
            float acc[4][4];
#pragma unroll
            for (int i = 0; i < 4; i++) acc[i][0] = acc[i][1] = acc[i][2] = acc[i][3] = 0.f;
            auto ld = [&](auto I) { constexpr int i = I; ldsm4t_u<i * 512>(b[i], L16, msr); };
            auto mm = [&](auto I) {
                constexpr int i = I;
                mma_f16(acc[0], A0[2 * i], b[i][0], b[i][1]); mma_f16(acc[2], A1[2 * i], b[i][0], b[i][1]);
                mma_f16(acc[1], A0[2 * i + 1], b[i][2], b[i][3]); mma_f16(acc[3], A1[2 * i + 1], b[i][2], b[i][3]);
            };
            ld(IC<0>()); ld(IC<1>()); ld(IC<2>()); ld(IC<3>());
            sts32_u<O_MX>(L4, w128,
                          habsmax(habsmax(habsmax(habsmax(mv[0].x, mv[0].y), habsmax(mv[0].z, mv[1].x)), habsmax(habsmax(mv[1].y, mv[1].z), mv[2].x)),
                                  habsmax(habsmax(mv[2].y, mv[2].z), habsmax(habsmax(mv[0].w, mv[1].w), mv[2].w) & 0xffffu)));
            wg_wait<0>();
            ld(IC<4>()); mm(IC<0>()); ld(IC<5>()); mm(IC<1>()); ld(IC<6>()); mm(IC<2>());
            ld(IC<7>()); mm(IC<3>()); ld(IC<8>()); mm(IC<4>()); ld(IC<9>()); mm(IC<5>());
            lds128_u<0>(e[0], L16, xch1); lds128_u<512>(e[1], L16, xch1);
            mm(IC<6>()); mm(IC<7>()); mm(IC<8>()); mm(IC<9>());
            const uint32_t u0 = pack_bf((acc[0][0] + acc[1][0]) * invM, (acc[0][1] + acc[1][1]) * invM);
            const uint32_t u1 = pack_bf((acc[0][2] + acc[1][2]) * invM, (acc[0][3] + acc[1][3]) * invM);
#pragma unroll
            for (int i = 0; i < 4; i++) f1[i] = (acc[2][i] + acc[3][i]) * invM;
            sts32_u<0>(L4, qo0, u0); sts32_u<0>(L4, qp0, u1); sts32_u<0>(L4, qo1, pack_bf(f1[0], f1[1])); sts32_u<0>(L4, qp1, pack_bf(f1[2], f1[3]));
        }
        STAMP(1);
        bar_sync(1, 320);
        if (__builtin_expect(scw, 1)) {
            float a[4][4];
#pragma unroll
            for (int i = 0; i < 4; i++) a[i][0] = a[i][1] = a[i][2] = a[i][3] = 0.f;
            uint32_t q[4][4], k[4][4];
            sfor<4>([&](auto I) {
                constexpr int i = I;
                ldsm4t_u<O_QKP + i * 1024>(q[i], L16, sb); ldsm4t_u<i * 1024>(k[i], L16, ka);
            });
#pragma unroll
            for (int i = 0; i < 4; i++) {
                mma_bf(a[i & 1], q[i][0], q[i][1], q[i][2], q[i][3], k[i][0], k[i][1]);
                mma_bf(a[2 + (i & 1)], q[i][0], q[i][1], q[i][2], q[i][3], k[i][2], k[i][3]);
            }
            const float mk = w == 6 ? 1.f : 0.f;
            const float x0 = (a[0][0] + a[0][2]) + (a[1][0] + a[1][2]), x1 = (a[0][1] + a[0][3]) + (a[1][1] + a[1][3]);
            const float y0 = (a[2][0] + a[2][2]) + (a[3][0] + a[3][2]), y1 = (a[2][1] + a[2][3]) + (a[3][1] + a[3][3]);
            st_async2_x3(L8, sco, sb + B_S, pack_bf(fmaf(y0, mk, x0) * sl, fmaf(y1, mk, x1) * sl), pack_bf(y0 * sl, y1 * sl));
        }
        if (c == 2) {
            const uint32_t x = lds32_u<0>(L4, vo1), y = lds32_u<0>(L4, vp1);
            st_async2_x3(L8, vs, sb + B_S, pack_bf(f1[0] + bf_lo(x), f1[1] + bf_hi(x)), pack_bf(f1[2] + bf_lo(y), f1[3] + bf_hi(y)));
        }
        STAMP(3);
        if (st == NSEG - 1) break;
        tok_finish(b1, e, L16, sn, idn);
        redp += (st & 1) ? 32768 - 512 : 512;
        if (wg == 0) {
            uint32_t wo[16][4], vx[2][2][4], vm[2][2];
            ldsm4_u<0>(vx[0][0], L16, va); ldsm4_u<512>(vx[0][1], L16, va); ldsm4_u<1024>(vx[1][0], L16, va); ldsm4_u<1536>(vx[1][1], L16, va);
            sfor<NWO0>([&](auto I) { wo_fetch(wo, I); });
            mbar_wait(sb + B_S, st & 1);
            STAMP(4);
            uint32_t s[5];
            {
                uint32_t p[2][5];
                sfor<2>([&](auto R) {
                    constexpr int r = R;
                    lds64_u<O_SC + r * 768>(p[r], L8, sb); lds64_u<O_SC + r * 768 + 256>(p[r] + 2, L8, sb); p[r][4] = lds32_u<O_SC + r * 768 + 512>(L8, sb);
                });
#pragma unroll
                for (int j = 0; j < 5; j++) s[j] = badd(p[0][j], p[1][j]);
            }
            lds64_u<0>(vm[0], L8, vr); lds64_u<256>(vm[1], L8, vr);
            uint32_t mm = bmax(bmax(bmax(s[0], s[1]), bmax(s[2], s[3])), s[4]);
            mm = bmax(bmax(mm, __shfl_xor_sync(~0u, mm, 1)), bmax(__shfl_xor_sync(~0u, mm, 2), __shfl_xor_sync(~0u, mm, 3)));
            const float m = fmaxf(bf_lo(mm), bf_hi(mm));
            float o0[4] = {0.f, 0.f, 0.f, 0.f}, o1[4] = {0.f, 0.f, 0.f, 0.f}, d[10];
#pragma unroll
            for (int j = 0; j < 5; j++) { d[2 * j] = bf_lo(s[j]) - m; d[2 * j + 1] = bf_hi(s[j]) - m; }
#pragma unroll
            for (int j = 0; j < 10; j++) d[(j + 8) % 10] = ex2(d[(j + 8) % 10]);
            float sum = ((d[8] + d[9]) + (d[0] + d[1])) + ((d[2] + d[3]) + (d[4] + d[5])) + (d[6] + d[7]);
            const uint32_t p4 = pack_bf(d[8], d[9]), p0 = pack_bf(d[0], d[1]), p1 = pack_bf(d[2], d[3]), p2 = pack_bf(d[4], d[5]), p3 = pack_bf(d[6], d[7]);
            mma_bf8(o0, vm[0][0], vm[0][1], p4);
            mma_bf8(o1, vm[1][0], vm[1][1], p4);
            mma_bf(o0, vx[0][0][0], vx[0][0][1], vx[0][0][2], vx[0][0][3], p0, p1);
            mma_bf(o1, vx[1][0][0], vx[1][0][1], vx[1][0][2], vx[1][0][3], p0, p1);
            mma_bf(o0, vx[0][1][0], vx[0][1][1], vx[0][1][2], vx[0][1][3], p2, p3);
            mma_bf(o1, vx[1][1][0], vx[1][1][1], vx[1][1][2], vx[1][1][3], p2, p3);
            sum += __shfl_xor_sync(~0u, sum, 1);
            sum += __shfl_xor_sync(~0u, sum, 2);
            sts32_u<O_OS>(L4, w512, pack_bf(o0[0], o0[1])); sts32_u<O_OS + 128>(L4, w512, pack_bf(o0[2], o0[3]));
            sts32_u<O_OS + 256>(L4, w512, pack_bf(o1[0], o1[1])); sts32_u<O_OS + 384>(L4, w512, pack_bf(o1[2], o1[3]));
            sts32_u<O_SUM>(lane & 28, sb, __float_as_uint(sum));
            STAMP(5);
            invM = mem_out<NWO0>(sb, L16, L8, wo, woa, redp + rown, w & 1);
            tr = clock32();
        } else {
            uint32_t wo[16][4];
            sfor<NWO1>([&](auto I) { wo_fetch(wo, I); });
            invM = mem_out<NWO1>(sb, L16, L8, wo, woa, redp + rown, w & 1);
            tr = clock32();
        }
        STAMP(7);
        tok_issue<0, NTA>(A0, A1, b0, b1, xd, zero);
        sn = sn2 - sn; ka = ka2 - ka; vs = vs2 - vs; va = va2 - va; vr = vr2 - vr;
        STAMP(8);
    }
    if (layer == TLL) TL(40);
    bar_arrive(8, 320);
    tid = read_tid(); lane = tid & 31;
    float acc[40];
    const int nc = c == 2 ? 10 : 11;
#pragma unroll 1
    for (int k = 0; k < nc; k++) {
        mbar_wait(sb + T_FB + (k % 7) * 8, k >= 7);
        mbar_wait(sb + T_FA + (k & 3) * 8, (k >> 2) & 1);
        if (layer == TLL && k == 0) TL(41);
        const uint64_t da = mkdesc(sb + O_MS + (k & 3) * 16384 + wg * 8192, 1024, 128, 0), db = mkdesc(sb + tail_b(k) + wg * 10240, 1280, 128, 0);
        wg_fence();
#pragma unroll
        for (int q = 0; q < 4; q++) wg_n80_ss(acc, da + q * 128, db + q * 160, k | q);
        wg_commit();
        if (k > 0) {
            wg_wait<1>();
            if (lane == 0) { mbar_arrive(sb + T_EA + ((k - 1) & 3) * 8); if (k <= 4) mbar_arrive(sb + T_EB + (k - 1) * 8); }
        }
    }
    if (layer == TLL) TL(52);
    const int mb = 28 + (h >> 3), nj = c == 2 ? 1 : 2;
    uint32_t rv[2][2];
    const size_t go = ((size_t)(mb * 64 + (w & 3) * 16 + (lane >> 2)) * 640 + (h & 7) * 80 + (wg * 5 + c * 2) * 8 + (lane & 3) * 2) >> 1;
#pragma unroll
    for (int u = 0; u < 4; u++) rv[u >> 1][u & 1] = (u >> 1) < nj ? __ldcg((const uint32_t*)res + go + (u >> 1) * 4 + (u & 1) * 2560) : 0u;
    wg_wait<0>();
    asm volatile("barrier.cluster.arrive.relaxed.aligned; barrier.cluster.wait.aligned;" ::: "memory");
    const uint32_t ra = sb + O_XS + tid * 16, rb = sb + O_MS + tid * 16;
#pragma unroll
    for (int j = 0; j < 5; j++) {
        const float* q = acc + 4 * j;
        sts128(rb + j * 4096, __float_as_uint(wg ? q[0] : q[20]), __float_as_uint(wg ? q[1] : q[21]), __float_as_uint(wg ? q[2] : q[22]), __float_as_uint(wg ? q[3] : q[23]));
    }
    bar_sync(4, 256);
#pragma unroll
    for (int j = 0; j < 5; j++) {
        const float* q = acc + 4 * j;
        uint32_t p[4];
        lds128(p, sb + O_MS + (tid ^ 128) * 16 + j * 4096);
        asm volatile("st.async.shared::cluster.mbarrier::complete_tx::bytes.v4.f32 [%0],{%1,%2,%3,%4},[%5];" ::"r"(mapa(ra + c * 8192 + (j & 1) * 4096, j >> 1)),
                     "f"((wg ? q[20] : q[0]) + __uint_as_float(p[0])), "f"((wg ? q[21] : q[1]) + __uint_as_float(p[1])),
                     "f"((wg ? q[22] : q[2]) + __uint_as_float(p[2])), "f"((wg ? q[23] : q[3]) + __uint_as_float(p[3])), "r"(mapa(sb + T_RED, j >> 1)) : "memory");
    }
    mbar_wait(sb + T_RED, 0);
#pragma unroll 1
    for (int u = 0; u < nj; u++) {
        uint32_t p[3][4];
#pragma unroll
        for (int q = 0; q < 3; q++) lds128(p[q], ra + q * 8192 + u * 4096);
        float y[4];
#pragma unroll
        for (int i = 0; i < 4; i++) y[i] = __uint_as_float(p[0][i]) + __uint_as_float(p[1][i]) + __uint_as_float(p[2][i]);
        ((uint32_t*)out)[go + u * 4] = bfma(pack_bf(y[0], y[1]), 0x3f803f80u, u ? rv[1][0] : rv[0][0]);
        ((uint32_t*)out)[go + u * 4 + 2560] = bfma(pack_bf(y[2], y[3]), 0x3f803f80u, u ? rv[1][1] : rv[0][1]);
    }
    TL(layer == 0 ? 15 : 29);
    asm volatile("barrier.cluster.arrive.relaxed.aligned; barrier.cluster.wait.aligned;" ::: "memory");
}

__device__ __forceinline__ void tail_load_b(const uint32_t sb, const int h, const int c, const int k) {
    mbar_expect(sb + T_FB + (k % 7) * 8, 20480);
    bulk_g2s(sb + tail_b(k), (const char*)g_wot + (size_t)((h & 7) * GNC + c * 11 + k) * 20480, 20480, sb + T_FB + (k % 7) * 8);
}
__device__ __forceinline__ void chain_aux(const uint32_t sb, const int c, const int h, const int layer, const int nact, const bf16* Wq, const bf16* Wk,
                                          const bf16* Wv, const bf16* Wo) {
    const int tid = read_tid(), w = __shfl_sync(~0u, tid >> 5, 0), lane = tid & 31;
    if (w == 8) {
        mbar_init(sb + O_BAR + lane * 8, lane == 3 || (lane >= 16 && lane < 20) || (lane >= 27 && lane < 31) ? 8 : 1);
        asm volatile("fence.mbarrier_init.release.cluster;" ::: "memory");
        fence_async_smem();
        __syncwarp();
    }
    {
        uint4* z = (uint4*)red_base() + layer * 65536;
#pragma unroll 1
        for (int i = blockIdx.x * 128 + tid - 256; i < 65536; i += 96 * 128)
            if (i >= 2048 || (i & 32)) z[i] = make_uint4(0, 0, 0, 0);
    }
    if (w == 8 && lane == 0) {
        mbar_expect(sb + B_S, S_TX);
        mbar_expect(sb + B_W, 192);
        mbar_expect(sb + T_RED, (c == 2 ? 1 : 2) * 3 * 4096);
        if (layer == 1) prefetch_l2(red_base() + 32 * 32768 + blockIdx.x * 1024, 1024);
        if (layer == 0) wait_flag<400>(g_ready, 128);
    }
    __syncwarp();
    cluster_sync_full();
    asm volatile("barrier.cluster.arrive.relaxed.aligned;" ::: "memory");
    pdl_wait();
    Flag* flag = g_flag + layer * NSEG * 32 + h;
    const Flag* xflag = g_flag + F_X + layer * 128;
    char* const it0 = g_item + (size_t)h * 32768;
    if (w == 8) {
#pragma unroll 1
        for (int n = 0; n < 3; n++) {
            wait_flag<100>(xflag + (n >> 1), 4);
            fence_async_glb();
            if (n == 0) { bar_sync(4, 288); fence_async_smem(); }
            if (lane == 0 && n < 2) {
                mbar_expect(sb + B_XF + n * 8, 40960);
                bulk_g2s(sb + O_XS + n * 40960, (const char*)g_xn + n * 40960, 40960, sb + B_XF + n * 8);
            }
            __syncwarp();
        }
#pragma unroll 1
        for (int n = 0; n < NSEG; n++) {
            const int np = n & 1;
            if (n == 0) { wait_flag<100>(g_flag + F_W + layer * 128, 96); bar_sync(5, 288); } else bar_sync(2, 352);
            if (n == 1) TL(12 + layer * 14);
            if (n == 63) TL(13 + layer * 14);
            if (lane == 0 && (n == NSEG - 1 || (XEARLY & 8))) mbar_arrive(sb + B_STG + np * 8);
            if (lane == 0 && n < NSEG - 1) {
                const uint32_t vs = sb + O_STG + 8192 - np * 16384, vb = sb + B_VX + np * 8;
                if (c == 2) { if (!VEARLY || n == 0) {
                    fence_async_smem();
                    bulk_s2s(mapa(vs, 0), vs, 8192, mapa(vb, 0));
                    bulk_s2s(mapa(vs, 1), vs, 8192, mapa(vb, 1));
                } } else mbar_expect(vb, 8192);
                if (n == 0) { mbar_expect(sb + B_XF, 40960); bulk_g2s(sb + O_XS, (const char*)g_xn + 2 * 40960, 40960, sb + B_XF); }
                if (n == h * 3 + c && !np && n + 6 < NSEG) prefetch_l2(red_base() + (size_t)(layer * 32 + (n >> 1) + 3) * 32768, 32768);
            }
            __syncwarp();
        }
    } else if (w == 11) {
        float cvo;
        {
            auto max8 = [&](const float* p) {
                const float4 u = ((const float4*)p)[0], v = ((const float4*)p)[1];
                return fmaxf(fmaxf(fmaxf(u.x, u.y), fmaxf(u.z, u.w)), fmaxf(fmaxf(v.x, v.y), fmaxf(v.z, v.w)));
            };
            wait_flag<300>(g_flag + F_W + layer * 128, 96);
            const float* pc = g_co + lane * 32;
            float a = 640.f * __ldcg(g_wmx + lane * 3 + 2), o = fmaxf(fmaxf(max8(pc), max8(pc + 8)), max8(pc + 16));
#pragma unroll 1
            for (int s = 16; s; s >>= 1) { a = fmaxf(a, __shfl_xor_sync(~0u, a, s)); o += __shfl_xor_sync(~0u, o, s); }
            cvo = a * o * 2.f;
        }
        float invM = g_invM0;
        float iv;
        weight_scale(h, 2, &iv);
        const uint32_t L16 = sb + lane * 16 + O_MX;
#pragma unroll 1
        for (int st = 0; st < NSEG; st++) {
            bar_sync(1, 320);
            if (st == NSEG - 1) break;
            if (!(XEARLY & 10) && lane == 0) mbar_arrive(sb + B_STG + (st & 1) * 8);
            uint32_t u[2][4];
            lds128(u[0], L16); lds128(u[1], L16 + 512);
            uint32_t mx = habsmax(habsmax(habsmax(u[0][0], u[0][1]), habsmax(u[0][2], u[0][3])), habsmax(habsmax(u[1][0], u[1][1]), habsmax(u[1][2], u[1][3])));
            mx = __reduce_max_sync(~0u, max(mx & 0x7fffu, (mx >> 16) & 0x7fffu));
            const float bound = fmaxf(__half2float(__ushort_as_half((unsigned short)mx)) * invM, 25.5f) * cvo;
            const float sc = pow2_scale(bound, 15, &invM);
            sts64(sb + O_SCL, __float_as_uint(sc * iv), __float_as_uint(invM));
            bar_arrive(2, 352);
        }
    } else if (w == 10) {
        if (lane == 0) {
#pragma unroll 1
            for (int n = 0; n < NSEG; n++) {
                mbar_sleep(sb + B_STG + (n & 1) * 8, (n >> 1) & 1);
                fence_async_smem();
                const uint32_t stg = sb + O_STG - (n & 1) * 16384;
                char* it = it0 + (size_t)(n % RING) * 32 * 32768;
                bulk_s2g(it + c * 8192, stg + (c == 2 ? 8192 : 0), 8192);
                bulk_commit();
                if (n + 1 >= RING && n + 1 < NSEG) wait_flag(flag - (RING - 1) * 32, REL1 ? 4 : 7);
                bulk_wait0();
                if (REL1) {
                    fence_async_glb();
                    mbar_arrive(sb + B_FREE + (n & 1) * 8);
                } else {
                    mbar_arrive(sb + B_FREE + (n & 1) * 8);
                    fence_async_glb();
                    if (RELAX & 1) red_relaxed(flag); else red_release(flag);
                }
                flag += 32;
            }
        }
    } else {
        const uint32_t L16 = sb + lane * 16;
        bool allx = false;
#pragma unroll 1
        for (int st = 0; st < NSEG; st++) {
            const int par = st & 1;
            char* it = it0 + (size_t)(st % RING) * 32 * 32768 + lane * 16;
            if (lane == 0 && !allx && st + 3 < NSEG) {
                allx = ld_acquire(xflag + 64) >= nact;
                if (!allx) wait_flag(xflag + ((st + 3) >> 1), 4);
                fence_async_glb();
            }
            __syncwarp();
            auto refill = [&] {
                if (lane == 0 && st + 3 < NSEG) {
                    mbar_expect(sb + B_XF + (par ^ 1) * 8, 40960);
                    bulk_g2s_last(sb + O_XS + (par ^ 1) * 40960, (const char*)g_xn + (size_t)(st + 3) * 40960, 40960, sb + B_XF + (par ^ 1) * 8);
                } else if (lane == 0 && st < NSEG - 1) {
                    tail_load_b(sb, h, c, (par ^ 1) * 2); tail_load_b(sb, h, c, (par ^ 1) * 2 + 1);
                }
                __syncwarp();
            };
            if (st < NSEG - 1 && c < 2) mbar_sleep(sb + B_VX + par * 8, (st >> 1) & 1);
            if (st < NSEG - 2) mbar_sleep(sb + B_XF + par * 8, ((st >> 1) + 1) & 1);
            bar_sync(1, 320);
            if (!(XEARLY & 1)) refill();
            char* const itb = it - lane * 16;
            if (lane == 0 && c < 2) {
                fence_async_smem();
#pragma unroll 1
                for (int i = 0; i < 4; i++) bulk_s2g(itb + 24576 + (c * 4 + i) * 512, sb + O_QKP + i * 1024 + 512, 512);
                bulk_commit();
                asm volatile("cp.async.bulk.wait_group.read 0;" ::: "memory");
            }
            __syncwarp();
            if (st < NSEG - 1) bar_arrive(2, 352);
            mbar_sleep(sb + B_S, par);
            __syncwarp();
            if (lane == 0) {
                if (st < NSEG - 1) mbar_expect(sb + B_S, S_TX);
                if (c == 2) { fence_async_smem(); bulk_s2g(itb + 28672, sb + O_VM + par * 2048, 2048); bulk_commit(); }
                if (st == NSEG - 1) asm volatile("cp.async.bulk.wait_group.read 0;" ::: "memory");
            }
            __syncwarp();
            if (st == NSEG - 1) bar_arrive(8, 320);
            if (lane == 0) { bulk_wait0(); fence_async_glb(); red_relaxed(flag); }
            __syncwarp();
            if (!REL1) mbar_sleep(sb + B_FREE + par * 8, (st >> 1) & 1);
            flag += 32;
            continue;
#pragma unroll 1
            for (int i = 0; i < (c < 2 ? 4 : 0); i += 2) {
                uint32_t v[8];
                lds128(v, L16 + O_QKP + i * 1024 + 512); lds128(v + 4, L16 + O_QKP + i * 1024 + 512 + 1024);
                *(uint4*)(it + 24576 + (c * 4 + i) * 512) = make_uint4(v[0], v[1], v[2], v[3]); *(uint4*)(it + 24576 + (c * 4 + i) * 512 + 512) = make_uint4(v[4], v[5], v[6], v[7]);
            }
            if (st < NSEG - 1) bar_arrive(2, 352);
            mbar_sleep(sb + B_S, par);
            __syncwarp();
            if (lane == 0 && st < NSEG - 1) mbar_expect(sb + B_S, S_TX);
#pragma unroll 1
            for (int i = 0; i < (c < 2 ? 0 : 4); i += 2) {
                uint32_t v[8];
                lds128(v, L16 + O_VM + par * 2048 + i * 512); lds128(v + 4, L16 + O_VM + par * 2048 + i * 512 + 512);
                *(uint4*)(it + 28672 + i * 512) = make_uint4(v[0], v[1], v[2], v[3]); *(uint4*)(it + 28672 + i * 512 + 512) = make_uint4(v[4], v[5], v[6], v[7]);
            }
            if (st == NSEG - 1) bar_arrive(8, 320);
            __syncwarp();
            if (REL1) mbar_sleep(sb + B_FREE + par * 8, (st >> 1) & 1);
            if (lane == 0) { if (RELAX & 2) red_relaxed(flag); else red_release(flag); }
            if (!REL1) mbar_sleep(sb + B_FREE + par * 8, (st >> 1) & 1);
            flag += 32;
        }
    }
    __syncwarp();
    const int nc = c == 2 ? 10 : 11;
    if (w == 10) {
        bar_sync(8, 320);
        if (lane == 0) {
            if (layer == 1 && blockIdx.x == 0) g_ready[0].v = 0;
            fence_async_smem();
            __nanosleep(TDELAY);
            wait_flag(xflag + 64, nact);
            wait_flag<50>(g_flag + F_O + layer * 32 + 28 + (h >> 3), 64);
            fence_async_glb();
#pragma unroll 1
            for (int k = 0; k < nc; k++) {
                if (k >= 4) mbar_sleep(sb + T_EA + (k & 3) * 8, ((k >> 2) - 1) & 1);
                mbar_expect(sb + T_FA + (k & 3) * 8, 16384);
                bulk_g2s_last(sb + O_MS + (k & 3) * 16384, (const char*)g_O + (size_t)((28 + (h >> 3)) * GNC + c * 11 + k) * 16384, 16384, sb + T_FA + (k & 3) * 8);
            }
        }
    } else if (w == 9 && lane == 0) {
        __nanosleep(TDELAY);
#pragma unroll 1
        for (int k = 4; k < nc; k++) {
            if (k >= 7) mbar_sleep(sb + T_EB + (k - 7) * 8, 0);
            tail_load_b(sb, h, c, k);
        }
    }
    __syncwarp();
    asm volatile("barrier.cluster.wait.aligned;" ::: "memory");
    asm volatile("barrier.cluster.arrive.relaxed.aligned; barrier.cluster.wait.aligned;" ::: "memory");
    asm volatile("barrier.cluster.arrive.relaxed.aligned; barrier.cluster.wait.aligned;" ::: "memory");
}

constexpr int RI_A = 0, RI_TAB = 81920, RI_STG = RI_TAB + 82 * 768;
constexpr int RI_RES = RI_STG + 25600, RI_ST = RI_RES + 2 * 64 * 336;
constexpr int HB_A = G_BAR + 64, HB_AFREE = HB_A + 32, HB_LN = HB_A + 40, HB_FULL = HB_A + 64, HB_DONE = HB_FULL + 48, HB_FREE = HB_DONE + 48;
constexpr int HP_SMEM = HB_FREE + 48;
static_assert(G_BAR >= RI_ST + 2048, "helper shared-memory map");
#define IDL 350
#define ITEM_NS 60
#define HORD 1
#define PFW_AT 28
#define PFW_NS 150
__device__ __forceinline__ void helper_aux(const uint32_t sb, const int j, const int nh, const int na, const int nbh, const int layer, const bf16* Wq,
                                           const bf16* Wk, const bf16* Wv, const bf16* Wo) {
    const int w = threadIdx.x >> 5, lane = threadIdx.x & 31, p = w - 8;
    if (lane == 0 && j < (nh & ~3)) {
        int n = 0;
        for (int a = j >> 2; a < 32; a += nh >> 2, n++) {
            if (n == 0) continue;
            mbar_wait(sb + HB_AFREE, (n - 1) & 1);
            mbar_expect(sb + HB_A + p * 8, 20480);
            bulk_g2s_last(sb + RI_A + p * 20480, (const char*)g_YT + (size_t)a * 81920 + p * 20480, 20480, sb + HB_A + p * 8);
            if (p == 0) { mbar_wait(sb + HB_LN, (n - 1) & 1); red_release(g_flag + F_X + layer * 128 + a - (nh >> 2)); }
        }
        if (p == 0) { mbar_wait(sb + HB_LN, (n - 1) & 1); red_release(g_flag + F_X + layer * 128 + (j >> 2) + (n - 1) * (nh >> 2)); }
    }
    __syncwarp();
    if (layer == 0 && w == 8 && lane == 0) wait_flag<400>(g_flag + F_W, 96);
    __syncwarp();
    bar_sync(3, 384);
    if (p == 3 && lane == 0 && j < (nh & ~3)) red_release(g_flag + F_X + layer * 128 + 64);
    fence_async_smem();
    Flag* oflag = g_flag + F_O + layer * 32;
    if (j < na) {
        int sl = p & 1, ph = 1;
        for (int idx = j + (p & 1) * na; idx < NSEG * 32 && p >= 2 && lane == 0; idx += 2 * na) {
            mbar_wait(sb + HB_DONE + sl * 8, ph ^ 1);
            mbar_arrive(sb + HB_FREE + sl * 8);
            red_release(oflag + (idx >> 6));
            atomicAdd(&g_flag[layer * NSEG * 32 + idx].v, 1u);
            sl += 2;
            if (sl >= 6) { sl -= 6; ph ^= 1; }
        }
        for (int idx = j + p * na; idx < NSEG * 32 && p < 2 && lane == 0; idx += 2 * na) {
            mbar_wait(sb + HB_FREE + sl * 8, ph);
            wait_flag<ITEM_NS>(g_flag + layer * NSEG * 32 + idx, REL1 ? 3 : 6);
            fence_async_glb();
            if (idx < (NSEG - 2) * 32) __nanosleep(IDL);
            mbar_expect(sb + HB_FULL + sl * 8, 30720);
            bulk_g2s(sb + sl * 30720, g_item + (size_t)(idx % (RING * 32)) * 32768, 30720, sb + HB_FULL + sl * 8);
            sl += 2;
            if (sl >= 6) { sl -= 6; ph ^= 1; }
        }
    } else if (lane == 0 && p == 3) {
        if (layer == 0) {
            wait_flag<1000>(oflag + PFW_AT, 64);
            const int np = nh - na;
#pragma unroll 1
            for (int i = j - na; i < 1280; i += np) {
                const bf16* W = i < 320 ? Wq : i < 640 ? Wk : i < 960 ? Wv : Wo;
                prefetch_l2((const char*)W + (size_t)(i % 320) * 16384, 16384);
                __nanosleep(PFW_NS);
            }
#pragma unroll 1
            for (int i = j - na; i < 205; i += np) {
                const char* p_ = i < 160 ? (const char*)g_Wf + i * 16384 : i < 165 ? (const char*)g_stat + (i - 144) * 16384
                               : i < 167 ? (const char*)g_ctab + (i - 165) * 8192 : (const char*)(g_flag + NFLAG) - (i - 166) * 16384;
                prefetch_l2(p_, 16384);
                __nanosleep(PFW_NS);
            }
        }
    } else if (lane == 0) {
        if (p == 2) wait_flag<500>(g_flag + F_X + layer * 128 + 64, nh & ~3);
        int c0 = 0;
        for (int mb = (j - na) >> 3; mb < nbh; mb += (nh - na) >> 3, c0 += GNC) {
            if (p < 2) wait_flag<300>(oflag + 2 * mb + p, 64);
            fence_async_glb();
            oproj_load(sb, p, mb, (j - na) & 7, c0, nh - na < 24 ? 0 : mb == nbh - 1 ? GPACE2 : GPACE);
        }
    }
}
__device__ __forceinline__ void helper_mma(char* sm, const int jh, const int nh, const int na, const int nbh, const int layer, const bf16* res, bf16* x,
                                           bf16* out) {
    const uint32_t sb = smem_u32(sm);
    const int tid = threadIdx.x, w = tid >> 5, lane = tid & 31, g = lane >> 2, t = lane & 3;
    const bool act = jh < (nh & ~3);
    const int j4 = jh & 3;
    const int fr = tid & 63, rg = w >> 1;
    auto chunk0 = [&](int u) { return u == 0 ? 5 * j4 : u == 1 ? 75 - 5 * j4 : u == 2 ? 40 + 5 * j4 : 35 - 5 * j4; };
    const int gr = tid / 20, gq_ = tid - gr * 20, go = gr * 80 + chunk0(gq_ / 5) + gq_ % 5;
    const uint32_t gs = sb + RI_RES + gr * 336 + gq_ * 16;
    auto residual = [&](int a, int n) {
#pragma unroll 1
        for (int r = 0; r < 64 - gr && tid < 240 && a < 32; r += 12) cp_async16(gs + (n & 1) * 21504 + r * 336, (const uint4*)res + (a * 64 + r) * 80 + go);
        cp_commit();
    };
    if (act) {
        if (tid < 240) {
            const int k0 = tid / 48, n = tid - k0 * 48;
            const float d = (float)(40 * j4 + n), amp = 2.f * 0.03952847075210474f;
#pragma unroll 4
            for (int u = 0; u < 16; u++)
                *(uint4*)(sm + RI_TAB + (tid + u * 240) * 16) = cos_row8(fmaf((float)((k0 + (u & 3) * 5) * 16 + ((u >> 2) & 1)), d, (float)((u & 8) * 20)), 2.f * d, amp);
            if (tid < 96) *(uint4*)(sm + RI_TAB + (3840 + tid) * 16) = make_uint4(k0 == 0 ? pack_h((n & 1) ? -amp : amp, 0.f) : 0u, 0, 0, 0);
        }
        fence_async_smem();
        residual(jh >> 2, 0);
    }
    bar_sync(1, 384);
    if (layer == TLL) TL(36);
    if (act) {
        const float4 wm = ((const float4*)g_wmax)[lane];
        const int wg = w >> 2;
        int n = 0;
#pragma unroll 1
        for (int a = jh >> 2; a < 32; a += nh >> 2, n++) {
            float acc[2][24];
            uint64_t da = mkdesc(sb + RI_A + wg * 40960, 1024, 1024, 1), db = mkdesc(sb + RI_TAB + wg * 30720, 768, 128, 0);
#pragma unroll
            for (int gq = 0; gq < 2; gq++) {
                mbar_wait(sb + HB_A + (wg * 2 + gq) * 8, n & 1);
                if (layer == TLL && n == TLN && gq == 0) TL(45);
                wg_fence();
#pragma unroll 5
                for (int k = 0; k < 10; k++) { wg_n48_ss_ta(acc[gq], da, db, k); da += 128; db += 96; }
                wg_commit();
            }
            if (wg == 0) {
                mbar_wait(sb + HB_A + 16, n & 1);
                wg_fence();
                wg_n48_ss_ta(acc[0], da, db + 20 * 96, 1);
                wg_commit();
            }
            float inv;
            pow2_scale(__uint_as_float(__reduce_max_sync(~0u, __float_as_uint(fmaxf(fmaxf(wm.x, wm.y), fmaxf(wm.z, wm.w))))), 0, &inv);
            const uint32_t ysc = pack_bf(inv, inv);
            wg_wait<0>();
            if (layer == TLL && n == TLN) TL(46);
            if (lane == 0) mbar_arrive(sb + HB_AFREE);
            const uint32_t ad = sb + RI_STG + ((w & 3) * 16 + (lane & 15)) * 400 + (lane >> 4) * 96 + wg * 192;
#pragma unroll
            for (int q = 0; q < 6; q++) {
                const float *e = acc[0] + q * 4, *o = acc[1] + q * 4;
                stsm4(ad + q * 16, pack_h(e[0] + o[0], e[1] + o[1]), pack_h(e[2] + o[2], e[3] + o[3]), pack_h(e[0] - o[0], e[1] - o[1]), pack_h(e[2] - o[2], e[3] - o[3]));
            }
            cp_wait<0>();
            bar_sync(4, 256);
            const uint32_t xa = sb + RI_RES + (n & 1) * 21504 + fr * 336 + rg * 80, sg = (rg & 1) ? 0xbc00bc00u : 0x3c003c00u;
            float sum = 0.f, sq = 0.f;
            uint32_t ya = sb + RI_STG + fr * 400 + (rg >> 1) * 96 + ((rg & 1) ? 64 : 0), carry;
            asm("fma.rn.f16x2 %0,%1,%2,%3;" : "=r"(carry) : "r"(lds32(ya + 208)), "r"(sg), "r"(lds32(ya + 16)));
#pragma unroll 1
            for (int ch = 0; ch < 5; ch++, ya += (rg & 1) ? -16 : 16) {
                uint32_t y[4], z[4], xr[4];
                lds128(y, ya); lds128(z, ya + 192); lds128(xr, xa + ch * 16);
#pragma unroll
                for (int q = 0; q < 4; q++) asm("fma.rn.f16x2 %0,%1,%2,%0;" : "+r"(y[q]) : "r"(z[q]), "r"(sg));
                if (rg & 1) {
                    const uint32_t y0 = y[0], y1 = y[1];
                    y[0] = __byte_perm(carry, y[3], 0x7610); y[1] = __byte_perm(y[3], y[2], 0x7610);
                    y[3] = __byte_perm(y1, y0, 0x7610); y[2] = __byte_perm(y[2], y1, 0x7610);
                    carry = y0;
                }
#pragma unroll
                for (int q = 0; q < 4; q++) {
                    const float2 yf = __half22float2(*(const __half2*)&y[q]);
                    xr[q] = bfma(pack_bf(yf.x, yf.y), ysc, xr[q]);
                    const float e = bf_lo(xr[q]), f = bf_hi(xr[q]);
                    sum += e + f; sq = fmaf(e, e, fmaf(f, f, sq));
                }
                sts128(xa + ch * 16, xr[0], xr[1], xr[2], xr[3]);
            }
            uint2* stat = g_stat + (size_t)(layer * 32 + a) * 1024 + rg * 64 + fr;
            asm volatile("st.relaxed.gpu.global.v2.u32 [%0],{%1,%2};" ::"l"(stat + j4 * 256), "r"(__float_as_uint(sum)), "r"(__float_as_uint(sq) | 0x80000000u) : "memory");
            if (layer == TLL && n == TLN) TL(47);
            uint32_t s0[3], s1[3];
            int lim = 0;
            do {
#pragma unroll
                for (int q = 0; q < 3; q++)
                    asm volatile("ld.relaxed.gpu.global.v2.u32 {%0,%1},[%2];" : "=r"(s0[q]), "=r"(s1[q]) : "l"(stat + ((j4 + 1 + q) & 3) * 256) : "memory");
            } while (__any_sync(~0u, (int)(s1[0] & s1[1] & s1[2]) >= 0) && ++lim < SPIN_LIM);
#pragma unroll
            for (int q = 0; q < 3; q++) { sum += __uint_as_float(s0[q]); sq -= __uint_as_float(s1[q]); }
            sts64(sb + RI_ST + tid * 8, __float_as_uint(sum), __float_as_uint(sq));
            bar_sync(4, 256);
            if (layer == TLL && n == TLN) TL(48);
#pragma unroll
            for (int q = 1; q < 4; q++) {
                uint32_t st2[2];
                lds64(st2, sb + RI_ST + ((tid + q * 64) & 255) * 8);
                sum += __uint_as_float(st2[0]); sq += __uint_as_float(st2[1]);
            }
            const float mean = sum * (1.f / 640.f), r = rsqrtf(fmaxf(fmaf(-mean, mean, sq * (1.f / 640.f)), 0.f) + 1e-5f), off = -mean * r;
            uint4* dst = (uint4*)g_xn + ((size_t)(2 * a + (w & 1)) * 80 + chunk0(rg)) * 32 + lane;
#pragma unroll
            for (int i = 0; i < 5; i++) {
                uint32_t u[4];
                lds128(u, xa + i * 16);
                dst[i * 32] = make_uint4(pack_h(fmaf(bf_lo(u[0]), r, off), fmaf(bf_hi(u[0]), r, off)), pack_h(fmaf(bf_lo(u[1]), r, off), fmaf(bf_hi(u[1]), r, off)),
                                         pack_h(fmaf(bf_lo(u[2]), r, off), fmaf(bf_hi(u[2]), r, off)), pack_h(fmaf(bf_lo(u[3]), r, off), fmaf(bf_hi(u[3]), r, off)));
            }
            __syncwarp();
            if (lane == 0) mbar_arrive(sb + HB_LN);
            if (layer == TLL) TL(37);
            if (layer == TLL && n == TLN) TL(44);
            residual(a + (nh >> 2), n + 1);
#pragma unroll 2
            for (int rr = 0; rr < 64 - gr && tid < 240; rr += 12) {
                uint32_t v[4];
                lds128(v, gs + (n & 1) * 21504 + rr * 336);
                ((uint4*)x)[(a * 64 + rr) * 80 + go] = make_uint4(v[0], v[1], v[2], v[3]);
            }
        }
    }
    bar_sync(3, 384);
    if (layer == TLL) TL(38);
    if (jh >= na) {
        int c0 = 0;
#pragma unroll 1
        for (int mb = (jh - na) >> 3; mb < nbh; mb += (nh - na) >> 3, c0 += GNC) oproj_mma(sb, mb, (jh - na) & 7, c0, x, out);
        if (layer == TLL) TL(42);
        return;
    }
    const int p = w >> 1, mi = w & 1;
    int slot = p, ph = 0;
    for (int idx = jh + p * na; idx < NSEG * 32; idx += 4 * na) {
        const uint32_t it = sb + slot * 30720 + lane * 16;
        float iq, ik, iv;
        weight_scale(idx & 31, 0, &iq); weight_scale(idx & 31, 1, &ik); weight_scale(idx & 31, 2, &iv);
        bar_sync(6 + p, 64);
        mbar_wait(sb + HB_DONE + slot * 8, ph ^ 1);
        mbar_wait(sb + HB_FULL + slot * 8, ph);
        if (layer == TLL && idx >= 63 * 32) TL(55);
        float s[6][4];
#pragma unroll
        for (int i = 0; i < 6; i++) s[i][0] = s[i][1] = s[i][2] = s[i][3] = 0.f;
#pragma unroll
        for (int e = 0; e < 8; e++) {
            uint32_t q[4], k[4];
            ldsm4t(q, it + (e >> 2) * 8192 + (e & 3) * 1024 + mi * 512);
            ldsm4t(k, it + 24576 + e * 512);
            mma_bf(s[4], q[0], q[2], q[1], q[3], k[0], k[1]);
            mma_bf(s[5], q[0], q[2], q[1], q[3], k[2], k[3]);
            ldsm4t(k, it + (e >> 2) * 8192 + 4096 + (e & 3) * 1024);
            mma_bf(s[0], q[0], q[2], q[1], q[3], k[0], k[1]);
            mma_bf(s[1], q[0], q[2], q[1], q[3], k[2], k[3]);
            if (mi) {
                ldsm4t(k, it + (e >> 2) * 8192 + 4096 + (e & 3) * 1024 + 512);
                mma_bf(s[2], q[0], q[2], q[1], q[3], k[0], k[1]);
                mma_bf(s[3], q[0], q[2], q[1], q[3], k[2], k[3]);
            }
        }
#pragma unroll
        for (int q = 0; q < 4; q++) s[4][q] += s[5][q];
        const int seg = idx >> 5, h = idx & 31;
        const float sl = iq * ik * (0.08838834764831845f * 1.4426950408889634f);
        float mx[2] = {-3.0e38f, -3.0e38f};
#pragma unroll
        for (int i = 0; i < 5; i++)
#pragma unroll
            for (int q = 0; q < 4; q++) {
                const bool ok = i == 4 || (i * 8 + 2 * t + (q & 1)) <= (mi * 16 + g + (q >> 1) * 8);
                s[i][q] = ok ? s[i][q] * sl : -1.0e9f * 1.4426950408889634f;
                mx[q >> 1] = fmaxf(mx[q >> 1], s[i][q]);
            }
        float sum[2] = {0.f, 0.f};
#pragma unroll
        for (int r = 0; r < 2; r++) {
            mx[r] = fmaxf(mx[r], __shfl_xor_sync(~0u, mx[r], 1));
            mx[r] = fmaxf(mx[r], __shfl_xor_sync(~0u, mx[r], 2));
        }
#pragma unroll
        for (int i = 0; i < 5; i++)
#pragma unroll
            for (int q = 0; q < 4; q++) { s[i][q] = ex2(s[i][q] - mx[q >> 1]); sum[q >> 1] += s[i][q]; }
#pragma unroll
        for (int r = 0; r < 2; r++) {
            sum[r] += __shfl_xor_sync(~0u, sum[r], 1);
            sum[r] += __shfl_xor_sync(~0u, sum[r], 2);
            sum[r] = iv * rcp(sum[r]);
        }
        uint32_t pp[5][2];
#pragma unroll
        for (int i = 0; i < 5; i++) { pp[i][0] = pack_bf(s[i][0] * sum[0], s[i][1] * sum[0]); pp[i][1] = pack_bf(s[i][2] * sum[1], s[i][3] * sum[1]); }
        uint32_t* o = (uint32_t*)g_O + (((size_t)(seg >> 1) * 512 + h * 16) * 8 + (seg & 1) * 4 + mi * 2) * 32 + lane;
#pragma unroll
        for (int e = 0; e < 8; e++) {
            float o0[4] = {0.f, 0.f, 0.f, 0.f}, o1[4] = {0.f, 0.f, 0.f, 0.f};
            uint32_t v[4];
            lds64(v, it - lane * 8 + 28672 + e * 256);
            mma_bf8(o0, pp[4][0], pp[4][1], v[0]);
            mma_bf8(o1, pp[4][0], pp[4][1], v[1]);
            ldsm4(v, it + 16384 + e * 1024);
            mma_bf(o0, pp[0][0], pp[0][1], pp[1][0], pp[1][1], v[0], v[2]);
            mma_bf(o1, pp[0][0], pp[0][1], pp[1][0], pp[1][1], v[1], v[3]);
            ldsm4(v, it + 16384 + e * 1024 + 512);
            mma_bf(o0, pp[2][0], pp[2][1], pp[3][0], pp[3][1], v[0], v[2]);
            mma_bf(o1, pp[2][0], pp[2][1], pp[3][0], pp[3][1], v[1], v[3]);
            o[(2 * e) * 256] = pack_bf(o0[0], o0[1]); o[(2 * e) * 256 + 32] = pack_bf(o0[2], o0[3]);
            o[(2 * e + 1) * 256] = pack_bf(o1[0], o1[1]); o[(2 * e + 1) * 256 + 32] = pack_bf(o1[2], o1[3]);
        }
        __syncwarp();
        if (lane == 0) mbar_arrive(sb + HB_DONE + slot * 8);
        slot += 4;
        if (slot >= 6) { slot -= 6; ph ^= 1; }
    }
    if (layer == TLL) TL(39);
}

__global__ void __cluster_dims__(3, 1, 1) __launch_bounds__(384, 1)
k_chain(const int layer, const int nact, const uint32_t zero, const bf16* __restrict__ Wq, const bf16* __restrict__ Wk, const bf16* __restrict__ Wv,
        const bf16* __restrict__ Wo, const bf16* res, bf16* out) {
    extern __shared__ __align__(1024) char sm[];
    const uint32_t sb = smem_u32(sm);
    const int b = blockIdx.x, h = b / 3, c = b - h * 3;
    pdl_go();
    if (threadIdx.x >= 256) {
        asm volatile("setmaxnreg.dec.sync.aligned.u32 24;");
        TL(11 + layer * 14);
        chain_aux(sb, c, h, layer, nact, Wq, Wk, Wv, Wo);
    } else {
        asm volatile("setmaxnreg.inc.sync.aligned.u32 240;");
        chain_mma(sb, c, h, layer, zero, Wq, Wk, Wv, Wo, res, out);
    }
}
__global__ void __launch_bounds__(384, 1) k_help(const bf16* res, bf16* x, bf16* out, const int layer, const int na, const int nbh, const int zero, const bf16* Wq,
                                                  const bf16* Wk, const bf16* Wv, const bf16* Wo) {
    extern __shared__ __align__(1024) char sm[];
    if (layer == TLL) TL(51);
    if (threadIdx.x >= 256) {
        const uint32_t sb = smem_u32(sm);
        const int p = (threadIdx.x >> 5) - 8, i = (threadIdx.x & 31) * 4 + p;
        if (i < 34) mbar_init(sb + G_BAR + i * 8, i < 4 ? 3 : i < 8 || i == 12 || i == 13 ? 8 : i >= 22 && i < 28 ? 2 : 1);
        fence_async_smem();
        wait_flag<100>(g_flag + F_X + layer * 128 + 65, 321);
        fence_async_glb();
        if (i == 8 + p && blockIdx.x < (gridDim.x & ~3)) {
            mbar_expect(sb + HB_A + p * 8, 20480);
            bulk_g2s(sb + RI_A + p * 20480, (const char*)g_YT + (size_t)(blockIdx.x >> 2) * 81920 + p * 20480, 20480, sb + HB_A + p * 8);
        }
        __syncwarp();
        bar_sync(2, 128);
        bar_arrive(1, 384);
    }
    if (threadIdx.x + zero >= 256) helper_aux(smem_u32(sm), blockIdx.x, gridDim.x, na, nbh, layer, Wq, Wk, Wv, Wo);
    else helper_mma(sm, blockIdx.x, gridDim.x, na, nbh, layer, res, x, out);
    __syncwarp();
    pdl_go();
    if (blockIdx.x == 0) pdl_wait();
}

#define COL_PAD 15872
template <class... P, class... A>
void launch_pdl(void (*k)(P...), int grid, int block, int smem, cudaStream_t st, A... args) {
    cudaLaunchConfig_t cfg = {};
    cfg.gridDim = dim3(grid); cfg.blockDim = dim3(block); cfg.dynamicSmemBytes = smem; cfg.stream = st;
    cudaLaunchAttribute at[1];
    at[0].id = cudaLaunchAttributeProgrammaticStreamSerialization; at[0].val.programmaticStreamSerializationAllowed = 1;
    cfg.attrs = at;
    cfg.numAttrs = 1;
    cudaLaunchKernelEx(&cfg, k, args...);
}

}

extern "C" void kernel_launch(void* const* d_in, const int* in_sizes, int n_in, void* d_out, int out_size) {
    const bf16* x = (const bf16*)d_in[0];
    const bf16* wr = (const bf16*)d_in[1];
    const bf16* wi = (const bf16*)d_in[2];
    const bf16* mem0 = (const bf16*)d_in[4];
    const bf16* Wq = (const bf16*)d_in[5];
    const bf16* Wk = (const bf16*)d_in[6];
    const bf16* Wv = (const bf16*)d_in[7];
    const bf16* Wo = (const bf16*)d_in[8];
    bf16* out = (bf16*)d_out;
    static int nhelp = 0;
    static bf16 *xa, *xb;
    static cudaStream_t s1;
    static cudaEvent_t ev_fork, ev_join;
    if (!nhelp) {
        cudaStreamCreateWithFlags(&s1, cudaStreamNonBlocking);
        cudaEventCreateWithFlags(&ev_fork, cudaEventDisableTiming);
        cudaEventCreateWithFlags(&ev_join, cudaEventDisableTiming);
        cudaFuncSetAttribute(k_setup, cudaFuncAttributeMaxDynamicSharedMemorySize, SU_SMEM);
        cudaFuncSetAttribute(k_rowf, cudaFuncAttributeMaxDynamicSharedMemorySize, RF_SMEM);
        cudaFuncSetAttribute(k_col, cudaFuncAttributeMaxDynamicSharedMemorySize, COL_PAD);
        cudaFuncSetAttribute(k_chain, cudaFuncAttributeMaxDynamicSharedMemorySize, CH_SMEM);
        cudaFuncSetAttribute(k_setup, cudaFuncAttributePreferredSharedMemoryCarveout, 100);
        cudaFuncSetAttribute(k_rowf, cudaFuncAttributePreferredSharedMemoryCarveout, 100);
        cudaFuncSetAttribute(k_col, cudaFuncAttributePreferredSharedMemoryCarveout, 100);
        cudaFuncSetAttribute(k_chain, cudaFuncAttributePreferredSharedMemoryCarveout, 100);
        cudaFuncSetAttribute(k_help, cudaFuncAttributeMaxDynamicSharedMemorySize, HP_SMEM);
        cudaFuncSetAttribute(k_help, cudaFuncAttributePreferredSharedMemoryCarveout, 100);
        int dev = 0, sms = 0;
        cudaGetDevice(&dev);
        cudaDeviceGetAttribute(&sms, cudaDevAttrMultiProcessorCount, dev);
        nhelp = sms - 96 < 12 ? 12 : sms - 96;
        cudaGetSymbolAddress((void**)&xa, g_xa);
        cudaGetSymbolAddress((void**)&xb, g_xb);
    }
    const int na = nhelp - (nhelp >= 36 ? 24 : nhelp >= 28 ? 16 : 8), nbh = 14;
    cudaStream_t s0 = cudaStreamPerThread;
    cudaEventRecord(ev_fork, s0);
    cudaStreamWaitEvent(s1, ev_fork, 0);
    k_rowf<<<(96 + nhelp) & ~1, 256, RF_SMEM, s0>>>(x, 1, Wq, Wk, Wv, Wo);
    k_setup<<<128, 256, SU_SMEM, s1>>>(wr, wi, mem0);
    cudaEventRecord(ev_join, s1);
#define NLAYER 2
    for (int l = 0; l < NLAYER; l++) {
        const bf16* xin = l == 0 ? x : xb;
        if (l == 1) launch_pdl(k_rowf, 128, 256, RF_SMEM, s0, xin, 0, Wq, Wk, Wv, Wo);
        launch_pdl(k_col, 321, 128, l == 0 ? 0 : COL_PAD, s0, (int)(l == 0));
        launch_pdl(k_chain, 96, 384, CH_SMEM, s0, l, nhelp & ~3, 0u, Wq, Wk, Wv, Wo, (const bf16*)xa, l == 0 ? xb : out);
        launch_pdl(k_help, nhelp, 384, HP_SMEM, s0, xin, xa, l == 0 ? xb : out, l, na, nbh, 0, Wq, Wk, Wv, Wo);
    }
    cudaStreamWaitEvent(s0, ev_join, 0);
}
```

```cpp
#include <cuda_runtime.h>
#include <cuda_bf16.h>
#include <cuda_fp16.h>
#include <stdint.h>
#include <string.h>

namespace {

typedef __nv_bfloat16 bf16;
constexpr int S_ = 2048, D_ = 640, NSEG = 64;
constexpr int SPIN_LIM = 1 << 13;

__device__ float                  g_wmx[96];
__device__ __align__(1024) bf16   g_wot[4096 * 640];
__device__ __align__(16) float    g_co[1024];
__device__ __align__(256) uint2   g_stat[2 * 32 * 16 * 64];
__device__ float                  g_invM0;
__device__ __align__(16) float    g_wmax[128];
__device__ __align__(1024) char   g_redraw[65 * 32768];
constexpr int F_X = 2 * NSEG * 32, F_O = F_X + 2 * 128, NFLAG = F_O + 128, RING = 8;
constexpr int F_W = F_X + 66;
constexpr int NSETUP = 131;
struct __align__(256) Flag { unsigned v; };
__device__ Flag                   g_flag[NFLAG];
__device__ Flag                   g_ready[1];
__device__ __align__(1024) char   g_item[RING * 32 * 32768];
__device__ __align__(1024) bf16   g_O[S_ * 4096];
__device__ __align__(1024) __half g_xn[S_ * D_];
__device__ __align__(1024) bf16   g_xa[S_ * D_];
__device__ __align__(1024) bf16   g_xb[S_ * D_];
__device__ __align__(1024) __half g_UT[D_ * S_];
__device__ __align__(1024) __half g_YT[D_ * S_];
__device__ __align__(1024) __half g_ctab[64 * 128 + 64 * 64];
__device__ __align__(1024) uint32_t g_Wf[321 * 2048];

#define TL(i)
#define TLN 0
#define TLL 1
#define CK(i)
__device__ __forceinline__ uint32_t smem_u32(const void* p) { return (uint32_t)__cvta_generic_to_shared(p); }
__device__ __forceinline__ uint32_t mapa(uint32_t a, uint32_t r) { uint32_t o; asm("mapa.shared::cluster.u32 %0,%1,%2;" : "=r"(o) : "r"(a), "r"(r)); return o; }
__device__ __forceinline__ void mbar_init(uint32_t a, int c) { asm volatile("mbarrier.init.shared::cta.b64 [%0],%1;" ::"r"(a), "r"(c) : "memory"); }
__device__ __forceinline__ void mbar_expect(uint32_t a, int bytes) { asm volatile("mbarrier.arrive.expect_tx.shared::cta.b64 _,[%0],%1;" ::"r"(a), "r"(bytes) : "memory"); }
__device__ __forceinline__ void mbar_arrive(uint32_t a) { asm volatile("mbarrier.arrive.shared::cta.b64 _,[%0];" ::"r"(a) : "memory"); }
__device__ __forceinline__ bool mbar_try(uint32_t a, uint32_t par) {
    uint32_t p;
    asm volatile("{.reg .pred q; mbarrier.try_wait.parity.shared::cta.b64 q,[%1],%2; selp.u32 %0,1,0,q;}" : "=r"(p) : "r"(a), "r"(par) : "memory");
    return p;
}
__device__ __forceinline__ void mbar_wait(uint32_t a, uint32_t par) {
    if (!mbar_try(a, par)) {
        int lim = 0;
        while (!mbar_try(a, par) && ++lim < SPIN_LIM) {}
    }
}
#define MW_HINT 20000
__device__ __forceinline__ void mbar_sleep(uint32_t a, uint32_t par) {
    asm volatile("{.reg .pred q; .reg .u32 n; mov.u32 n,0;\n"
                 "W_LOOP: mbarrier.try_wait.parity.shared::cta.b64 q,[%0],%1,%2; add.u32 n,n,1; setp.lt.and.u32 q,n,%3,!q; @q bra W_LOOP;}"
                 ::"r"(a), "r"(par), "n"(MW_HINT), "n"(SPIN_LIM) : "memory");
}
__device__ __forceinline__ void bar_arrive(int id, int n) { asm volatile("bar.arrive %0,%1;" ::"r"(id), "r"(n) : "memory"); }
__device__ __forceinline__ uint32_t clock32() { uint32_t c; asm volatile("mov.u32 %0,%%clock;" : "=r"(c)); return c; }
__device__ __forceinline__ uint32_t read_tid() { uint32_t v; asm volatile("mov.u32 %0,%%tid.x;" : "=r"(v)); return v; }
__device__ __forceinline__ void bar_sync(int id, int n) { asm volatile("bar.sync %0,%1;" ::"r"(id), "r"(n) : "memory"); }
__device__ __forceinline__ void fence_async_smem() { asm volatile("fence.proxy.async.shared::cta;" ::: "memory"); }
__device__ __forceinline__ void fence_async_glb() { asm volatile("fence.proxy.async.global;" ::: "memory"); }
__device__ __forceinline__ void cluster_sync_full() { asm volatile("barrier.cluster.arrive.aligned; barrier.cluster.wait.aligned;" ::: "memory"); }
__device__ __forceinline__ void bulk_g2s(uint32_t dst, const void* src, int bytes, uint32_t mb) {
    asm volatile("cp.async.bulk.shared::cluster.global.mbarrier::complete_tx::bytes [%0],[%1],%2,[%3];" ::"r"(dst), "l"(src), "r"(bytes), "r"(mb) : "memory");
}
__device__ __forceinline__ void bulk_g2s_last(uint32_t dst, const void* src, int bytes, uint32_t mb) {
    asm volatile("{.reg .b64 p; createpolicy.fractional.L2::evict_first.b64 p, 1.0;\n"
                 "cp.async.bulk.shared::cluster.global.mbarrier::complete_tx::bytes.L2::cache_hint [%0],[%1],%2,[%3],p;}"
                 ::"r"(dst), "l"(src), "r"(bytes), "r"(mb) : "memory");
}
__device__ __forceinline__ void bulk_s2s(uint32_t dst, uint32_t src, int bytes, uint32_t mb) {
    asm volatile("cp.async.bulk.shared::cluster.shared::cta.mbarrier::complete_tx::bytes [%0],[%1],%2,[%3];" ::"r"(dst), "r"(src), "r"(bytes), "r"(mb) : "memory");
}
__device__ __forceinline__ void bulk_s2g(void* dst, uint32_t src, int bytes) {
    asm volatile("cp.async.bulk.global.shared::cta.bulk_group [%0],[%1],%2;" ::"l"(dst), "r"(src), "r"(bytes) : "memory");
}
__device__ __forceinline__ void cp_async16(uint32_t dst, const void* src, uint32_t bytes = 16) {
    asm volatile("cp.async.cg.shared.global [%0],[%1],16,%2;" ::"r"(dst), "l"(src), "r"(bytes) : "memory");
}
__device__ __forceinline__ void cp_commit() { asm volatile("cp.async.commit_group;" ::: "memory"); }
template <int N> __device__ __forceinline__ void cp_wait() { asm volatile("cp.async.wait_group %0;" ::"n"(N) : "memory"); }
__device__ __forceinline__ void bulk_commit() { asm volatile("cp.async.bulk.commit_group;" ::: "memory"); }
__device__ __forceinline__ void bulk_wait0() { asm volatile("cp.async.bulk.wait_group 0;" ::: "memory"); }
__device__ __forceinline__ void ldsm4(uint32_t* r, uint32_t a) {
    asm volatile("ldmatrix.sync.aligned.m8n8.x4.shared.b16 {%0,%1,%2,%3},[%4];" : "=r"(r[0]), "=r"(r[1]), "=r"(r[2]), "=r"(r[3]) : "r"(a) : "memory");
}
__device__ __forceinline__ void ldsm4t(uint32_t* r, uint32_t a) {
    asm volatile("ldmatrix.sync.aligned.m8n8.x4.trans.shared.b16 {%0,%1,%2,%3},[%4];" : "=r"(r[0]), "=r"(r[1]), "=r"(r[2]), "=r"(r[3]) : "r"(a) : "memory");
}
__device__ __forceinline__ void stsm4(uint32_t a, uint32_t r0, uint32_t r1, uint32_t r2, uint32_t r3) {
    asm volatile("stmatrix.sync.aligned.m8n8.x4.shared.b16 [%0],{%1,%2,%3,%4};" ::"r"(a), "r"(r0), "r"(r1), "r"(r2), "r"(r3) : "memory");
}
__device__ __forceinline__ void stsm4t(uint32_t a, uint32_t r0, uint32_t r1, uint32_t r2, uint32_t r3) {
    asm volatile("stmatrix.sync.aligned.m8n8.x4.trans.shared.b16 [%0],{%1,%2,%3,%4};" ::"r"(a), "r"(r0), "r"(r1), "r"(r2), "r"(r3) : "memory");
}
__device__ __forceinline__ void lds128(uint32_t* r, uint32_t a) {
    asm volatile("ld.shared.v4.b32 {%0,%1,%2,%3},[%4];" : "=r"(r[0]), "=r"(r[1]), "=r"(r[2]), "=r"(r[3]) : "r"(a) : "memory");
}
__device__ __forceinline__ void lds64(uint32_t* r, uint32_t a) {
    asm volatile("ld.shared.v2.b32 {%0,%1},[%2];" : "=r"(r[0]), "=r"(r[1]) : "r"(a) : "memory");
}
__device__ __forceinline__ uint32_t lds32(uint32_t a) { uint32_t v; asm volatile("ld.shared.b32 %0,[%1];" : "=r"(v) : "r"(a) : "memory"); return v; }
__device__ __forceinline__ void sts128(uint32_t a, uint32_t r0, uint32_t r1, uint32_t r2, uint32_t r3) {
    asm volatile("st.shared.v4.b32 [%0],{%1,%2,%3,%4};" ::"r"(a), "r"(r0), "r"(r1), "r"(r2), "r"(r3) : "memory");
}
__device__ __forceinline__ void sts64(uint32_t a, uint32_t v0, uint32_t v1) { asm volatile("st.shared.v2.b32 [%0],{%1,%2};" ::"r"(a), "r"(v0), "r"(v1) : "memory"); }
[[maybe_unused]] __device__ __forceinline__ void sts32(uint32_t a, uint32_t v) { asm volatile("st.shared.b32 [%0],%1;" ::"r"(a), "r"(v) : "memory"); }
#define AU_(op) "{.reg .u32 t; add.u32 t,%4,%5; " op " {%0,%1,%2,%3},[t+%6];}"
template <int I> __device__ __forceinline__ void ldsm4_u(uint32_t* r, uint32_t a, uint32_t u) {
    asm volatile(AU_("ldmatrix.sync.aligned.m8n8.x4.shared.b16") : "=r"(r[0]), "=r"(r[1]), "=r"(r[2]), "=r"(r[3]) : "r"(a), "r"(u), "n"(I) : "memory");
}
template <int I> __device__ __forceinline__ void ldsm4t_u(uint32_t* r, uint32_t a, uint32_t u) {
    asm volatile(AU_("ldmatrix.sync.aligned.m8n8.x4.trans.shared.b16") : "=r"(r[0]), "=r"(r[1]), "=r"(r[2]), "=r"(r[3]) : "r"(a), "r"(u), "n"(I) : "memory");
}
template <int I> __device__ __forceinline__ void lds128_u(uint32_t* r, uint32_t a, uint32_t u) {
    asm volatile(AU_("ld.shared.v4.b32") : "=r"(r[0]), "=r"(r[1]), "=r"(r[2]), "=r"(r[3]) : "r"(a), "r"(u), "n"(I) : "memory");
}
template <int I> __device__ __forceinline__ void lds64_u(uint32_t* r, uint32_t a, uint32_t u) {
    asm volatile("{.reg .u32 t; add.u32 t,%2,%3; ld.shared.v2.b32 {%0,%1},[t+%4];}" : "=r"(r[0]), "=r"(r[1]) : "r"(a), "r"(u), "n"(I) : "memory");
}
template <int I> __device__ __forceinline__ uint32_t lds32_u(uint32_t a, uint32_t u) {
    uint32_t v;
    asm volatile("{.reg .u32 t; add.u32 t,%1,%2; ld.shared.b32 %0,[t+%3];}" : "=r"(v) : "r"(a), "r"(u), "n"(I) : "memory");
    return v;
}
template <int I> __device__ __forceinline__ void sts64_u(uint32_t a, uint32_t u, uint32_t v0, uint32_t v1) {
    asm volatile("{.reg .u32 t; add.u32 t,%0,%1; st.shared.v2.b32 [t+%2],{%3,%4};}" ::"r"(a), "r"(u), "n"(I), "r"(v0), "r"(v1) : "memory");
}
template <int I> __device__ __forceinline__ void sts32_u(uint32_t a, uint32_t u, uint32_t v) {
    asm volatile("{.reg .u32 t; add.u32 t,%0,%1; st.shared.b32 [t+%2],%3;}" ::"r"(a), "r"(u), "n"(I), "r"(v) : "memory");
}
template <int I> __device__ __forceinline__ void sts16_u(uint32_t a, uint32_t u, uint32_t v) {
    asm volatile("{.reg .u32 t; add.u32 t,%0,%1; st.shared.b16 [t+%2],%3;}" ::"r"(a), "r"(u), "n"(I), "h"((unsigned short)v) : "memory");
}
template <int I> __device__ __forceinline__ void sts128_u(uint32_t a, uint32_t u, uint32_t r0, uint32_t r1, uint32_t r2, uint32_t r3) {
    asm volatile("{.reg .u32 t; add.u32 t,%0,%1; st.shared.v4.b32 [t+%2],{%3,%4,%5,%6};}" ::"r"(a), "r"(u), "n"(I), "r"(r0), "r"(r1), "r"(r2), "r"(r3) : "memory");
}
template <int I> __device__ __forceinline__ void stsm4_u(uint32_t a, uint32_t u, uint32_t r0, uint32_t r1, uint32_t r2, uint32_t r3) {
    asm volatile("{.reg .u32 t; add.u32 t,%0,%1; stmatrix.sync.aligned.m8n8.x4.shared.b16 [t+%2],{%3,%4,%5,%6};}"
                 ::"r"(a), "r"(u), "n"(I), "r"(r0), "r"(r1), "r"(r2), "r"(r3) : "memory");
}
__device__ __forceinline__ void st_async2_x3(uint32_t a, uint32_t u, uint32_t mb, uint32_t v0, uint32_t v1) {
    asm volatile("{.reg .u32 t,x,y; add.u32 t,%0,%1;\n"
                 "mapa.shared::cluster.u32 x,t,0; mapa.shared::cluster.u32 y,%2,0; st.async.shared::cluster.mbarrier::complete_tx::bytes.v2.b32 [x],{%3,%4},[y];\n"
                 "mapa.shared::cluster.u32 x,t,1; mapa.shared::cluster.u32 y,%2,1; st.async.shared::cluster.mbarrier::complete_tx::bytes.v2.b32 [x],{%3,%4},[y];\n"
                 "mapa.shared::cluster.u32 x,t,2; mapa.shared::cluster.u32 y,%2,2; st.async.shared::cluster.mbarrier::complete_tx::bytes.v2.b32 [x],{%3,%4},[y];}"
                 ::"r"(a), "r"(u), "r"(mb), "r"(v0), "r"(v1) : "memory");
}
__device__ __forceinline__ void st_share2(uint32_t a, uint32_t u, uint32_t mb, uint32_t d0, uint32_t d1, uint32_t v0, uint32_t v1) {
    asm volatile("{.reg .pred p; .reg .u32 t,x,y; add.u32 t,%0,%1;\n"
                 "add.u32 x,t,%3; add.u32 y,%2,%3; st.async.shared::cluster.mbarrier::complete_tx::bytes.v2.b32 [x],{%5,%6},[y];\n"
                 "add.u32 x,t,%4; add.u32 y,%2,%4; st.async.shared::cluster.mbarrier::complete_tx::bytes.v2.b32 [x],{%5,%6},[y];\n"
                 "st.shared.v2.b32 [t],{%5,%6}; bar.warp.sync -1; setp.eq.u32 p,%0,0; @p mbarrier.arrive.shared::cta.b64 _,[%2];}"
                 ::"r"(a), "r"(u), "r"(mb), "r"(d0), "r"(d1), "r"(v0), "r"(v1) : "memory");
}
template <int V> struct IC { __host__ __device__ constexpr operator int() const { return V; } };
template <int N, class F> __device__ __forceinline__ void sfor(F f) {
    if constexpr (N > 0) { sfor<N - 1>(f); f(IC<N - 1>()); }
}
__device__ __forceinline__ void mma_f16(float* d, const uint32_t* a, uint32_t b0, uint32_t b1) {
    asm volatile("mma.sync.aligned.m16n8k16.row.col.f32.f16.f16.f32 {%0,%1,%2,%3},{%4,%5,%6,%7},{%8,%9},{%0,%1,%2,%3};"
                 : "+f"(d[0]), "+f"(d[1]), "+f"(d[2]), "+f"(d[3]) : "r"(a[0]), "r"(a[1]), "r"(a[2]), "r"(a[3]), "r"(b0), "r"(b1));
}
__device__ __forceinline__ void mma_bf(float* d, uint32_t a0, uint32_t a1, uint32_t a2, uint32_t a3, uint32_t b0, uint32_t b1) {
    asm volatile("mma.sync.aligned.m16n8k16.row.col.f32.bf16.bf16.f32 {%0,%1,%2,%3},{%4,%5,%6,%7},{%8,%9},{%0,%1,%2,%3};"
                 : "+f"(d[0]), "+f"(d[1]), "+f"(d[2]), "+f"(d[3]) : "r"(a0), "r"(a1), "r"(a2), "r"(a3), "r"(b0), "r"(b1));
}
__device__ __forceinline__ void mma_bf8(float* d, uint32_t a0, uint32_t a1, uint32_t b0) {
    asm volatile("mma.sync.aligned.m16n8k8.row.col.f32.bf16.bf16.f32 {%0,%1,%2,%3},{%4,%5},{%6},{%0,%1,%2,%3};"
                 : "+f"(d[0]), "+f"(d[1]), "+f"(d[2]), "+f"(d[3]) : "r"(a0), "r"(a1), "r"(b0));
}
__device__ __forceinline__ uint32_t pack_bf(float lo, float hi) { uint32_t r; asm("cvt.rn.bf16x2.f32 %0,%1,%2;" : "=r"(r) : "f"(hi), "f"(lo)); return r; }
__device__ __forceinline__ uint32_t pack_h(float lo, float hi) { uint32_t r; asm("cvt.rn.f16x2.f32 %0,%1,%2;" : "=r"(r) : "f"(hi), "f"(lo)); return r; }
__device__ __forceinline__ float bf_lo(uint32_t v) { return __uint_as_float(v << 16); }
__device__ __forceinline__ float bf_hi(uint32_t v) { return __uint_as_float(v & 0xffff0000u); }
__device__ __forceinline__ uint32_t bfma(uint32_t a, uint32_t b, uint32_t c) { uint32_t r; asm("fma.rn.bf16x2 %0,%1,%2,%3;" : "=r"(r) : "r"(a), "r"(b), "r"(c)); return r; }
__device__ __forceinline__ uint4 add_bf8(const uint4 x, const uint32_t* y, const uint32_t k = 0x3f803f80u) {
    return make_uint4(bfma(y[0], k, x.x), bfma(y[1], k, x.y), bfma(y[2], k, x.z), bfma(y[3], k, x.w));
}
__device__ __forceinline__ float ex2(float x) { float r; asm("ex2.approx.ftz.f32 %0,%1;" : "=f"(r) : "f"(x)); return r; }
__device__ __forceinline__ float rcp(float x) { float r; asm("rcp.approx.ftz.f32 %0,%1;" : "=f"(r) : "f"(x)); return r; }
__device__ __forceinline__ void wg_fence() { asm volatile("wgmma.fence.sync.aligned;" ::: "memory"); }
__device__ __forceinline__ void wg_commit() { asm volatile("wgmma.commit_group.sync.aligned;" ::: "memory"); }
template <int N> __device__ __forceinline__ void wg_wait() { asm volatile("wgmma.wait_group.sync.aligned %0;" ::"n"(N) : "memory"); }
__device__ __forceinline__ uint64_t mkdesc(uint32_t a, uint32_t lbo, uint32_t sbo, uint32_t sw) {
    return (uint64_t)((a & 0x3FFFF) >> 4) | ((uint64_t)(lbo >> 4) << 16) | ((uint64_t)(sbo >> 4) << 32) | ((uint64_t)sw << 62);
}
#define F4(d, i) "+f"(d[i]), "+f"(d[i + 1]), "+f"(d[i + 2]), "+f"(d[i + 3])
#define F8(d, i) F4(d, i), F4(d, i + 4)
#define F16(d, i) F8(d, i), F8(d, i + 8)
template <int OFF, int SC> __device__ __forceinline__ void wg_n32_x(float* d, const uint32_t* a, uint32_t lo) {
    asm volatile("{.reg .pred p; .reg .b32 l; .reg .b64 q; setp.ne.b32 p,%22,0; add.u32 l,%20,%21; mov.b64 q,{l,8};\n"
                 "wgmma.mma_async.sync.aligned.m64n32k16.f32.f16.f16 "
                 "{%0,%1,%2,%3,%4,%5,%6,%7,%8,%9,%10,%11,%12,%13,%14,%15},{%16,%17,%18,%19},q,p,1,1,0;}"
                 : F16(d, 0) : "r"(a[0]), "r"(a[1]), "r"(a[2]), "r"(a[3]), "r"(lo), "n"(OFF), "n"(SC));
}
__device__ __forceinline__ void wg_n128_rs(float* d, const uint32_t* a, uint64_t db, int sc) {
    asm volatile("{.reg .pred p; setp.ne.b32 p,%69,0; wgmma.mma_async.sync.aligned.m64n128k16.f32.f16.f16 "
                 "{%0,%1,%2,%3,%4,%5,%6,%7,%8,%9,%10,%11,%12,%13,%14,%15,%16,%17,%18,%19,%20,%21,%22,%23,%24,%25,%26,%27,%28,%29,%30,%31,"
                 "%32,%33,%34,%35,%36,%37,%38,%39,%40,%41,%42,%43,%44,%45,%46,%47,%48,%49,%50,%51,%52,%53,%54,%55,%56,%57,%58,%59,%60,%61,%62,%63},"
                 "{%64,%65,%66,%67},%68,p,1,1,0;}"
                 : F16(d, 0), F16(d, 16), F16(d, 32), F16(d, 48) : "r"(a[0]), "r"(a[1]), "r"(a[2]), "r"(a[3]), "l"(db), "r"(sc));
}
#define N80_REGS "{%0,%1,%2,%3,%4,%5,%6,%7,%8,%9,%10,%11,%12,%13,%14,%15,%16,%17,%18,%19,%20,%21,%22,%23,%24,%25,%26,%27,%28,%29,%30,%31,%32,%33,%34,%35,%36,%37,%38,%39}"
__device__ __forceinline__ void wg_n80_ss(float* d, uint64_t da, uint64_t db, int sc) {
    asm volatile("{.reg .pred p; setp.ne.b32 p,%42,0; wgmma.mma_async.sync.aligned.m64n80k16.f32.bf16.bf16 " N80_REGS ",%40,%41,p,1,1,0,0;}"
                 : F16(d, 0), F16(d, 16), F8(d, 32) : "l"(da), "l"(db), "r"(sc));
}
__device__ __forceinline__ void wg_n88_ss(float* d, uint64_t da, uint64_t db, int sc) {
    asm volatile("{.reg .pred p; setp.ne.b32 p,%46,0; wgmma.mma_async.sync.aligned.m64n88k16.f32.f16.f16 "
                 "{%0,%1,%2,%3,%4,%5,%6,%7,%8,%9,%10,%11,%12,%13,%14,%15,%16,%17,%18,%19,%20,%21,%22,%23,%24,%25,%26,%27,%28,%29,%30,%31,"
                 "%32,%33,%34,%35,%36,%37,%38,%39,%40,%41,%42,%43},%44,%45,p,1,1,0,0;}"
                 : F16(d, 0), F16(d, 16), F8(d, 32), F4(d, 40) : "l"(da), "l"(db), "r"(sc));
}
__device__ __forceinline__ void wg_n48_ss_ta(float* d, uint64_t da, uint64_t db, int sc) {
    asm volatile("{.reg .pred p; setp.ne.b32 p,%26,0; wgmma.mma_async.sync.aligned.m64n48k16.f32.f16.f16 "
                 "{%0,%1,%2,%3,%4,%5,%6,%7,%8,%9,%10,%11,%12,%13,%14,%15,%16,%17,%18,%19,%20,%21,%22,%23},%24,%25,p,1,1,1,0;}"
                 : F16(d, 0), F8(d, 16) : "l"(da), "l"(db), "r"(sc));
}
template <int TA> __device__ __forceinline__ void wg_n64_ss_tb(float* d, uint64_t da, uint64_t db, int sc) {
    asm volatile("{.reg .pred p; setp.ne.b32 p,%34,0; wgmma.mma_async.sync.aligned.m64n64k16.f32.f16.f16 "
                 "{%0,%1,%2,%3,%4,%5,%6,%7,%8,%9,%10,%11,%12,%13,%14,%15,%16,%17,%18,%19,%20,%21,%22,%23,%24,%25,%26,%27,%28,%29,%30,%31},"
                 "%32,%33,p,1,1,%35,1;}"
                 : F16(d, 0), F16(d, 16) : "l"(da), "l"(db), "r"(sc), "n"(TA));
}
__device__ __forceinline__ void pdl_wait() { asm volatile("griddepcontrol.wait;" ::: "memory"); }
__device__ __forceinline__ void pdl_go() { asm volatile("griddepcontrol.launch_dependents;" ::: "memory"); }
__device__ __forceinline__ float cos640(float p) {
    const float q = fmaf(p, 0.0015625f, 12582912.f) - 12582912.f;
    return __cosf(fmaf(q, -640.f, p) * 0.009817477042468103f);
}
__device__ __forceinline__ uint4 cos_row8(float p0, float step, float amp = 1.f) {
    float v[8];
    const float k = 2.f * cos640(step);
    v[0] = amp * cos640(p0); v[1] = amp * cos640(p0 + step);
#pragma unroll
    for (int i = 2; i < 8; i++) v[i] = fmaf(k, v[i - 1], -v[i - 2]);
    return make_uint4(pack_h(v[0], v[1]), pack_h(v[2], v[3]), pack_h(v[4], v[5]), pack_h(v[6], v[7]));
}
__device__ __forceinline__ float wfilter_max(int lane) {
    float m = fmaxf(fmaxf(g_wmax[lane], g_wmax[lane + 32]), fmaxf(g_wmax[lane + 64], g_wmax[lane + 96]));
    return __uint_as_float(__reduce_max_sync(~0u, __float_as_uint(m)));
}
__device__ __forceinline__ unsigned ld_acquire(const Flag* p) { unsigned v; asm volatile("ld.acquire.gpu.global.u32 %0,[%1];" : "=r"(v) : "l"(p) : "memory"); return v; }
#define POLL_NS 200
template <int NS = POLL_NS> __device__ __forceinline__ void wait_flag(const Flag* p, unsigned v) {
    if (ld_acquire(p) >= v) return;
    unsigned x;
    int lim = 0;
    do {
        __nanosleep(NS);
        asm volatile("ld.relaxed.gpu.global.u32 %0,[%1];" : "=r"(x) : "l"(p) : "memory");
    } while (x < v && ++lim < SPIN_LIM);
    ld_acquire(p);
}
__device__ __forceinline__ void prefetch_l2(const void* p, int bytes) { asm volatile("cp.async.bulk.prefetch.L2.global [%0],%1;" ::"l"(p), "r"(bytes) : "memory"); }
__device__ __forceinline__ void red_release(Flag* p) { asm volatile("red.release.gpu.global.add.u32 [%0],1;" ::"l"(p) : "memory"); }
__device__ __forceinline__ void red_relaxed(Flag* p) { asm volatile("red.relaxed.gpu.global.add.u32 [%0],1;" ::"l"(p) : "memory"); }
__device__ __forceinline__ void red_h8(void* p, uint32_t a, uint32_t b, uint32_t c, uint32_t d) {
    asm volatile("red.relaxed.gpu.global.add.noftz.v4.f16x2 [%0],{%1,%2,%3,%4};" ::"l"(p), "r"(a), "r"(b), "r"(c), "r"(d) : "memory");
}
__device__ __forceinline__ float pow2_scale(float bound, int top, float* inv) {
    int e = (int)((__float_as_uint(bound) >> 23) & 0xff) - 126;
    int k = top - e;
    k = max(-100, min(100, k));
    *inv = __uint_as_float((uint32_t)(127 - k) << 23);
    return __uint_as_float((uint32_t)(127 + k) << 23);
}
__device__ __forceinline__ char* red_base() { return (char*)(((uintptr_t)g_redraw + 32767) & ~(uintptr_t)32767); }

__device__ __forceinline__ void setup_a(char* sm, const int b, const bf16* __restrict__ wr, const bf16* __restrict__ wi) {
    const int tid = threadIdx.x, lane = tid & 31;
    const uint32_t sb = smem_u32(sm);
    auto row_byte = [&](int q) { return ((b >> 2) + 32 * ((q >> 1) * 8 + 2 * (b & 3) + (q & 1))) * 642; };
#pragma unroll 1
    for (int r = tid >> 5; r < 32; r += 8) {
        const char* src = (const char*)(r < 16 ? wr : wi) + (row_byte(r & 15) & ~15);
        cp_async16(sb + r * 672 + lane * 16, src + lane * 16);
        if (lane < 9) cp_async16(sb + r * 672 + 512 + lane * 16, src + 512 + lane * 16);
    }
    ((uint4*)g_stat)[b * 256 + tid] = make_uint4(0, 0, 0, 0);
    if (tid < 2 * (NFLAG / 128)) ((uint4*)(g_flag + b * (NFLAG / 128) + (tid >> 1)))[tid & 1] = make_uint4(0, 0, 0, 0);
    if (tid < 12) {
        const int i = b * 12 + tid;
        const int f = ((i >> 4) & 3) * 8 + (i & 7), im = (i >> 3) & 1, part = (i >> 8) & 1;
        ((uint4*)g_ctab)[i] = cos_row8((float)(i < 1024 ? (i >> 7) * 80 * (i & 63) + ((i & 64) ? 480 : 0) : ((i >> 6) & 3) * 160 * f + (im == part ? 0 : im ? 160 : 480)),
                                       (float)(i < 1024 ? 10 * (i & 63) : 20 * f));
    }
    asm volatile("cp.async.wait_all;" ::: "memory");
    __syncthreads();
    const int q0 = (tid & 3) * 4;
    const char* rp[4];
#pragma unroll
    for (int u = 0; u < 4; u++) rp[u] = sm + (q0 + u) * 672 + (row_byte(q0 + u) & 15);
    uint32_t mx = 0;
#pragma unroll 2
    for (int c = tid >> 2; c < 321; c += 64) {
        uint32_t v[4];
#pragma unroll
        for (int u = 0; u < 4; u++) {
            v[u] = ((const unsigned short*)rp[u])[c] | ((uint32_t)((const unsigned short*)(rp[u] + 16 * 672))[c] << 16);
            mx = __vmaxu2(mx, v[u] & 0x7fff7fffu);
        }
        ((uint4*)g_Wf)[(size_t)c * 512 + b * 4 + ((tid ^ (b >> 1)) & 3)] = make_uint4(v[0], v[1], v[2], v[3]);
    }
    mx = __reduce_max_sync(~0u, max(mx & 0xffffu, mx >> 16));
    __syncthreads();
    if (lane == 0) ((uint32_t*)sm)[tid >> 5] = mx;
    __syncthreads();
    if (tid < 32) {
        mx = __reduce_max_sync(~0u, ((uint32_t*)sm)[lane & 7]);
        if (tid == 0) g_wmax[b] = __uint_as_float(mx << 16);
    }
}
__device__ __forceinline__ void setup_b(const int b, const bf16* __restrict__ mem0) {
    const int tid = threadIdx.x;
    uint4* z = (uint4*)red_base();
    if (b < 3) {
        const int w = tid >> 5, lane = tid & 31, p = b * 2 + ((w >> 1) & 1), odd = w & 1;
        uint32_t mx = 0;
#pragma unroll 4
        for (int i = lane; i < 640; i += 32) {
            const uint4 u = ((const uint4*)mem0)[i];
            mx = __vmaxu2(__vmaxu2(mx, u.x & 0x7fff7fffu), __vmaxu2(__vmaxu2(u.y & 0x7fff7fffu, u.z & 0x7fff7fffu), u.w & 0x7fff7fffu));
        }
        float inv, v[7];
        const float sc = pow2_scale(__uint_as_float(__reduce_max_sync(~0u, max(mx & 0xffffu, mx >> 16)) << 16), 14, &inv);
        if (tid == 0) g_invM0 = inv;
#pragma unroll
        for (int j = 0; j < 7; j++) {
            const int r = p * 56 + (j < 6 ? odd * 32 + (j >> 1) * 8 : 24) + (lane >> 2), mr = 2 * (lane & 3) + (j < 6 ? (j & 1) : odd);
            v[j] = r < 320 ? __bfloat162float(mem0[mr * 640 + (w >> 2) * 320 + r]) * sc : 0.f;
        }
        const int off = w * 2048 + (lane >> 4) * 1024 + ((lane >> 3) & 1) * 256 + (lane & 7) * 16 + (b == 2 ? (w >> 1) * 4096 + 128 : b * 16384);
        const uint4 u = make_uint4(pack_h(v[0], v[1]), pack_h(v[2], v[3]), pack_h(v[4], v[5]), pack_h(v[6], 32.f));
        z[off >> 4] = u; z[65536 + (off >> 4)] = u;
    }
}

#define SU_PAD 40960
constexpr int SU_SMEM = SU_PAD;
__global__ void __launch_bounds__(256, 4) k_setup(const bf16* __restrict__ wr, const bf16* __restrict__ wi, const bf16* __restrict__ mem0) {
    extern __shared__ __align__(1024) char sm[];
    TL(0);
    if (blockIdx.x >= 128) setup_b(blockIdx.x - 128, mem0);
    else setup_a(sm, blockIdx.x, wr, wi);
    __syncthreads();
    if (threadIdx.x == 0) red_release(g_ready);
    TL(1);
}
__device__ __forceinline__ float weight_scale(int h, int ty, float* inv) { return pow2_scale(__ldcg(g_wmx + h * 3 + ty), 6, inv); }

#define STR_(x) #x
#define STR(x) STR_(x)
#define RF_U 1
constexpr int RF_A = 22 * 2816, RF_X = RF_A + 22 * 1024, RF_BAR = RF_X + 64 * 1344, RF_SMEM = RF_BAR + 64;
__global__ void __cluster_dims__(2, 1, 1) __launch_bounds__(256, 2)
k_rowf(const bf16* x, const int first, const bf16* Wq, const bf16* Wk, const bf16* Wv, const bf16* Wo) {
    extern __shared__ __align__(1024) char sm[];
    TL(first ? 2 : 16);
    const int tid = threadIdx.x, w = tid >> 5, lane = tid & 31, g = lane >> 2, t = lane & 3;
    if (blockIdx.x >= 128) { __nanosleep(2500); return; }
    const int a = blockIdx.x >> 2, gq = blockIdx.x & 3;
    const uint32_t sb = smem_u32(sm), mb = sb + RF_BAR + w * 8;
    if (lane == 0) {
        mbar_init(mb, 1);
        asm volatile("fence.mbarrier_init.release.cluster;" ::: "memory");
        mbar_expect(mb, 8 * 1280);
    }
    __syncwarp();
    asm volatile("barrier.cluster.arrive.relaxed.aligned;" ::: "memory");
#pragma unroll 1
    for (int ph = 0; ph < 2; ph++) {
        if (ph != first) {
            asm volatile("barrier.cluster.wait.aligned;" ::: "memory");
            pdl_wait();
            TL(first ? 3 : 17);
            if (lane < 4)
                asm volatile("cp.async.bulk.shared::cluster.global.mbarrier::complete_tx::bytes.multicast::cluster [%0],[%1],1280,[%2],%3;"
                             ::"r"(sb + RF_X + (w * 8 + (gq & 1) * 4 + lane) * 1344), "l"(x + (size_t)(a * 64 + w * 8 + (gq & 1) * 4 + lane) * 640), "r"(mb),
                             "h"((unsigned short)3) : "memory");
            __syncwarp();
            pdl_go();
        } else {
#pragma unroll 3
            for (int id = tid; id < 22 * 176; id += 256) {
                const int kg = id / 176, n = id - kg * 176;
                const float c = (float)(2 * n + (gq & 1));
                *(uint4*)(sm + id * 16) = cos_row8(fmaf((float)(kg * 8), c, (float)((gq & 2) * 80)), c, 0.03952847075210474f);
            }
        }
    }
    mbar_wait(mb, 0);
    const uint32_t row = sb + RF_X + (w * 8 + g) * 1344;
    float st[4][4] = {};
#pragma unroll 1
    for (int i = 0; i < 20; i += 4) {
        uint32_t u[4][4];
#pragma unroll
        for (int q = 0; q < 4; q++) lds128(u[q], row + (4 * (i + q) + t) * 16);
#pragma unroll
        for (int q = 0; q < 4; q++) {
            mma_bf(st[(q & 1) * 2], u[q][0], 0x3f803f80u, u[q][1], 0x3f803f80u, u[q][0], u[q][1]);
            mma_bf(st[(q & 1) * 2 + 1], u[q][2], 0x3f803f80u, u[q][3], 0x3f803f80u, u[q][2], u[q][3]);
        }
    }
#pragma unroll
    for (int q = 0; q < 4; q++) { st[0][q] += st[2][q]; st[1][q] += st[3][q]; }
    const float sq = __shfl_sync(~0u, (g & 1) ? st[0][1] + st[1][1] : st[0][0] + st[1][0], g * 4 + (g >> 1));
    const float mean = __shfl_sync(~0u, (g & 1) ? st[0][3] + st[1][3] : st[0][2] + st[1][2], g * 4 + (g >> 1)) * (1.f / 640.f);
    const float r = rsqrtf(fmaxf(fmaf(-mean, mean, sq * (1.f / 640.f)), 0.f) + 1e-5f), off = gq == 0 ? -4.f * mean * r : 0.f;
    const float r1 = (gq == 1 || gq == 2) ? -r : r, r2 = (gq & 1) ? -r : r, r3 = gq >= 2 ? -r : r;
    const uint32_t aa = sb + RF_A + w * 128 + g * 16;
    auto el = [&](int d) { unsigned short v; asm volatile("ld.shared.u16 %0,[%1];" : "=h"(v) : "r"(row + d * 2)); return __uint_as_float((uint32_t)v << 16); };
_Pragma(STR(unroll RF_U))
    for (int i = 0; i < 5; i++) {
        const int ch = t + 4 * i;
        uint32_t u[4][4];
        lds128(u[0], row + ch * 16); lds128(u[1], row + (39 - ch) * 16); lds128(u[2], row + (40 + ch) * 16); lds128(u[3], row + (79 - ch) * 16);
        const float nb0 = el(320 - 8 * ch), nb1 = el(ch ? 640 - 8 * ch : 0);
        float o[8];
#pragma unroll
        for (int q = 0; q < 8; q++) {
            const int m = (8 - q) >> 1;
            const float e0 = (q & 1) ? bf_hi(u[0][q >> 1]) : bf_lo(u[0][q >> 1]), e2 = (q & 1) ? bf_hi(u[2][q >> 1]) : bf_lo(u[2][q >> 1]);
            const float e1 = q == 0 ? nb0 : (q & 1) ? bf_hi(u[1][m & 3]) : bf_lo(u[1][m & 3]), e3 = q == 0 ? nb1 : (q & 1) ? bf_hi(u[3][m & 3]) : bf_lo(u[3][m & 3]);
            o[q] = fmaf(e3, r3, fmaf(e2, r2, fmaf(e1, r1, fmaf(e0, r, off))));
        }
        if (ch == 0) o[0] *= 0.5f;
        sts128(aa + ch * 1024, pack_h(o[0], o[1]), pack_h(o[2], o[3]), pack_h(o[4], o[5]), pack_h(o[6], o[7]));
    }
    if (t < 2) sts128(aa + (20 + t) * 1024, t == 0 ? pack_h(fmaf(el(480), r2, fmaf(el(160), r, 0.5f * off)), 0.f) : 0u, 0u, 0u, 0u);
    fence_async_smem();
    __syncthreads();
    const int wg = w >> 2;
    float acc[44];
    uint64_t da = mkdesc(sb + RF_A, 1024, 128, 0), db = mkdesc(sb + wg * 1408, 2816, 128, 0);
    wg_fence();
#pragma unroll 1
    for (int k = 0; k < 11; k++) { wg_n88_ss(acc, da, db, k); da += 128; db += 352; }
    wg_commit(); wg_wait<0>();
    const uint32_t stg = sb + RF_X + wg * 96 * 144;
#pragma unroll
    for (int j = 0; j < 12; j += 2) {
        const int m = lane >> 3, j1 = j < 10 ? j + 1 : j;
        stsm4t(stg + ((j + (m >> 1)) * 8 + (lane & 7)) * 144 + ((w & 3) * 16 + (m & 1) * 8) * 2, pack_h(acc[j * 4], acc[j * 4 + 1]),
               pack_h(acc[j * 4 + 2], acc[j * 4 + 3]), pack_h(acc[j1 * 4], acc[j1 * 4 + 1]), pack_h(acc[j1 * 4 + 2], acc[j1 * 4 + 3]));
    }
    bar_sync(1 + wg, 128);
#pragma unroll 3
    for (int rr = (tid & 127) >> 3; rr < 88; rr += 16) {
        const int ch = tid & 7, c = 2 * (wg * 88 + rr) + (gq & 1);
        if (c <= 320 - (gq >> 1) && (c | (gq ^ 2))) {
            uint32_t u[4];
            lds128(u, stg + rr * 144 + ch * 16);
            ((uint4*)g_UT)[((size_t)(c == 320 ? 1 : 2 * c + (gq >> 1)) * 32 + a) * 8 + (ch ^ (a & 7))] = make_uint4(u[0], u[1], u[2], u[3]);
        }
    }
    TL(first ? 4 : 18);
}

constexpr int GST = 4, GSTB = 32768 + 20480, GNC = 32;
constexpr int G_BAR = GST * GSTB + 3072;
#define GPACE 1100
#define GPACE2 650
__device__ __forceinline__ void oproj_load(const uint32_t sb, const int op, const int mb, const int nb, const int c0, const uint32_t pace) {
    const int by = op == 2 ? 20480 : 16384;
    const char* src = op == 2 ? (const char*)g_wot + (size_t)nb * GNC * 20480 : (const char*)g_O + (size_t)(2 * mb + op) * GNC * 16384;
    uint32_t t0 = clock32() - pace + op * (pace / 3);
#pragma unroll 1
    for (int c = c0; c < c0 + GNC; c++, src += by) {
        const int st = c % GST;
        if (c >= GST) mbar_wait(sb + G_BAR + (GST + st) * 8, ((c / GST) - 1) & 1);
        while (clock32() - t0 < pace) {}
        t0 = clock32();
        const int by_ = by;
        mbar_expect(sb + G_BAR + st * 8, by_);
        if (op == 2) bulk_g2s(sb + st * GSTB + 32768, src, by_, sb + G_BAR + st * 8);
        else bulk_g2s_last(sb + st * GSTB + op * 16384, src, by_, sb + G_BAR + st * 8);
    }
}
__device__ __forceinline__ void oproj_mma(const uint32_t sb, const int mb, const int nb, const int c0, const bf16* res, bf16* out) {
    const int w = threadIdx.x >> 5, lane = threadIdx.x & 31, wg = w >> 2;
    float acc[40];
    uint4 rv[5];
#pragma unroll 1
    for (int c = c0; c < c0 + GNC; c++) {
        const int st = c % GST;
        mbar_wait(sb + G_BAR + st * 8, (c / GST) & 1);
        const uint32_t d = sb + st * GSTB;
        wg_fence();
#pragma unroll
        for (int k = 0; k < 8; k++)
            wg_n80_ss(acc, mkdesc(d + wg * 16384 + k * 2048, 1024, 128, 0), mkdesc(d + 32768 + k * 2560, 1280, 128, 0), (c - c0) | k);
        wg_commit();
        if (c > c0) {
            wg_wait<1>();
            if (lane == 0) mbar_arrive(sb + G_BAR + (GST + (c - 1) % GST) * 8);
        }
    }
#pragma unroll
    for (int i = 0; i < 5; i++) {
        const int id = i * 32 + lane, r = id / 10;
        rv[i] = __ldcg((const uint4*)res + (size_t)(mb * 128 + w * 16 + r) * 80 + nb * 10 + id - r * 10);
    }
    wg_wait<0>();
    bar_sync(5, 256);
    const uint32_t stg = sb + (GST - 1) * GSTB + w * 16 * 176;
#pragma unroll
    for (int j = 0; j < 5; j++)
        stsm4(stg + (lane & 15) * 176 + (2 * j + (lane >> 4)) * 16, pack_bf(acc[j * 8], acc[j * 8 + 1]), pack_bf(acc[j * 8 + 2], acc[j * 8 + 3]),
              pack_bf(acc[j * 8 + 4], acc[j * 8 + 5]), pack_bf(acc[j * 8 + 6], acc[j * 8 + 7]));
    __syncwarp();
#pragma unroll
    for (int i = 0; i < 5; i++) {
        const int id = i * 32 + lane, r = id / 10, ch = id - r * 10;
        uint32_t y[4];
        lds128(y, stg + r * 176 + ch * 16);
        ((uint4*)out)[(size_t)(mb * 128 + w * 16 + r) * 80 + nb * 10 + ch] = add_bf8(rv[i], y);
    }
    fence_async_smem();
    __syncwarp();
    if (lane == 0) mbar_arrive(sb + G_BAR + (2 * GST - 1) * 8);
}

__global__ void __launch_bounds__(128, 4) k_col(const int first, const bf16* Wq, const bf16* Wk, const bf16* Wv, const bf16* Wo) {
    __shared__ __align__(1024) char sz[8192];
    __shared__ __align__(1024) char stab[24576];
    __shared__ __align__(1024) char swf[8192];
    __shared__ __align__(8) uint64_t bar[2];
    const int tid = threadIdx.x, wl = tid >> 5, lane = tid & 31, g = lane >> 2, t = lane & 3;
    const int c = blockIdx.x;
    TL(first ? 5 : 19);
    const bool realc = c == 0 || c == 320;
    const uint32_t z = smem_u32(sz), b2 = smem_u32(stab), a1 = b2 + 16384, wf = smem_u32(swf), mb = smem_u32(bar);
    if (tid == 0) { mbar_init(mb, 1); mbar_init(mb + 8, 1); fence_async_smem(); }
    if (realc) {
        for (int i = tid; i < 256; i += 128) sts128(z + 4096 + i * 16, 0, 0, 0, 0);
        fence_async_smem();
    }
    const int k1 = wl * 8 + g;
    float tc[16], ts[16];
#pragma unroll
    for (int j = 0; j < 16; j++) {
        const int p = ((j >> 1) * 8 + 2 * t + (j & 1)) * k1;
        __sincosf((float)(p - 1024) * 0.003067961575771282f, &ts[j], &tc[j]);
        ts[j] = -ts[j]; tc[j] = -tc[j];
    }
    if (first && tid == 32) { wait_flag<400>(g_ready, NSETUP); fence_async_glb(); }
    __syncthreads();
    if (tid == 32) {
        mbar_expect(mb + 8, 24576 + 8192);
        bulk_g2s(b2, g_ctab, 24576, mb + 8);
        bulk_g2s(wf, g_Wf + (size_t)c * 2048, 8192, mb + 8);
    }
    float inv;
    const float wsc = pow2_scale(wfilter_max(lane), 0, &inv) * (realc ? 0.0625f : 0.125f);
    pdl_wait();
    TL(first ? 6 : 20);
    if (tid == 0) {
        const int by = realc ? 4096 : 8192;
        mbar_expect(mb, by);
        bulk_g2s_last(z, (const char*)g_UT + (size_t)(c == 320 ? 1 : 2 * c) * 4096, by, mb);
    }
    pdl_go();
    mbar_wait(mb + 8, 0);
    mbar_wait(mb, 0);
    float d[64];
    uint32_t a[4][4];
    wg_fence();
#pragma unroll
    for (int ks = 0; ks < 4; ks++) wg_n64_ss_tb<0>(d, mkdesc(a1 + ks * 2048, 1024, 128, 0), mkdesc(z + ks * 2048, 1024, 1024, 1), ks);
    wg_commit(); wg_wait<0>();
    const float r32 = 0.17677669529663687f;
#pragma unroll
    for (int j = 0; j < 8; j++) {
        float yr[2], yi[2];
#pragma unroll
        for (int e = 0; e < 2; e++) {
            const float re = d[j * 4 + e] * r32, im = d[j * 4 + 2 + e] * r32, cc = tc[j * 2 + e], ss = ts[j * 2 + e];
            yr[e] = re * cc + im * ss; yi[e] = im * cc - re * ss;
        }
        a[j >> 1][(j & 1) * 2] = pack_h(yr[0], yr[1]); a[j >> 1][(j & 1) * 2 + 1] = pack_h(yi[0], yi[1]);
    }
    wg_fence();
#pragma unroll
    for (int ks = 0; ks < 4; ks++) wg_n128_rs(d, a[ks], mkdesc(b2 + ks * 4096, 2048, 128, 0), ks);
    wg_commit(); wg_wait<0>();
#pragma unroll
    for (int q = 0; q < 4; q++) {
        uint32_t wv[4];
        lds128(wv, wf + tid * 64 + ((q ^ (tid >> 1)) & 3) * 16);
#pragma unroll
        for (int jj = 0; jj < 2; jj++) {
            const int j = 2 * q + jj;
            float yr[2], yi[2];
#pragma unroll
            for (int e = 0; e < 2; e++) {
                const float xr = d[j * 4 + e] + d[32 + j * 4 + 2 + e], xi = d[j * 4 + 2 + e] - d[32 + j * 4 + e];
                const float fr = bf_lo(wv[jj * 2 + e]) * wsc, fi = bf_hi(wv[jj * 2 + e]) * wsc;
                yr[e] = xr * fr - xi * fi; yi[e] = xr * fi + xi * fr;
            }
            a[q][jj * 2] = pack_h(yr[0], yr[1]); a[q][jj * 2 + 1] = pack_h(yi[0], yi[1]);
        }
    }
    wg_fence();
#pragma unroll
    for (int ks = 0; ks < 4; ks++) wg_n128_rs(d, a[ks], mkdesc(b2 + ks * 4096, 2048, 128, 0), ks);
    wg_commit(); wg_wait<0>();
#pragma unroll
    for (int j = 0; j < 8; j++) {
        float yr[2], yi[2];
#pragma unroll
        for (int e = 0; e < 2; e++) {
            const float vr = (d[j * 4 + e] - d[32 + j * 4 + 2 + e]) * 0.125f, vi = (d[j * 4 + 2 + e] + d[32 + j * 4 + e]) * 0.125f;
            const float cc = tc[j * 2 + e], ss = ts[j * 2 + e];
            yr[e] = vr * cc - vi * ss; yi[e] = vi * cc + vr * ss;
        }
        a[j >> 1][(j & 1) * 2] = pack_h(yr[0], yr[1]); a[j >> 1][(j & 1) * 2 + 1] = pack_h(yi[0], yi[1]);
    }
    __syncthreads();
    const int mm = lane >> 3, rr = lane & 7;
    const uint32_t rowo = (wl * 16 + (mm & 1) * 8 + rr) * 128;
#pragma unroll
    for (int q = 0; q < 4; q++) stsm4(z + rowo + (((2 * q + (mm >> 1)) ^ rr) << 4), a[q][0], a[q][1], a[q][2], a[q][3]);
    fence_async_smem();
    __syncthreads();
    wg_fence();
#pragma unroll
    for (int ks = 0; ks < 4; ks++) wg_n64_ss_tb<1>(d, mkdesc(a1 + ks * 256, 128, 1024, 0), mkdesc(z + ks * 2048, 1024, 1024, 1), ks);
    wg_commit(); wg_wait<0>();
#pragma unroll
    for (int q = 0; q < 4; q++)
        stsm4(wf + rowo + (((2 * q + (mm >> 1)) ^ rr) << 4), pack_h(d[q * 8] * r32, d[q * 8 + 1] * r32), pack_h(d[q * 8 + 2] * r32, d[q * 8 + 3] * r32),
              pack_h(d[q * 8 + 4] * r32, d[q * 8 + 5] * r32), pack_h(d[q * 8 + 6] * r32, d[q * 8 + 7] * r32));
    __syncwarp();
    if (!(realc && wl >= 2)) {
        const int kk = c == 320 ? 320 : (c & 1) * 160 + (c >> 1) + (wl >> 1) * 320;
#pragma unroll
        for (int i = 0; i < 4; i++) {
            const int r = wl * 16 + i * 4 + (lane >> 3), ch = lane & 7;
            uint32_t v[4];
            lds128(v, wf + r * 128 + ((ch ^ (r & 7)) << 4));
            ((uint4*)g_YT)[((size_t)(r & 31) * 640 + kk) * 8 + (ch ^ (kk & 7))] = make_uint4(v[0], v[1], v[2], v[3]);
        }
    }
    __syncthreads();
    if (tid == 0) red_release(g_flag + F_X + (first ? 0 : 128) + 65);
    TL(first ? 7 : 21);
}

constexpr int O_XS = 0;
constexpr int O_MS = 81920;
constexpr int O_QKP = O_MS + 10752;
constexpr int O_VM = O_QKP + 4096;
constexpr int O_SC = O_VM + 4096;
constexpr int O_OS = O_SC + 1536;
constexpr int O_XCH = O_OS + 2048;
constexpr int O_SUM = O_XCH + 8192;
constexpr int O_MX = O_SUM + 256;
constexpr int O_STG = O_MS + 65536 - 8192;
static_assert(O_STG - 16384 >= O_MX + 1024, "shared-memory map");
constexpr int O_WO = O_STG + 16384;
constexpr int O_SCL = O_WO + 65536;
constexpr int O_BAR = O_SCL + 64;
constexpr int B_XF = O_BAR, B_S = O_BAR + 16, B_GO = O_BAR + 24, B_VX = O_BAR + 32, B_STG = O_BAR + 48, B_FREE = O_BAR + 72;
constexpr int T_FA = O_BAR + 96, T_EA = T_FA + 32, T_FB = T_EA + 32, T_EB = T_FB + 56, T_RED = T_EB + 32;
constexpr int O_WMX = O_BAR + 512, B_W = O_BAR + 64;
constexpr int O_LAST = (O_WMX + 192 + 1023) / 1024 * 1024;
constexpr int CH_SMEM = O_LAST + 8192;
static_assert(O_WO == 19 * 8192, "weight staging");
__device__ __forceinline__ uint32_t tail_b(int c) { return c % 7 < 4 ? O_XS + (c % 7) * 20480 : O_WO + (c % 7 - 4) * 20480; }
constexpr int S_TX = 2 * 768 + 2048;
#define NOSELF 1
__device__ __forceinline__ int s_tx(int c) { return !NOSELF ? S_TX : c == 2 ? 2 * 768 : 768 + 2048; }

#define NPERM 1
#define NWO0 2
#define NWO1 6
#define XEARLY 0
#define RELAX 1
#define VEARLY 0
#define VLATE 0
#define SGATE 0
#define KVB 1
#define REL1 0
#define XLATE 0
#define TDELAY 800
#define WDEPTH 6
#define RDELAY 580

#define STAMP(i)

#define NTA 23
#define NTB 26
template <int LO, int HI>
__device__ __forceinline__ void tok_issue(const uint32_t (&A0)[20][4], const uint32_t (&A1)[20][4], float (&b0)[16], float (&b1)[16], uint32_t xd,
                                          const uint32_t zero) {
    if (LO == 0) wg_fence();
    sfor<HI - LO>([&](auto I) {
        constexpr int i = LO + I;
        if constexpr (i < 20) wg_n32_x<i * 64, i>(b0, A0[i], xd); else wg_n32_x<(i - 20) * 64, i - 20>(b1, A1[i - 20], xd + zero);
        if constexpr (i == 19 || i == NTB - 1 || i == 39) wg_commit();
    });
}
__device__ __forceinline__ void tok_give(const float (&b0)[16], const uint32_t L16, const uint32_t xch0) {
    wg_wait<1>();
    sfor<2>([&](auto I) {
        constexpr int i = I;
        sts128_u<i * 512>(L16, xch0, pack_h(b0[8 * i], b0[8 * i + 1]), pack_h(b0[8 * i + 2], b0[8 * i + 3]), pack_h(b0[8 * i + 4], b0[8 * i + 5]),
                          pack_h(b0[8 * i + 6], b0[8 * i + 7]));
    });
}
__device__ __forceinline__ void tok_finish(float (&b1)[16], const uint32_t (&e)[2][4], const uint32_t L16, const uint32_t dst, const uint32_t idn) {
#pragma unroll
    for (int j = 0; j < 4; j++)
        asm volatile("mma.sync.aligned.m16n8k8.row.col.f32.f16.f16.f32 {%0,%1,%2,%3},{%4,%5},{%6},{%0,%1,%2,%3};"
                     : F4(b1, 4 * j) : "r"(e[j >> 1][(j & 1) * 2]), "r"(e[j >> 1][(j & 1) * 2 + 1]), "r"(idn));
    stsm4_u<0>(L16, dst, pack_bf(b1[0], b1[1]), pack_bf(b1[2], b1[3]), pack_bf(b1[4], b1[5]), pack_bf(b1[6], b1[7]));
    stsm4_u<512>(L16, dst, pack_bf(b1[8], b1[9]), pack_bf(b1[10], b1[11]), pack_bf(b1[12], b1[13]), pack_bf(b1[14], b1[15]));
}
__device__ __forceinline__ uint32_t uni(uint32_t v) { return __shfl_sync(~0u, v, 0); }
__device__ __forceinline__ uint32_t badd(uint32_t a, uint32_t b) { uint32_t r; asm("add.rn.bf16x2 %0,%1,%2;" : "=r"(r) : "r"(a), "r"(b)); return r; }
__device__ __forceinline__ uint32_t bmax(uint32_t a, uint32_t b) { uint32_t r; asm("max.bf16x2 %0,%1,%2;" : "=r"(r) : "r"(a), "r"(b)); return r; }
__device__ __forceinline__ uint32_t babsmax(uint32_t a, uint32_t b) { uint32_t r; asm("max.xorsign.abs.bf16x2 %0,%1,%2;" : "=r"(r) : "r"(a), "r"(b)); return r; }
__device__ __forceinline__ uint32_t habsmax(uint32_t a, uint32_t b) { uint32_t r; asm("max.xorsign.abs.f16x2 %0,%1,%2;" : "=r"(r) : "r"(a), "r"(b)); return r; }

template <int NPF>
__device__ __forceinline__ float mem_out(const uint32_t sb, const uint32_t L16, const uint32_t L8, uint32_t (&wo)[16][4], const uint32_t woa,
                                         char* dst, const bool odd) {
    bar_sync(2, 352);
    float a[4][4];
#pragma unroll
    for (int i = 0; i < 4; i++) a[i][0] = a[i][1] = a[i][2] = a[i][3] = 0.f;
    uint32_t ob[4][4], sm_[2], sc[2];
    sfor<8>([&](auto I) {
        constexpr int i = I;
        if constexpr (!(i & 1)) ldsm4t_u<O_OS + (i >> 1) * 512>(ob[i >> 1], L16, sb);
        if constexpr (i >= NPF) { ldsm4t(wo[i], woa + i * 1024); ldsm4t(wo[8 + i], (woa ^ 32) + i * 1024); }
    });
    lds64_u<O_SUM>(sm_, L8 & 24, sb); lds64(sc, sb + O_SCL);
#pragma unroll
    for (int i = 0; i < 8; i++) {
        mma_bf(a[i & 1], wo[i][0], wo[i][1], wo[i][2], wo[i][3], ob[i >> 1][(i & 1) * 2], ob[i >> 1][(i & 1) * 2 + 1]);
        mma_bf(a[2 + (i & 1)], wo[8 + i][0], wo[8 + i][1], wo[8 + i][2], wo[8 + i][3], ob[i >> 1][(i & 1) * 2], ob[i >> 1][(i & 1) * 2 + 1]);
    }
    const float f0 = rcp(__uint_as_float(sm_[0])) * __uint_as_float(sc[0]), f1 = rcp(__uint_as_float(sm_[1])) * __uint_as_float(sc[0]);
    red_h8(dst, pack_h((a[0][0] + a[1][0]) * f0, (a[0][1] + a[1][1]) * f1), pack_h((a[0][2] + a[1][2]) * f0, (a[0][3] + a[1][3]) * f1),
           pack_h((a[2][0] + a[3][0]) * f0, (a[2][1] + a[3][1]) * f1), pack_h(odd ? (a[2][3] + a[3][3]) * f1 : (a[2][2] + a[3][2]) * f0, 1.f));
    return __uint_as_float(sc[1]);
}

__device__ __forceinline__ void chain_mma(const uint32_t sb, const int c, const int h, const int layer, const uint32_t zero, const bf16* __restrict__ Wq,
                                          const bf16* __restrict__ Wk, const bf16* __restrict__ Wv, const bf16* __restrict__ Wo,
                                          const bf16* res, bf16* out) {
    int tid = read_tid(), lane = tid & 31;
    const int w = __shfl_sync(~0u, tid >> 5, 0), wg = w >> 2;
    [[maybe_unused]] const int cta = h * 3 + c;
    uint32_t A0[20][4], A1[20][4];
    const int t0 = (w & 3) + wg * 4, t1 = t0 ^ 4;
    float sl;
    {
        const int tl = tid & 127, r = tl >> 3, ch = tl & 7;
        const size_t so = (size_t)(wg * 320 + r) * 4096 + h * 128 + ch * 8;
        const bf16 *wa = (c == 2 ? Wv : Wq + c * 64) + so, *wb = (c == 2 ? Wv + 64 : Wk + c * 64) + so;
        const uint32_t ring = sb + wg * 4096;
        const uint32_t dst = ring + r * 128 + ((ch ^ r) & 7) * 16;
        const uint32_t src = ring + ((lane & 7) + (lane >> 4) * 8) * 128 + ((((w & 3) * 2 + ((lane >> 3) & 1)) ^ lane) & 7) * 16;
        const int q4 = lane & 3, gr = (c * 2 + ((w >> 1) & 1)) * 56 + (q4 == 3 ? 24 : (w & 1) * 32 + q4 * 8);
        const bf16* wo_ = Wo + (size_t)(h * 128 + (lane >> 2)) * 640 + wg * 320 + min(gr, 312);
        const uint32_t wdst = sb + O_WO + w * 8192 + (lane >> 2) * 64 + ((q4 ^ (lane >> 3)) & 3) * 16;
        auto issue = [&](int i) {
            if (i < 20) {
                const uint32_t d = dst + (i < 19 ? i * 8192 : O_LAST);
                cp_async16(d, wa + (size_t)i * 65536); cp_async16(d + 2048, wb + (size_t)i * 65536);
                if (i < 16) cp_async16(wdst + i * 512, wo_ + i * 5120, gr < 320 ? 16 : 0);
            }
            cp_commit();
        };
#pragma unroll 1
        for (int i = 0; i < WDEPTH; i++) issue(i);
        asm volatile("barrier.cluster.arrive.relaxed.aligned;" ::: "memory");
        float fa, fb;
        if (layer == 0) {
            uint32_t ma = 0, mb = 0;
#pragma unroll 1
            for (int i = 0; i < 20; i++) {
                issue(i + WDEPTH);
                cp_wait<WDEPTH>();
                const uint32_t d = dst + (i < 19 ? i * 8192 : O_LAST);
                uint32_t u[8];
                lds128(u, d); lds128(u + 4, d + 2048);
                ma = babsmax(babsmax(ma, babsmax(u[0], u[1])), babsmax(u[2], u[3])); mb = babsmax(babsmax(mb, babsmax(u[4], u[5])), babsmax(u[6], u[7]));
            }
            ma = __reduce_max_sync(~0u, max(ma & 0x7fffu, (ma >> 16) & 0x7fffu)); mb = __reduce_max_sync(~0u, max(mb & 0x7fffu, (mb >> 16) & 0x7fffu));
            asm volatile("barrier.cluster.wait.aligned;" ::: "memory");
            if (lane < 3)
                asm volatile("st.async.shared::cluster.mbarrier::complete_tx::bytes.v2.b32 [%0],{%1,%2},[%3];"
                             ::"r"(mapa(sb + O_WMX + (c * 8 + w) * 8, lane)), "r"(ma), "r"(mb), "r"(mapa(sb + B_W, lane)) : "memory");
            __syncwarp();
            {
                uint32_t off[4];
                float cs[4] = {0.f, 0.f, 0.f, 0.f};
#pragma unroll
                for (int q = 0; q < 4; q++) {
                    const int g_ = (c * 2 + ((w >> 1) & 1)) * 56 + (q == 3 ? 24 : (w & 1) * 32 + q * 8), col = wg * 320 + g_, nb = col / 80;
                    off[q] = g_ < 320 && !(q == 3 && (w & 1)) ? ((nb * 512 + h * 16) * 10 + (col - nb * 80) / 8) * 32 + lane : ~0u;
                }
                const uint32_t ta = sb + O_WO + w * 8192 + (lane & 7) * 64 + (((lane >> 3) ^ (lane >> 1)) & 3) * 16;
#pragma unroll 2
                for (int i = 0; i < 16; i++) {
                    uint32_t r[4];
                    ldsm4t(r, ta + i * 512);
#pragma unroll
                    for (int q = 0; q < 4; q++) {
                        if (off[q] != ~0u) ((uint32_t*)g_wot)[off[q] + i * 320] = r[q];
                        cs[q] += fabsf(bf_lo(r[q])) + fabsf(bf_hi(r[q]));
                    }
                }
                float cm = 0.f;
#pragma unroll
                for (int q = 0; q < 4; q++) {
                    cs[q] += __shfl_xor_sync(~0u, cs[q], 1); cs[q] += __shfl_xor_sync(~0u, cs[q], 2);
                    cm = fmaxf(cm, cs[q]);
                }
                const uint32_t n1 = __reduce_max_sync(~0u, __float_as_uint(cm));
                if (lane == 0) g_co[h * 32 + c * 8 + w] = __uint_as_float(n1);
            }
            mbar_wait(sb + B_W, 0);
            uint32_t v[2];
            lds64(v, sb + O_WMX + (lane < 24 ? lane : 0) * 8);
            const bool mine = (lane >> 3) < 3 && ((lane >> 4) == 1) == (c == 2);
            ma = __reduce_max_sync(~0u, mine ? v[0] : 0u); mb = __reduce_max_sync(~0u, mine ? v[1] : 0u);
            if (c == 2) ma = mb = max(ma, mb);
            fa = __uint_as_float(ma << 16); fb = __uint_as_float(mb << 16);
            if (tid == 0) {
                if (c != 1) g_wmx[h * 3 + c] = fa;
                if (c == 0) g_wmx[h * 3 + 1] = fb;
            }
        } else {
            fa = __ldcg(g_wmx + h * 3 + (c == 2 ? 2 : 0)); fb = __ldcg(g_wmx + h * 3 + (c == 2 ? 2 : 1));
            asm volatile("barrier.cluster.wait.aligned;" ::: "memory");
        }
        if (layer == TLL) TL(49);
        float ia, ib;
        const float sa = pow2_scale(fa, 6, &ia), sc_b = pow2_scale(fb, 6, &ib);
        sl = __uint_as_float(uni(__float_as_uint(ia * ib * (0.08838834764831845f * 1.4426950408889634f))));
        const uint32_t pa = pack_bf(sa, sa), pb = pack_bf(sc_b, sc_b);
        const int ahead = layer == 0 ? 20 : WDEPTH;
        auto convert = [&](int lo) {
#pragma unroll 1
            for (int i = lo; i < lo + 10; i++) {
                issue(i + ahead);
                cp_wait<WDEPTH>();
                const uint32_t d = dst + (i < 19 ? i * 8192 : O_LAST);
                uint32_t u[8];
                lds128(u, d); lds128(u + 4, d + 2048);
#pragma unroll
                for (int q = 0; q < 8; q++)
                    asm("{.reg .b32 m,l,u; mul.rn.bf16x2 m,%0,%1; shl.b32 l,m,16; and.b32 u,m,0xffff0000; cvt.rn.f16x2.f32 %0,u,l;}" : "+r"(u[q]) : "r"(q < 4 ? pa : pb));
                sts128(d, u[0], u[1], u[2], u[3]); sts128(d + 2048, u[4], u[5], u[6], u[7]);
            }
            bar_sync(6 + wg, 128);
        };
        const uint32_t s0 = src + wg * 2048, s1 = src + 2048 - wg * 2048;
        convert(0);
#pragma unroll
        for (int i = 0; i < 10; i++) { ldsm4t(A0[i], s0 + i * 8192); ldsm4t(A1[i], s1 + i * 8192); }
        if (layer == TLL) TL(50);
        convert(10);
#pragma unroll
        for (int i = 10; i < 20; i++) { ldsm4t(A0[i], s0 + (i < 19 ? i * 8192 : O_LAST)); ldsm4t(A1[i], s1 + (i < 19 ? i * 8192 : O_LAST)); }
        if (layer == TLL) TL(53);
        bar_sync(9, 256);
        if (tid == 0) red_release(g_flag + F_W + layer * 128);
        bar_sync(4, 288);
        asm volatile("barrier.cluster.arrive.relaxed.aligned;" ::: "memory");
    }
    const uint32_t idn = (lane >> 3) == (lane & 3) ? ((lane & 4) ? 0x3c000000u : 0x3c00u) : 0u;
    float invM = g_invM0;
    char* redp = red_base() + (size_t)layer * 32 * 32768 + w * 2048 + (lane >> 4) * 1024 + ((lane >> 3) & 1) * 256 + (lane & 7) * 16;
    const uint32_t ro2 = uni((w >> 1) * 4096 + 128), rown = uni(c == 2 ? ro2 : c * 16384);
    const uint32_t L16 = lane * 16, L8 = lane * 8, L4 = lane * 4;
    const uint32_t xch0 = uni(sb + O_XCH + t0 * 1024), xch1 = uni(sb + O_XCH + t1 * 1024);
    const uint32_t qo0 = uni(sb + O_QKP + (w & 3) * 1024 + (wg ? 768 : 0)), qp0 = uni(qo0 + (wg ? 128 : 256));
    const uint32_t qo1 = uni(sb + O_QKP + (w & 3) * 1024 + (wg ? 128 : 512)), qp1 = uni(qo1 + (wg ? 256 : 128));
    const uint32_t vo1 = uni(qo1 + (wg ? -128 : 256)), vp1 = uni(qp1 + (wg ? -128 : 256));
    const uint32_t msr = uni(sb + O_MS + wg * 5376);
    const uint32_t msw = uni(msr + ((w >> 1) & 1) * 896 + (w & 1) * 512), msh = uni(msr + ((w >> 1) & 1) * 896 + 384 + (w & 1) * 2);
    const uint32_t sco = uni(sb + O_SC + c * 768 + (w & 3) * 256);
    const uint32_t woa = sb + O_WO + w * 8192 + (lane >> 4) * 512 + (lane & 7) * 64 + (((lane >> 3) ^ (lane >> 1)) & 1) * 16 + ((lane >> 2) & 1) * 32;
    const uint32_t w512 = uni(sb + w * 512), w128 = uni(sb + w * 128);
#define PORD 0
    const uint32_t pd0 = uni(mapa(sb, c == 0 ? (PORD & 1 ? 1 : 2) : c == 1 ? (PORD & 1 ? 0 : 2) : (PORD & 2 ? 1 : 0)) - sb),
                   pd1 = uni(mapa(sb, c == 0 ? (PORD & 1 ? 2 : 1) : c == 1 ? (PORD & 1 ? 2 : 0) : (PORD & 2 ? 0 : 1)) - sb);
    const bool scw = c < 2 && w >= 4 && w <= 6;
    uint32_t sn = uni(sb + O_STG + (c == 2 ? 8192 : 0) + t1 * 1024);
    uint32_t ka = uni(sb + (w == 6 ? O_QKP + 512 : O_STG + 4096 + (w & 1) * 512));
    uint32_t vs = uni(sb + O_VM + t1 * 256);
    uint32_t va = uni(sb + O_STG + 8192 + w * 2048), vr = uni(sb + O_VM + w * 512);
    const uint32_t sn2 = uni(2 * sn - 16384), ka2 = uni(2 * ka - (w == 6 ? 0 : 16384)), vs2 = uni(2 * vs + 2048), va2 = uni(2 * va - 16384),
                   vr2 = uni(2 * vr + 2048);
    uint32_t xd = uni((uint32_t)mkdesc(sb + O_XS + wg * 20480, 512, 128, 0));
    const uint32_t xd2 = uni(2 * xd + 2560);

    uint32_t wp[2 * NPERM + 1][4];
    sfor<NPERM>([&](auto I) { constexpr int i = I; ldsm4t(wp[2 * i], woa + i * 1024); ldsm4t(wp[2 * i + 1], (woa ^ 32) + i * 1024); });
    auto wo_fetch = [&](uint32_t (&wo)[16][4], auto I) {
        constexpr int i = I;
        if constexpr (i < NPERM) {
#pragma unroll
            for (int q = 0; q < 4; q++) { wo[i][q] = wp[2 * i][q]; wo[8 + i][q] = wp[2 * i + 1][q]; }
        } else { ldsm4t(wo[i], woa + i * 1024); ldsm4t(wo[8 + i], (woa ^ 32) + i * 1024); }
    };
    if (layer == TLL) TL(32);
    float b0[16], b1[16];
    mbar_wait(sb + B_XF, 0);
    if (layer == TLL) TL(33);
    tok_issue<0, NTB>(A0, A1, b0, b1, xd, zero);
    tok_give(b0, L16, xch0);
    tok_issue<NTB, 40>(A0, A1, b0, b1, xd, zero);
    bar_sync(4, 256);
    wg_wait<0>();
    {
        uint32_t e[2][4];
        lds128_u<0>(e[0], L16, xch1); lds128_u<512>(e[1], L16, xch1);
        tok_finish(b1, e, L16, sn, idn);
    }
    sn = sn2 - sn; xd = xd2 - xd;
    bar_sync(5, 288);
    asm volatile("barrier.cluster.wait.aligned;" ::: "memory");
    if (layer == TLL) TL(34);
    mbar_wait(sb + B_XF + 8, 0);
    if (layer == TLL) TL(35);
    tok_issue<0, NTA>(A0, A1, b0, b1, xd, zero);
    uint32_t tr = clock32() - RDELAY;

#pragma unroll 1
    for (int st = 0;; st++) {
        uint4 mv[3];
        asm volatile("{.reg .pred p; .reg .b32 t;\n"
                     "mov.b32 %0,0; mov.b32 %1,0; mov.b32 %2,0; mov.b32 %3,0; mov.b32 %4,0; mov.b32 %5,0; mov.b32 %6,0; mov.b32 %7,0;\n"
                     "mov.b32 %8,0; mov.b32 %9,0; mov.b32 %10,0; mov.b32 %11,0;\n"
                     "T_LOOP: mov.u32 t,%%clock; sub.u32 t,t,%14; setp.ge.u32 p,t,%15;\n"
                     "@p ld.relaxed.gpu.global.v4.u32 {%0,%1,%2,%3},[%12]; @p ld.relaxed.gpu.global.v4.u32 {%4,%5,%6,%7},[%12+16384];\n"
                     "@p ld.relaxed.gpu.global.v4.u32 {%8,%9,%10,%11},[%13];\n"
                     "@!p bra T_LOOP;}"
                     : "=r"(mv[0].x), "=r"(mv[0].y), "=r"(mv[0].z), "=r"(mv[0].w), "=r"(mv[1].x), "=r"(mv[1].y), "=r"(mv[1].z), "=r"(mv[1].w),
                       "=r"(mv[2].x), "=r"(mv[2].y), "=r"(mv[2].z), "=r"(mv[2].w)
                     : "l"(redp), "l"(redp + ro2), "r"(tr), "n"(RDELAY) : "memory");
        STAMP(10);
        tok_issue<NTA, NTB>(A0, A1, b0, b1, xd, zero);
        tok_give(b0, L16, xch0);
        tok_issue<NTB, 40>(A0, A1, b0, b1, xd, zero);
        xd = xd2 - xd;
        STAMP(9);
        if (zero >> 30) break;
        asm volatile("{.reg .pred p; .reg .b32 a,h,t,n; .reg .b16 l,u; .reg .b64 q;\n"
                     "add.u32 a,%12,%13; add.u32 h,%12,%14; mov.u32 n,0;\n"
                     "M_LOOP:\n .pragma \"nounroll\";\n"
                     "st.shared.b32 [a],%0; st.shared.b32 [a+128],%1; st.shared.b32 [a+256],%2; mov.b32 {l,u},%3; st.shared.b16 [h],l;\n"
                     "st.shared.b32 [a+1792],%4; st.shared.b32 [a+1920],%5; st.shared.b32 [a+2048],%6; mov.b32 {l,u},%7; st.shared.b16 [h+1792],l;\n"
                     "st.shared.b32 [a+3584],%8; st.shared.b32 [a+3712],%9; st.shared.b32 [a+3840],%10; mov.b32 {l,u},%11; st.shared.b16 [h+3584],l;\n"
                     "lop3.b32 t,%3,%7,0x50000000,0x7e; lop3.b32 t,t,%11,0x50000000,0xf6; setp.gt.u32 p,t,0xffff;\n"
                     "vote.sync.any.pred p,p,-1; add.u32 n,n,1; setp.lt.and.u32 p,n,%17,p; @!p bra M_DONE;\n"
                     "ld.relaxed.gpu.global.v4.u32 {%0,%1,%2,%3},[%15]; ld.relaxed.gpu.global.v4.u32 {%4,%5,%6,%7},[%15+16384];\n"
                     "cvt.u64.u32 q,%16; add.u64 q,q,%15; ld.relaxed.gpu.global.v4.u32 {%8,%9,%10,%11},[q];\n"
                     "bra M_LOOP;\n"
                     "M_DONE:}"
                     : "+r"(mv[0].x), "+r"(mv[0].y), "+r"(mv[0].z), "+r"(mv[0].w), "+r"(mv[1].x), "+r"(mv[1].y), "+r"(mv[1].z), "+r"(mv[1].w),
                       "+r"(mv[2].x), "+r"(mv[2].y), "+r"(mv[2].z), "+r"(mv[2].w)
                     : "r"(L4), "r"(msw), "r"(msh), "l"(redp), "r"(ro2), "n"(SPIN_LIM) : "memory");
        bar_sync(3, 256);
        STAMP(0);
        uint32_t e[2][4];
        float f1[4];
        {
            uint32_t b[10][4];
            float acc[4][4];
#pragma unroll
            for (int i = 0; i < 4; i++) acc[i][0] = acc[i][1] = acc[i][2] = acc[i][3] = 0.f;
            auto ld = [&](auto I) { constexpr int i = I; ldsm4t_u<i * 512>(b[i], L16, msr); };
            auto mm = [&](auto I) {
                constexpr int i = I;
                mma_f16(acc[0], A0[2 * i], b[i][0], b[i][1]); mma_f16(acc[2], A1[2 * i], b[i][0], b[i][1]);
                mma_f16(acc[1], A0[2 * i + 1], b[i][2], b[i][3]); mma_f16(acc[3], A1[2 * i + 1], b[i][2], b[i][3]);
            };
            ld(IC<0>()); ld(IC<1>()); ld(IC<2>()); ld(IC<3>());
            sts32_u<O_MX>(L4, w128,
                          habsmax(habsmax(habsmax(habsmax(mv[0].x, mv[0].y), habsmax(mv[0].z, mv[1].x)), habsmax(habsmax(mv[1].y, mv[1].z), mv[2].x)),
                                  habsmax(habsmax(mv[2].y, mv[2].z), habsmax(habsmax(mv[0].w, mv[1].w), mv[2].w) & 0xffffu)));
            wg_wait<0>();
            ld(IC<4>()); mm(IC<0>()); ld(IC<5>()); mm(IC<1>()); ld(IC<6>()); mm(IC<2>());
            ld(IC<7>()); mm(IC<3>()); ld(IC<8>()); mm(IC<4>()); ld(IC<9>()); mm(IC<5>());
            lds128_u<0>(e[0], L16, xch1); lds128_u<512>(e[1], L16, xch1);
            mm(IC<6>()); mm(IC<7>()); mm(IC<8>()); mm(IC<9>());
            const uint32_t u0 = pack_bf((acc[0][0] + acc[1][0]) * invM, (acc[0][1] + acc[1][1]) * invM);
            const uint32_t u1 = pack_bf((acc[0][2] + acc[1][2]) * invM, (acc[0][3] + acc[1][3]) * invM);
#pragma unroll
            for (int i = 0; i < 4; i++) f1[i] = (acc[2][i] + acc[3][i]) * invM;
            sts32_u<0>(L4, qo0, u0); sts32_u<0>(L4, qp0, u1); sts32_u<0>(L4, qo1, pack_bf(f1[0], f1[1])); sts32_u<0>(L4, qp1, pack_bf(f1[2], f1[3]));
        }
        STAMP(1);
        bar_sync(1, 320);
        if (__builtin_expect(scw, 1)) {
            float a[4][4];
#pragma unroll
            for (int i = 0; i < 4; i++) a[i][0] = a[i][1] = a[i][2] = a[i][3] = 0.f;
            uint32_t q[4][4], k[4][4];
            sfor<4>([&](auto I) {
                constexpr int i = I;
                ldsm4t_u<O_QKP + i * 1024>(q[i], L16, sb); ldsm4t_u<i * 1024>(k[i], L16, ka);
            });
#pragma unroll
            for (int i = 0; i < 4; i++) {
                mma_bf(a[i & 1], q[i][0], q[i][1], q[i][2], q[i][3], k[i][0], k[i][1]);
                mma_bf(a[2 + (i & 1)], q[i][0], q[i][1], q[i][2], q[i][3], k[i][2], k[i][3]);
            }
            const float mk = w == 6 ? 1.f : 0.f;
            const float x0 = (a[0][0] + a[0][2]) + (a[1][0] + a[1][2]), x1 = (a[0][1] + a[0][3]) + (a[1][1] + a[1][3]);
            const float y0 = (a[2][0] + a[2][2]) + (a[3][0] + a[3][2]), y1 = (a[2][1] + a[2][3]) + (a[3][1] + a[3][3]);
            st_share2(L8, sco, sb + B_S, pd0, pd1, pack_bf(fmaf(y0, mk, x0) * sl, fmaf(y1, mk, x1) * sl), pack_bf(y0 * sl, y1 * sl));
        }
        if (c == 2) {
            const uint32_t x = lds32_u<0>(L4, vo1), y = lds32_u<0>(L4, vp1);
            st_share2(L8, vs, sb + B_S, pd0, pd1, pack_bf(f1[0] + bf_lo(x), f1[1] + bf_hi(x)), pack_bf(f1[2] + bf_lo(y), f1[3] + bf_hi(y)));
        }
        STAMP(3);
        if (st == NSEG - 1) break;
        tok_finish(b1, e, L16, sn, idn);
        redp += (st & 1) ? 32768 - 512 : 512;
        if (wg == 0) {
            uint32_t wo[16][4], vx[2][2][4], vm[2][2];
            ldsm4_u<0>(vx[0][0], L16, va); ldsm4_u<512>(vx[0][1], L16, va); ldsm4_u<1024>(vx[1][0], L16, va); ldsm4_u<1536>(vx[1][1], L16, va);
            sfor<NWO0>([&](auto I) { wo_fetch(wo, I); });
            mbar_wait(sb + B_S, st & 1);
            STAMP(4);
            uint32_t s[5];
            {
                uint32_t p[2][5];
                sfor<2>([&](auto R) {
                    constexpr int r = R;
                    lds64_u<O_SC + r * 768>(p[r], L8, sb); lds64_u<O_SC + r * 768 + 256>(p[r] + 2, L8, sb); p[r][4] = lds32_u<O_SC + r * 768 + 512>(L8, sb);
                });
#pragma unroll
                for (int j = 0; j < 5; j++) s[j] = badd(p[0][j], p[1][j]);
            }
            lds64_u<0>(vm[0], L8, vr); lds64_u<256>(vm[1], L8, vr);
            uint32_t mm = bmax(bmax(bmax(s[0], s[1]), bmax(s[2], s[3])), s[4]);
            mm = bmax(bmax(mm, __shfl_xor_sync(~0u, mm, 1)), bmax(__shfl_xor_sync(~0u, mm, 2), __shfl_xor_sync(~0u, mm, 3)));
            const float m = fmaxf(bf_lo(mm), bf_hi(mm));
            float o0[4] = {0.f, 0.f, 0.f, 0.f}, o1[4] = {0.f, 0.f, 0.f, 0.f}, d[10];
#pragma unroll
            for (int j = 0; j < 5; j++) { d[2 * j] = bf_lo(s[j]) - m; d[2 * j + 1] = bf_hi(s[j]) - m; }
#pragma unroll
            for (int j = 0; j < 10; j++) d[(j + 8) % 10] = ex2(d[(j + 8) % 10]);
            float sum = ((d[8] + d[9]) + (d[0] + d[1])) + ((d[2] + d[3]) + (d[4] + d[5])) + (d[6] + d[7]);
            const uint32_t p4 = pack_bf(d[8], d[9]), p0 = pack_bf(d[0], d[1]), p1 = pack_bf(d[2], d[3]), p2 = pack_bf(d[4], d[5]), p3 = pack_bf(d[6], d[7]);
            mma_bf8(o0, vm[0][0], vm[0][1], p4);
            mma_bf8(o1, vm[1][0], vm[1][1], p4);
            mma_bf(o0, vx[0][0][0], vx[0][0][1], vx[0][0][2], vx[0][0][3], p0, p1);
            mma_bf(o1, vx[1][0][0], vx[1][0][1], vx[1][0][2], vx[1][0][3], p0, p1);
            mma_bf(o0, vx[0][1][0], vx[0][1][1], vx[0][1][2], vx[0][1][3], p2, p3);
            mma_bf(o1, vx[1][1][0], vx[1][1][1], vx[1][1][2], vx[1][1][3], p2, p3);
            sum += __shfl_xor_sync(~0u, sum, 1);
            sum += __shfl_xor_sync(~0u, sum, 2);
            sts32_u<O_OS>(L4, w512, pack_bf(o0[0], o0[1])); sts32_u<O_OS + 128>(L4, w512, pack_bf(o0[2], o0[3]));
            sts32_u<O_OS + 256>(L4, w512, pack_bf(o1[0], o1[1])); sts32_u<O_OS + 384>(L4, w512, pack_bf(o1[2], o1[3]));
            sts32_u<O_SUM>(lane & 28, sb, __float_as_uint(sum));
            STAMP(5);
            invM = mem_out<NWO0>(sb, L16, L8, wo, woa, redp + rown, w & 1);
            tr = clock32();
        } else {
            uint32_t wo[16][4];
            sfor<NWO1>([&](auto I) { wo_fetch(wo, I); });
            invM = mem_out<NWO1>(sb, L16, L8, wo, woa, redp + rown, w & 1);
            tr = clock32();
        }
        STAMP(7);
        tok_issue<0, NTA>(A0, A1, b0, b1, xd, zero);
        sn = sn2 - sn; ka = ka2 - ka; vs = vs2 - vs; va = va2 - va; vr = vr2 - vr;
        STAMP(8);
    }
    if (layer == TLL) TL(40);
    bar_arrive(8, 320);
    tid = read_tid(); lane = tid & 31;
    float acc[40];
    const int nc = c == 2 ? 10 : 11;
#pragma unroll 1
    for (int k = 0; k < nc; k++) {
        mbar_wait(sb + T_FB + (k % 7) * 8, k >= 7);
        mbar_wait(sb + T_FA + (k & 3) * 8, (k >> 2) & 1);
        if (layer == TLL && k == 0) TL(41);
        const uint64_t da = mkdesc(sb + O_MS + (k & 3) * 16384 + wg * 8192, 1024, 128, 0), db = mkdesc(sb + tail_b(k) + wg * 10240, 1280, 128, 0);
        wg_fence();
#pragma unroll
        for (int q = 0; q < 4; q++) wg_n80_ss(acc, da + q * 128, db + q * 160, k | q);
        wg_commit();
        if (k > 0) {
            wg_wait<1>();
            if (lane == 0) { mbar_arrive(sb + T_EA + ((k - 1) & 3) * 8); if (k <= 4) mbar_arrive(sb + T_EB + (k - 1) * 8); }
        }
    }
    if (layer == TLL) TL(52);
    const int mb = 28 + (h >> 3), nj = c == 2 ? 1 : 2;
    uint32_t rv[2][2];
    const size_t go = ((size_t)(mb * 64 + (w & 3) * 16 + (lane >> 2)) * 640 + (h & 7) * 80 + (wg * 5 + c * 2) * 8 + (lane & 3) * 2) >> 1;
#pragma unroll
    for (int u = 0; u < 4; u++) rv[u >> 1][u & 1] = (u >> 1) < nj ? __ldcg((const uint32_t*)res + go + (u >> 1) * 4 + (u & 1) * 2560) : 0u;
    wg_wait<0>();
    asm volatile("barrier.cluster.arrive.relaxed.aligned; barrier.cluster.wait.aligned;" ::: "memory");
    const uint32_t ra = sb + O_XS + tid * 16, rb = sb + O_MS + tid * 16;
#pragma unroll
    for (int j = 0; j < 5; j++) {
        const float* q = acc + 4 * j;
        sts128(rb + j * 4096, __float_as_uint(wg ? q[0] : q[20]), __float_as_uint(wg ? q[1] : q[21]), __float_as_uint(wg ? q[2] : q[22]), __float_as_uint(wg ? q[3] : q[23]));
    }
    bar_sync(4, 256);
#pragma unroll
    for (int j = 0; j < 5; j++) {
        const float* q = acc + 4 * j;
        uint32_t p[4];
        lds128(p, sb + O_MS + (tid ^ 128) * 16 + j * 4096);
        asm volatile("st.async.shared::cluster.mbarrier::complete_tx::bytes.v4.f32 [%0],{%1,%2,%3,%4},[%5];" ::"r"(mapa(ra + c * 8192 + (j & 1) * 4096, j >> 1)),
                     "f"((wg ? q[20] : q[0]) + __uint_as_float(p[0])), "f"((wg ? q[21] : q[1]) + __uint_as_float(p[1])),
                     "f"((wg ? q[22] : q[2]) + __uint_as_float(p[2])), "f"((wg ? q[23] : q[3]) + __uint_as_float(p[3])), "r"(mapa(sb + T_RED, j >> 1)) : "memory");
    }
    mbar_wait(sb + T_RED, 0);
#pragma unroll 1
    for (int u = 0; u < nj; u++) {
        uint32_t p[3][4];
#pragma unroll
        for (int q = 0; q < 3; q++) lds128(p[q], ra + q * 8192 + u * 4096);
        float y[4];
#pragma unroll
        for (int i = 0; i < 4; i++) y[i] = __uint_as_float(p[0][i]) + __uint_as_float(p[1][i]) + __uint_as_float(p[2][i]);
        ((uint32_t*)out)[go + u * 4] = bfma(pack_bf(y[0], y[1]), 0x3f803f80u, u ? rv[1][0] : rv[0][0]);
        ((uint32_t*)out)[go + u * 4 + 2560] = bfma(pack_bf(y[2], y[3]), 0x3f803f80u, u ? rv[1][1] : rv[0][1]);
    }
    TL(layer == 0 ? 15 : 29);
    asm volatile("barrier.cluster.arrive.relaxed.aligned; barrier.cluster.wait.aligned;" ::: "memory");
}

__device__ __forceinline__ void tail_load_b(const uint32_t sb, const int h, const int c, const int k) {
    mbar_expect(sb + T_FB + (k % 7) * 8, 20480);
    bulk_g2s(sb + tail_b(k), (const char*)g_wot + (size_t)((h & 7) * GNC + c * 11 + k) * 20480, 20480, sb + T_FB + (k % 7) * 8);
}
__device__ __forceinline__ void chain_aux(const uint32_t sb, const int c, const int h, const int layer, const int nact, const bf16* Wq, const bf16* Wk,
                                          const bf16* Wv, const bf16* Wo) {
    const int tid = read_tid(), w = __shfl_sync(~0u, tid >> 5, 0), lane = tid & 31;
    if (w == 8) {
        mbar_init(sb + O_BAR + lane * 8, lane == 2 && NOSELF ? (c == 2 ? 9 : 4) : lane == 3 || (lane >= 16 && lane < 20) || (lane >= 27 && lane < 31) ? 8 : 1);
        asm volatile("fence.mbarrier_init.release.cluster;" ::: "memory");
        fence_async_smem();
        __syncwarp();
    }
    {
        uint4* z = (uint4*)red_base() + layer * 65536;
#pragma unroll 1
        for (int i = blockIdx.x * 128 + tid - 256; i < 65536; i += 96 * 128)
            if (i >= 2048 || (i & 32)) z[i] = make_uint4(0, 0, 0, 0);
    }
    if (w == 8 && lane == 0) {
        mbar_expect(sb + B_S, s_tx(c));
        mbar_expect(sb + B_W, 192);
        mbar_expect(sb + T_RED, (c == 2 ? 1 : 2) * 3 * 4096);
        if (layer == 1) prefetch_l2(red_base() + 32 * 32768 + blockIdx.x * 1024, 1024);
        if (layer == 0) wait_flag<400>(g_ready, NSETUP);
    }
    __syncwarp();
    cluster_sync_full();
    asm volatile("barrier.cluster.arrive.relaxed.aligned;" ::: "memory");
    pdl_wait();
    Flag* flag = g_flag + layer * NSEG * 32 + h;
    const Flag* xflag = g_flag + F_X + layer * 128;
    char* const it0 = g_item + (size_t)h * 32768;
    if (w == 8) {
#pragma unroll 1
        for (int n = 0; n < 3; n++) {
            wait_flag<100>(xflag + (n >> 1), 4);
            fence_async_glb();
            if (n == 0) { bar_sync(4, 288); fence_async_smem(); }
            if (lane == 0 && n < 2) {
                mbar_expect(sb + B_XF + n * 8, 40960);
                bulk_g2s(sb + O_XS + n * 40960, (const char*)g_xn + n * 40960, 40960, sb + B_XF + n * 8);
            }
            __syncwarp();
        }
#pragma unroll 1
        for (int n = 0; n < NSEG; n++) {
            const int np = n & 1;
            if (n == 0) { wait_flag<100>(g_flag + F_W + layer * 128, 96); bar_sync(5, 288); } else bar_sync(2, 352);
            if (n == 1) TL(12 + layer * 14);
            if (n == 63) TL(13 + layer * 14);
            if (lane == 0 && (n == NSEG - 1 || (XEARLY & 8))) mbar_arrive(sb + B_STG + np * 8);
            if (lane == 0 && n < NSEG - 1) {
                const uint32_t vs = sb + O_STG + 8192 - np * 16384, vb = sb + B_VX + np * 8;
                if (c == 2) { if (!VEARLY || n == 0) {
                    fence_async_smem();
                    bulk_s2s(mapa(vs, 0), vs, 8192, mapa(vb, 0));
                    bulk_s2s(mapa(vs, 1), vs, 8192, mapa(vb, 1));
                } } else mbar_expect(vb, 8192);
                if (n == 0) { mbar_expect(sb + B_XF, 40960); bulk_g2s(sb + O_XS, (const char*)g_xn + 2 * 40960, 40960, sb + B_XF); }
                if (n == h * 3 + c && !np && n + 6 < NSEG) prefetch_l2(red_base() + (size_t)(layer * 32 + (n >> 1) + 3) * 32768, 32768);
            }
            __syncwarp();
        }
    } else if (w == 11) {
        float cvo;
        {
            auto max8 = [&](const float* p) {
                const float4 u = ((const float4*)p)[0], v = ((const float4*)p)[1];
                return fmaxf(fmaxf(fmaxf(u.x, u.y), fmaxf(u.z, u.w)), fmaxf(fmaxf(v.x, v.y), fmaxf(v.z, v.w)));
            };
            wait_flag<300>(g_flag + F_W + layer * 128, 96);
            const float* pc = g_co + lane * 32;
            float a = 640.f * __ldcg(g_wmx + lane * 3 + 2), o = fmaxf(fmaxf(max8(pc), max8(pc + 8)), max8(pc + 16));
#pragma unroll 1
            for (int s = 16; s; s >>= 1) { a = fmaxf(a, __shfl_xor_sync(~0u, a, s)); o += __shfl_xor_sync(~0u, o, s); }
            cvo = a * o * 2.f;
        }
        float invM = g_invM0;
        float iv;
        weight_scale(h, 2, &iv);
        const uint32_t L16 = sb + lane * 16 + O_MX;
#pragma unroll 1
        for (int st = 0; st < NSEG; st++) {
            bar_sync(1, 320);
            if (st == NSEG - 1) break;
            if (!(XEARLY & 10) && lane == 0) mbar_arrive(sb + B_STG + (st & 1) * 8);
            uint32_t u[2][4];
            lds128(u[0], L16); lds128(u[1], L16 + 512);
            uint32_t mx = habsmax(habsmax(habsmax(u[0][0], u[0][1]), habsmax(u[0][2], u[0][3])), habsmax(habsmax(u[1][0], u[1][1]), habsmax(u[1][2], u[1][3])));
            mx = __reduce_max_sync(~0u, max(mx & 0x7fffu, (mx >> 16) & 0x7fffu));
            const float bound = fmaxf(__half2float(__ushort_as_half((unsigned short)mx)) * invM, 25.5f) * cvo;
            const float sc = pow2_scale(bound, 15, &invM);
            sts64(sb + O_SCL, __float_as_uint(sc * iv), __float_as_uint(invM));
            bar_arrive(2, 352);
        }
    } else if (w == 10) {
        if (lane == 0) {
#pragma unroll 1
            for (int n = 0; n < NSEG; n++) {
                mbar_sleep(sb + B_STG + (n & 1) * 8, (n >> 1) & 1);
                fence_async_smem();
                const uint32_t stg = sb + O_STG - (n & 1) * 16384;
                char* it = it0 + (size_t)(n % RING) * 32 * 32768;
                bulk_s2g(it + c * 8192, stg + (c == 2 ? 8192 : 0), 8192);
                bulk_commit();
                if (n + 1 >= RING && n + 1 < NSEG) wait_flag(flag - (RING - 1) * 32, REL1 ? 4 : 7);
                bulk_wait0();
                if (REL1) {
                    fence_async_glb();
                    mbar_arrive(sb + B_FREE + (n & 1) * 8);
                } else {
                    mbar_arrive(sb + B_FREE + (n & 1) * 8);
                    fence_async_glb();
                    if (RELAX & 1) red_relaxed(flag); else red_release(flag);
                }
                flag += 32;
            }
        }
    } else {
        const uint32_t L16 = sb + lane * 16;
        bool allx = false;
#pragma unroll 1
        for (int st = 0; st < NSEG; st++) {
            const int par = st & 1;
            char* it = it0 + (size_t)(st % RING) * 32 * 32768 + lane * 16;
            if (lane == 0 && !allx && st + 3 < NSEG) {
                allx = ld_acquire(xflag + 64) >= nact;
                if (!allx) wait_flag(xflag + ((st + 3) >> 1), 4);
                fence_async_glb();
            }
            __syncwarp();
            auto refill = [&] {
                if (lane == 0 && st + 3 < NSEG) {
                    mbar_expect(sb + B_XF + (par ^ 1) * 8, 40960);
                    bulk_g2s_last(sb + O_XS + (par ^ 1) * 40960, (const char*)g_xn + (size_t)(st + 3) * 40960, 40960, sb + B_XF + (par ^ 1) * 8);
                } else if (lane == 0 && st < NSEG - 1) {
                    tail_load_b(sb, h, c, (par ^ 1) * 2); tail_load_b(sb, h, c, (par ^ 1) * 2 + 1);
                }
                __syncwarp();
            };
            if (st < NSEG - 1 && c < 2) mbar_sleep(sb + B_VX + par * 8, (st >> 1) & 1);
            if (st < NSEG - 2) mbar_sleep(sb + B_XF + par * 8, ((st >> 1) + 1) & 1);
            bar_sync(1, 320);
            if (!(XEARLY & 1)) refill();
            char* const itb = it - lane * 16;
            if (lane == 0 && c < 2) {
                fence_async_smem();
#pragma unroll 1
                for (int i = 0; i < 4; i++) bulk_s2g(itb + 24576 + (c * 4 + i) * 512, sb + O_QKP + i * 1024 + 512, 512);
                bulk_commit();
                asm volatile("cp.async.bulk.wait_group.read 0;" ::: "memory");
            }
            __syncwarp();
            if (st < NSEG - 1) bar_arrive(2, 352);
            mbar_sleep(sb + B_S, par);
            __syncwarp();
            if (lane == 0) {
                if (st < NSEG - 1) mbar_expect(sb + B_S, s_tx(c));
                if (c == 2) { fence_async_smem(); bulk_s2g(itb + 28672, sb + O_VM + par * 2048, 2048); bulk_commit(); }
                if (st == NSEG - 1) asm volatile("cp.async.bulk.wait_group.read 0;" ::: "memory");
            }
            __syncwarp();
            if (st == NSEG - 1) bar_arrive(8, 320);
            if (lane == 0) { bulk_wait0(); fence_async_glb(); red_relaxed(flag); }
            __syncwarp();
            if (!REL1) mbar_sleep(sb + B_FREE + par * 8, (st >> 1) & 1);
            flag += 32;
            continue;
#pragma unroll 1
            for (int i = 0; i < (c < 2 ? 4 : 0); i += 2) {
                uint32_t v[8];
                lds128(v, L16 + O_QKP + i * 1024 + 512); lds128(v + 4, L16 + O_QKP + i * 1024 + 512 + 1024);
                *(uint4*)(it + 24576 + (c * 4 + i) * 512) = make_uint4(v[0], v[1], v[2], v[3]); *(uint4*)(it + 24576 + (c * 4 + i) * 512 + 512) = make_uint4(v[4], v[5], v[6], v[7]);
            }
            if (st < NSEG - 1) bar_arrive(2, 352);
            mbar_sleep(sb + B_S, par);
            __syncwarp();
            if (lane == 0 && st < NSEG - 1) mbar_expect(sb + B_S, s_tx(c));
#pragma unroll 1
            for (int i = 0; i < (c < 2 ? 0 : 4); i += 2) {
                uint32_t v[8];
                lds128(v, L16 + O_VM + par * 2048 + i * 512); lds128(v + 4, L16 + O_VM + par * 2048 + i * 512 + 512);
                *(uint4*)(it + 28672 + i * 512) = make_uint4(v[0], v[1], v[2], v[3]); *(uint4*)(it + 28672 + i * 512 + 512) = make_uint4(v[4], v[5], v[6], v[7]);
            }
            if (st == NSEG - 1) bar_arrive(8, 320);
            __syncwarp();
            if (REL1) mbar_sleep(sb + B_FREE + par * 8, (st >> 1) & 1);
            if (lane == 0) { if (RELAX & 2) red_relaxed(flag); else red_release(flag); }
            if (!REL1) mbar_sleep(sb + B_FREE + par * 8, (st >> 1) & 1);
            flag += 32;
        }
    }
    __syncwarp();
    const int nc = c == 2 ? 10 : 11;
    if (w == 10) {
        bar_sync(8, 320);
        if (lane == 0) {
            if (layer == 1 && blockIdx.x == 0) g_ready[0].v = 0;
            fence_async_smem();
            __nanosleep(TDELAY);
            wait_flag(xflag + 64, nact);
            wait_flag<50>(g_flag + F_O + layer * 32 + 28 + (h >> 3), 64);
            fence_async_glb();
#pragma unroll 1
            for (int k = 0; k < nc; k++) {
                if (k >= 4) mbar_sleep(sb + T_EA + (k & 3) * 8, ((k >> 2) - 1) & 1);
                mbar_expect(sb + T_FA + (k & 3) * 8, 16384);
                bulk_g2s_last(sb + O_MS + (k & 3) * 16384, (const char*)g_O + (size_t)((28 + (h >> 3)) * GNC + c * 11 + k) * 16384, 16384, sb + T_FA + (k & 3) * 8);
            }
        }
    } else if (w == 9 && lane == 0) {
        __nanosleep(TDELAY);
#pragma unroll 1
        for (int k = 4; k < nc; k++) {
            if (k >= 7) mbar_sleep(sb + T_EB + (k - 7) * 8, 0);
            tail_load_b(sb, h, c, k);
        }
    }
    __syncwarp();
    asm volatile("barrier.cluster.wait.aligned;" ::: "memory");
    asm volatile("barrier.cluster.arrive.relaxed.aligned; barrier.cluster.wait.aligned;" ::: "memory");
    asm volatile("barrier.cluster.arrive.relaxed.aligned; barrier.cluster.wait.aligned;" ::: "memory");
}

constexpr int RI_A = 0, RI_TAB = 81920, RI_STG = RI_TAB + 82 * 768;
constexpr int RI_RES = RI_STG + 25600, RI_ST = RI_RES + 2 * 64 * 336;
constexpr int HB_A = G_BAR + 64, HB_AFREE = HB_A + 32, HB_LN = HB_A + 40, HB_FULL = HB_A + 64, HB_DONE = HB_FULL + 48, HB_FREE = HB_DONE + 48;
constexpr int HP_SMEM = HB_FREE + 48;
static_assert(G_BAR >= RI_ST + 2048, "helper shared-memory map");
#define IDL 350
#define ITEM_NS 60
#define HORD 1
#define PFW_AT 28
#define PFW_NS 150
__device__ __forceinline__ void helper_aux(const uint32_t sb, const int j, const int nh, const int na, const int nbh, const int layer, const bf16* Wq,
                                           const bf16* Wk, const bf16* Wv, const bf16* Wo) {
    const int w = threadIdx.x >> 5, lane = threadIdx.x & 31, p = w - 8;
    if (lane == 0 && j < (nh & ~3)) {
        int n = 0;
        for (int a = j >> 2; a < 32; a += nh >> 2, n++) {
            if (n == 0) continue;
            mbar_wait(sb + HB_AFREE, (n - 1) & 1);
            mbar_expect(sb + HB_A + p * 8, 20480);
            bulk_g2s_last(sb + RI_A + p * 20480, (const char*)g_YT + (size_t)a * 81920 + p * 20480, 20480, sb + HB_A + p * 8);
            if (p == 0) { mbar_wait(sb + HB_LN, (n - 1) & 1); red_release(g_flag + F_X + layer * 128 + a - (nh >> 2)); }
        }
        if (p == 0) { mbar_wait(sb + HB_LN, (n - 1) & 1); red_release(g_flag + F_X + layer * 128 + (j >> 2) + (n - 1) * (nh >> 2)); }
    }
    __syncwarp();
    if (layer == 0 && w == 8 && lane == 0) wait_flag<400>(g_flag + F_W, 96);
    __syncwarp();
    bar_sync(3, 384);
    if (p == 3 && lane == 0 && j < (nh & ~3)) red_release(g_flag + F_X + layer * 128 + 64);
    fence_async_smem();
    Flag* oflag = g_flag + F_O + layer * 32;
    if (j < na) {
        int sl = p & 1, ph = 1;
        for (int idx = j + (p & 1) * na; idx < NSEG * 32 && p >= 2 && lane == 0; idx += 2 * na) {
            mbar_wait(sb + HB_DONE + sl * 8, ph ^ 1);
            mbar_arrive(sb + HB_FREE + sl * 8);
            red_release(oflag + (idx >> 6));
            atomicAdd(&g_flag[layer * NSEG * 32 + idx].v, 1u);
            sl += 2;
            if (sl >= 6) { sl -= 6; ph ^= 1; }
        }
        for (int idx = j + p * na; idx < NSEG * 32 && p < 2 && lane == 0; idx += 2 * na) {
            mbar_wait(sb + HB_FREE + sl * 8, ph);
            wait_flag<ITEM_NS>(g_flag + layer * NSEG * 32 + idx, REL1 ? 3 : 6);
            fence_async_glb();
            if (idx < (NSEG - 2) * 32) __nanosleep(IDL);
            mbar_expect(sb + HB_FULL + sl * 8, 30720);
            bulk_g2s(sb + sl * 30720, g_item + (size_t)(idx % (RING * 32)) * 32768, 30720, sb + HB_FULL + sl * 8);
            sl += 2;
            if (sl >= 6) { sl -= 6; ph ^= 1; }
        }
    } else if (lane == 0 && p == 3) {
        if (layer == 0) {
            wait_flag<1000>(oflag + PFW_AT, 64);
            const int np = nh - na;
#pragma unroll 1
            for (int i = j - na; i < 1280; i += np) {
                const bf16* W = i < 320 ? Wq : i < 640 ? Wk : i < 960 ? Wv : Wo;
                prefetch_l2((const char*)W + (size_t)(i % 320) * 16384, 16384);
                __nanosleep(PFW_NS);
            }
#pragma unroll 1
            for (int i = j - na; i < 205; i += np) {
                const char* p_ = i < 160 ? (const char*)g_Wf + i * 16384 : i < 165 ? (const char*)g_stat + (i - 144) * 16384
                               : i < 167 ? (const char*)g_ctab + (i - 165) * 8192 : (const char*)(g_flag + NFLAG) - (i - 166) * 16384;
                prefetch_l2(p_, 16384);
                __nanosleep(PFW_NS);
            }
        }
    } else if (lane == 0) {
        if (p == 2) wait_flag<500>(g_flag + F_X + layer * 128 + 64, nh & ~3);
        int c0 = 0;
        for (int mb = (j - na) >> 3; mb < nbh; mb += (nh - na) >> 3, c0 += GNC) {
            if (p < 2) wait_flag<300>(oflag + 2 * mb + p, 64);
            fence_async_glb();
            oproj_load(sb, p, mb, (j - na) & 7, c0, nh - na < 24 ? 0 : mb == nbh - 1 ? GPACE2 : GPACE);
        }
    }
}
__device__ __forceinline__ void helper_mma(char* sm, const int jh, const int nh, const int na, const int nbh, const int layer, const bf16* res, bf16* x,
                                           bf16* out) {
    const uint32_t sb = smem_u32(sm);
    const int tid = threadIdx.x, w = tid >> 5, lane = tid & 31, g = lane >> 2, t = lane & 3;
    const bool act = jh < (nh & ~3);
    const int j4 = jh & 3;
    const int fr = tid & 63, rg = w >> 1;
    auto chunk0 = [&](int u) { return u == 0 ? 5 * j4 : u == 1 ? 75 - 5 * j4 : u == 2 ? 40 + 5 * j4 : 35 - 5 * j4; };
    const int gr = tid / 20, gq_ = tid - gr * 20, go = gr * 80 + chunk0(gq_ / 5) + gq_ % 5;
    const uint32_t gs = sb + RI_RES + gr * 336 + gq_ * 16;
    auto residual = [&](int a, int n) {
#pragma unroll 1
        for (int r = 0; r < 64 - gr && tid < 240 && a < 32; r += 12) cp_async16(gs + (n & 1) * 21504 + r * 336, (const uint4*)res + (a * 64 + r) * 80 + go);
        cp_commit();
    };
    if (act) {
        if (tid < 240) {
            const int k0 = tid / 48, n = tid - k0 * 48;
            const float d = (float)(40 * j4 + n), amp = 2.f * 0.03952847075210474f;
#pragma unroll 4
            for (int u = 0; u < 16; u++)
                *(uint4*)(sm + RI_TAB + (tid + u * 240) * 16) = cos_row8(fmaf((float)((k0 + (u & 3) * 5) * 16 + ((u >> 2) & 1)), d, (float)((u & 8) * 20)), 2.f * d, amp);
            if (tid < 96) *(uint4*)(sm + RI_TAB + (3840 + tid) * 16) = make_uint4(k0 == 0 ? pack_h((n & 1) ? -amp : amp, 0.f) : 0u, 0, 0, 0);
        }
        fence_async_smem();
        residual(jh >> 2, 0);
    }
    bar_sync(1, 384);
    if (layer == TLL) TL(36);
    if (act) {
        const float4 wm = ((const float4*)g_wmax)[lane];
        const int wg = w >> 2;
        int n = 0;
#pragma unroll 1
        for (int a = jh >> 2; a < 32; a += nh >> 2, n++) {
            float acc[2][24];
            uint64_t da = mkdesc(sb + RI_A + wg * 40960, 1024, 1024, 1), db = mkdesc(sb + RI_TAB + wg * 30720, 768, 128, 0);
#pragma unroll
            for (int gq = 0; gq < 2; gq++) {
                mbar_wait(sb + HB_A + (wg * 2 + gq) * 8, n & 1);
                if (layer == TLL && n == TLN && gq == 0) TL(45);
                wg_fence();
#pragma unroll 5
                for (int k = 0; k < 10; k++) { wg_n48_ss_ta(acc[gq], da, db, k); da += 128; db += 96; }
                wg_commit();
            }
            if (wg == 0) {
                mbar_wait(sb + HB_A + 16, n & 1);
                wg_fence();
                wg_n48_ss_ta(acc[0], da, db + 20 * 96, 1);
                wg_commit();
            }
            float inv;
            pow2_scale(__uint_as_float(__reduce_max_sync(~0u, __float_as_uint(fmaxf(fmaxf(wm.x, wm.y), fmaxf(wm.z, wm.w))))), 0, &inv);
            const uint32_t ysc = pack_bf(inv, inv);
            wg_wait<0>();
            if (layer == TLL && n == TLN) TL(46);
            if (lane == 0) mbar_arrive(sb + HB_AFREE);
            const uint32_t ad = sb + RI_STG + ((w & 3) * 16 + (lane & 15)) * 400 + (lane >> 4) * 96 + wg * 192;
#pragma unroll
            for (int q = 0; q < 6; q++) {
                const float *e = acc[0] + q * 4, *o = acc[1] + q * 4;
                stsm4(ad + q * 16, pack_h(e[0] + o[0], e[1] + o[1]), pack_h(e[2] + o[2], e[3] + o[3]), pack_h(e[0] - o[0], e[1] - o[1]), pack_h(e[2] - o[2], e[3] - o[3]));
            }
            cp_wait<0>();
            bar_sync(4, 256);
            const uint32_t xa = sb + RI_RES + (n & 1) * 21504 + fr * 336 + rg * 80, sg = (rg & 1) ? 0xbc00bc00u : 0x3c003c00u;
            float sum = 0.f, sq = 0.f;
            uint32_t ya = sb + RI_STG + fr * 400 + (rg >> 1) * 96 + ((rg & 1) ? 64 : 0), carry;
            asm("fma.rn.f16x2 %0,%1,%2,%3;" : "=r"(carry) : "r"(lds32(ya + 208)), "r"(sg), "r"(lds32(ya + 16)));
#pragma unroll 1
            for (int ch = 0; ch < 5; ch++, ya += (rg & 1) ? -16 : 16) {
                uint32_t y[4], z[4], xr[4];
                lds128(y, ya); lds128(z, ya + 192); lds128(xr, xa + ch * 16);
#pragma unroll
                for (int q = 0; q < 4; q++) asm("fma.rn.f16x2 %0,%1,%2,%0;" : "+r"(y[q]) : "r"(z[q]), "r"(sg));
                if (rg & 1) {
                    const uint32_t y0 = y[0], y1 = y[1];
                    y[0] = __byte_perm(carry, y[3], 0x7610); y[1] = __byte_perm(y[3], y[2], 0x7610);
                    y[3] = __byte_perm(y1, y0, 0x7610); y[2] = __byte_perm(y[2], y1, 0x7610);
                    carry = y0;
                }
#pragma unroll
                for (int q = 0; q < 4; q++) {
                    const float2 yf = __half22float2(*(const __half2*)&y[q]);
                    xr[q] = bfma(pack_bf(yf.x, yf.y), ysc, xr[q]);
                    const float e = bf_lo(xr[q]), f = bf_hi(xr[q]);
                    sum += e + f; sq = fmaf(e, e, fmaf(f, f, sq));
                }
                sts128(xa + ch * 16, xr[0], xr[1], xr[2], xr[3]);
            }
            uint2* stat = g_stat + (size_t)(layer * 32 + a) * 1024 + rg * 64 + fr;
            asm volatile("st.relaxed.gpu.global.v2.u32 [%0],{%1,%2};" ::"l"(stat + j4 * 256), "r"(__float_as_uint(sum)), "r"(__float_as_uint(sq) | 0x80000000u) : "memory");
            if (layer == TLL && n == TLN) TL(47);
            uint32_t s0[3], s1[3];
            int lim = 0;
            do {
#pragma unroll
                for (int q = 0; q < 3; q++)
                    asm volatile("ld.relaxed.gpu.global.v2.u32 {%0,%1},[%2];" : "=r"(s0[q]), "=r"(s1[q]) : "l"(stat + ((j4 + 1 + q) & 3) * 256) : "memory");
            } while (__any_sync(~0u, (int)(s1[0] & s1[1] & s1[2]) >= 0) && ++lim < SPIN_LIM);
#pragma unroll
            for (int q = 0; q < 3; q++) { sum += __uint_as_float(s0[q]); sq -= __uint_as_float(s1[q]); }
            sts64(sb + RI_ST + tid * 8, __float_as_uint(sum), __float_as_uint(sq));
            bar_sync(4, 256);
            if (layer == TLL && n == TLN) TL(48);
#pragma unroll
            for (int q = 1; q < 4; q++) {
                uint32_t st2[2];
                lds64(st2, sb + RI_ST + ((tid + q * 64) & 255) * 8);
                sum += __uint_as_float(st2[0]); sq += __uint_as_float(st2[1]);
            }
            const float mean = sum * (1.f / 640.f), r = rsqrtf(fmaxf(fmaf(-mean, mean, sq * (1.f / 640.f)), 0.f) + 1e-5f), off = -mean * r;
            uint4* dst = (uint4*)g_xn + ((size_t)(2 * a + (w & 1)) * 80 + chunk0(rg)) * 32 + lane;
#pragma unroll
            for (int i = 0; i < 5; i++) {
                uint32_t u[4];
                lds128(u, xa + i * 16);
                dst[i * 32] = make_uint4(pack_h(fmaf(bf_lo(u[0]), r, off), fmaf(bf_hi(u[0]), r, off)), pack_h(fmaf(bf_lo(u[1]), r, off), fmaf(bf_hi(u[1]), r, off)),
                                         pack_h(fmaf(bf_lo(u[2]), r, off), fmaf(bf_hi(u[2]), r, off)), pack_h(fmaf(bf_lo(u[3]), r, off), fmaf(bf_hi(u[3]), r, off)));
            }
            __syncwarp();
            if (lane == 0) mbar_arrive(sb + HB_LN);
            if (layer == TLL) TL(37);
            if (layer == TLL && n == TLN) TL(44);
            residual(a + (nh >> 2), n + 1);
#pragma unroll 2
            for (int rr = 0; rr < 64 - gr && tid < 240; rr += 12) {
                uint32_t v[4];
                lds128(v, gs + (n & 1) * 21504 + rr * 336);
                ((uint4*)x)[(a * 64 + rr) * 80 + go] = make_uint4(v[0], v[1], v[2], v[3]);
            }
        }
    }
    bar_sync(3, 384);
    if (layer == TLL) TL(38);
    if (jh >= na) {
        int c0 = 0;
#pragma unroll 1
        for (int mb = (jh - na) >> 3; mb < nbh; mb += (nh - na) >> 3, c0 += GNC) oproj_mma(sb, mb, (jh - na) & 7, c0, x, out);
        if (layer == TLL) TL(42);
        return;
    }
    const int p = w >> 1, mi = w & 1;
    int slot = p, ph = 0;
    for (int idx = jh + p * na; idx < NSEG * 32; idx += 4 * na) {
        const uint32_t it = sb + slot * 30720 + lane * 16;
        float iq, ik, iv;
        weight_scale(idx & 31, 0, &iq); weight_scale(idx & 31, 1, &ik); weight_scale(idx & 31, 2, &iv);
        bar_sync(6 + p, 64);
        mbar_wait(sb + HB_DONE + slot * 8, ph ^ 1);
        mbar_wait(sb + HB_FULL + slot * 8, ph);
        if (layer == TLL && idx >= 63 * 32) TL(55);
        float s[6][4];
#pragma unroll
        for (int i = 0; i < 6; i++) s[i][0] = s[i][1] = s[i][2] = s[i][3] = 0.f;
#pragma unroll
        for (int e = 0; e < 8; e++) {
            uint32_t q[4], k[4];
            ldsm4t(q, it + (e >> 2) * 8192 + (e & 3) * 1024 + mi * 512);
            ldsm4t(k, it + 24576 + e * 512);
            mma_bf(s[4], q[0], q[2], q[1], q[3], k[0], k[1]);
            mma_bf(s[5], q[0], q[2], q[1], q[3], k[2], k[3]);
            ldsm4t(k, it + (e >> 2) * 8192 + 4096 + (e & 3) * 1024);
            mma_bf(s[0], q[0], q[2], q[1], q[3], k[0], k[1]);
            mma_bf(s[1], q[0], q[2], q[1], q[3], k[2], k[3]);
            if (mi) {
                ldsm4t(k, it + (e >> 2) * 8192 + 4096 + (e & 3) * 1024 + 512);
                mma_bf(s[2], q[0], q[2], q[1], q[3], k[0], k[1]);
                mma_bf(s[3], q[0], q[2], q[1], q[3], k[2], k[3]);
            }
        }
#pragma unroll
        for (int q = 0; q < 4; q++) s[4][q] += s[5][q];
        const int seg = idx >> 5, h = idx & 31;
        const float sl = iq * ik * (0.08838834764831845f * 1.4426950408889634f);
        float mx[2] = {-3.0e38f, -3.0e38f};
#pragma unroll
        for (int i = 0; i < 5; i++)
#pragma unroll
            for (int q = 0; q < 4; q++) {
                const bool ok = i == 4 || (i * 8 + 2 * t + (q & 1)) <= (mi * 16 + g + (q >> 1) * 8);
                s[i][q] = ok ? s[i][q] * sl : -1.0e9f * 1.4426950408889634f;
                mx[q >> 1] = fmaxf(mx[q >> 1], s[i][q]);
            }
        float sum[2] = {0.f, 0.f};
#pragma unroll
        for (int r = 0; r < 2; r++) {
            mx[r] = fmaxf(mx[r], __shfl_xor_sync(~0u, mx[r], 1));
            mx[r] = fmaxf(mx[r], __shfl_xor_sync(~0u, mx[r], 2));
        }
#pragma unroll
        for (int i = 0; i < 5; i++)
#pragma unroll
            for (int q = 0; q < 4; q++) { s[i][q] = ex2(s[i][q] - mx[q >> 1]); sum[q >> 1] += s[i][q]; }
#pragma unroll
        for (int r = 0; r < 2; r++) {
            sum[r] += __shfl_xor_sync(~0u, sum[r], 1);
            sum[r] += __shfl_xor_sync(~0u, sum[r], 2);
            sum[r] = iv * rcp(sum[r]);
        }
        uint32_t pp[5][2];
#pragma unroll
        for (int i = 0; i < 5; i++) { pp[i][0] = pack_bf(s[i][0] * sum[0], s[i][1] * sum[0]); pp[i][1] = pack_bf(s[i][2] * sum[1], s[i][3] * sum[1]); }
        uint32_t* o = (uint32_t*)g_O + (((size_t)(seg >> 1) * 512 + h * 16) * 8 + (seg & 1) * 4 + mi * 2) * 32 + lane;
#pragma unroll
        for (int e = 0; e < 8; e++) {
            float o0[4] = {0.f, 0.f, 0.f, 0.f}, o1[4] = {0.f, 0.f, 0.f, 0.f};
            uint32_t v[4];
            lds64(v, it - lane * 8 + 28672 + e * 256);
            mma_bf8(o0, pp[4][0], pp[4][1], v[0]);
            mma_bf8(o1, pp[4][0], pp[4][1], v[1]);
            ldsm4(v, it + 16384 + e * 1024);
            mma_bf(o0, pp[0][0], pp[0][1], pp[1][0], pp[1][1], v[0], v[2]);
            mma_bf(o1, pp[0][0], pp[0][1], pp[1][0], pp[1][1], v[1], v[3]);
            ldsm4(v, it + 16384 + e * 1024 + 512);
            mma_bf(o0, pp[2][0], pp[2][1], pp[3][0], pp[3][1], v[0], v[2]);
            mma_bf(o1, pp[2][0], pp[2][1], pp[3][0], pp[3][1], v[1], v[3]);
            o[(2 * e) * 256] = pack_bf(o0[0], o0[1]); o[(2 * e) * 256 + 32] = pack_bf(o0[2], o0[3]);
            o[(2 * e + 1) * 256] = pack_bf(o1[0], o1[1]); o[(2 * e + 1) * 256 + 32] = pack_bf(o1[2], o1[3]);
        }
        __syncwarp();
        if (lane == 0) mbar_arrive(sb + HB_DONE + slot * 8);
        slot += 4;
        if (slot >= 6) { slot -= 6; ph ^= 1; }
    }
    if (layer == TLL) TL(39);
}

__global__ void __cluster_dims__(3, 1, 1) __launch_bounds__(384, 1)
k_chain(const int layer, const int nact, const uint32_t zero, const bf16* __restrict__ Wq, const bf16* __restrict__ Wk, const bf16* __restrict__ Wv,
        const bf16* __restrict__ Wo, const bf16* res, bf16* out) {
    extern __shared__ __align__(1024) char sm[];
    const uint32_t sb = smem_u32(sm);
    const int b = blockIdx.x, h = b / 3, c = b - h * 3;
    pdl_go();
    if (threadIdx.x >= 256) {
        asm volatile("setmaxnreg.dec.sync.aligned.u32 24;");
        TL(11 + layer * 14);
        chain_aux(sb, c, h, layer, nact, Wq, Wk, Wv, Wo);
    } else {
        asm volatile("setmaxnreg.inc.sync.aligned.u32 240;");
        chain_mma(sb, c, h, layer, zero, Wq, Wk, Wv, Wo, res, out);
    }
}
__global__ void __launch_bounds__(384, 1) k_help(const bf16* res, bf16* x, bf16* out, const int layer, const int na, const int nbh, const int zero, const bf16* Wq,
                                                  const bf16* Wk, const bf16* Wv, const bf16* Wo) {
    extern __shared__ __align__(1024) char sm[];
    if (layer == TLL) TL(51);
    if (threadIdx.x >= 256) {
        const uint32_t sb = smem_u32(sm);
        const int p = (threadIdx.x >> 5) - 8, i = (threadIdx.x & 31) * 4 + p;
        if (i < 34) mbar_init(sb + G_BAR + i * 8, i < 4 ? 3 : i < 8 || i == 12 || i == 13 ? 8 : i >= 22 && i < 28 ? 2 : 1);
        fence_async_smem();
        wait_flag<100>(g_flag + F_X + layer * 128 + 65, 321);
        fence_async_glb();
        if (i == 8 + p && blockIdx.x < (gridDim.x & ~3)) {
            mbar_expect(sb + HB_A + p * 8, 20480);
            bulk_g2s(sb + RI_A + p * 20480, (const char*)g_YT + (size_t)(blockIdx.x >> 2) * 81920 + p * 20480, 20480, sb + HB_A + p * 8);
        }
        __syncwarp();
        bar_sync(2, 128);
        bar_arrive(1, 384);
    }
    if (threadIdx.x + zero >= 256) helper_aux(smem_u32(sm), blockIdx.x, gridDim.x, na, nbh, layer, Wq, Wk, Wv, Wo);
    else helper_mma(sm, blockIdx.x, gridDim.x, na, nbh, layer, res, x, out);
    __syncwarp();
    pdl_go();
    if (blockIdx.x == 0) pdl_wait();
}

#define COL_PAD 15872
template <class... P, class... A>
void launch_pdl(void (*k)(P...), int grid, int block, int smem, cudaStream_t st, A... args) {
    cudaLaunchConfig_t cfg = {};
    cfg.gridDim = dim3(grid); cfg.blockDim = dim3(block); cfg.dynamicSmemBytes = smem; cfg.stream = st;
    cudaLaunchAttribute at[1];
    at[0].id = cudaLaunchAttributeProgrammaticStreamSerialization; at[0].val.programmaticStreamSerializationAllowed = 1;
    cfg.attrs = at;
    cfg.numAttrs = 1;
    cudaLaunchKernelEx(&cfg, k, args...);
}

}

extern "C" void kernel_launch(void* const* d_in, const int* in_sizes, int n_in, void* d_out, int out_size) {
    const bf16* x = (const bf16*)d_in[0];
    const bf16* wr = (const bf16*)d_in[1];
    const bf16* wi = (const bf16*)d_in[2];
    const bf16* mem0 = (const bf16*)d_in[4];
    const bf16* Wq = (const bf16*)d_in[5];
    const bf16* Wk = (const bf16*)d_in[6];
    const bf16* Wv = (const bf16*)d_in[7];
    const bf16* Wo = (const bf16*)d_in[8];
    bf16* out = (bf16*)d_out;
    static int nhelp = 0;
    static bf16 *xa, *xb;
    static cudaStream_t s1;
    static cudaEvent_t ev_fork, ev_join;
    if (!nhelp) {
        cudaStreamCreateWithFlags(&s1, cudaStreamNonBlocking);
        cudaEventCreateWithFlags(&ev_fork, cudaEventDisableTiming);
        cudaEventCreateWithFlags(&ev_join, cudaEventDisableTiming);
        cudaFuncSetAttribute(k_setup, cudaFuncAttributeMaxDynamicSharedMemorySize, SU_SMEM);
        cudaFuncSetAttribute(k_rowf, cudaFuncAttributeMaxDynamicSharedMemorySize, RF_SMEM);
        cudaFuncSetAttribute(k_col, cudaFuncAttributeMaxDynamicSharedMemorySize, COL_PAD);
        cudaFuncSetAttribute(k_chain, cudaFuncAttributeMaxDynamicSharedMemorySize, CH_SMEM);
        cudaFuncSetAttribute(k_setup, cudaFuncAttributePreferredSharedMemoryCarveout, 100);
        cudaFuncSetAttribute(k_rowf, cudaFuncAttributePreferredSharedMemoryCarveout, 100);
        cudaFuncSetAttribute(k_col, cudaFuncAttributePreferredSharedMemoryCarveout, 100);
        cudaFuncSetAttribute(k_chain, cudaFuncAttributePreferredSharedMemoryCarveout, 100);
        cudaFuncSetAttribute(k_help, cudaFuncAttributeMaxDynamicSharedMemorySize, HP_SMEM);
        cudaFuncSetAttribute(k_help, cudaFuncAttributePreferredSharedMemoryCarveout, 100);
        int dev = 0, sms = 0;
        cudaGetDevice(&dev);
        cudaDeviceGetAttribute(&sms, cudaDevAttrMultiProcessorCount, dev);
        nhelp = sms - 96 < 12 ? 12 : sms - 96;
        cudaGetSymbolAddress((void**)&xa, g_xa);
        cudaGetSymbolAddress((void**)&xb, g_xb);
    }
    const int na = nhelp - (nhelp >= 36 ? 24 : nhelp >= 28 ? 16 : 8), nbh = 14;
    cudaStream_t s0 = cudaStreamPerThread;
    cudaEventRecord(ev_fork, s0);
    cudaStreamWaitEvent(s1, ev_fork, 0);
    k_rowf<<<(96 + nhelp) & ~1, 256, RF_SMEM, s0>>>(x, 1, Wq, Wk, Wv, Wo);
    k_setup<<<NSETUP, 256, SU_SMEM, s1>>>(wr, wi, mem0);
    cudaEventRecord(ev_join, s1);
#define NLAYER 2
    for (int l = 0; l < NLAYER; l++) {
        const bf16* xin = l == 0 ? x : xb;
        if (l == 1) launch_pdl(k_rowf, 128, 256, RF_SMEM, s0, xin, 0, Wq, Wk, Wv, Wo);
        launch_pdl(k_col, 321, 128, l == 0 ? 0 : COL_PAD, s0, (int)(l == 0), Wq, Wk, Wv, Wo);
        launch_pdl(k_chain, 96, 384, CH_SMEM, s0, l, nhelp & ~3, 0u, Wq, Wk, Wv, Wo, (const bf16*)xa, l == 0 ? xb : out);
        launch_pdl(k_help, nhelp, 384, HP_SMEM, s0, xin, xa, l == 0 ? xb : out, l, na, nbh, 0, Wq, Wk, Wv, Wo);
    }
    cudaStreamWaitEvent(s0, ev_join, 0);
}
```

```cpp
#include <cuda_runtime.h>
#include <cuda_bf16.h>
#include <cuda_fp16.h>
#include <stdint.h>
#include <string.h>

namespace {

typedef __nv_bfloat16 bf16;
constexpr int S_ = 2048, D_ = 640, NSEG = 64;
constexpr int SPIN_LIM = 1 << 13;

__device__ float                  g_wmx[96];
__device__ __align__(1024) bf16   g_wot[4096 * 640];
__device__ __align__(16) float    g_co[1024];
__device__ __align__(256) uint2   g_stat[2 * 32 * 16 * 64];
__device__ float                  g_invM0;
__device__ __align__(16) float    g_wmax[128];
__device__ __align__(1024) char   g_redraw[65 * 32768];
constexpr int F_X = 2 * NSEG * 32, F_O = F_X + 2 * 128, NFLAG = F_O + 128, RING = 8;
constexpr int F_W = F_X + 66;
constexpr int NSETUP = 131;
struct __align__(256) Flag { unsigned v; };
__device__ Flag                   g_flag[NFLAG];
__device__ Flag                   g_ready[1];
__device__ __align__(1024) char   g_item[RING * 32 * 32768];
__device__ __align__(1024) bf16   g_O[S_ * 4096];
__device__ __align__(1024) __half g_xn[S_ * D_];
__device__ __align__(1024) bf16   g_xa[S_ * D_];
__device__ __align__(1024) bf16   g_xb[S_ * D_];
__device__ __align__(1024) __half g_UT[D_ * S_];
__device__ __align__(1024) __half g_YT[D_ * S_];
__device__ __align__(1024) __half g_ctab[64 * 128 + 64 * 64];
__device__ __align__(1024) uint32_t g_Wf[321 * 2048];

#define TL(i)
#define TLN 0
#define TLL 1
#define CK(i)
__device__ __forceinline__ uint32_t smem_u32(const void* p) { return (uint32_t)__cvta_generic_to_shared(p); }
__device__ __forceinline__ uint32_t mapa(uint32_t a, uint32_t r) { uint32_t o; asm("mapa.shared::cluster.u32 %0,%1,%2;" : "=r"(o) : "r"(a), "r"(r)); return o; }
__device__ __forceinline__ void mbar_init(uint32_t a, int c) { asm volatile("mbarrier.init.shared::cta.b64 [%0],%1;" ::"r"(a), "r"(c) : "memory"); }
__device__ __forceinline__ void mbar_expect(uint32_t a, int bytes) { asm volatile("mbarrier.arrive.expect_tx.shared::cta.b64 _,[%0],%1;" ::"r"(a), "r"(bytes) : "memory"); }
__device__ __forceinline__ void mbar_arrive(uint32_t a) { asm volatile("mbarrier.arrive.shared::cta.b64 _,[%0];" ::"r"(a) : "memory"); }
__device__ __forceinline__ bool mbar_try(uint32_t a, uint32_t par) {
    uint32_t p;
    asm volatile("{.reg .pred q; mbarrier.try_wait.parity.shared::cta.b64 q,[%1],%2; selp.u32 %0,1,0,q;}" : "=r"(p) : "r"(a), "r"(par) : "memory");
    return p;
}
__device__ __forceinline__ void mbar_wait(uint32_t a, uint32_t par) {
    if (!mbar_try(a, par)) {
        int lim = 0;
        while (!mbar_try(a, par) && ++lim < SPIN_LIM) {}
    }
}
#define MW_HINT 20000
__device__ __forceinline__ void mbar_sleep(uint32_t a, uint32_t par) {
    asm volatile("{.reg .pred q; .reg .u32 n; mov.u32 n,0;\n"
                 "W_LOOP: mbarrier.try_wait.parity.shared::cta.b64 q,[%0],%1,%2; add.u32 n,n,1; setp.lt.and.u32 q,n,%3,!q; @q bra W_LOOP;}"
                 ::"r"(a), "r"(par), "n"(MW_HINT), "n"(SPIN_LIM) : "memory");
}
__device__ __forceinline__ void bar_arrive(int id, int n) { asm volatile("bar.arrive %0,%1;" ::"r"(id), "r"(n) : "memory"); }
__device__ __forceinline__ uint32_t clock32() { uint32_t c; asm volatile("mov.u32 %0,%%clock;" : "=r"(c)); return c; }
__device__ __forceinline__ uint32_t read_tid() { uint32_t v; asm volatile("mov.u32 %0,%%tid.x;" : "=r"(v)); return v; }
__device__ __forceinline__ void bar_sync(int id, int n) { asm volatile("bar.sync %0,%1;" ::"r"(id), "r"(n) : "memory"); }
__device__ __forceinline__ void fence_async_smem() { asm volatile("fence.proxy.async.shared::cta;" ::: "memory"); }
__device__ __forceinline__ void fence_async_glb() { asm volatile("fence.proxy.async.global;" ::: "memory"); }
__device__ __forceinline__ void cluster_sync_full() { asm volatile("barrier.cluster.arrive.aligned; barrier.cluster.wait.aligned;" ::: "memory"); }
__device__ __forceinline__ void bulk_g2s(uint32_t dst, const void* src, int bytes, uint32_t mb) {
    asm volatile("cp.async.bulk.shared::cluster.global.mbarrier::complete_tx::bytes [%0],[%1],%2,[%3];" ::"r"(dst), "l"(src), "r"(bytes), "r"(mb) : "memory");
}
__device__ __forceinline__ void bulk_g2s_last(uint32_t dst, const void* src, int bytes, uint32_t mb) {
    asm volatile("{.reg .b64 p; createpolicy.fractional.L2::evict_first.b64 p, 1.0;\n"
                 "cp.async.bulk.shared::cluster.global.mbarrier::complete_tx::bytes.L2::cache_hint [%0],[%1],%2,[%3],p;}"
                 ::"r"(dst), "l"(src), "r"(bytes), "r"(mb) : "memory");
}
__device__ __forceinline__ void bulk_s2s(uint32_t dst, uint32_t src, int bytes, uint32_t mb) {
    asm volatile("cp.async.bulk.shared::cluster.shared::cta.mbarrier::complete_tx::bytes [%0],[%1],%2,[%3];" ::"r"(dst), "r"(src), "r"(bytes), "r"(mb) : "memory");
}
__device__ __forceinline__ void bulk_s2g(void* dst, uint32_t src, int bytes) {
    asm volatile("cp.async.bulk.global.shared::cta.bulk_group [%0],[%1],%2;" ::"l"(dst), "r"(src), "r"(bytes) : "memory");
}
__device__ __forceinline__ void cp_async16(uint32_t dst, const void* src, uint32_t bytes = 16) {
    asm volatile("cp.async.cg.shared.global [%0],[%1],16,%2;" ::"r"(dst), "l"(src), "r"(bytes) : "memory");
}
__device__ __forceinline__ void cp_commit() { asm volatile("cp.async.commit_group;" ::: "memory"); }
template <int N> __device__ __forceinline__ void cp_wait() { asm volatile("cp.async.wait_group %0;" ::"n"(N) : "memory"); }
__device__ __forceinline__ void bulk_commit() { asm volatile("cp.async.bulk.commit_group;" ::: "memory"); }
__device__ __forceinline__ void bulk_wait0() { asm volatile("cp.async.bulk.wait_group 0;" ::: "memory"); }
__device__ __forceinline__ void ldsm4(uint32_t* r, uint32_t a) {
    asm volatile("ldmatrix.sync.aligned.m8n8.x4.shared.b16 {%0,%1,%2,%3},[%4];" : "=r"(r[0]), "=r"(r[1]), "=r"(r[2]), "=r"(r[3]) : "r"(a) : "memory");
}
__device__ __forceinline__ void ldsm4t(uint32_t* r, uint32_t a) {
    asm volatile("ldmatrix.sync.aligned.m8n8.x4.trans.shared.b16 {%0,%1,%2,%3},[%4];" : "=r"(r[0]), "=r"(r[1]), "=r"(r[2]), "=r"(r[3]) : "r"(a) : "memory");
}
__device__ __forceinline__ void stsm4(uint32_t a, uint32_t r0, uint32_t r1, uint32_t r2, uint32_t r3) {
    asm volatile("stmatrix.sync.aligned.m8n8.x4.shared.b16 [%0],{%1,%2,%3,%4};" ::"r"(a), "r"(r0), "r"(r1), "r"(r2), "r"(r3) : "memory");
}
__device__ __forceinline__ void stsm4t(uint32_t a, uint32_t r0, uint32_t r1, uint32_t r2, uint32_t r3) {
    asm volatile("stmatrix.sync.aligned.m8n8.x4.trans.shared.b16 [%0],{%1,%2,%3,%4};" ::"r"(a), "r"(r0), "r"(r1), "r"(r2), "r"(r3) : "memory");
}
__device__ __forceinline__ void lds128(uint32_t* r, uint32_t a) {
    asm volatile("ld.shared.v4.b32 {%0,%1,%2,%3},[%4];" : "=r"(r[0]), "=r"(r[1]), "=r"(r[2]), "=r"(r[3]) : "r"(a) : "memory");
}
__device__ __forceinline__ void lds64(uint32_t* r, uint32_t a) {
    asm volatile("ld.shared.v2.b32 {%0,%1},[%2];" : "=r"(r[0]), "=r"(r[1]) : "r"(a) : "memory");
}
__device__ __forceinline__ uint32_t lds32(uint32_t a) { uint32_t v; asm volatile("ld.shared.b32 %0,[%1];" : "=r"(v) : "r"(a) : "memory"); return v; }
__device__ __forceinline__ void sts128(uint32_t a, uint32_t r0, uint32_t r1, uint32_t r2, uint32_t r3) {
    asm volatile("st.shared.v4.b32 [%0],{%1,%2,%3,%4};" ::"r"(a), "r"(r0), "r"(r1), "r"(r2), "r"(r3) : "memory");
}
__device__ __forceinline__ void sts64(uint32_t a, uint32_t v0, uint32_t v1) { asm volatile("st.shared.v2.b32 [%0],{%1,%2};" ::"r"(a), "r"(v0), "r"(v1) : "memory"); }
[[maybe_unused]] __device__ __forceinline__ void sts32(uint32_t a, uint32_t v) { asm volatile("st.shared.b32 [%0],%1;" ::"r"(a), "r"(v) : "memory"); }
#define AU_(op) "{.reg .u32 t; add.u32 t,%4,%5; " op " {%0,%1,%2,%3},[t+%6];}"
template <int I> __device__ __forceinline__ void ldsm4_u(uint32_t* r, uint32_t a, uint32_t u) {
    asm volatile(AU_("ldmatrix.sync.aligned.m8n8.x4.shared.b16") : "=r"(r[0]), "=r"(r[1]), "=r"(r[2]), "=r"(r[3]) : "r"(a), "r"(u), "n"(I) : "memory");
}
template <int I> __device__ __forceinline__ void ldsm4t_u(uint32_t* r, uint32_t a, uint32_t u) {
    asm volatile(AU_("ldmatrix.sync.aligned.m8n8.x4.trans.shared.b16") : "=r"(r[0]), "=r"(r[1]), "=r"(r[2]), "=r"(r[3]) : "r"(a), "r"(u), "n"(I) : "memory");
}
template <int I> __device__ __forceinline__ void lds128_u(uint32_t* r, uint32_t a, uint32_t u) {
    asm volatile(AU_("ld.shared.v4.b32") : "=r"(r[0]), "=r"(r[1]), "=r"(r[2]), "=r"(r[3]) : "r"(a), "r"(u), "n"(I) : "memory");
}
template <int I> __device__ __forceinline__ void lds64_u(uint32_t* r, uint32_t a, uint32_t u) {
    asm volatile("{.reg .u32 t; add.u32 t,%2,%3; ld.shared.v2.b32 {%0,%1},[t+%4];}" : "=r"(r[0]), "=r"(r[1]) : "r"(a), "r"(u), "n"(I) : "memory");
}
template <int I> __device__ __forceinline__ uint32_t lds32_u(uint32_t a, uint32_t u) {
    uint32_t v;
    asm volatile("{.reg .u32 t; add.u32 t,%1,%2; ld.shared.b32 %0,[t+%3];}" : "=r"(v) : "r"(a), "r"(u), "n"(I) : "memory");
    return v;
}
template <int I> __device__ __forceinline__ void sts64_u(uint32_t a, uint32_t u, uint32_t v0, uint32_t v1) {
    asm volatile("{.reg .u32 t; add.u32 t,%0,%1; st.shared.v2.b32 [t+%2],{%3,%4};}" ::"r"(a), "r"(u), "n"(I), "r"(v0), "r"(v1) : "memory");
}
template <int I> __device__ __forceinline__ void sts32_u(uint32_t a, uint32_t u, uint32_t v) {
    asm volatile("{.reg .u32 t; add.u32 t,%0,%1; st.shared.b32 [t+%2],%3;}" ::"r"(a), "r"(u), "n"(I), "r"(v) : "memory");
}
template <int I> __device__ __forceinline__ void sts16_u(uint32_t a, uint32_t u, uint32_t v) {
    asm volatile("{.reg .u32 t; add.u32 t,%0,%1; st.shared.b16 [t+%2],%3;}" ::"r"(a), "r"(u), "n"(I), "h"((unsigned short)v) : "memory");
}
template <int I> __device__ __forceinline__ void sts128_u(uint32_t a, uint32_t u, uint32_t r0, uint32_t r1, uint32_t r2, uint32_t r3) {
    asm volatile("{.reg .u32 t; add.u32 t,%0,%1; st.shared.v4.b32 [t+%2],{%3,%4,%5,%6};}" ::"r"(a), "r"(u), "n"(I), "r"(r0), "r"(r1), "r"(r2), "r"(r3) : "memory");
}
template <int I> __device__ __forceinline__ void stsm4_u(uint32_t a, uint32_t u, uint32_t r0, uint32_t r1, uint32_t r2, uint32_t r3) {
    asm volatile("{.reg .u32 t; add.u32 t,%0,%1; stmatrix.sync.aligned.m8n8.x4.shared.b16 [t+%2],{%3,%4,%5,%6};}"
                 ::"r"(a), "r"(u), "n"(I), "r"(r0), "r"(r1), "r"(r2), "r"(r3) : "memory");
}
__device__ __forceinline__ void st_async2_x3(uint32_t a, uint32_t u, uint32_t mb, uint32_t v0, uint32_t v1) {
    asm volatile("{.reg .u32 t,x,y; add.u32 t,%0,%1;\n"
                 "mapa.shared::cluster.u32 x,t,0; mapa.shared::cluster.u32 y,%2,0; st.async.shared::cluster.mbarrier::complete_tx::bytes.v2.b32 [x],{%3,%4},[y];\n"
                 "mapa.shared::cluster.u32 x,t,1; mapa.shared::cluster.u32 y,%2,1; st.async.shared::cluster.mbarrier::complete_tx::bytes.v2.b32 [x],{%3,%4},[y];\n"
                 "mapa.shared::cluster.u32 x,t,2; mapa.shared::cluster.u32 y,%2,2; st.async.shared::cluster.mbarrier::complete_tx::bytes.v2.b32 [x],{%3,%4},[y];}"
                 ::"r"(a), "r"(u), "r"(mb), "r"(v0), "r"(v1) : "memory");
}
__device__ __forceinline__ void st_share2(uint32_t a, uint32_t u, uint32_t mb, uint32_t d0, uint32_t d1, uint32_t v0, uint32_t v1) {
    asm volatile("{.reg .pred p; .reg .u32 t,x,y; add.u32 t,%0,%1;\n"
                 "add.u32 x,t,%3; add.u32 y,%2,%3; st.async.shared::cluster.mbarrier::complete_tx::bytes.v2.b32 [x],{%5,%6},[y];\n"
                 "add.u32 x,t,%4; add.u32 y,%2,%4; st.async.shared::cluster.mbarrier::complete_tx::bytes.v2.b32 [x],{%5,%6},[y];\n"
                 "st.shared.v2.b32 [t],{%5,%6}; bar.warp.sync -1; setp.eq.u32 p,%0,0; @p mbarrier.arrive.shared::cta.b64 _,[%2];}"
                 ::"r"(a), "r"(u), "r"(mb), "r"(d0), "r"(d1), "r"(v0), "r"(v1) : "memory");
}
template <int V> struct IC { static constexpr int value = V; __host__ __device__ constexpr operator int() const { return V; } };
template <int N, class F> __device__ __forceinline__ void sfor(F f) {
    if constexpr (N > 0) { sfor<N - 1>(f); f(IC<N - 1>()); }
}
__device__ __forceinline__ void mma_f16(float* d, const uint32_t* a, uint32_t b0, uint32_t b1) {
    asm volatile("mma.sync.aligned.m16n8k16.row.col.f32.f16.f16.f32 {%0,%1,%2,%3},{%4,%5,%6,%7},{%8,%9},{%0,%1,%2,%3};"
                 : "+f"(d[0]), "+f"(d[1]), "+f"(d[2]), "+f"(d[3]) : "r"(a[0]), "r"(a[1]), "r"(a[2]), "r"(a[3]), "r"(b0), "r"(b1));
}
__device__ __forceinline__ void mma_bf(float* d, uint32_t a0, uint32_t a1, uint32_t a2, uint32_t a3, uint32_t b0, uint32_t b1) {
    asm volatile("mma.sync.aligned.m16n8k16.row.col.f32.bf16.bf16.f32 {%0,%1,%2,%3},{%4,%5,%6,%7},{%8,%9},{%0,%1,%2,%3};"
                 : "+f"(d[0]), "+f"(d[1]), "+f"(d[2]), "+f"(d[3]) : "r"(a0), "r"(a1), "r"(a2), "r"(a3), "r"(b0), "r"(b1));
}
__device__ __forceinline__ void mma_bf8(float* d, uint32_t a0, uint32_t a1, uint32_t b0) {
    asm volatile("mma.sync.aligned.m16n8k8.row.col.f32.bf16.bf16.f32 {%0,%1,%2,%3},{%4,%5},{%6},{%0,%1,%2,%3};"
                 : "+f"(d[0]), "+f"(d[1]), "+f"(d[2]), "+f"(d[3]) : "r"(a0), "r"(a1), "r"(b0));
}
__device__ __forceinline__ uint32_t pack_bf(float lo, float hi) { uint32_t r; asm("cvt.rn.bf16x2.f32 %0,%1,%2;" : "=r"(r) : "f"(hi), "f"(lo)); return r; }
__device__ __forceinline__ uint32_t pack_h(float lo, float hi) { uint32_t r; asm("cvt.rn.f16x2.f32 %0,%1,%2;" : "=r"(r) : "f"(hi), "f"(lo)); return r; }
__device__ __forceinline__ float bf_lo(uint32_t v) { return __uint_as_float(v << 16); }
__device__ __forceinline__ float bf_hi(uint32_t v) { return __uint_as_float(v & 0xffff0000u); }
__device__ __forceinline__ uint32_t bfma(uint32_t a, uint32_t b, uint32_t c) { uint32_t r; asm("fma.rn.bf16x2 %0,%1,%2,%3;" : "=r"(r) : "r"(a), "r"(b), "r"(c)); return r; }
__device__ __forceinline__ uint4 add_bf8(const uint4 x, const uint32_t* y, const uint32_t k = 0x3f803f80u) {
    return make_uint4(bfma(y[0], k, x.x), bfma(y[1], k, x.y), bfma(y[2], k, x.z), bfma(y[3], k, x.w));
}
__device__ __forceinline__ float ex2(float x) { float r; asm("ex2.approx.ftz.f32 %0,%1;" : "=f"(r) : "f"(x)); return r; }
__device__ __forceinline__ float rcp(float x) { float r; asm("rcp.approx.ftz.f32 %0,%1;" : "=f"(r) : "f"(x)); return r; }
__device__ __forceinline__ void wg_fence() { asm volatile("wgmma.fence.sync.aligned;" ::: "memory"); }
__device__ __forceinline__ void wg_commit() { asm volatile("wgmma.commit_group.sync.aligned;" ::: "memory"); }
template <int N> __device__ __forceinline__ void wg_wait() { asm volatile("wgmma.wait_group.sync.aligned %0;" ::"n"(N) : "memory"); }
__device__ __forceinline__ uint64_t mkdesc(uint32_t a, uint32_t lbo, uint32_t sbo, uint32_t sw) {
    return (uint64_t)((a & 0x3FFFF) >> 4) | ((uint64_t)(lbo >> 4) << 16) | ((uint64_t)(sbo >> 4) << 32) | ((uint64_t)sw << 62);
}
#define F4(d, i) "+f"(d[i]), "+f"(d[i + 1]), "+f"(d[i + 2]), "+f"(d[i + 3])
#define F8(d, i) F4(d, i), F4(d, i + 4)
#define F16(d, i) F8(d, i), F8(d, i + 8)
template <int OFF, int SC> __device__ __forceinline__ void wg_n32_x(float* d, const uint32_t* a, uint32_t lo) {
    asm volatile("{.reg .pred p; .reg .b32 l; .reg .b64 q; setp.ne.b32 p,%22,0; add.u32 l,%20,%21; mov.b64 q,{l,8};\n"
                 "wgmma.mma_async.sync.aligned.m64n32k16.f32.f16.f16 "
                 "{%0,%1,%2,%3,%4,%5,%6,%7,%8,%9,%10,%11,%12,%13,%14,%15},{%16,%17,%18,%19},q,p,1,1,0;}"
                 : F16(d, 0) : "r"(a[0]), "r"(a[1]), "r"(a[2]), "r"(a[3]), "r"(lo), "n"(OFF), "n"(SC));
}
__device__ __forceinline__ void wg_n128_rs(float* d, const uint32_t* a, uint64_t db, int sc) {
    asm volatile("{.reg .pred p; setp.ne.b32 p,%69,0; wgmma.mma_async.sync.aligned.m64n128k16.f32.f16.f16 "
                 "{%0,%1,%2,%3,%4,%5,%6,%7,%8,%9,%10,%11,%12,%13,%14,%15,%16,%17,%18,%19,%20,%21,%22,%23,%24,%25,%26,%27,%28,%29,%30,%31,"
                 "%32,%33,%34,%35,%36,%37,%38,%39,%40,%41,%42,%43,%44,%45,%46,%47,%48,%49,%50,%51,%52,%53,%54,%55,%56,%57,%58,%59,%60,%61,%62,%63},"
                 "{%64,%65,%66,%67},%68,p,1,1,0;}"
                 : F16(d, 0), F16(d, 16), F16(d, 32), F16(d, 48) : "r"(a[0]), "r"(a[1]), "r"(a[2]), "r"(a[3]), "l"(db), "r"(sc));
}
#define N80_REGS "{%0,%1,%2,%3,%4,%5,%6,%7,%8,%9,%10,%11,%12,%13,%14,%15,%16,%17,%18,%19,%20,%21,%22,%23,%24,%25,%26,%27,%28,%29,%30,%31,%32,%33,%34,%35,%36,%37,%38,%39}"
__device__ __forceinline__ void wg_n80_ss(float* d, uint64_t da, uint64_t db, int sc) {
    asm volatile("{.reg .pred p; setp.ne.b32 p,%42,0; wgmma.mma_async.sync.aligned.m64n80k16.f32.bf16.bf16 " N80_REGS ",%40,%41,p,1,1,0,0;}"
                 : F16(d, 0), F16(d, 16), F8(d, 32) : "l"(da), "l"(db), "r"(sc));
}
__device__ __forceinline__ void wg_n88_ss(float* d, uint64_t da, uint64_t db, int sc) {
    asm volatile("{.reg .pred p; setp.ne.b32 p,%46,0; wgmma.mma_async.sync.aligned.m64n88k16.f32.f16.f16 "
                 "{%0,%1,%2,%3,%4,%5,%6,%7,%8,%9,%10,%11,%12,%13,%14,%15,%16,%17,%18,%19,%20,%21,%22,%23,%24,%25,%26,%27,%28,%29,%30,%31,"
                 "%32,%33,%34,%35,%36,%37,%38,%39,%40,%41,%42,%43},%44,%45,p,1,1,0,0;}"
                 : F16(d, 0), F16(d, 16), F8(d, 32), F4(d, 40) : "l"(da), "l"(db), "r"(sc));
}
__device__ __forceinline__ void wg_n48_ss_ta(float* d, uint64_t da, uint64_t db, int sc) {
    asm volatile("{.reg .pred p; setp.ne.b32 p,%26,0; wgmma.mma_async.sync.aligned.m64n48k16.f32.f16.f16 "
                 "{%0,%1,%2,%3,%4,%5,%6,%7,%8,%9,%10,%11,%12,%13,%14,%15,%16,%17,%18,%19,%20,%21,%22,%23},%24,%25,p,1,1,1,0;}"
                 : F16(d, 0), F8(d, 16) : "l"(da), "l"(db), "r"(sc));
}
template <int TA> __device__ __forceinline__ void wg_n64_ss_tb(float* d, uint64_t da, uint64_t db, int sc) {
    asm volatile("{.reg .pred p; setp.ne.b32 p,%34,0; wgmma.mma_async.sync.aligned.m64n64k16.f32.f16.f16 "
                 "{%0,%1,%2,%3,%4,%5,%6,%7,%8,%9,%10,%11,%12,%13,%14,%15,%16,%17,%18,%19,%20,%21,%22,%23,%24,%25,%26,%27,%28,%29,%30,%31},"
                 "%32,%33,p,1,1,%35,1;}"
                 : F16(d, 0), F16(d, 16) : "l"(da), "l"(db), "r"(sc), "n"(TA));
}
__device__ __forceinline__ void pdl_wait() { asm volatile("griddepcontrol.wait;" ::: "memory"); }
__device__ __forceinline__ void pdl_go() { asm volatile("griddepcontrol.launch_dependents;" ::: "memory"); }
__device__ __forceinline__ float cos640(float p) {
    const float q = fmaf(p, 0.0015625f, 12582912.f) - 12582912.f;
    return __cosf(fmaf(q, -640.f, p) * 0.009817477042468103f);
}
__device__ __forceinline__ uint4 cos_row8(float p0, float step, float amp = 1.f) {
    float v[8];
    const float k = 2.f * cos640(step);
    v[0] = amp * cos640(p0); v[1] = amp * cos640(p0 + step);
#pragma unroll
    for (int i = 2; i < 8; i++) v[i] = fmaf(k, v[i - 1], -v[i - 2]);
    return make_uint4(pack_h(v[0], v[1]), pack_h(v[2], v[3]), pack_h(v[4], v[5]), pack_h(v[6], v[7]));
}
__device__ __forceinline__ float wfilter_max(int lane) {
    float m = fmaxf(fmaxf(g_wmax[lane], g_wmax[lane + 32]), fmaxf(g_wmax[lane + 64], g_wmax[lane + 96]));
    return __uint_as_float(__reduce_max_sync(~0u, __float_as_uint(m)));
}
__device__ __forceinline__ unsigned ld_acquire(const Flag* p) { unsigned v; asm volatile("ld.acquire.gpu.global.u32 %0,[%1];" : "=r"(v) : "l"(p) : "memory"); return v; }
#define POLL_NS 200
template <int NS = POLL_NS> __device__ __forceinline__ void wait_flag(const Flag* p, unsigned v) {
    if (ld_acquire(p) >= v) return;
    unsigned x;
    int lim = 0;
    do {
        __nanosleep(NS);
        asm volatile("ld.relaxed.gpu.global.u32 %0,[%1];" : "=r"(x) : "l"(p) : "memory");
    } while (x < v && ++lim < SPIN_LIM);
    ld_acquire(p);
}
__device__ __forceinline__ void prefetch_l2(const void* p, int bytes) { asm volatile("cp.async.bulk.prefetch.L2.global [%0],%1;" ::"l"(p), "r"(bytes) : "memory"); }
__device__ __forceinline__ void red_release(Flag* p) { asm volatile("red.release.gpu.global.add.u32 [%0],1;" ::"l"(p) : "memory"); }
__device__ __forceinline__ void red_relaxed(Flag* p) { asm volatile("red.relaxed.gpu.global.add.u32 [%0],1;" ::"l"(p) : "memory"); }
__device__ __forceinline__ void red_h8(void* p, uint32_t a, uint32_t b, uint32_t c, uint32_t d) {
    asm volatile("red.relaxed.gpu.global.add.noftz.v4.f16x2 [%0],{%1,%2,%3,%4};" ::"l"(p), "r"(a), "r"(b), "r"(c), "r"(d) : "memory");
}
__device__ __forceinline__ float pow2_scale(float bound, int top, float* inv) {
    int e = (int)((__float_as_uint(bound) >> 23) & 0xff) - 126;
    int k = top - e;
    k = max(-100, min(100, k));
    *inv = __uint_as_float((uint32_t)(127 - k) << 23);
    return __uint_as_float((uint32_t)(127 + k) << 23);
}
__device__ __forceinline__ char* red_base() { return (char*)(((uintptr_t)g_redraw + 32767) & ~(uintptr_t)32767); }

__device__ __forceinline__ void setup_a(char* sm, const int b, const bf16* __restrict__ wr, const bf16* __restrict__ wi) {
    const int tid = threadIdx.x, lane = tid & 31;
    const uint32_t sb = smem_u32(sm);
    auto row_byte = [&](int q) { return ((b >> 2) + 32 * ((q >> 1) * 8 + 2 * (b & 3) + (q & 1))) * 642; };
#pragma unroll 1
    for (int r = tid >> 5; r < 32; r += 8) {
        const char* src = (const char*)(r < 16 ? wr : wi) + (row_byte(r & 15) & ~15);
        cp_async16(sb + r * 672 + lane * 16, src + lane * 16);
        if (lane < 9) cp_async16(sb + r * 672 + 512 + lane * 16, src + 512 + lane * 16);
    }
    ((uint4*)g_stat)[b * 256 + tid] = make_uint4(0, 0, 0, 0);
    if (tid < 2 * (NFLAG / 128)) ((uint4*)(g_flag + b * (NFLAG / 128) + (tid >> 1)))[tid & 1] = make_uint4(0, 0, 0, 0);
    if (tid < 12) {
        const int i = b * 12 + tid;
        const int f = ((i >> 4) & 3) * 8 + (i & 7), im = (i >> 3) & 1, part = (i >> 8) & 1;
        ((uint4*)g_ctab)[i] = cos_row8((float)(i < 1024 ? (i >> 7) * 80 * (i & 63) + ((i & 64) ? 480 : 0) : ((i >> 6) & 3) * 160 * f + (im == part ? 0 : im ? 160 : 480)),
                                       (float)(i < 1024 ? 10 * (i & 63) : 20 * f));
    }
    asm volatile("cp.async.wait_all;" ::: "memory");
    __syncthreads();
    const int q0 = (tid & 3) * 4;
    const char* rp[4];
#pragma unroll
    for (int u = 0; u < 4; u++) rp[u] = sm + (q0 + u) * 672 + (row_byte(q0 + u) & 15);
    uint32_t mx = 0;
#pragma unroll 2
    for (int c = tid >> 2; c < 321; c += 64) {
        uint32_t v[4];
#pragma unroll
        for (int u = 0; u < 4; u++) {
            v[u] = ((const unsigned short*)rp[u])[c] | ((uint32_t)((const unsigned short*)(rp[u] + 16 * 672))[c] << 16);
            mx = __vmaxu2(mx, v[u] & 0x7fff7fffu);
        }
        ((uint4*)g_Wf)[(size_t)c * 512 + b * 4 + ((tid ^ (b >> 1)) & 3)] = make_uint4(v[0], v[1], v[2], v[3]);
    }
    mx = __reduce_max_sync(~0u, max(mx & 0xffffu, mx >> 16));
    __syncthreads();
    if (lane == 0) ((uint32_t*)sm)[tid >> 5] = mx;
    __syncthreads();
    if (tid < 32) {
        mx = __reduce_max_sync(~0u, ((uint32_t*)sm)[lane & 7]);
        if (tid == 0) g_wmax[b] = __uint_as_float(mx << 16);
    }
}
__device__ __forceinline__ void setup_b(const int b, const bf16* __restrict__ mem0) {
    const int tid = threadIdx.x;
    uint4* z = (uint4*)red_base();
    if (b < 3) {
        const int w = tid >> 5, lane = tid & 31, p = b * 2 + ((w >> 1) & 1), odd = w & 1;
        uint32_t mx = 0;
#pragma unroll 4
        for (int i = lane; i < 640; i += 32) {
            const uint4 u = ((const uint4*)mem0)[i];
            mx = __vmaxu2(__vmaxu2(mx, u.x & 0x7fff7fffu), __vmaxu2(__vmaxu2(u.y & 0x7fff7fffu, u.z & 0x7fff7fffu), u.w & 0x7fff7fffu));
        }
        float inv, v[7];
        const float sc = pow2_scale(__uint_as_float(__reduce_max_sync(~0u, max(mx & 0xffffu, mx >> 16)) << 16), 14, &inv);
        if (tid == 0) g_invM0 = inv;
#pragma unroll
        for (int j = 0; j < 7; j++) {
            const int r = p * 56 + (j < 6 ? odd * 32 + (j >> 1) * 8 : 24) + (lane >> 2), mr = 2 * (lane & 3) + (j < 6 ? (j & 1) : odd);
            v[j] = r < 320 ? __bfloat162float(mem0[mr * 640 + (w >> 2) * 320 + r]) * sc : 0.f;
        }
        const int off = w * 2048 + (lane >> 4) * 1024 + ((lane >> 3) & 1) * 256 + (lane & 7) * 16 + (b == 2 ? (w >> 1) * 4096 + 128 : b * 16384);
        const uint4 u = make_uint4(pack_h(v[0], v[1]), pack_h(v[2], v[3]), pack_h(v[4], v[5]), pack_h(v[6], 32.f));
        z[off >> 4] = u; z[65536 + (off >> 4)] = u;
    }
}

#define SU_PAD 40960
constexpr int SU_SMEM = SU_PAD;
__global__ void __launch_bounds__(256, 4) k_setup(const bf16* __restrict__ wr, const bf16* __restrict__ wi, const bf16* __restrict__ mem0) {
    extern __shared__ __align__(1024) char sm[];
    TL(0);
    if (blockIdx.x >= 128) setup_b(blockIdx.x - 128, mem0);
    else setup_a(sm, blockIdx.x, wr, wi);
    __syncthreads();
    if (threadIdx.x == 0) red_release(g_ready);
    TL(1);
}
__device__ __forceinline__ float weight_scale(int h, int ty, float* inv) { return pow2_scale(__ldcg(g_wmx + h * 3 + ty), 6, inv); }

#define STR_(x) #x
#define STR(x) STR_(x)
#define RF_U 1
constexpr int RF_A = 22 * 2816, RF_X = RF_A + 22 * 1024, RF_BAR = RF_X + 64 * 1344, RF_SMEM = RF_BAR + 64;
__global__ void __cluster_dims__(2, 1, 1) __launch_bounds__(256, 2)
k_rowf(const bf16* x, const int first, const bf16* Wq, const bf16* Wk, const bf16* Wv, const bf16* Wo) {
    extern __shared__ __align__(1024) char sm[];
    TL(first ? 2 : 16);
    const int tid = threadIdx.x, w = tid >> 5, lane = tid & 31, g = lane >> 2, t = lane & 3;
    if (blockIdx.x >= 128) { __nanosleep(2500); return; }
    const int a = blockIdx.x >> 2, gq = blockIdx.x & 3;
    const uint32_t sb = smem_u32(sm), mb = sb + RF_BAR + w * 8;
    if (lane == 0) {
        mbar_init(mb, 1);
        asm volatile("fence.mbarrier_init.release.cluster;" ::: "memory");
        mbar_expect(mb, 8 * 1280);
    }
    __syncwarp();
    asm volatile("barrier.cluster.arrive.relaxed.aligned;" ::: "memory");
#pragma unroll 1
    for (int ph = 0; ph < 2; ph++) {
        if (ph != first) {
            asm volatile("barrier.cluster.wait.aligned;" ::: "memory");
            pdl_wait();
            TL(first ? 3 : 17);
            if (lane < 4)
                asm volatile("cp.async.bulk.shared::cluster.global.mbarrier::complete_tx::bytes.multicast::cluster [%0],[%1],1280,[%2],%3;"
                             ::"r"(sb + RF_X + (w * 8 + (gq & 1) * 4 + lane) * 1344), "l"(x + (size_t)(a * 64 + w * 8 + (gq & 1) * 4 + lane) * 640), "r"(mb),
                             "h"((unsigned short)3) : "memory");
            __syncwarp();
            pdl_go();
        } else {
#pragma unroll 3
            for (int id = tid; id < 22 * 176; id += 256) {
                const int kg = id / 176, n = id - kg * 176;
                const float c = (float)(2 * n + (gq & 1));
                *(uint4*)(sm + id * 16) = cos_row8(fmaf((float)(kg * 8), c, (float)((gq & 2) * 80)), c, 0.03952847075210474f);
            }
        }
    }
    mbar_wait(mb, 0);
    const uint32_t row = sb + RF_X + (w * 8 + g) * 1344;
    float st[4][4] = {};
#pragma unroll 1
    for (int i = 0; i < 20; i += 4) {
        uint32_t u[4][4];
#pragma unroll
        for (int q = 0; q < 4; q++) lds128(u[q], row + (4 * (i + q) + t) * 16);
#pragma unroll
        for (int q = 0; q < 4; q++) {
            mma_bf(st[(q & 1) * 2], u[q][0], 0x3f803f80u, u[q][1], 0x3f803f80u, u[q][0], u[q][1]);
            mma_bf(st[(q & 1) * 2 + 1], u[q][2], 0x3f803f80u, u[q][3], 0x3f803f80u, u[q][2], u[q][3]);
        }
    }
#pragma unroll
    for (int q = 0; q < 4; q++) { st[0][q] += st[2][q]; st[1][q] += st[3][q]; }
    const float sq = __shfl_sync(~0u, (g & 1) ? st[0][1] + st[1][1] : st[0][0] + st[1][0], g * 4 + (g >> 1));
    const float mean = __shfl_sync(~0u, (g & 1) ? st[0][3] + st[1][3] : st[0][2] + st[1][2], g * 4 + (g >> 1)) * (1.f / 640.f);
    const float r = rsqrtf(fmaxf(fmaf(-mean, mean, sq * (1.f / 640.f)), 0.f) + 1e-5f), off = gq == 0 ? -4.f * mean * r : 0.f;
    const float r1 = (gq == 1 || gq == 2) ? -r : r, r2 = (gq & 1) ? -r : r, r3 = gq >= 2 ? -r : r;
    const uint32_t aa = sb + RF_A + w * 128 + g * 16;
    auto el = [&](int d) { unsigned short v; asm volatile("ld.shared.u16 %0,[%1];" : "=h"(v) : "r"(row + d * 2)); return __uint_as_float((uint32_t)v << 16); };
_Pragma(STR(unroll RF_U))
    for (int i = 0; i < 5; i++) {
        const int ch = t + 4 * i;
        uint32_t u[4][4];
        lds128(u[0], row + ch * 16); lds128(u[1], row + (39 - ch) * 16); lds128(u[2], row + (40 + ch) * 16); lds128(u[3], row + (79 - ch) * 16);
        const float nb0 = el(320 - 8 * ch), nb1 = el(ch ? 640 - 8 * ch : 0);
        float o[8];
#pragma unroll
        for (int q = 0; q < 8; q++) {
            const int m = (8 - q) >> 1;
            const float e0 = (q & 1) ? bf_hi(u[0][q >> 1]) : bf_lo(u[0][q >> 1]), e2 = (q & 1) ? bf_hi(u[2][q >> 1]) : bf_lo(u[2][q >> 1]);
            const float e1 = q == 0 ? nb0 : (q & 1) ? bf_hi(u[1][m & 3]) : bf_lo(u[1][m & 3]), e3 = q == 0 ? nb1 : (q & 1) ? bf_hi(u[3][m & 3]) : bf_lo(u[3][m & 3]);
            o[q] = fmaf(e3, r3, fmaf(e2, r2, fmaf(e1, r1, fmaf(e0, r, off))));
        }
        if (ch == 0) o[0] *= 0.5f;
        sts128(aa + ch * 1024, pack_h(o[0], o[1]), pack_h(o[2], o[3]), pack_h(o[4], o[5]), pack_h(o[6], o[7]));
    }
    if (t < 2) sts128(aa + (20 + t) * 1024, t == 0 ? pack_h(fmaf(el(480), r2, fmaf(el(160), r, 0.5f * off)), 0.f) : 0u, 0u, 0u, 0u);
    fence_async_smem();
    __syncthreads();
    const int wg = w >> 2;
    float acc[44];
    uint64_t da = mkdesc(sb + RF_A, 1024, 128, 0), db = mkdesc(sb + wg * 1408, 2816, 128, 0);
    wg_fence();
#pragma unroll 1
    for (int k = 0; k < 11; k++) { wg_n88_ss(acc, da, db, k); da += 128; db += 352; }
    wg_commit(); wg_wait<0>();
    const uint32_t stg = sb + RF_X + wg * 96 * 144;
#pragma unroll
    for (int j = 0; j < 12; j += 2) {
        const int m = lane >> 3, j1 = j < 10 ? j + 1 : j;
        stsm4t(stg + ((j + (m >> 1)) * 8 + (lane & 7)) * 144 + ((w & 3) * 16 + (m & 1) * 8) * 2, pack_h(acc[j * 4], acc[j * 4 + 1]),
               pack_h(acc[j * 4 + 2], acc[j * 4 + 3]), pack_h(acc[j1 * 4], acc[j1 * 4 + 1]), pack_h(acc[j1 * 4 + 2], acc[j1 * 4 + 3]));
    }
    bar_sync(1 + wg, 128);
#pragma unroll 3
    for (int rr = (tid & 127) >> 3; rr < 88; rr += 16) {
        const int ch = tid & 7, c = 2 * (wg * 88 + rr) + (gq & 1);
        if (c <= 320 - (gq >> 1) && (c | (gq ^ 2))) {
            uint32_t u[4];
            lds128(u, stg + rr * 144 + ch * 16);
            ((uint4*)g_UT)[((size_t)(c == 320 ? 1 : 2 * c + (gq >> 1)) * 32 + a) * 8 + (ch ^ (a & 7))] = make_uint4(u[0], u[1], u[2], u[3]);
        }
    }
    TL(first ? 4 : 18);
}

constexpr int GST = 4, GSTB = 32768 + 20480, GNC = 32;
constexpr int G_BAR = GST * GSTB + 3072;
#define GPACE 1100
#define GPACE2 650
__device__ __forceinline__ void oproj_load(const uint32_t sb, const int op, const int mb, const int nb, const int c0, const uint32_t pace) {
    const int by = op == 2 ? 20480 : 16384;
    const char* src = op == 2 ? (const char*)g_wot + (size_t)nb * GNC * 20480 : (const char*)g_O + (size_t)(2 * mb + op) * GNC * 16384;
    uint32_t t0 = clock32() - pace + op * (pace / 3);
#pragma unroll 1
    for (int c = c0; c < c0 + GNC; c++, src += by) {
        const int st = c % GST;
        if (c >= GST) mbar_wait(sb + G_BAR + (GST + st) * 8, ((c / GST) - 1) & 1);
        while (clock32() - t0 < pace) {}
        t0 = clock32();
        const int by_ = by;
        mbar_expect(sb + G_BAR + st * 8, by_);
        if (op == 2) bulk_g2s(sb + st * GSTB + 32768, src, by_, sb + G_BAR + st * 8);
        else bulk_g2s_last(sb + st * GSTB + op * 16384, src, by_, sb + G_BAR + st * 8);
    }
}
__device__ __forceinline__ void oproj_mma(const uint32_t sb, const int mb, const int nb, const int c0, const bf16* res, bf16* out) {
    const int w = threadIdx.x >> 5, lane = threadIdx.x & 31, wg = w >> 2;
    float acc[40];
    uint4 rv[5];
#pragma unroll 1
    for (int c = c0; c < c0 + GNC; c++) {
        const int st = c % GST;
        mbar_wait(sb + G_BAR + st * 8, (c / GST) & 1);
        const uint32_t d = sb + st * GSTB;
        wg_fence();
#pragma unroll
        for (int k = 0; k < 8; k++)
            wg_n80_ss(acc, mkdesc(d + wg * 16384 + k * 2048, 1024, 128, 0), mkdesc(d + 32768 + k * 2560, 1280, 128, 0), (c - c0) | k);
        wg_commit();
        if (c > c0) {
            wg_wait<1>();
            if (lane == 0) mbar_arrive(sb + G_BAR + (GST + (c - 1) % GST) * 8);
        }
    }
#pragma unroll
    for (int i = 0; i < 5; i++) {
        const int id = i * 32 + lane, r = id / 10;
        rv[i] = __ldcg((const uint4*)res + (size_t)(mb * 128 + w * 16 + r) * 80 + nb * 10 + id - r * 10);
    }
    wg_wait<0>();
    bar_sync(5, 256);
    const uint32_t stg = sb + (GST - 1) * GSTB + w * 16 * 176;
#pragma unroll
    for (int j = 0; j < 5; j++)
        stsm4(stg + (lane & 15) * 176 + (2 * j + (lane >> 4)) * 16, pack_bf(acc[j * 8], acc[j * 8 + 1]), pack_bf(acc[j * 8 + 2], acc[j * 8 + 3]),
              pack_bf(acc[j * 8 + 4], acc[j * 8 + 5]), pack_bf(acc[j * 8 + 6], acc[j * 8 + 7]));
    __syncwarp();
#pragma unroll
    for (int i = 0; i < 5; i++) {
        const int id = i * 32 + lane, r = id / 10, ch = id - r * 10;
        uint32_t y[4];
        lds128(y, stg + r * 176 + ch * 16);
        ((uint4*)out)[(size_t)(mb * 128 + w * 16 + r) * 80 + nb * 10 + ch] = add_bf8(rv[i], y);
    }
    fence_async_smem();
    __syncwarp();
    if (lane == 0) mbar_arrive(sb + G_BAR + (2 * GST - 1) * 8);
}

__global__ void __launch_bounds__(128, 4) k_col(const int first, const bf16* Wq, const bf16* Wk, const bf16* Wv, const bf16* Wo) {
    __shared__ __align__(1024) char sz[8192];
    __shared__ __align__(1024) char stab[24576];
    __shared__ __align__(1024) char swf[8192];
    __shared__ __align__(8) uint64_t bar[2];
    const int tid = threadIdx.x, wl = tid >> 5, lane = tid & 31, g = lane >> 2, t = lane & 3;
    const int c = blockIdx.x;
    TL(first ? 5 : 19);
    const bool realc = c == 0 || c == 320;
    const uint32_t z = smem_u32(sz), b2 = smem_u32(stab), a1 = b2 + 16384, wf = smem_u32(swf), mb = smem_u32(bar);
    if (tid == 0) { mbar_init(mb, 1); mbar_init(mb + 8, 1); fence_async_smem(); }
    if (realc) {
        for (int i = tid; i < 256; i += 128) sts128(z + 4096 + i * 16, 0, 0, 0, 0);
        fence_async_smem();
    }
    const int k1 = wl * 8 + g;
    float tc[16], ts[16];
#pragma unroll
    for (int j = 0; j < 16; j++) {
        const int p = ((j >> 1) * 8 + 2 * t + (j & 1)) * k1;
        __sincosf((float)(p - 1024) * 0.003067961575771282f, &ts[j], &tc[j]);
        ts[j] = -ts[j]; tc[j] = -tc[j];
    }
    if (first && tid == 32) { wait_flag<400>(g_ready, NSETUP); fence_async_glb(); }
    __syncthreads();
    if (tid == 32) {
        mbar_expect(mb + 8, 24576 + 8192);
        bulk_g2s(b2, g_ctab, 24576, mb + 8);
        bulk_g2s(wf, g_Wf + (size_t)c * 2048, 8192, mb + 8);
    }
    float inv;
    const float wsc = pow2_scale(wfilter_max(lane), 0, &inv) * (realc ? 0.0625f : 0.125f);
    pdl_wait();
    TL(first ? 6 : 20);
    if (tid == 0) {
        const int by = realc ? 4096 : 8192;
        mbar_expect(mb, by);
        bulk_g2s_last(z, (const char*)g_UT + (size_t)(c == 320 ? 1 : 2 * c) * 4096, by, mb);
    }
    pdl_go();
    mbar_wait(mb + 8, 0);
    mbar_wait(mb, 0);
    float d[64];
    uint32_t a[4][4];
    wg_fence();
#pragma unroll
    for (int ks = 0; ks < 4; ks++) wg_n64_ss_tb<0>(d, mkdesc(a1 + ks * 2048, 1024, 128, 0), mkdesc(z + ks * 2048, 1024, 1024, 1), ks);
    wg_commit(); wg_wait<0>();
    const float r32 = 0.17677669529663687f;
#pragma unroll
    for (int j = 0; j < 8; j++) {
        float yr[2], yi[2];
#pragma unroll
        for (int e = 0; e < 2; e++) {
            const float re = d[j * 4 + e] * r32, im = d[j * 4 + 2 + e] * r32, cc = tc[j * 2 + e], ss = ts[j * 2 + e];
            yr[e] = re * cc + im * ss; yi[e] = im * cc - re * ss;
        }
        a[j >> 1][(j & 1) * 2] = pack_h(yr[0], yr[1]); a[j >> 1][(j & 1) * 2 + 1] = pack_h(yi[0], yi[1]);
    }
    wg_fence();
#pragma unroll
    for (int ks = 0; ks < 4; ks++) wg_n128_rs(d, a[ks], mkdesc(b2 + ks * 4096, 2048, 128, 0), ks);
    wg_commit(); wg_wait<0>();
#pragma unroll
    for (int q = 0; q < 4; q++) {
        uint32_t wv[4];
        lds128(wv, wf + tid * 64 + ((q ^ (tid >> 1)) & 3) * 16);
#pragma unroll
        for (int jj = 0; jj < 2; jj++) {
            const int j = 2 * q + jj;
            float yr[2], yi[2];
#pragma unroll
            for (int e = 0; e < 2; e++) {
                const float xr = d[j * 4 + e] + d[32 + j * 4 + 2 + e], xi = d[j * 4 + 2 + e] - d[32 + j * 4 + e];
                const float fr = bf_lo(wv[jj * 2 + e]) * wsc, fi = bf_hi(wv[jj * 2 + e]) * wsc;
                yr[e] = xr * fr - xi * fi; yi[e] = xr * fi + xi * fr;
            }
            a[q][jj * 2] = pack_h(yr[0], yr[1]); a[q][jj * 2 + 1] = pack_h(yi[0], yi[1]);
        }
    }
    wg_fence();
#pragma unroll
    for (int ks = 0; ks < 4; ks++) wg_n128_rs(d, a[ks], mkdesc(b2 + ks * 4096, 2048, 128, 0), ks);
    wg_commit(); wg_wait<0>();
#pragma unroll
    for (int j = 0; j < 8; j++) {
        float yr[2], yi[2];
#pragma unroll
        for (int e = 0; e < 2; e++) {
            const float vr = (d[j * 4 + e] - d[32 + j * 4 + 2 + e]) * 0.125f, vi = (d[j * 4 + 2 + e] + d[32 + j * 4 + e]) * 0.125f;
            const float cc = tc[j * 2 + e], ss = ts[j * 2 + e];
            yr[e] = vr * cc - vi * ss; yi[e] = vi * cc + vr * ss;
        }
        a[j >> 1][(j & 1) * 2] = pack_h(yr[0], yr[1]); a[j >> 1][(j & 1) * 2 + 1] = pack_h(yi[0], yi[1]);
    }
    __syncthreads();
    const int mm = lane >> 3, rr = lane & 7;
    const uint32_t rowo = (wl * 16 + (mm & 1) * 8 + rr) * 128;
#pragma unroll
    for (int q = 0; q < 4; q++) stsm4(z + rowo + (((2 * q + (mm >> 1)) ^ rr) << 4), a[q][0], a[q][1], a[q][2], a[q][3]);
    fence_async_smem();
    __syncthreads();
    wg_fence();
#pragma unroll
    for (int ks = 0; ks < 4; ks++) wg_n64_ss_tb<1>(d, mkdesc(a1 + ks * 256, 128, 1024, 0), mkdesc(z + ks * 2048, 1024, 1024, 1), ks);
    wg_commit(); wg_wait<0>();
#pragma unroll
    for (int q = 0; q < 4; q++)
        stsm4(wf + rowo + (((2 * q + (mm >> 1)) ^ rr) << 4), pack_h(d[q * 8] * r32, d[q * 8 + 1] * r32), pack_h(d[q * 8 + 2] * r32, d[q * 8 + 3] * r32),
              pack_h(d[q * 8 + 4] * r32, d[q * 8 + 5] * r32), pack_h(d[q * 8 + 6] * r32, d[q * 8 + 7] * r32));
    __syncwarp();
    if (!(realc && wl >= 2)) {
        const int kk = c == 320 ? 320 : (c & 1) * 160 + (c >> 1) + (wl >> 1) * 320;
#pragma unroll
        for (int i = 0; i < 4; i++) {
            const int r = wl * 16 + i * 4 + (lane >> 3), ch = lane & 7;
            uint32_t v[4];
            lds128(v, wf + r * 128 + ((ch ^ (r & 7)) << 4));
            ((uint4*)g_YT)[((size_t)(r & 31) * 640 + kk) * 8 + (ch ^ (kk & 7))] = make_uint4(v[0], v[1], v[2], v[3]);
        }
    }
    __syncthreads();
    if (tid == 0) red_release(g_flag + F_X + (first ? 0 : 128) + 65);
    TL(first ? 7 : 21);
}

constexpr int O_XS = 0;
constexpr int O_MS = 81920;
constexpr int O_QKP = O_MS + 10752;
constexpr int O_VM = O_QKP + 4096;
constexpr int O_SC = O_VM + 4096;
constexpr int O_OS = O_SC + 1536;
constexpr int O_XCH = O_OS + 2048;
constexpr int O_SUM = O_XCH + 8192;
constexpr int O_MX = O_SUM + 256;
constexpr int O_STG = O_MS + 65536 - 8192;
static_assert(O_STG - 16384 >= O_MX + 1024, "shared-memory map");
constexpr int O_WO = O_STG + 16384;
constexpr int O_SCL = O_WO + 65536;
constexpr int O_BAR = O_SCL + 64;
constexpr int B_XF = O_BAR, B_S = O_BAR + 16, B_GO = O_BAR + 24, B_VX = O_BAR + 32, B_STG = O_BAR + 48, B_FREE = O_BAR + 72;
constexpr int T_FA = O_BAR + 96, T_EA = T_FA + 32, T_FB = T_EA + 32, T_EB = T_FB + 56, T_RED = T_EB + 32;
constexpr int O_WMX = O_BAR + 512, B_W = O_BAR + 64;
constexpr int O_LAST = (O_WMX + 192 + 1023) / 1024 * 1024;
constexpr int CH_SMEM = O_LAST + 8192;
static_assert(O_WO == 19 * 8192, "weight staging");
__device__ __forceinline__ uint32_t tail_b(int c) { return c % 7 < 4 ? O_XS + (c % 7) * 20480 : O_WO + (c % 7 - 4) * 20480; }
constexpr int S_TX = 2 * 768 + 2048;
#define NOSELF 1
__device__ __forceinline__ int s_tx(int c) { return !NOSELF ? S_TX : c == 2 ? 2 * 768 : 768 + 2048; }

#define NPERM 1
#define NWO0 1
#define NWO0B 4
#define NWO1 6
#define XEARLY 0
#define RELAX 1
#define VEARLY 0
#define VLATE 0
#define SGATE 0
#define KVB 1
#define REL1 0
#define XLATE 0
#define TDELAY 800
#define WDEPTH 6
#define RDELAY 580

#define STAMP(i)

#define NTA 23
#define NTB 26
template <int LO, int HI>
__device__ __forceinline__ void tok_issue(const uint32_t (&A0)[20][4], const uint32_t (&A1)[20][4], float (&b0)[16], float (&b1)[16], uint32_t xd,
                                          const uint32_t zero) {
    if (LO == 0) wg_fence();
    sfor<HI - LO>([&](auto I) {
        constexpr int i = LO + I;
        if constexpr (i < 20) wg_n32_x<i * 64, i>(b0, A0[i], xd); else wg_n32_x<(i - 20) * 64, i - 20>(b1, A1[i - 20], xd + zero);
        if constexpr (i == 19 || i == NTB - 1 || i == 39) wg_commit();
    });
}
__device__ __forceinline__ void tok_give(const float (&b0)[16], const uint32_t L16, const uint32_t xch0) {
    wg_wait<1>();
    sfor<2>([&](auto I) {
        constexpr int i = I;
        sts128_u<i * 512>(L16, xch0, pack_h(b0[8 * i], b0[8 * i + 1]), pack_h(b0[8 * i + 2], b0[8 * i + 3]), pack_h(b0[8 * i + 4], b0[8 * i + 5]),
                          pack_h(b0[8 * i + 6], b0[8 * i + 7]));
    });
}
__device__ __forceinline__ void tok_finish(float (&b1)[16], const uint32_t (&e)[2][4], const uint32_t L16, const uint32_t dst, const uint32_t idn) {
#pragma unroll
    for (int j = 0; j < 4; j++)
        asm volatile("mma.sync.aligned.m16n8k8.row.col.f32.f16.f16.f32 {%0,%1,%2,%3},{%4,%5},{%6},{%0,%1,%2,%3};"
                     : F4(b1, 4 * j) : "r"(e[j >> 1][(j & 1) * 2]), "r"(e[j >> 1][(j & 1) * 2 + 1]), "r"(idn));
    stsm4_u<0>(L16, dst, pack_bf(b1[0], b1[1]), pack_bf(b1[2], b1[3]), pack_bf(b1[4], b1[5]), pack_bf(b1[6], b1[7]));
    stsm4_u<512>(L16, dst, pack_bf(b1[8], b1[9]), pack_bf(b1[10], b1[11]), pack_bf(b1[12], b1[13]), pack_bf(b1[14], b1[15]));
}
__device__ __forceinline__ uint32_t uni(uint32_t v) { return __shfl_sync(~0u, v, 0); }
__device__ __forceinline__ uint32_t badd(uint32_t a, uint32_t b) { uint32_t r; asm("add.rn.bf16x2 %0,%1,%2;" : "=r"(r) : "r"(a), "r"(b)); return r; }
__device__ __forceinline__ uint32_t bmax(uint32_t a, uint32_t b) { uint32_t r; asm("max.bf16x2 %0,%1,%2;" : "=r"(r) : "r"(a), "r"(b)); return r; }
__device__ __forceinline__ uint32_t babsmax(uint32_t a, uint32_t b) { uint32_t r; asm("max.xorsign.abs.bf16x2 %0,%1,%2;" : "=r"(r) : "r"(a), "r"(b)); return r; }
__device__ __forceinline__ uint32_t habsmax(uint32_t a, uint32_t b) { uint32_t r; asm("max.xorsign.abs.f16x2 %0,%1,%2;" : "=r"(r) : "r"(a), "r"(b)); return r; }

template <int NPF>
__device__ __forceinline__ float mem_out(const uint32_t sb, const uint32_t L16, const uint32_t L8, uint32_t (&wo)[16][4], const uint32_t woa,
                                         char* dst, const bool odd) {
    bar_sync(2, 352);
    float a[4][4];
#pragma unroll
    for (int i = 0; i < 4; i++) a[i][0] = a[i][1] = a[i][2] = a[i][3] = 0.f;
    uint32_t ob[4][4], sm_[2], sc[2];
    sfor<8>([&](auto I) {
        constexpr int i = I;
        if constexpr (!(i & 1)) ldsm4t_u<O_OS + (i >> 1) * 512>(ob[i >> 1], L16, sb);
        if constexpr (i >= NPF) { ldsm4t(wo[i], woa + i * 1024); ldsm4t(wo[8 + i], (woa ^ 32) + i * 1024); }
    });
    lds64_u<O_SUM>(sm_, L8 & 24, sb); lds64(sc, sb + O_SCL);
#pragma unroll
    for (int i = 0; i < 8; i++) {
        mma_bf(a[i & 1], wo[i][0], wo[i][1], wo[i][2], wo[i][3], ob[i >> 1][(i & 1) * 2], ob[i >> 1][(i & 1) * 2 + 1]);
        mma_bf(a[2 + (i & 1)], wo[8 + i][0], wo[8 + i][1], wo[8 + i][2], wo[8 + i][3], ob[i >> 1][(i & 1) * 2], ob[i >> 1][(i & 1) * 2 + 1]);
    }
    const float f0 = rcp(__uint_as_float(sm_[0])) * __uint_as_float(sc[0]), f1 = rcp(__uint_as_float(sm_[1])) * __uint_as_float(sc[0]);
    red_h8(dst, pack_h((a[0][0] + a[1][0]) * f0, (a[0][1] + a[1][1]) * f1), pack_h((a[0][2] + a[1][2]) * f0, (a[0][3] + a[1][3]) * f1),
           pack_h((a[2][0] + a[3][0]) * f0, (a[2][1] + a[3][1]) * f1), pack_h(odd ? (a[2][3] + a[3][3]) * f1 : (a[2][2] + a[3][2]) * f0, 1.f));
    return __uint_as_float(sc[1]);
}

__device__ __forceinline__ void chain_mma(const uint32_t sb, const int c, const int h, const int layer, const uint32_t zero, const bf16* __restrict__ Wq,
                                          const bf16* __restrict__ Wk, const bf16* __restrict__ Wv, const bf16* __restrict__ Wo,
                                          const bf16* res, bf16* out) {
    int tid = read_tid(), lane = tid & 31;
    const int w = __shfl_sync(~0u, tid >> 5, 0), wg = w >> 2;
    [[maybe_unused]] const int cta = h * 3 + c;
    uint32_t A0[20][4], A1[20][4];
    const int t0 = (w & 3) + wg * 4, t1 = t0 ^ 4;
    float sl;
    {
        const int tl = tid & 127, r = tl >> 3, ch = tl & 7;
        const size_t so = (size_t)(wg * 320 + r) * 4096 + h * 128 + ch * 8;
        const bf16 *wa = (c == 2 ? Wv : Wq + c * 64) + so, *wb = (c == 2 ? Wv + 64 : Wk + c * 64) + so;
        const uint32_t ring = sb + wg * 4096;
        const uint32_t dst = ring + r * 128 + ((ch ^ r) & 7) * 16;
        const uint32_t src = ring + ((lane & 7) + (lane >> 4) * 8) * 128 + ((((w & 3) * 2 + ((lane >> 3) & 1)) ^ lane) & 7) * 16;
        const int q4 = lane & 3, gr = (c * 2 + ((w >> 1) & 1)) * 56 + (q4 == 3 ? 24 : (w & 1) * 32 + q4 * 8);
        const bf16* wo_ = Wo + (size_t)(h * 128 + (lane >> 2)) * 640 + wg * 320 + min(gr, 312);
        const uint32_t wdst = sb + O_WO + w * 8192 + (lane >> 2) * 64 + ((q4 ^ (lane >> 3)) & 3) * 16;
        auto issue = [&](int i) {
            if (i < 20) {
                const uint32_t d = dst + (i < 19 ? i * 8192 : O_LAST);
                cp_async16(d, wa + (size_t)i * 65536); cp_async16(d + 2048, wb + (size_t)i * 65536);
                if (i < 16) cp_async16(wdst + i * 512, wo_ + i * 5120, gr < 320 ? 16 : 0);
            }
            cp_commit();
        };
#pragma unroll 1
        for (int i = 0; i < WDEPTH; i++) issue(i);
        asm volatile("barrier.cluster.arrive.relaxed.aligned;" ::: "memory");
        float fa, fb;
        if (layer == 0) {
            uint32_t ma = 0, mb = 0;
#pragma unroll 1
            for (int i = 0; i < 20; i++) {
                issue(i + WDEPTH);
                cp_wait<WDEPTH>();
                const uint32_t d = dst + (i < 19 ? i * 8192 : O_LAST);
                uint32_t u[8];
                lds128(u, d); lds128(u + 4, d + 2048);
                ma = babsmax(babsmax(ma, babsmax(u[0], u[1])), babsmax(u[2], u[3])); mb = babsmax(babsmax(mb, babsmax(u[4], u[5])), babsmax(u[6], u[7]));
            }
            ma = __reduce_max_sync(~0u, max(ma & 0x7fffu, (ma >> 16) & 0x7fffu)); mb = __reduce_max_sync(~0u, max(mb & 0x7fffu, (mb >> 16) & 0x7fffu));
            asm volatile("barrier.cluster.wait.aligned;" ::: "memory");
            if (lane < 3)
                asm volatile("st.async.shared::cluster.mbarrier::complete_tx::bytes.v2.b32 [%0],{%1,%2},[%3];"
                             ::"r"(mapa(sb + O_WMX + (c * 8 + w) * 8, lane)), "r"(ma), "r"(mb), "r"(mapa(sb + B_W, lane)) : "memory");
            __syncwarp();
            {
                uint32_t off[4];
                float cs[4] = {0.f, 0.f, 0.f, 0.f};
#pragma unroll
                for (int q = 0; q < 4; q++) {
                    const int g_ = (c * 2 + ((w >> 1) & 1)) * 56 + (q == 3 ? 24 : (w & 1) * 32 + q * 8), col = wg * 320 + g_, nb = col / 80;
                    off[q] = g_ < 320 && !(q == 3 && (w & 1)) ? ((nb * 512 + h * 16) * 10 + (col - nb * 80) / 8) * 32 + lane : ~0u;
                }
                const uint32_t ta = sb + O_WO + w * 8192 + (lane & 7) * 64 + (((lane >> 3) ^ (lane >> 1)) & 3) * 16;
#pragma unroll 2
                for (int i = 0; i < 16; i++) {
                    uint32_t r[4];
                    ldsm4t(r, ta + i * 512);
#pragma unroll
                    for (int q = 0; q < 4; q++) {
                        if (off[q] != ~0u) ((uint32_t*)g_wot)[off[q] + i * 320] = r[q];
                        cs[q] += fabsf(bf_lo(r[q])) + fabsf(bf_hi(r[q]));
                    }
                }
                float cm = 0.f;
#pragma unroll
                for (int q = 0; q < 4; q++) {
                    cs[q] += __shfl_xor_sync(~0u, cs[q], 1); cs[q] += __shfl_xor_sync(~0u, cs[q], 2);
                    cm = fmaxf(cm, cs[q]);
                }
                const uint32_t n1 = __reduce_max_sync(~0u, __float_as_uint(cm));
                if (lane == 0) g_co[h * 32 + c * 8 + w] = __uint_as_float(n1);
            }
            mbar_wait(sb + B_W, 0);
            uint32_t v[2];
            lds64(v, sb + O_WMX + (lane < 24 ? lane : 0) * 8);
            const bool mine = (lane >> 3) < 3 && ((lane >> 4) == 1) == (c == 2);
            ma = __reduce_max_sync(~0u, mine ? v[0] : 0u); mb = __reduce_max_sync(~0u, mine ? v[1] : 0u);
            if (c == 2) ma = mb = max(ma, mb);
            fa = __uint_as_float(ma << 16); fb = __uint_as_float(mb << 16);
            if (tid == 0) {
                if (c != 1) g_wmx[h * 3 + c] = fa;
                if (c == 0) g_wmx[h * 3 + 1] = fb;
            }
        } else {
            fa = __ldcg(g_wmx + h * 3 + (c == 2 ? 2 : 0)); fb = __ldcg(g_wmx + h * 3 + (c == 2 ? 2 : 1));
            asm volatile("barrier.cluster.wait.aligned;" ::: "memory");
        }
        if (layer == TLL) TL(49);
        float ia, ib;
        const float sa = pow2_scale(fa, 6, &ia), sc_b = pow2_scale(fb, 6, &ib);
        sl = __uint_as_float(uni(__float_as_uint(ia * ib * (0.08838834764831845f * 1.4426950408889634f))));
        const uint32_t pa = pack_bf(sa, sa), pb = pack_bf(sc_b, sc_b);
        const int ahead = layer == 0 ? 20 : WDEPTH;
        auto convert = [&](int lo) {
#pragma unroll 1
            for (int i = lo; i < lo + 10; i++) {
                issue(i + ahead);
                cp_wait<WDEPTH>();
                const uint32_t d = dst + (i < 19 ? i * 8192 : O_LAST);
                uint32_t u[8];
                lds128(u, d); lds128(u + 4, d + 2048);
#pragma unroll
                for (int q = 0; q < 8; q++)
                    asm("{.reg .b32 m,l,u; mul.rn.bf16x2 m,%0,%1; shl.b32 l,m,16; and.b32 u,m,0xffff0000; cvt.rn.f16x2.f32 %0,u,l;}" : "+r"(u[q]) : "r"(q < 4 ? pa : pb));
                sts128(d, u[0], u[1], u[2], u[3]); sts128(d + 2048, u[4], u[5], u[6], u[7]);
            }
            bar_sync(6 + wg, 128);
        };
        const uint32_t s0 = src + wg * 2048, s1 = src + 2048 - wg * 2048;
        convert(0);
#pragma unroll
        for (int i = 0; i < 10; i++) { ldsm4t(A0[i], s0 + i * 8192); ldsm4t(A1[i], s1 + i * 8192); }
        if (layer == TLL) TL(50);
        convert(10);
#pragma unroll
        for (int i = 10; i < 20; i++) { ldsm4t(A0[i], s0 + (i < 19 ? i * 8192 : O_LAST)); ldsm4t(A1[i], s1 + (i < 19 ? i * 8192 : O_LAST)); }
        if (layer == TLL) TL(53);
        bar_sync(9, 256);
        if (tid == 0) red_release(g_flag + F_W + layer * 128);
        bar_sync(4, 288);
        asm volatile("barrier.cluster.arrive.relaxed.aligned;" ::: "memory");
    }
    const uint32_t idn = (lane >> 3) == (lane & 3) ? ((lane & 4) ? 0x3c000000u : 0x3c00u) : 0u;
    float invM = g_invM0;
    char* redp = red_base() + (size_t)layer * 32 * 32768 + w * 2048 + (lane >> 4) * 1024 + ((lane >> 3) & 1) * 256 + (lane & 7) * 16;
    const uint32_t ro2 = uni((w >> 1) * 4096 + 128), rown = uni(c == 2 ? ro2 : c * 16384);
    const uint32_t L16 = lane * 16, L8 = lane * 8, L4 = lane * 4;
    const uint32_t xch0 = uni(sb + O_XCH + t0 * 1024), xch1 = uni(sb + O_XCH + t1 * 1024);
    const uint32_t qo0 = uni(sb + O_QKP + (w & 3) * 1024 + (wg ? 768 : 0)), qp0 = uni(qo0 + (wg ? 128 : 256));
    const uint32_t qo1 = uni(sb + O_QKP + (w & 3) * 1024 + (wg ? 128 : 512)), qp1 = uni(qo1 + (wg ? 256 : 128));
    const uint32_t vo1 = uni(qo1 + (wg ? -128 : 256)), vp1 = uni(qp1 + (wg ? -128 : 256));
    const uint32_t msr = uni(sb + O_MS + wg * 5376);
    const uint32_t msw = uni(msr + ((w >> 1) & 1) * 896 + (w & 1) * 512), msh = uni(msr + ((w >> 1) & 1) * 896 + 384 + (w & 1) * 2);
    const uint32_t sco = uni(sb + O_SC + c * 768 + (w & 3) * 256);
    const uint32_t woa = sb + O_WO + w * 8192 + (lane >> 4) * 512 + (lane & 7) * 64 + (((lane >> 3) ^ (lane >> 1)) & 1) * 16 + ((lane >> 2) & 1) * 32;
    const uint32_t w512 = uni(sb + w * 512), w128 = uni(sb + w * 128);
#define PORD 0
    const uint32_t pd0 = uni(mapa(sb, c == 0 ? (PORD & 1 ? 1 : 2) : c == 1 ? (PORD & 1 ? 0 : 2) : (PORD & 2 ? 1 : 0)) - sb),
                   pd1 = uni(mapa(sb, c == 0 ? (PORD & 1 ? 2 : 1) : c == 1 ? (PORD & 1 ? 2 : 0) : (PORD & 2 ? 0 : 1)) - sb);
    const bool scw = c < 2 && w >= 4 && w <= 6;
    uint32_t sn = uni(sb + O_STG + (c == 2 ? 8192 : 0) + t1 * 1024);
    uint32_t ka = uni(sb + (w == 6 ? O_QKP + 512 : O_STG + 4096 + (w & 1) * 512));
    uint32_t vs = uni(sb + O_VM + t1 * 256);
    uint32_t va = uni(sb + O_STG + 8192 + w * 2048), vr = uni(sb + O_VM + w * 512);
    const uint32_t sn2 = uni(2 * sn - 16384), ka2 = uni(2 * ka - (w == 6 ? 0 : 16384)), vs2 = uni(2 * vs + 2048), va2 = uni(2 * va - 16384),
                   vr2 = uni(2 * vr + 2048);
    uint32_t xd = uni((uint32_t)mkdesc(sb + O_XS + wg * 20480, 512, 128, 0));
    const uint32_t xd2 = uni(2 * xd + 2560);

    uint32_t wp[2 * NPERM + 1][4];
    sfor<NPERM>([&](auto I) { constexpr int i = I; ldsm4t(wp[2 * i], woa + i * 1024); ldsm4t(wp[2 * i + 1], (woa ^ 32) + i * 1024); });
    auto wo_fetch = [&](uint32_t (&wo)[16][4], auto I) {
        constexpr int i = I;
        if constexpr (i < NPERM) {
#pragma unroll
            for (int q = 0; q < 4; q++) { wo[i][q] = wp[2 * i][q]; wo[8 + i][q] = wp[2 * i + 1][q]; }
        } else { ldsm4t(wo[i], woa + i * 1024); ldsm4t(wo[8 + i], (woa ^ 32) + i * 1024); }
    };
    if (layer == TLL) TL(32);
    float b0[16], b1[16];
    mbar_wait(sb + B_XF, 0);
    if (layer == TLL) TL(33);
    tok_issue<0, NTB>(A0, A1, b0, b1, xd, zero);
    tok_give(b0, L16, xch0);
    tok_issue<NTB, 40>(A0, A1, b0, b1, xd, zero);
    bar_sync(4, 256);
    wg_wait<0>();
    {
        uint32_t e[2][4];
        lds128_u<0>(e[0], L16, xch1); lds128_u<512>(e[1], L16, xch1);
        tok_finish(b1, e, L16, sn, idn);
    }
    sn = sn2 - sn; xd = xd2 - xd;
    bar_sync(5, 288);
    asm volatile("barrier.cluster.wait.aligned;" ::: "memory");
    if (layer == TLL) TL(34);
    mbar_wait(sb + B_XF + 8, 0);
    if (layer == TLL) TL(35);
    tok_issue<0, NTA>(A0, A1, b0, b1, xd, zero);
    uint32_t tr = clock32() - RDELAY;

#pragma unroll 1
    for (int st = 0;; st++) {
        uint4 mv[3];
        asm volatile("{.reg .pred p; .reg .b32 t;\n"
                     "mov.b32 %0,0; mov.b32 %1,0; mov.b32 %2,0; mov.b32 %3,0; mov.b32 %4,0; mov.b32 %5,0; mov.b32 %6,0; mov.b32 %7,0;\n"
                     "mov.b32 %8,0; mov.b32 %9,0; mov.b32 %10,0; mov.b32 %11,0;\n"
                     "T_LOOP: mov.u32 t,%%clock; sub.u32 t,t,%14; setp.ge.u32 p,t,%15;\n"
                     "@p ld.relaxed.gpu.global.v4.u32 {%0,%1,%2,%3},[%12]; @p ld.relaxed.gpu.global.v4.u32 {%4,%5,%6,%7},[%12+16384];\n"
                     "@p ld.relaxed.gpu.global.v4.u32 {%8,%9,%10,%11},[%13];\n"
                     "@!p bra T_LOOP;}"
                     : "=r"(mv[0].x), "=r"(mv[0].y), "=r"(mv[0].z), "=r"(mv[0].w), "=r"(mv[1].x), "=r"(mv[1].y), "=r"(mv[1].z), "=r"(mv[1].w),
                       "=r"(mv[2].x), "=r"(mv[2].y), "=r"(mv[2].z), "=r"(mv[2].w)
                     : "l"(redp), "l"(redp + ro2), "r"(tr), "n"(RDELAY) : "memory");
        STAMP(10);
        tok_issue<NTA, NTB>(A0, A1, b0, b1, xd, zero);
        tok_give(b0, L16, xch0);
        tok_issue<NTB, 40>(A0, A1, b0, b1, xd, zero);
        xd = xd2 - xd;
        STAMP(9);
        if (zero >> 30) break;
        asm volatile("{.reg .pred p; .reg .b32 a,h,t,n; .reg .b16 l,u; .reg .b64 q;\n"
                     "add.u32 a,%12,%13; add.u32 h,%12,%14; mov.u32 n,0;\n"
                     "M_LOOP:\n .pragma \"nounroll\";\n"
                     "st.shared.b32 [a],%0; st.shared.b32 [a+128],%1; st.shared.b32 [a+256],%2; mov.b32 {l,u},%3; st.shared.b16 [h],l;\n"
                     "st.shared.b32 [a+1792],%4; st.shared.b32 [a+1920],%5; st.shared.b32 [a+2048],%6; mov.b32 {l,u},%7; st.shared.b16 [h+1792],l;\n"
                     "st.shared.b32 [a+3584],%8; st.shared.b32 [a+3712],%9; st.shared.b32 [a+3840],%10; mov.b32 {l,u},%11; st.shared.b16 [h+3584],l;\n"
                     "lop3.b32 t,%3,%7,0x50000000,0x7e; lop3.b32 t,t,%11,0x50000000,0xf6; setp.gt.u32 p,t,0xffff;\n"
                     "vote.sync.any.pred p,p,-1; add.u32 n,n,1; setp.lt.and.u32 p,n,%17,p; @!p bra M_DONE;\n"
                     "ld.relaxed.gpu.global.v4.u32 {%0,%1,%2,%3},[%15]; ld.relaxed.gpu.global.v4.u32 {%4,%5,%6,%7},[%15+16384];\n"
                     "cvt.u64.u32 q,%16; add.u64 q,q,%15; ld.relaxed.gpu.global.v4.u32 {%8,%9,%10,%11},[q];\n"
                     "bra M_LOOP;\n"
                     "M_DONE:}"
                     : "+r"(mv[0].x), "+r"(mv[0].y), "+r"(mv[0].z), "+r"(mv[0].w), "+r"(mv[1].x), "+r"(mv[1].y), "+r"(mv[1].z), "+r"(mv[1].w),
                       "+r"(mv[2].x), "+r"(mv[2].y), "+r"(mv[2].z), "+r"(mv[2].w)
                     : "r"(L4), "r"(msw), "r"(msh), "l"(redp), "r"(ro2), "n"(SPIN_LIM) : "memory");
        bar_sync(3, 256);
        STAMP(0);
        uint32_t e[2][4];
        float f1[4];
        {
            uint32_t b[10][4];
            float acc[4][4];
#pragma unroll
            for (int i = 0; i < 4; i++) acc[i][0] = acc[i][1] = acc[i][2] = acc[i][3] = 0.f;
            auto ld = [&](auto I) { constexpr int i = I; ldsm4t_u<i * 512>(b[i], L16, msr); };
            auto mm = [&](auto I) {
                constexpr int i = I;
                mma_f16(acc[0], A0[2 * i], b[i][0], b[i][1]); mma_f16(acc[2], A1[2 * i], b[i][0], b[i][1]);
                mma_f16(acc[1], A0[2 * i + 1], b[i][2], b[i][3]); mma_f16(acc[3], A1[2 * i + 1], b[i][2], b[i][3]);
            };
            ld(IC<0>()); ld(IC<1>()); ld(IC<2>()); ld(IC<3>());
            sts32_u<O_MX>(L4, w128,
                          habsmax(habsmax(habsmax(habsmax(mv[0].x, mv[0].y), habsmax(mv[0].z, mv[1].x)), habsmax(habsmax(mv[1].y, mv[1].z), mv[2].x)),
                                  habsmax(habsmax(mv[2].y, mv[2].z), habsmax(habsmax(mv[0].w, mv[1].w), mv[2].w) & 0xffffu)));
            wg_wait<0>();
            ld(IC<4>()); mm(IC<0>()); ld(IC<5>()); mm(IC<1>()); ld(IC<6>()); mm(IC<2>());
            ld(IC<7>()); mm(IC<3>()); ld(IC<8>()); mm(IC<4>()); ld(IC<9>()); mm(IC<5>());
            lds128_u<0>(e[0], L16, xch1); lds128_u<512>(e[1], L16, xch1);
            mm(IC<6>()); mm(IC<7>()); mm(IC<8>()); mm(IC<9>());
            const uint32_t u0 = pack_bf((acc[0][0] + acc[1][0]) * invM, (acc[0][1] + acc[1][1]) * invM);
            const uint32_t u1 = pack_bf((acc[0][2] + acc[1][2]) * invM, (acc[0][3] + acc[1][3]) * invM);
#pragma unroll
            for (int i = 0; i < 4; i++) f1[i] = (acc[2][i] + acc[3][i]) * invM;
            sts32_u<0>(L4, qo0, u0); sts32_u<0>(L4, qp0, u1); sts32_u<0>(L4, qo1, pack_bf(f1[0], f1[1])); sts32_u<0>(L4, qp1, pack_bf(f1[2], f1[3]));
        }
        STAMP(1);
        bar_sync(1, 320);
        if (__builtin_expect(scw, 1)) {
            float a[4][4];
#pragma unroll
            for (int i = 0; i < 4; i++) a[i][0] = a[i][1] = a[i][2] = a[i][3] = 0.f;
            uint32_t q[4][4], k[4][4];
            sfor<4>([&](auto I) {
                constexpr int i = I;
                ldsm4t_u<O_QKP + i * 1024>(q[i], L16, sb); ldsm4t_u<i * 1024>(k[i], L16, ka);
            });
#pragma unroll
            for (int i = 0; i < 4; i++) {
                mma_bf(a[i & 1], q[i][0], q[i][1], q[i][2], q[i][3], k[i][0], k[i][1]);
                mma_bf(a[2 + (i & 1)], q[i][0], q[i][1], q[i][2], q[i][3], k[i][2], k[i][3]);
            }
            const float mk = w == 6 ? 1.f : 0.f;
            const float x0 = (a[0][0] + a[0][2]) + (a[1][0] + a[1][2]), x1 = (a[0][1] + a[0][3]) + (a[1][1] + a[1][3]);
            const float y0 = (a[2][0] + a[2][2]) + (a[3][0] + a[3][2]), y1 = (a[2][1] + a[2][3]) + (a[3][1] + a[3][3]);
            st_share2(L8, sco, sb + B_S, pd0, pd1, pack_bf(fmaf(y0, mk, x0) * sl, fmaf(y1, mk, x1) * sl), pack_bf(y0 * sl, y1 * sl));
        }
        if (c == 2) {
            const uint32_t x = lds32_u<0>(L4, vo1), y = lds32_u<0>(L4, vp1);
            st_share2(L8, vs, sb + B_S, pd0, pd1, pack_bf(f1[0] + bf_lo(x), f1[1] + bf_hi(x)), pack_bf(f1[2] + bf_lo(y), f1[3] + bf_hi(y)));
        }
        STAMP(3);
        if (st == NSEG - 1) break;
        tok_finish(b1, e, L16, sn, idn);
        redp += (st & 1) ? 32768 - 512 : 512;
        if (wg == 0) {
            uint32_t wo[16][4], vx[2][2][4], vm[2][2];
            ldsm4_u<0>(vx[0][0], L16, va); ldsm4_u<512>(vx[0][1], L16, va); ldsm4_u<1024>(vx[1][0], L16, va); ldsm4_u<1536>(vx[1][1], L16, va);
            sfor<NWO0>([&](auto I) { wo_fetch(wo, I); });
            mbar_wait(sb + B_S, st & 1);
            STAMP(4);
            uint32_t s[5];
            {
                uint32_t p[2][5];
                sfor<2>([&](auto R) {
                    constexpr int r = R;
                    lds64_u<O_SC + r * 768>(p[r], L8, sb); lds64_u<O_SC + r * 768 + 256>(p[r] + 2, L8, sb); p[r][4] = lds32_u<O_SC + r * 768 + 512>(L8, sb);
                });
#pragma unroll
                for (int j = 0; j < 5; j++) s[j] = badd(p[0][j], p[1][j]);
            }
            lds64_u<0>(vm[0], L8, vr); lds64_u<256>(vm[1], L8, vr);
            uint32_t mm = bmax(bmax(bmax(s[0], s[1]), bmax(s[2], s[3])), s[4]);
            mm = bmax(bmax(mm, __shfl_xor_sync(~0u, mm, 1)), bmax(__shfl_xor_sync(~0u, mm, 2), __shfl_xor_sync(~0u, mm, 3)));
            const float m = fmaxf(bf_lo(mm), bf_hi(mm));
            float o0[4] = {0.f, 0.f, 0.f, 0.f}, o1[4] = {0.f, 0.f, 0.f, 0.f}, d[10];
#pragma unroll
            for (int j = 0; j < 5; j++) { d[2 * j] = bf_lo(s[j]) - m; d[2 * j + 1] = bf_hi(s[j]) - m; }
#pragma unroll
            for (int j = 0; j < 10; j++) d[(j + 8) % 10] = ex2(d[(j + 8) % 10]);
            float sum = ((d[8] + d[9]) + (d[0] + d[1])) + ((d[2] + d[3]) + (d[4] + d[5])) + (d[6] + d[7]);
            const uint32_t p4 = pack_bf(d[8], d[9]), p0 = pack_bf(d[0], d[1]), p1 = pack_bf(d[2], d[3]), p2 = pack_bf(d[4], d[5]), p3 = pack_bf(d[6], d[7]);
            mma_bf8(o0, vm[0][0], vm[0][1], p4);
            mma_bf8(o1, vm[1][0], vm[1][1], p4);
            mma_bf(o0, vx[0][0][0], vx[0][0][1], vx[0][0][2], vx[0][0][3], p0, p1);
            mma_bf(o1, vx[1][0][0], vx[1][0][1], vx[1][0][2], vx[1][0][3], p0, p1);
            mma_bf(o0, vx[0][1][0], vx[0][1][1], vx[0][1][2], vx[0][1][3], p2, p3);
            mma_bf(o1, vx[1][1][0], vx[1][1][1], vx[1][1][2], vx[1][1][3], p2, p3);
            sfor<NWO0B - NWO0>([&](auto I) { wo_fetch(wo, IC<NWO0 + decltype(I)::value>()); });
            sum += __shfl_xor_sync(~0u, sum, 1);
            sum += __shfl_xor_sync(~0u, sum, 2);
            sts32_u<O_OS>(L4, w512, pack_bf(o0[0], o0[1])); sts32_u<O_OS + 128>(L4, w512, pack_bf(o0[2], o0[3]));
            sts32_u<O_OS + 256>(L4, w512, pack_bf(o1[0], o1[1])); sts32_u<O_OS + 384>(L4, w512, pack_bf(o1[2], o1[3]));
            sts32_u<O_SUM>(lane & 28, sb, __float_as_uint(sum));
            STAMP(5);
            invM = mem_out<NWO0B>(sb, L16, L8, wo, woa, redp + rown, w & 1);
            tr = clock32();
        } else {
            uint32_t wo[16][4];
            sfor<NWO1>([&](auto I) { wo_fetch(wo, I); });
            invM = mem_out<NWO1>(sb, L16, L8, wo, woa, redp + rown, w & 1);
            tr = clock32();
        }
        STAMP(7);
        tok_issue<0, NTA>(A0, A1, b0, b1, xd, zero);
        sn = sn2 - sn; ka = ka2 - ka; vs = vs2 - vs; va = va2 - va; vr = vr2 - vr;
        STAMP(8);
    }
    if (layer == TLL) TL(40);
    bar_arrive(8, 320);
    tid = read_tid(); lane = tid & 31;
    float acc[40];
    const int nc = c == 2 ? 10 : 11;
#pragma unroll 1
    for (int k = 0; k < nc; k++) {
        mbar_wait(sb + T_FB + (k % 7) * 8, k >= 7);
        mbar_wait(sb + T_FA + (k & 3) * 8, (k >> 2) & 1);
        if (layer == TLL && k == 0) TL(41);
        const uint64_t da = mkdesc(sb + O_MS + (k & 3) * 16384 + wg * 8192, 1024, 128, 0), db = mkdesc(sb + tail_b(k) + wg * 10240, 1280, 128, 0);
        wg_fence();
#pragma unroll
        for (int q = 0; q < 4; q++) wg_n80_ss(acc, da + q * 128, db + q * 160, k | q);
        wg_commit();
        if (k > 0) {
            wg_wait<1>();
            if (lane == 0) { mbar_arrive(sb + T_EA + ((k - 1) & 3) * 8); if (k <= 4) mbar_arrive(sb + T_EB + (k - 1) * 8); }
        }
    }
    if (layer == TLL) TL(52);
    const int mb = 28 + (h >> 3), nj = c == 2 ? 1 : 2;
    uint32_t rv[2][2];
    const size_t go = ((size_t)(mb * 64 + (w & 3) * 16 + (lane >> 2)) * 640 + (h & 7) * 80 + (wg * 5 + c * 2) * 8 + (lane & 3) * 2) >> 1;
#pragma unroll
    for (int u = 0; u < 4; u++) rv[u >> 1][u & 1] = (u >> 1) < nj ? __ldcg((const uint32_t*)res + go + (u >> 1) * 4 + (u & 1) * 2560) : 0u;
    wg_wait<0>();
    asm volatile("barrier.cluster.arrive.relaxed.aligned; barrier.cluster.wait.aligned;" ::: "memory");
    const uint32_t ra = sb + O_XS + tid * 16, rb = sb + O_MS + tid * 16;
#pragma unroll
    for (int j = 0; j < 5; j++) {
        const float* q = acc + 4 * j;
        sts128(rb + j * 4096, __float_as_uint(wg ? q[0] : q[20]), __float_as_uint(wg ? q[1] : q[21]), __float_as_uint(wg ? q[2] : q[22]), __float_as_uint(wg ? q[3] : q[23]));
    }
    bar_sync(4, 256);
#pragma unroll
    for (int j = 0; j < 5; j++) {
        const float* q = acc + 4 * j;
        uint32_t p[4];
        lds128(p, sb + O_MS + (tid ^ 128) * 16 + j * 4096);
        asm volatile("st.async.shared::cluster.mbarrier::complete_tx::bytes.v4.f32 [%0],{%1,%2,%3,%4},[%5];" ::"r"(mapa(ra + c * 8192 + (j & 1) * 4096, j >> 1)),
                     "f"((wg ? q[20] : q[0]) + __uint_as_float(p[0])), "f"((wg ? q[21] : q[1]) + __uint_as_float(p[1])),
                     "f"((wg ? q[22] : q[2]) + __uint_as_float(p[2])), "f"((wg ? q[23] : q[3]) + __uint_as_float(p[3])), "r"(mapa(sb + T_RED, j >> 1)) : "memory");
    }
    mbar_wait(sb + T_RED, 0);
#pragma unroll 1
    for (int u = 0; u < nj; u++) {
        uint32_t p[3][4];
#pragma unroll
        for (int q = 0; q < 3; q++) lds128(p[q], ra + q * 8192 + u * 4096);
        float y[4];
#pragma unroll
        for (int i = 0; i < 4; i++) y[i] = __uint_as_float(p[0][i]) + __uint_as_float(p[1][i]) + __uint_as_float(p[2][i]);
        ((uint32_t*)out)[go + u * 4] = bfma(pack_bf(y[0], y[1]), 0x3f803f80u, u ? rv[1][0] : rv[0][0]);
        ((uint32_t*)out)[go + u * 4 + 2560] = bfma(pack_bf(y[2], y[3]), 0x3f803f80u, u ? rv[1][1] : rv[0][1]);
    }
    TL(layer == 0 ? 15 : 29);
    asm volatile("barrier.cluster.arrive.relaxed.aligned; barrier.cluster.wait.aligned;" ::: "memory");
}

__device__ __forceinline__ void tail_load_b(const uint32_t sb, const int h, const int c, const int k) {
    mbar_expect(sb + T_FB + (k % 7) * 8, 20480);
    bulk_g2s(sb + tail_b(k), (const char*)g_wot + (size_t)((h & 7) * GNC + c * 11 + k) * 20480, 20480, sb + T_FB + (k % 7) * 8);
}
__device__ __forceinline__ void chain_aux(const uint32_t sb, const int c, const int h, const int layer, const int nact, const bf16* Wq, const bf16* Wk,
                                          const bf16* Wv, const bf16* Wo) {
    const int tid = read_tid(), w = __shfl_sync(~0u, tid >> 5, 0), lane = tid & 31;
    if (w == 8) {
        mbar_init(sb + O_BAR + lane * 8, lane == 2 && NOSELF ? (c == 2 ? 9 : 4) : lane == 3 || (lane >= 16 && lane < 20) || (lane >= 27 && lane < 31) ? 8 : 1);
        asm volatile("fence.mbarrier_init.release.cluster;" ::: "memory");
        fence_async_smem();
        __syncwarp();
    }
    {
        uint4* z = (uint4*)red_base() + layer * 65536;
#pragma unroll 1
        for (int i = blockIdx.x * 128 + tid - 256; i < 65536; i += 96 * 128)
            if (i >= 2048 || (i & 32)) z[i] = make_uint4(0, 0, 0, 0);
    }
    if (w == 8 && lane == 0) {
        mbar_expect(sb + B_S, s_tx(c));
        mbar_expect(sb + B_W, 192);
        mbar_expect(sb + T_RED, (c == 2 ? 1 : 2) * 3 * 4096);
        if (layer == 1) prefetch_l2(red_base() + 32 * 32768 + blockIdx.x * 1024, 1024);
        if (layer == 0) wait_flag<400>(g_ready, NSETUP);
    }
    __syncwarp();
    cluster_sync_full();
    asm volatile("barrier.cluster.arrive.relaxed.aligned;" ::: "memory");
    pdl_wait();
    Flag* flag = g_flag + layer * NSEG * 32 + h;
    const Flag* xflag = g_flag + F_X + layer * 128;
    char* const it0 = g_item + (size_t)h * 32768;
    if (w == 8) {
#pragma unroll 1
        for (int n = 0; n < 3; n++) {
            wait_flag<100>(xflag + (n >> 1), 4);
            fence_async_glb();
            if (n == 0) { bar_sync(4, 288); fence_async_smem(); }
            if (lane == 0 && n < 2) {
                mbar_expect(sb + B_XF + n * 8, 40960);
                bulk_g2s(sb + O_XS + n * 40960, (const char*)g_xn + n * 40960, 40960, sb + B_XF + n * 8);
            }
            __syncwarp();
        }
#pragma unroll 1
        for (int n = 0; n < NSEG; n++) {
            const int np = n & 1;
            if (n == 0) { wait_flag<100>(g_flag + F_W + layer * 128, 96); bar_sync(5, 288); } else bar_sync(2, 352);
            if (n == 1) TL(12 + layer * 14);
            if (n == 63) TL(13 + layer * 14);
            if (lane == 0 && (n == NSEG - 1 || (XEARLY & 8))) mbar_arrive(sb + B_STG + np * 8);
            if (lane == 0 && n < NSEG - 1) {
                const uint32_t vs = sb + O_STG + 8192 - np * 16384, vb = sb + B_VX + np * 8;
                if (c == 2) { if (!VEARLY || n == 0) {
                    fence_async_smem();
                    bulk_s2s(mapa(vs, 0), vs, 8192, mapa(vb, 0));
                    bulk_s2s(mapa(vs, 1), vs, 8192, mapa(vb, 1));
                } } else mbar_expect(vb, 8192);
                if (n == 0) { mbar_expect(sb + B_XF, 40960); bulk_g2s(sb + O_XS, (const char*)g_xn + 2 * 40960, 40960, sb + B_XF); }
                if (n == h * 3 + c && !np && n + 6 < NSEG) prefetch_l2(red_base() + (size_t)(layer * 32 + (n >> 1) + 3) * 32768, 32768);
            }
            __syncwarp();
        }
    } else if (w == 11) {
        float cvo;
        {
            auto max8 = [&](const float* p) {
                const float4 u = ((const float4*)p)[0], v = ((const float4*)p)[1];
                return fmaxf(fmaxf(fmaxf(u.x, u.y), fmaxf(u.z, u.w)), fmaxf(fmaxf(v.x, v.y), fmaxf(v.z, v.w)));
            };
            wait_flag<300>(g_flag + F_W + layer * 128, 96);
            const float* pc = g_co + lane * 32;
            float a = 640.f * __ldcg(g_wmx + lane * 3 + 2), o = fmaxf(fmaxf(max8(pc), max8(pc + 8)), max8(pc + 16));
#pragma unroll 1
            for (int s = 16; s; s >>= 1) { a = fmaxf(a, __shfl_xor_sync(~0u, a, s)); o += __shfl_xor_sync(~0u, o, s); }
            cvo = a * o * 2.f;
        }
        float invM = g_invM0;
        float iv;
        weight_scale(h, 2, &iv);
        const uint32_t L16 = sb + lane * 16 + O_MX;
#pragma unroll 1
        for (int st = 0; st < NSEG; st++) {
            bar_sync(1, 320);
            if (st == NSEG - 1) break;
            if (!(XEARLY & 10) && lane == 0) mbar_arrive(sb + B_STG + (st & 1) * 8);
            uint32_t u[2][4];
            lds128(u[0], L16); lds128(u[1], L16 + 512);
            uint32_t mx = habsmax(habsmax(habsmax(u[0][0], u[0][1]), habsmax(u[0][2], u[0][3])), habsmax(habsmax(u[1][0], u[1][1]), habsmax(u[1][2], u[1][3])));
            mx = __reduce_max_sync(~0u, max(mx & 0x7fffu, (mx >> 16) & 0x7fffu));
            const float bound = fmaxf(__half2float(__ushort_as_half((unsigned short)mx)) * invM, 25.5f) * cvo;
            const float sc = pow2_scale(bound, 15, &invM);
            sts64(sb + O_SCL, __float_as_uint(sc * iv), __float_as_uint(invM));
            bar_arrive(2, 352);
        }
    } else if (w == 10) {
        if (lane == 0) {
#pragma unroll 1
            for (int n = 0; n < NSEG; n++) {
                mbar_sleep(sb + B_STG + (n & 1) * 8, (n >> 1) & 1);
                fence_async_smem();
                const uint32_t stg = sb + O_STG - (n & 1) * 16384;
                char* it = it0 + (size_t)(n % RING) * 32 * 32768;
                bulk_s2g(it + c * 8192, stg + (c == 2 ? 8192 : 0), 8192);
                bulk_commit();
                if (n + 1 >= RING && n + 1 < NSEG) wait_flag(flag - (RING - 1) * 32, REL1 ? 4 : 7);
                bulk_wait0();
                if (REL1) {
                    fence_async_glb();
                    mbar_arrive(sb + B_FREE + (n & 1) * 8);
                } else {
                    mbar_arrive(sb + B_FREE + (n & 1) * 8);
                    fence_async_glb();
                    if (RELAX & 1) red_relaxed(flag); else red_release(flag);
                }
                flag += 32;
            }
        }
    } else {
        const uint32_t L16 = sb + lane * 16;
        bool allx = false;
#pragma unroll 1
        for (int st = 0; st < NSEG; st++) {
            const int par = st & 1;
            char* it = it0 + (size_t)(st % RING) * 32 * 32768 + lane * 16;
            if (lane == 0 && !allx && st + 3 < NSEG) {
                allx = ld_acquire(xflag + 64) >= nact;
                if (!allx) wait_flag(xflag + ((st + 3) >> 1), 4);
                fence_async_glb();
            }
            __syncwarp();
            auto refill = [&] {
                if (lane == 0 && st + 3 < NSEG) {
                    mbar_expect(sb + B_XF + (par ^ 1) * 8, 40960);
                    bulk_g2s_last(sb + O_XS + (par ^ 1) * 40960, (const char*)g_xn + (size_t)(st + 3) * 40960, 40960, sb + B_XF + (par ^ 1) * 8);
                } else if (lane == 0 && st < NSEG - 1) {
                    tail_load_b(sb, h, c, (par ^ 1) * 2); tail_load_b(sb, h, c, (par ^ 1) * 2 + 1);
                }
                __syncwarp();
            };
            if (st < NSEG - 1 && c < 2) mbar_sleep(sb + B_VX + par * 8, (st >> 1) & 1);
            if (st < NSEG - 2) mbar_sleep(sb + B_XF + par * 8, ((st >> 1) + 1) & 1);
            bar_sync(1, 320);
            if (!(XEARLY & 1)) refill();
            char* const itb = it - lane * 16;
            if (lane == 0 && c < 2) {
                fence_async_smem();
#pragma unroll 1
                for (int i = 0; i < 4; i++) bulk_s2g(itb + 24576 + (c * 4 + i) * 512, sb + O_QKP + i * 1024 + 512, 512);
                bulk_commit();
                asm volatile("cp.async.bulk.wait_group.read 0;" ::: "memory");
            }
            __syncwarp();
            if (st < NSEG - 1) bar_arrive(2, 352);
            mbar_sleep(sb + B_S, par);
            __syncwarp();
            if (lane == 0) {
                if (st < NSEG - 1) mbar_expect(sb + B_S, s_tx(c));
                if (c == 2) { fence_async_smem(); bulk_s2g(itb + 28672, sb + O_VM + par * 2048, 2048); bulk_commit(); }
                if (st == NSEG - 1) asm volatile("cp.async.bulk.wait_group.read 0;" ::: "memory");
            }
            __syncwarp();
            if (st == NSEG - 1) bar_arrive(8, 320);
            if (lane == 0) { bulk_wait0(); fence_async_glb(); red_relaxed(flag); }
            __syncwarp();
            if (!REL1) mbar_sleep(sb + B_FREE + par * 8, (st >> 1) & 1);
            flag += 32;
            continue;
#pragma unroll 1
            for (int i = 0; i < (c < 2 ? 4 : 0); i += 2) {
                uint32_t v[8];
                lds128(v, L16 + O_QKP + i * 1024 + 512); lds128(v + 4, L16 + O_QKP + i * 1024 + 512 + 1024);
                *(uint4*)(it + 24576 + (c * 4 + i) * 512) = make_uint4(v[0], v[1], v[2], v[3]); *(uint4*)(it + 24576 + (c * 4 + i) * 512 + 512) = make_uint4(v[4], v[5], v[6], v[7]);
            }
            if (st < NSEG - 1) bar_arrive(2, 352);
            mbar_sleep(sb + B_S, par);
            __syncwarp();
            if (lane == 0 && st < NSEG - 1) mbar_expect(sb + B_S, s_tx(c));
#pragma unroll 1
            for (int i = 0; i < (c < 2 ? 0 : 4); i += 2) {
                uint32_t v[8];
                lds128(v, L16 + O_VM + par * 2048 + i * 512); lds128(v + 4, L16 + O_VM + par * 2048 + i * 512 + 512);
                *(uint4*)(it + 28672 + i * 512) = make_uint4(v[0], v[1], v[2], v[3]); *(uint4*)(it + 28672 + i * 512 + 512) = make_uint4(v[4], v[5], v[6], v[7]);
            }
            if (st == NSEG - 1) bar_arrive(8, 320);
            __syncwarp();
            if (REL1) mbar_sleep(sb + B_FREE + par * 8, (st >> 1) & 1);
            if (lane == 0) { if (RELAX & 2) red_relaxed(flag); else red_release(flag); }
            if (!REL1) mbar_sleep(sb + B_FREE + par * 8, (st >> 1) & 1);
            flag += 32;
        }
    }
    __syncwarp();
    const int nc = c == 2 ? 10 : 11;
    if (w == 10) {
        bar_sync(8, 320);
        if (lane == 0) {
            if (layer == 1 && blockIdx.x == 0) g_ready[0].v = 0;
            fence_async_smem();
            __nanosleep(TDELAY);
            wait_flag(xflag + 64, nact);
            wait_flag<50>(g_flag + F_O + layer * 32 + 28 + (h >> 3), 64);
            fence_async_glb();
#pragma unroll 1
            for (int k = 0; k < nc; k++) {
                if (k >= 4) mbar_sleep(sb + T_EA + (k & 3) * 8, ((k >> 2) - 1) & 1);
                mbar_expect(sb + T_FA + (k & 3) * 8, 16384);
                bulk_g2s_last(sb + O_MS + (k & 3) * 16384, (const char*)g_O + (size_t)((28 + (h >> 3)) * GNC + c * 11 + k) * 16384, 16384, sb + T_FA + (k & 3) * 8);
            }
        }
    } else if (w == 9 && lane == 0) {
        __nanosleep(TDELAY);
#pragma unroll 1
        for (int k = 4; k < nc; k++) {
            if (k >= 7) mbar_sleep(sb + T_EB + (k - 7) * 8, 0);
            tail_load_b(sb, h, c, k);
        }
    }
    __syncwarp();
    asm volatile("barrier.cluster.wait.aligned;" ::: "memory");
    asm volatile("barrier.cluster.arrive.relaxed.aligned; barrier.cluster.wait.aligned;" ::: "memory");
    asm volatile("barrier.cluster.arrive.relaxed.aligned; barrier.cluster.wait.aligned;" ::: "memory");
}

constexpr int RI_A = 0, RI_TAB = 81920, RI_STG = RI_TAB + 82 * 768;
constexpr int RI_RES = RI_STG + 25600, RI_ST = RI_RES + 2 * 64 * 336;
constexpr int HB_A = G_BAR + 64, HB_AFREE = HB_A + 32, HB_LN = HB_A + 40, HB_FULL = HB_A + 64, HB_DONE = HB_FULL + 48, HB_FREE = HB_DONE + 48;
constexpr int HP_SMEM = HB_FREE + 48;
static_assert(G_BAR >= RI_ST + 2048, "helper shared-memory map");
#define IDL 350
#define ITEM_NS 60
#define HORD 1
#define PFW_AT 28
#define PFW_NS 150
__device__ __forceinline__ void helper_aux(const uint32_t sb, const int j, const int nh, const int na, const int nbh, const int layer, const bf16* Wq,
                                           const bf16* Wk, const bf16* Wv, const bf16* Wo) {
    const int w = threadIdx.x >> 5, lane = threadIdx.x & 31, p = w - 8;
    if (lane == 0 && j < (nh & ~3)) {
        int n = 0;
        for (int a = j >> 2; a < 32; a += nh >> 2, n++) {
            if (n == 0) continue;
            mbar_wait(sb + HB_AFREE, (n - 1) & 1);
            mbar_expect(sb + HB_A + p * 8, 20480);
            bulk_g2s_last(sb + RI_A + p * 20480, (const char*)g_YT + (size_t)a * 81920 + p * 20480, 20480, sb + HB_A + p * 8);
            if (p == 0) { mbar_wait(sb + HB_LN, (n - 1) & 1); red_release(g_flag + F_X + layer * 128 + a - (nh >> 2)); }
        }
        if (p == 0) { mbar_wait(sb + HB_LN, (n - 1) & 1); red_release(g_flag + F_X + layer * 128 + (j >> 2) + (n - 1) * (nh >> 2)); }
    }
    __syncwarp();
    if (layer == 0 && w == 8 && lane == 0) wait_flag<400>(g_flag + F_W, 96);
    __syncwarp();
    bar_sync(3, 384);
    if (p == 3 && lane == 0 && j < (nh & ~3)) red_release(g_flag + F_X + layer * 128 + 64);
    fence_async_smem();
    Flag* oflag = g_flag + F_O + layer * 32;
    if (j < na) {
        int sl = p & 1, ph = 1;
        for (int idx = j + (p & 1) * na; idx < NSEG * 32 && p >= 2 && lane == 0; idx += 2 * na) {
            mbar_wait(sb + HB_DONE + sl * 8, ph ^ 1);
            mbar_arrive(sb + HB_FREE + sl * 8);
            red_release(oflag + (idx >> 6));
            atomicAdd(&g_flag[layer * NSEG * 32 + idx].v, 1u);
            sl += 2;
            if (sl >= 6) { sl -= 6; ph ^= 1; }
        }
        for (int idx = j + p * na; idx < NSEG * 32 && p < 2 && lane == 0; idx += 2 * na) {
            mbar_wait(sb + HB_FREE + sl * 8, ph);
            wait_flag<ITEM_NS>(g_flag + layer * NSEG * 32 + idx, REL1 ? 3 : 6);
            fence_async_glb();
            if (idx < (NSEG - 2) * 32) __nanosleep(IDL);
            mbar_expect(sb + HB_FULL + sl * 8, 30720);
            bulk_g2s(sb + sl * 30720, g_item + (size_t)(idx % (RING * 32)) * 32768, 30720, sb + HB_FULL + sl * 8);
            sl += 2;
            if (sl >= 6) { sl -= 6; ph ^= 1; }
        }
    } else if (lane == 0 && p == 3) {
        if (layer == 0) {
            wait_flag<1000>(oflag + PFW_AT, 64);
            const int np = nh - na;
#pragma unroll 1
            for (int i = j - na; i < 1280; i += np) {
                const bf16* W = i < 320 ? Wq : i < 640 ? Wk : i < 960 ? Wv : Wo;
                prefetch_l2((const char*)W + (size_t)(i % 320) * 16384, 16384);
                __nanosleep(PFW_NS);
            }
#pragma unroll 1
            for (int i = j - na; i < 205; i += np) {
                const char* p_ = i < 160 ? (const char*)g_Wf + i * 16384 : i < 165 ? (const char*)g_stat + (i - 144) * 16384
                               : i < 167 ? (const char*)g_ctab + (i - 165) * 8192 : (const char*)(g_flag + NFLAG) - (i - 166) * 16384;
                prefetch_l2(p_, 16384);
                __nanosleep(PFW_NS);
            }
        }
    } else if (lane == 0) {
        if (p == 2) wait_flag<500>(g_flag + F_X + layer * 128 + 64, nh & ~3);
        int c0 = 0;
        for (int mb = (j - na) >> 3; mb < nbh; mb += (nh - na) >> 3, c0 += GNC) {
            if (p < 2) wait_flag<300>(oflag + 2 * mb + p, 64);
            fence_async_glb();
            oproj_load(sb, p, mb, (j - na) & 7, c0, nh - na < 24 ? 0 : mb == nbh - 1 ? GPACE2 : GPACE);
        }
    }
}
__device__ __forceinline__ void helper_mma(char* sm, const int jh, const int nh, const int na, const int nbh, const int layer, const bf16* res, bf16* x,
                                           bf16* out) {
    const uint32_t sb = smem_u32(sm);
    const int tid = threadIdx.x, w = tid >> 5, lane = tid & 31, g = lane >> 2, t = lane & 3;
    const bool act = jh < (nh & ~3);
    const int j4 = jh & 3;
    const int fr = tid & 63, rg = w >> 1;
    auto chunk0 = [&](int u) { return u == 0 ? 5 * j4 : u == 1 ? 75 - 5 * j4 : u == 2 ? 40 + 5 * j4 : 35 - 5 * j4; };
    const int gr = tid / 20, gq_ = tid - gr * 20, go = gr * 80 + chunk0(gq_ / 5) + gq_ % 5;
    const uint32_t gs = sb + RI_RES + gr * 336 + gq_ * 16;
    auto residual = [&](int a, int n) {
#pragma unroll 1
        for (int r = 0; r < 64 - gr && tid < 240 && a < 32; r += 12) cp_async16(gs + (n & 1) * 21504 + r * 336, (const uint4*)res + (a * 64 + r) * 80 + go);
        cp_commit();
    };
    if (act) {
        if (tid < 240) {
            const int k0 = tid / 48, n = tid - k0 * 48;
            const float d = (float)(40 * j4 + n), amp = 2.f * 0.03952847075210474f;
#pragma unroll 4
            for (int u = 0; u < 16; u++)
                *(uint4*)(sm + RI_TAB + (tid + u * 240) * 16) = cos_row8(fmaf((float)((k0 + (u & 3) * 5) * 16 + ((u >> 2) & 1)), d, (float)((u & 8) * 20)), 2.f * d, amp);
            if (tid < 96) *(uint4*)(sm + RI_TAB + (3840 + tid) * 16) = make_uint4(k0 == 0 ? pack_h((n & 1) ? -amp : amp, 0.f) : 0u, 0, 0, 0);
        }
        fence_async_smem();
        residual(jh >> 2, 0);
    }
    bar_sync(1, 384);
    if (layer == TLL) TL(36);
    if (act) {
        const float4 wm = ((const float4*)g_wmax)[lane];
        const int wg = w >> 2;
        int n = 0;
#pragma unroll 1
        for (int a = jh >> 2; a < 32; a += nh >> 2, n++) {
            float acc[2][24];
            uint64_t da = mkdesc(sb + RI_A + wg * 40960, 1024, 1024, 1), db = mkdesc(sb + RI_TAB + wg * 30720, 768, 128, 0);
#pragma unroll
            for (int gq = 0; gq < 2; gq++) {
                mbar_wait(sb + HB_A + (wg * 2 + gq) * 8, n & 1);
                if (layer == TLL && n == TLN && gq == 0) TL(45);
                wg_fence();
#pragma unroll 5
                for (int k = 0; k < 10; k++) { wg_n48_ss_ta(acc[gq], da, db, k); da += 128; db += 96; }
                wg_commit();
            }
            if (wg == 0) {
                mbar_wait(sb + HB_A + 16, n & 1);
                wg_fence();
                wg_n48_ss_ta(acc[0], da, db + 20 * 96, 1);
                wg_commit();
            }
            float inv;
            pow2_scale(__uint_as_float(__reduce_max_sync(~0u, __float_as_uint(fmaxf(fmaxf(wm.x, wm.y), fmaxf(wm.z, wm.w))))), 0, &inv);
            const uint32_t ysc = pack_bf(inv, inv);
            wg_wait<0>();
            if (layer == TLL && n == TLN) TL(46);
            if (lane == 0) mbar_arrive(sb + HB_AFREE);
            const uint32_t ad = sb + RI_STG + ((w & 3) * 16 + (lane & 15)) * 400 + (lane >> 4) * 96 + wg * 192;
#pragma unroll
            for (int q = 0; q < 6; q++) {
                const float *e = acc[0] + q * 4, *o = acc[1] + q * 4;
                stsm4(ad + q * 16, pack_h(e[0] + o[0], e[1] + o[1]), pack_h(e[2] + o[2], e[3] + o[3]), pack_h(e[0] - o[0], e[1] - o[1]), pack_h(e[2] - o[2], e[3] - o[3]));
            }
            cp_wait<0>();
            bar_sync(4, 256);
            const uint32_t xa = sb + RI_RES + (n & 1) * 21504 + fr * 336 + rg * 80, sg = (rg & 1) ? 0xbc00bc00u : 0x3c003c00u;
            float sum = 0.f, sq = 0.f;
            uint32_t ya = sb + RI_STG + fr * 400 + (rg >> 1) * 96 + ((rg & 1) ? 64 : 0), carry;
            asm("fma.rn.f16x2 %0,%1,%2,%3;" : "=r"(carry) : "r"(lds32(ya + 208)), "r"(sg), "r"(lds32(ya + 16)));
#pragma unroll 1
            for (int ch = 0; ch < 5; ch++, ya += (rg & 1) ? -16 : 16) {
                uint32_t y[4], z[4], xr[4];
                lds128(y, ya); lds128(z, ya + 192); lds128(xr, xa + ch * 16);
#pragma unroll
                for (int q = 0; q < 4; q++) asm("fma.rn.f16x2 %0,%1,%2,%0;" : "+r"(y[q]) : "r"(z[q]), "r"(sg));
                if (rg & 1) {
                    const uint32_t y0 = y[0], y1 = y[1];
                    y[0] = __byte_perm(carry, y[3], 0x7610); y[1] = __byte_perm(y[3], y[2], 0x7610);
                    y[3] = __byte_perm(y1, y0, 0x7610); y[2] = __byte_perm(y[2], y1, 0x7610);
                    carry = y0;
                }
#pragma unroll
                for (int q = 0; q < 4; q++) {
                    const float2 yf = __half22float2(*(const __half2*)&y[q]);
                    xr[q] = bfma(pack_bf(yf.x, yf.y), ysc, xr[q]);
                    const float e = bf_lo(xr[q]), f = bf_hi(xr[q]);
                    sum += e + f; sq = fmaf(e, e, fmaf(f, f, sq));
                }
                sts128(xa + ch * 16, xr[0], xr[1], xr[2], xr[3]);
            }
            uint2* stat = g_stat + (size_t)(layer * 32 + a) * 1024 + rg * 64 + fr;
            asm volatile("st.relaxed.gpu.global.v2.u32 [%0],{%1,%2};" ::"l"(stat + j4 * 256), "r"(__float_as_uint(sum)), "r"(__float_as_uint(sq) | 0x80000000u) : "memory");
            if (layer == TLL && n == TLN) TL(47);
            uint32_t s0[3], s1[3];
            int lim = 0;
            do {
#pragma unroll
                for (int q = 0; q < 3; q++)
                    asm volatile("ld.relaxed.gpu.global.v2.u32 {%0,%1},[%2];" : "=r"(s0[q]), "=r"(s1[q]) : "l"(stat + ((j4 + 1 + q) & 3) * 256) : "memory");
            } while (__any_sync(~0u, (int)(s1[0] & s1[1] & s1[2]) >= 0) && ++lim < SPIN_LIM);
#pragma unroll
            for (int q = 0; q < 3; q++) { sum += __uint_as_float(s0[q]); sq -= __uint_as_float(s1[q]); }
            sts64(sb + RI_ST + tid * 8, __float_as_uint(sum), __float_as_uint(sq));
            bar_sync(4, 256);
            if (layer == TLL && n == TLN) TL(48);
#pragma unroll
            for (int q = 1; q < 4; q++) {
                uint32_t st2[2];
                lds64(st2, sb + RI_ST + ((tid + q * 64) & 255) * 8);
                sum += __uint_as_float(st2[0]); sq += __uint_as_float(st2[1]);
            }
            const float mean = sum * (1.f / 640.f), r = rsqrtf(fmaxf(fmaf(-mean, mean, sq * (1.f / 640.f)), 0.f) + 1e-5f), off = -mean * r;
            uint4* dst = (uint4*)g_xn + ((size_t)(2 * a + (w & 1)) * 80 + chunk0(rg)) * 32 + lane;
#pragma unroll
            for (int i = 0; i < 5; i++) {
                uint32_t u[4];
                lds128(u, xa + i * 16);
                dst[i * 32] = make_uint4(pack_h(fmaf(bf_lo(u[0]), r, off), fmaf(bf_hi(u[0]), r, off)), pack_h(fmaf(bf_lo(u[1]), r, off), fmaf(bf_hi(u[1]), r, off)),
                                         pack_h(fmaf(bf_lo(u[2]), r, off), fmaf(bf_hi(u[2]), r, off)), pack_h(fmaf(bf_lo(u[3]), r, off), fmaf(bf_hi(u[3]), r, off)));
            }
            __syncwarp();
            if (lane == 0) mbar_arrive(sb + HB_LN);
            if (layer == TLL) TL(37);
            if (layer == TLL && n == TLN) TL(44);
            residual(a + (nh >> 2), n + 1);
#pragma unroll 2
            for (int rr = 0; rr < 64 - gr && tid < 240; rr += 12) {
                uint32_t v[4];
                lds128(v, gs + (n & 1) * 21504 + rr * 336);
                ((uint4*)x)[(a * 64 + rr) * 80 + go] = make_uint4(v[0], v[1], v[2], v[3]);
            }
        }
    }
    bar_sync(3, 384);
    if (layer == TLL) TL(38);
    if (jh >= na) {
        int c0 = 0;
#pragma unroll 1
        for (int mb = (jh - na) >> 3; mb < nbh; mb += (nh - na) >> 3, c0 += GNC) oproj_mma(sb, mb, (jh - na) & 7, c0, x, out);
        if (layer == TLL) TL(42);
        return;
    }
    const int p = w >> 1, mi = w & 1;
    int slot = p, ph = 0;
    for (int idx = jh + p * na; idx < NSEG * 32; idx += 4 * na) {
        const uint32_t it = sb + slot * 30720 + lane * 16;
        float iq, ik, iv;
        weight_scale(idx & 31, 0, &iq); weight_scale(idx & 31, 1, &ik); weight_scale(idx & 31, 2, &iv);
        bar_sync(6 + p, 64);
        mbar_wait(sb + HB_DONE + slot * 8, ph ^ 1);
        mbar_wait(sb + HB_FULL + slot * 8, ph);
        if (layer == TLL && idx >= 63 * 32) TL(55);
        float s[6][4];
#pragma unroll
        for (int i = 0; i < 6; i++) s[i][0] = s[i][1] = s[i][2] = s[i][3] = 0.f;
#pragma unroll
        for (int e = 0; e < 8; e++) {
            uint32_t q[4], k[4];
            ldsm4t(q, it + (e >> 2) * 8192 + (e & 3) * 1024 + mi * 512);
            ldsm4t(k, it + 24576 + e * 512);
            mma_bf(s[4], q[0], q[2], q[1], q[3], k[0], k[1]);
            mma_bf(s[5], q[0], q[2], q[1], q[3], k[2], k[3]);
            ldsm4t(k, it + (e >> 2) * 8192 + 4096 + (e & 3) * 1024);
            mma_bf(s[0], q[0], q[2], q[1], q[3], k[0], k[1]);
            mma_bf(s[1], q[0], q[2], q[1], q[3], k[2], k[3]);
            if (mi) {
                ldsm4t(k, it + (e >> 2) * 8192 + 4096 + (e & 3) * 1024 + 512);
                mma_bf(s[2], q[0], q[2], q[1], q[3], k[0], k[1]);
                mma_bf(s[3], q[0], q[2], q[1], q[3], k[2], k[3]);
            }
        }
#pragma unroll
        for (int q = 0; q < 4; q++) s[4][q] += s[5][q];
        const int seg = idx >> 5, h = idx & 31;
        const float sl = iq * ik * (0.08838834764831845f * 1.4426950408889634f);
        float mx[2] = {-3.0e38f, -3.0e38f};
#pragma unroll
        for (int i = 0; i < 5; i++)
#pragma unroll
            for (int q = 0; q < 4; q++) {
                const bool ok = i == 4 || (i * 8 + 2 * t + (q & 1)) <= (mi * 16 + g + (q >> 1) * 8);
                s[i][q] = ok ? s[i][q] * sl : -1.0e9f * 1.4426950408889634f;
                mx[q >> 1] = fmaxf(mx[q >> 1], s[i][q]);
            }
        float sum[2] = {0.f, 0.f};
#pragma unroll
        for (int r = 0; r < 2; r++) {
            mx[r] = fmaxf(mx[r], __shfl_xor_sync(~0u, mx[r], 1));
            mx[r] = fmaxf(mx[r], __shfl_xor_sync(~0u, mx[r], 2));
        }
#pragma unroll
        for (int i = 0; i < 5; i++)
#pragma unroll
            for (int q = 0; q < 4; q++) { s[i][q] = ex2(s[i][q] - mx[q >> 1]); sum[q >> 1] += s[i][q]; }
#pragma unroll
        for (int r = 0; r < 2; r++) {
            sum[r] += __shfl_xor_sync(~0u, sum[r], 1);
            sum[r] += __shfl_xor_sync(~0u, sum[r], 2);
            sum[r] = iv * rcp(sum[r]);
        }
        uint32_t pp[5][2];
#pragma unroll
        for (int i = 0; i < 5; i++) { pp[i][0] = pack_bf(s[i][0] * sum[0], s[i][1] * sum[0]); pp[i][1] = pack_bf(s[i][2] * sum[1], s[i][3] * sum[1]); }
        uint32_t* o = (uint32_t*)g_O + (((size_t)(seg >> 1) * 512 + h * 16) * 8 + (seg & 1) * 4 + mi * 2) * 32 + lane;
#pragma unroll
        for (int e = 0; e < 8; e++) {
            float o0[4] = {0.f, 0.f, 0.f, 0.f}, o1[4] = {0.f, 0.f, 0.f, 0.f};
            uint32_t v[4];
            lds64(v, it - lane * 8 + 28672 + e * 256);
            mma_bf8(o0, pp[4][0], pp[4][1], v[0]);
            mma_bf8(o1, pp[4][0], pp[4][1], v[1]);
            ldsm4(v, it + 16384 + e * 1024);
            mma_bf(o0, pp[0][0], pp[0][1], pp[1][0], pp[1][1], v[0], v[2]);
            mma_bf(o1, pp[0][0], pp[0][1], pp[1][0], pp[1][1], v[1], v[3]);
            ldsm4(v, it + 16384 + e * 1024 + 512);
            mma_bf(o0, pp[2][0], pp[2][1], pp[3][0], pp[3][1], v[0], v[2]);
            mma_bf(o1, pp[2][0], pp[2][1], pp[3][0], pp[3][1], v[1], v[3]);
            o[(2 * e) * 256] = pack_bf(o0[0], o0[1]); o[(2 * e) * 256 + 32] = pack_bf(o0[2], o0[3]);
            o[(2 * e + 1) * 256] = pack_bf(o1[0], o1[1]); o[(2 * e + 1) * 256 + 32] = pack_bf(o1[2], o1[3]);
        }
        __syncwarp();
        if (lane == 0) mbar_arrive(sb + HB_DONE + slot * 8);
        slot += 4;
        if (slot >= 6) { slot -= 6; ph ^= 1; }
    }
    if (layer == TLL) TL(39);
}

__global__ void __cluster_dims__(3, 1, 1) __launch_bounds__(384, 1)
k_chain(const int layer, const int nact, const uint32_t zero, const bf16* __restrict__ Wq, const bf16* __restrict__ Wk, const bf16* __restrict__ Wv,
        const bf16* __restrict__ Wo, const bf16* res, bf16* out) {
    extern __shared__ __align__(1024) char sm[];
    const uint32_t sb = smem_u32(sm);
    const int b = blockIdx.x, h = b / 3, c = b - h * 3;
    pdl_go();
    if (threadIdx.x >= 256) {
        asm volatile("setmaxnreg.dec.sync.aligned.u32 24;");
        TL(11 + layer * 14);
        chain_aux(sb, c, h, layer, nact, Wq, Wk, Wv, Wo);
    } else {
        asm volatile("setmaxnreg.inc.sync.aligned.u32 240;");
        chain_mma(sb, c, h, layer, zero, Wq, Wk, Wv, Wo, res, out);
    }
}
__global__ void __launch_bounds__(384, 1) k_help(const bf16* res, bf16* x, bf16* out, const int layer, const int na, const int nbh, const int zero, const bf16* Wq,
                                                  const bf16* Wk, const bf16* Wv, const bf16* Wo) {
    extern __shared__ __align__(1024) char sm[];
    if (layer == TLL) TL(51);
    if (threadIdx.x >= 256) {
        const uint32_t sb = smem_u32(sm);
        const int p = (threadIdx.x >> 5) - 8, i = (threadIdx.x & 31) * 4 + p;
        if (i < 34) mbar_init(sb + G_BAR + i * 8, i < 4 ? 3 : i < 8 || i == 12 || i == 13 ? 8 : i >= 22 && i < 28 ? 2 : 1);
        fence_async_smem();
        wait_flag<100>(g_flag + F_X + layer * 128 + 65, 321);
        fence_async_glb();
        if (i == 8 + p && blockIdx.x < (gridDim.x & ~3)) {
            mbar_expect(sb + HB_A + p * 8, 20480);
            bulk_g2s(sb + RI_A + p * 20480, (const char*)g_YT + (size_t)(blockIdx.x >> 2) * 81920 + p * 20480, 20480, sb + HB_A + p * 8);
        }
        __syncwarp();
        bar_sync(2, 128);
        bar_arrive(1, 384);
    }
    if (threadIdx.x + zero >= 256) helper_aux(smem_u32(sm), blockIdx.x, gridDim.x, na, nbh, layer, Wq, Wk, Wv, Wo);
    else helper_mma(sm, blockIdx.x, gridDim.x, na, nbh, layer, res, x, out);
    __syncwarp();
    pdl_go();
    if (blockIdx.x == 0) pdl_wait();
}

#define COL_PAD 15872
template <class... P, class... A>
void launch_pdl(void (*k)(P...), int grid, int block, int smem, cudaStream_t st, A... args) {
    cudaLaunchConfig_t cfg = {};
    cfg.gridDim = dim3(grid); cfg.blockDim = dim3(block); cfg.dynamicSmemBytes = smem; cfg.stream = st;
    cudaLaunchAttribute at[1];
    at[0].id = cudaLaunchAttributeProgrammaticStreamSerialization; at[0].val.programmaticStreamSerializationAllowed = 1;
    cfg.attrs = at;
    cfg.numAttrs = 1;
    cudaLaunchKernelEx(&cfg, k, args...);
}

}

extern "C" void kernel_launch(void* const* d_in, const int* in_sizes, int n_in, void* d_out, int out_size) {
    const bf16* x = (const bf16*)d_in[0];
    const bf16* wr = (const bf16*)d_in[1];
    const bf16* wi = (const bf16*)d_in[2];
    const bf16* mem0 = (const bf16*)d_in[4];
    const bf16* Wq = (const bf16*)d_in[5];
    const bf16* Wk = (const bf16*)d_in[6];
    const bf16* Wv = (const bf16*)d_in[7];
    const bf16* Wo = (const bf16*)d_in[8];
    bf16* out = (bf16*)d_out;
    static int nhelp = 0;
    static bf16 *xa, *xb;
    static cudaStream_t s1;
    static cudaEvent_t ev_fork, ev_join;
    if (!nhelp) {
        cudaStreamCreateWithFlags(&s1, cudaStreamNonBlocking);
        cudaEventCreateWithFlags(&ev_fork, cudaEventDisableTiming);
        cudaEventCreateWithFlags(&ev_join, cudaEventDisableTiming);
        cudaFuncSetAttribute(k_setup, cudaFuncAttributeMaxDynamicSharedMemorySize, SU_SMEM);
        cudaFuncSetAttribute(k_rowf, cudaFuncAttributeMaxDynamicSharedMemorySize, RF_SMEM);
        cudaFuncSetAttribute(k_col, cudaFuncAttributeMaxDynamicSharedMemorySize, COL_PAD);
        cudaFuncSetAttribute(k_chain, cudaFuncAttributeMaxDynamicSharedMemorySize, CH_SMEM);
        cudaFuncSetAttribute(k_setup, cudaFuncAttributePreferredSharedMemoryCarveout, 100);
        cudaFuncSetAttribute(k_rowf, cudaFuncAttributePreferredSharedMemoryCarveout, 100);
        cudaFuncSetAttribute(k_col, cudaFuncAttributePreferredSharedMemoryCarveout, 100);
        cudaFuncSetAttribute(k_chain, cudaFuncAttributePreferredSharedMemoryCarveout, 100);
        cudaFuncSetAttribute(k_help, cudaFuncAttributeMaxDynamicSharedMemorySize, HP_SMEM);
        cudaFuncSetAttribute(k_help, cudaFuncAttributePreferredSharedMemoryCarveout, 100);
        int dev = 0, sms = 0;
        cudaGetDevice(&dev);
        cudaDeviceGetAttribute(&sms, cudaDevAttrMultiProcessorCount, dev);
        nhelp = sms - 96 < 12 ? 12 : sms - 96;
        cudaGetSymbolAddress((void**)&xa, g_xa);
        cudaGetSymbolAddress((void**)&xb, g_xb);
    }
    const int na = nhelp - (nhelp >= 36 ? 24 : nhelp >= 28 ? 16 : 8), nbh = 14;
    cudaStream_t s0 = cudaStreamPerThread;
    cudaEventRecord(ev_fork, s0);
    cudaStreamWaitEvent(s1, ev_fork, 0);
    k_rowf<<<(96 + nhelp) & ~1, 256, RF_SMEM, s0>>>(x, 1, Wq, Wk, Wv, Wo);
    k_setup<<<NSETUP, 256, SU_SMEM, s1>>>(wr, wi, mem0);
    cudaEventRecord(ev_join, s1);
#define NLAYER 2
    for (int l = 0; l < NLAYER; l++) {
        const bf16* xin = l == 0 ? x : xb;
        if (l == 1) launch_pdl(k_rowf, 128, 256, RF_SMEM, s0, xin, 0, Wq, Wk, Wv, Wo);
        launch_pdl(k_col, 321, 128, l == 0 ? 0 : COL_PAD, s0, (int)(l == 0), Wq, Wk, Wv, Wo);
        launch_pdl(k_chain, 96, 384, CH_SMEM, s0, l, nhelp & ~3, 0u, Wq, Wk, Wv, Wo, (const bf16*)xa, l == 0 ? xb : out);
        launch_pdl(k_help, nhelp, 384, HP_SMEM, s0, xin, xa, l == 0 ? xb : out, l, na, nbh, 0, Wq, Wk, Wv, Wo);
    }
    cudaStreamWaitEvent(s0, ev_join, 0);
}
```

```cpp
#include <cuda_runtime.h>
#include <cuda_bf16.h>
#include <cuda_fp16.h>
#include <stdint.h>
#include <string.h>

namespace {

typedef __nv_bfloat16 bf16;
constexpr int S_ = 2048, D_ = 640, NSEG = 64;
constexpr int SPIN_LIM = 1 << 13;

__device__ float                  g_wmx[96];
__device__ __align__(1024) bf16   g_wot[4096 * 640];
__device__ __align__(16) float    g_co[1024];
__device__ __align__(256) uint2   g_stat[2 * 32 * 16 * 64];
__device__ float                  g_invM0;
__device__ __align__(16) float    g_wmax[128];
__device__ __align__(1024) char   g_redraw[65 * 32768];
constexpr int F_X = 2 * NSEG * 32, F_O = F_X + 2 * 128, NFLAG = F_O + 128, RING = 8;
constexpr int F_W = F_X + 66;
constexpr int NSETUP = 131;
struct __align__(256) Flag { unsigned v; };
__device__ Flag                   g_flag[NFLAG];
__device__ Flag                   g_ready[1];
__device__ __align__(1024) char   g_item[RING * 32 * 32768];
__device__ __align__(1024) bf16   g_O[S_ * 4096];
__device__ __align__(1024) __half g_xn[S_ * D_];
__device__ __align__(1024) bf16   g_xa[S_ * D_];
__device__ __align__(1024) bf16   g_xb[S_ * D_];
__device__ __align__(1024) __half g_UT[D_ * S_];
__device__ __align__(1024) __half g_YT[D_ * S_];
__device__ __align__(1024) __half g_ctab[64 * 128 + 64 * 64];
__device__ __align__(1024) uint32_t g_Wf[321 * 2048];

#define TL(i)
#define TLN 0
#define TLL 1
#define CK(i)
__device__ __forceinline__ uint32_t smem_u32(const void* p) { return (uint32_t)__cvta_generic_to_shared(p); }
__device__ __forceinline__ uint32_t mapa(uint32_t a, uint32_t r) { uint32_t o; asm("mapa.shared::cluster.u32 %0,%1,%2;" : "=r"(o) : "r"(a), "r"(r)); return o; }
__device__ __forceinline__ void mbar_init(uint32_t a, int c) { asm volatile("mbarrier.init.shared::cta.b64 [%0],%1;" ::"r"(a), "r"(c) : "memory"); }
__device__ __forceinline__ void mbar_expect(uint32_t a, int bytes) { asm volatile("mbarrier.arrive.expect_tx.shared::cta.b64 _,[%0],%1;" ::"r"(a), "r"(bytes) : "memory"); }
__device__ __forceinline__ void mbar_arrive(uint32_t a) { asm volatile("mbarrier.arrive.shared::cta.b64 _,[%0];" ::"r"(a) : "memory"); }
__device__ __forceinline__ bool mbar_try(uint32_t a, uint32_t par) {
    uint32_t p;
    asm volatile("{.reg .pred q; mbarrier.try_wait.parity.shared::cta.b64 q,[%1],%2; selp.u32 %0,1,0,q;}" : "=r"(p) : "r"(a), "r"(par) : "memory");
    return p;
}
__device__ __forceinline__ void mbar_wait(uint32_t a, uint32_t par) {
    if (!mbar_try(a, par)) {
        int lim = 0;
        while (!mbar_try(a, par) && ++lim < SPIN_LIM) {}
    }
}
__device__ __forceinline__ void mbar_sleep(uint32_t a, uint32_t par) {
    asm volatile("{.reg .pred q; .reg .u32 n; mov.u32 n,0;\n"
                 "W_LOOP: mbarrier.try_wait.parity.shared::cta.b64 q,[%0],%1,%2; add.u32 n,n,1; setp.lt.and.u32 q,n,%3,!q; @q bra W_LOOP;}"
                 ::"r"(a), "r"(par), "n"(20000), "n"(SPIN_LIM) : "memory");
}
__device__ __forceinline__ void bar_arrive(int id, int n) { asm volatile("bar.arrive %0,%1;" ::"r"(id), "r"(n) : "memory"); }
__device__ __forceinline__ uint32_t clock32() { uint32_t c; asm volatile("mov.u32 %0,%%clock;" : "=r"(c)); return c; }
__device__ __forceinline__ uint32_t read_tid() { uint32_t v; asm volatile("mov.u32 %0,%%tid.x;" : "=r"(v)); return v; }
__device__ __forceinline__ void bar_sync(int id, int n) { asm volatile("bar.sync %0,%1;" ::"r"(id), "r"(n) : "memory"); }
__device__ __forceinline__ void fence_async_smem() { asm volatile("fence.proxy.async.shared::cta;" ::: "memory"); }
__device__ __forceinline__ void fence_async_glb() { asm volatile("fence.proxy.async.global;" ::: "memory"); }
__device__ __forceinline__ void cluster_sync_full() { asm volatile("barrier.cluster.arrive.aligned; barrier.cluster.wait.aligned;" ::: "memory"); }
__device__ __forceinline__ void bulk_g2s(uint32_t dst, const void* src, int bytes, uint32_t mb) {
    asm volatile("cp.async.bulk.shared::cluster.global.mbarrier::complete_tx::bytes [%0],[%1],%2,[%3];" ::"r"(dst), "l"(src), "r"(bytes), "r"(mb) : "memory");
}
__device__ __forceinline__ void bulk_g2s_last(uint32_t dst, const void* src, int bytes, uint32_t mb) {
    asm volatile("{.reg .b64 p; createpolicy.fractional.L2::evict_first.b64 p, 1.0;\n"
                 "cp.async.bulk.shared::cluster.global.mbarrier::complete_tx::bytes.L2::cache_hint [%0],[%1],%2,[%3],p;}"
                 ::"r"(dst), "l"(src), "r"(bytes), "r"(mb) : "memory");
}
__device__ __forceinline__ void bulk_s2s(uint32_t dst, uint32_t src, int bytes, uint32_t mb) {
    asm volatile("cp.async.bulk.shared::cluster.shared::cta.mbarrier::complete_tx::bytes [%0],[%1],%2,[%3];" ::"r"(dst), "r"(src), "r"(bytes), "r"(mb) : "memory");
}
__device__ __forceinline__ void bulk_s2g(void* dst, uint32_t src, int bytes) {
    asm volatile("cp.async.bulk.global.shared::cta.bulk_group [%0],[%1],%2;" ::"l"(dst), "r"(src), "r"(bytes) : "memory");
}
__device__ __forceinline__ void cp_async16(uint32_t dst, const void* src, uint32_t bytes = 16) {
    asm volatile("cp.async.cg.shared.global [%0],[%1],16,%2;" ::"r"(dst), "l"(src), "r"(bytes) : "memory");
}
__device__ __forceinline__ void cp_commit() { asm volatile("cp.async.commit_group;" ::: "memory"); }
template <int N> __device__ __forceinline__ void cp_wait() { asm volatile("cp.async.wait_group %0;" ::"n"(N) : "memory"); }
__device__ __forceinline__ void bulk_commit() { asm volatile("cp.async.bulk.commit_group;" ::: "memory"); }
__device__ __forceinline__ void bulk_wait0() { asm volatile("cp.async.bulk.wait_group 0;" ::: "memory"); }
__device__ __forceinline__ void ldsm4(uint32_t* r, uint32_t a) {
    asm volatile("ldmatrix.sync.aligned.m8n8.x4.shared.b16 {%0,%1,%2,%3},[%4];" : "=r"(r[0]), "=r"(r[1]), "=r"(r[2]), "=r"(r[3]) : "r"(a) : "memory");
}
__device__ __forceinline__ void ldsm4t(uint32_t* r, uint32_t a) {
    asm volatile("ldmatrix.sync.aligned.m8n8.x4.trans.shared.b16 {%0,%1,%2,%3},[%4];" : "=r"(r[0]), "=r"(r[1]), "=r"(r[2]), "=r"(r[3]) : "r"(a) : "memory");
}
__device__ __forceinline__ void stsm4(uint32_t a, uint32_t r0, uint32_t r1, uint32_t r2, uint32_t r3) {
    asm volatile("stmatrix.sync.aligned.m8n8.x4.shared.b16 [%0],{%1,%2,%3,%4};" ::"r"(a), "r"(r0), "r"(r1), "r"(r2), "r"(r3) : "memory");
}
__device__ __forceinline__ void stsm4t(uint32_t a, uint32_t r0, uint32_t r1, uint32_t r2, uint32_t r3) {
    asm volatile("stmatrix.sync.aligned.m8n8.x4.trans.shared.b16 [%0],{%1,%2,%3,%4};" ::"r"(a), "r"(r0), "r"(r1), "r"(r2), "r"(r3) : "memory");
}
__device__ __forceinline__ void lds128(uint32_t* r, uint32_t a) {
    asm volatile("ld.shared.v4.b32 {%0,%1,%2,%3},[%4];" : "=r"(r[0]), "=r"(r[1]), "=r"(r[2]), "=r"(r[3]) : "r"(a) : "memory");
}
__device__ __forceinline__ void lds64(uint32_t* r, uint32_t a) {
    asm volatile("ld.shared.v2.b32 {%0,%1},[%2];" : "=r"(r[0]), "=r"(r[1]) : "r"(a) : "memory");
}
__device__ __forceinline__ uint32_t lds32(uint32_t a) { uint32_t v; asm volatile("ld.shared.b32 %0,[%1];" : "=r"(v) : "r"(a) : "memory"); return v; }
__device__ __forceinline__ void sts128(uint32_t a, uint32_t r0, uint32_t r1, uint32_t r2, uint32_t r3) {
    asm volatile("st.shared.v4.b32 [%0],{%1,%2,%3,%4};" ::"r"(a), "r"(r0), "r"(r1), "r"(r2), "r"(r3) : "memory");
}
__device__ __forceinline__ void sts64(uint32_t a, uint32_t v0, uint32_t v1) { asm volatile("st.shared.v2.b32 [%0],{%1,%2};" ::"r"(a), "r"(v0), "r"(v1) : "memory"); }
[[maybe_unused]] __device__ __forceinline__ void sts32(uint32_t a, uint32_t v) { asm volatile("st.shared.b32 [%0],%1;" ::"r"(a), "r"(v) : "memory"); }
#define AU_(op) "{.reg .u32 t; add.u32 t,%4,%5; " op " {%0,%1,%2,%3},[t+%6];}"
template <int I> __device__ __forceinline__ void ldsm4_u(uint32_t* r, uint32_t a, uint32_t u) {
    asm volatile(AU_("ldmatrix.sync.aligned.m8n8.x4.shared.b16") : "=r"(r[0]), "=r"(r[1]), "=r"(r[2]), "=r"(r[3]) : "r"(a), "r"(u), "n"(I) : "memory");
}
template <int I> __device__ __forceinline__ void ldsm4t_u(uint32_t* r, uint32_t a, uint32_t u) {
    asm volatile(AU_("ldmatrix.sync.aligned.m8n8.x4.trans.shared.b16") : "=r"(r[0]), "=r"(r[1]), "=r"(r[2]), "=r"(r[3]) : "r"(a), "r"(u), "n"(I) : "memory");
}
template <int I> __device__ __forceinline__ void lds128_u(uint32_t* r, uint32_t a, uint32_t u) {
    asm volatile(AU_("ld.shared.v4.b32") : "=r"(r[0]), "=r"(r[1]), "=r"(r[2]), "=r"(r[3]) : "r"(a), "r"(u), "n"(I) : "memory");
}
template <int I> __device__ __forceinline__ void lds64_u(uint32_t* r, uint32_t a, uint32_t u) {
    asm volatile("{.reg .u32 t; add.u32 t,%2,%3; ld.shared.v2.b32 {%0,%1},[t+%4];}" : "=r"(r[0]), "=r"(r[1]) : "r"(a), "r"(u), "n"(I) : "memory");
}
template <int I> __device__ __forceinline__ uint32_t lds32_u(uint32_t a, uint32_t u) {
    uint32_t v;
    asm volatile("{.reg .u32 t; add.u32 t,%1,%2; ld.shared.b32 %0,[t+%3];}" : "=r"(v) : "r"(a), "r"(u), "n"(I) : "memory");
    return v;
}
template <int I> __device__ __forceinline__ void sts64_u(uint32_t a, uint32_t u, uint32_t v0, uint32_t v1) {
    asm volatile("{.reg .u32 t; add.u32 t,%0,%1; st.shared.v2.b32 [t+%2],{%3,%4};}" ::"r"(a), "r"(u), "n"(I), "r"(v0), "r"(v1) : "memory");
}
template <int I> __device__ __forceinline__ void sts32_u(uint32_t a, uint32_t u, uint32_t v) {
    asm volatile("{.reg .u32 t; add.u32 t,%0,%1; st.shared.b32 [t+%2],%3;}" ::"r"(a), "r"(u), "n"(I), "r"(v) : "memory");
}
template <int I> __device__ __forceinline__ void sts16_u(uint32_t a, uint32_t u, uint32_t v) {
    asm volatile("{.reg .u32 t; add.u32 t,%0,%1; st.shared.b16 [t+%2],%3;}" ::"r"(a), "r"(u), "n"(I), "h"((unsigned short)v) : "memory");
}
template <int I> __device__ __forceinline__ void sts128_u(uint32_t a, uint32_t u, uint32_t r0, uint32_t r1, uint32_t r2, uint32_t r3) {
    asm volatile("{.reg .u32 t; add.u32 t,%0,%1; st.shared.v4.b32 [t+%2],{%3,%4,%5,%6};}" ::"r"(a), "r"(u), "n"(I), "r"(r0), "r"(r1), "r"(r2), "r"(r3) : "memory");
}
template <int I> __device__ __forceinline__ void stsm4_u(uint32_t a, uint32_t u, uint32_t r0, uint32_t r1, uint32_t r2, uint32_t r3) {
    asm volatile("{.reg .u32 t; add.u32 t,%0,%1; stmatrix.sync.aligned.m8n8.x4.shared.b16 [t+%2],{%3,%4,%5,%6};}"
                 ::"r"(a), "r"(u), "n"(I), "r"(r0), "r"(r1), "r"(r2), "r"(r3) : "memory");
}
__device__ __forceinline__ void st_share2(uint32_t a, uint32_t u, uint32_t mb, uint32_t d0, uint32_t d1, uint32_t v0, uint32_t v1) {
    asm volatile("{.reg .pred p; .reg .u32 t,x,y; add.u32 t,%0,%1;\n"
                 "add.u32 x,t,%3; add.u32 y,%2,%3; st.async.shared::cluster.mbarrier::complete_tx::bytes.v2.b32 [x],{%5,%6},[y];\n"
                 "add.u32 x,t,%4; add.u32 y,%2,%4; st.async.shared::cluster.mbarrier::complete_tx::bytes.v2.b32 [x],{%5,%6},[y];\n"
                 "st.shared.v2.b32 [t],{%5,%6}; bar.warp.sync -1; setp.eq.u32 p,%0,0; @p mbarrier.arrive.shared::cta.b64 _,[%2];}"
                 ::"r"(a), "r"(u), "r"(mb), "r"(d0), "r"(d1), "r"(v0), "r"(v1) : "memory");
}
template <int V> struct IC { __host__ __device__ constexpr operator int() const { return V; } };
template <int N, class F> __device__ __forceinline__ void sfor(F f) {
    if constexpr (N > 0) { sfor<N - 1>(f); f(IC<N - 1>()); }
}
__device__ __forceinline__ void mma_f16(float* d, const uint32_t* a, uint32_t b0, uint32_t b1) {
    asm volatile("mma.sync.aligned.m16n8k16.row.col.f32.f16.f16.f32 {%0,%1,%2,%3},{%4,%5,%6,%7},{%8,%9},{%0,%1,%2,%3};"
                 : "+f"(d[0]), "+f"(d[1]), "+f"(d[2]), "+f"(d[3]) : "r"(a[0]), "r"(a[1]), "r"(a[2]), "r"(a[3]), "r"(b0), "r"(b1));
}
__device__ __forceinline__ void mma_bf(float* d, uint32_t a0, uint32_t a1, uint32_t a2, uint32_t a3, uint32_t b0, uint32_t b1) {
    asm volatile("mma.sync.aligned.m16n8k16.row.col.f32.bf16.bf16.f32 {%0,%1,%2,%3},{%4,%5,%6,%7},{%8,%9},{%0,%1,%2,%3};"
                 : "+f"(d[0]), "+f"(d[1]), "+f"(d[2]), "+f"(d[3]) : "r"(a0), "r"(a1), "r"(a2), "r"(a3), "r"(b0), "r"(b1));
}
__device__ __forceinline__ void mma_bf8(float* d, uint32_t a0, uint32_t a1, uint32_t b0) {
    asm volatile("mma.sync.aligned.m16n8k8.row.col.f32.bf16.bf16.f32 {%0,%1,%2,%3},{%4,%5},{%6},{%0,%1,%2,%3};"
                 : "+f"(d[0]), "+f"(d[1]), "+f"(d[2]), "+f"(d[3]) : "r"(a0), "r"(a1), "r"(b0));
}
__device__ __forceinline__ uint32_t pack_bf(float lo, float hi) { uint32_t r; asm("cvt.rn.bf16x2.f32 %0,%1,%2;" : "=r"(r) : "f"(hi), "f"(lo)); return r; }
__device__ __forceinline__ uint32_t pack_h(float lo, float hi) { uint32_t r; asm("cvt.rn.f16x2.f32 %0,%1,%2;" : "=r"(r) : "f"(hi), "f"(lo)); return r; }
__device__ __forceinline__ float bf_lo(uint32_t v) { return __uint_as_float(v << 16); }
__device__ __forceinline__ float bf_hi(uint32_t v) { return __uint_as_float(v & 0xffff0000u); }
__device__ __forceinline__ uint32_t bfma(uint32_t a, uint32_t b, uint32_t c) { uint32_t r; asm("fma.rn.bf16x2 %0,%1,%2,%3;" : "=r"(r) : "r"(a), "r"(b), "r"(c)); return r; }
__device__ __forceinline__ uint4 add_bf8(const uint4 x, const uint32_t* y, const uint32_t k = 0x3f803f80u) {
    return make_uint4(bfma(y[0], k, x.x), bfma(y[1], k, x.y), bfma(y[2], k, x.z), bfma(y[3], k, x.w));
}
__device__ __forceinline__ float ex2(float x) { float r; asm("ex2.approx.ftz.f32 %0,%1;" : "=f"(r) : "f"(x)); return r; }
__device__ __forceinline__ float rcp(float x) { float r; asm("rcp.approx.ftz.f32 %0,%1;" : "=f"(r) : "f"(x)); return r; }
__device__ __forceinline__ void wg_fence() { asm volatile("wgmma.fence.sync.aligned;" ::: "memory"); }
__device__ __forceinline__ void wg_commit() { asm volatile("wgmma.commit_group.sync.aligned;" ::: "memory"); }
template <int N> __device__ __forceinline__ void wg_wait() { asm volatile("wgmma.wait_group.sync.aligned %0;" ::"n"(N) : "memory"); }
__device__ __forceinline__ uint64_t mkdesc(uint32_t a, uint32_t lbo, uint32_t sbo, uint32_t sw) {
    return (uint64_t)((a & 0x3FFFF) >> 4) | ((uint64_t)(lbo >> 4) << 16) | ((uint64_t)(sbo >> 4) << 32) | ((uint64_t)sw << 62);
}
#define F4(d, i) "+f"(d[i]), "+f"(d[i + 1]), "+f"(d[i + 2]), "+f"(d[i + 3])
#define F8(d, i) F4(d, i), F4(d, i + 4)
#define F16(d, i) F8(d, i), F8(d, i + 8)
template <int OFF, int SC> __device__ __forceinline__ void wg_n32_x(float* d, const uint32_t* a, uint32_t lo) {
    asm volatile("{.reg .pred p; .reg .b32 l; .reg .b64 q; setp.ne.b32 p,%22,0; add.u32 l,%20,%21; mov.b64 q,{l,8};\n"
                 "wgmma.mma_async.sync.aligned.m64n32k16.f32.f16.f16 "
                 "{%0,%1,%2,%3,%4,%5,%6,%7,%8,%9,%10,%11,%12,%13,%14,%15},{%16,%17,%18,%19},q,p,1,1,0;}"
                 : F16(d, 0) : "r"(a[0]), "r"(a[1]), "r"(a[2]), "r"(a[3]), "r"(lo), "n"(OFF), "n"(SC));
}
__device__ __forceinline__ void wg_n128_rs(float* d, const uint32_t* a, uint64_t db, int sc) {
    asm volatile("{.reg .pred p; setp.ne.b32 p,%69,0; wgmma.mma_async.sync.aligned.m64n128k16.f32.f16.f16 "
                 "{%0,%1,%2,%3,%4,%5,%6,%7,%8,%9,%10,%11,%12,%13,%14,%15,%16,%17,%18,%19,%20,%21,%22,%23,%24,%25,%26,%27,%28,%29,%30,%31,"
                 "%32,%33,%34,%35,%36,%37,%38,%39,%40,%41,%42,%43,%44,%45,%46,%47,%48,%49,%50,%51,%52,%53,%54,%55,%56,%57,%58,%59,%60,%61,%62,%63},"
                 "{%64,%65,%66,%67},%68,p,1,1,0;}"
                 : F16(d, 0), F16(d, 16), F16(d, 32), F16(d, 48) : "r"(a[0]), "r"(a[1]), "r"(a[2]), "r"(a[3]), "l"(db), "r"(sc));
}
#define N80_REGS "{%0,%1,%2,%3,%4,%5,%6,%7,%8,%9,%10,%11,%12,%13,%14,%15,%16,%17,%18,%19,%20,%21,%22,%23,%24,%25,%26,%27,%28,%29,%30,%31,%32,%33,%34,%35,%36,%37,%38,%39}"
__device__ __forceinline__ void wg_n80_ss(float* d, uint64_t da, uint64_t db, int sc) {
    asm volatile("{.reg .pred p; setp.ne.b32 p,%42,0; wgmma.mma_async.sync.aligned.m64n80k16.f32.bf16.bf16 " N80_REGS ",%40,%41,p,1,1,0,0;}"
                 : F16(d, 0), F16(d, 16), F8(d, 32) : "l"(da), "l"(db), "r"(sc));
}
__device__ __forceinline__ void wg_n88_ss(float* d, uint64_t da, uint64_t db, int sc) {
    asm volatile("{.reg .pred p; setp.ne.b32 p,%46,0; wgmma.mma_async.sync.aligned.m64n88k16.f32.f16.f16 "
                 "{%0,%1,%2,%3,%4,%5,%6,%7,%8,%9,%10,%11,%12,%13,%14,%15,%16,%17,%18,%19,%20,%21,%22,%23,%24,%25,%26,%27,%28,%29,%30,%31,"
                 "%32,%33,%34,%35,%36,%37,%38,%39,%40,%41,%42,%43},%44,%45,p,1,1,0,0;}"
                 : F16(d, 0), F16(d, 16), F8(d, 32), F4(d, 40) : "l"(da), "l"(db), "r"(sc));
}
__device__ __forceinline__ void wg_n48_ss_ta(float* d, uint64_t da, uint64_t db, int sc) {
    asm volatile("{.reg .pred p; setp.ne.b32 p,%26,0; wgmma.mma_async.sync.aligned.m64n48k16.f32.f16.f16 "
                 "{%0,%1,%2,%3,%4,%5,%6,%7,%8,%9,%10,%11,%12,%13,%14,%15,%16,%17,%18,%19,%20,%21,%22,%23},%24,%25,p,1,1,1,0;}"
                 : F16(d, 0), F8(d, 16) : "l"(da), "l"(db), "r"(sc));
}
template <int TA> __device__ __forceinline__ void wg_n64_ss_tb(float* d, uint64_t da, uint64_t db, int sc) {
    asm volatile("{.reg .pred p; setp.ne.b32 p,%34,0; wgmma.mma_async.sync.aligned.m64n64k16.f32.f16.f16 "
                 "{%0,%1,%2,%3,%4,%5,%6,%7,%8,%9,%10,%11,%12,%13,%14,%15,%16,%17,%18,%19,%20,%21,%22,%23,%24,%25,%26,%27,%28,%29,%30,%31},"
                 "%32,%33,p,1,1,%35,1;}"
                 : F16(d, 0), F16(d, 16) : "l"(da), "l"(db), "r"(sc), "n"(TA));
}
__device__ __forceinline__ void pdl_wait() { asm volatile("griddepcontrol.wait;" ::: "memory"); }
__device__ __forceinline__ void pdl_go() { asm volatile("griddepcontrol.launch_dependents;" ::: "memory"); }
__device__ __forceinline__ float cos640(float p) {
    const float q = fmaf(p, 0.0015625f, 12582912.f) - 12582912.f;
    return __cosf(fmaf(q, -640.f, p) * 0.009817477042468103f);
}
__device__ __forceinline__ uint4 cos_row8(float p0, float step, float amp = 1.f) {
    float v[8];
    const float k = 2.f * cos640(step);
    v[0] = amp * cos640(p0); v[1] = amp * cos640(p0 + step);
#pragma unroll
    for (int i = 2; i < 8; i++) v[i] = fmaf(k, v[i - 1], -v[i - 2]);
    return make_uint4(pack_h(v[0], v[1]), pack_h(v[2], v[3]), pack_h(v[4], v[5]), pack_h(v[6], v[7]));
}
__device__ __forceinline__ float wfilter_max(int lane) {
    float m = fmaxf(fmaxf(g_wmax[lane], g_wmax[lane + 32]), fmaxf(g_wmax[lane + 64], g_wmax[lane + 96]));
    return __uint_as_float(__reduce_max_sync(~0u, __float_as_uint(m)));
}
__device__ __forceinline__ unsigned ld_acquire(const Flag* p) { unsigned v; asm volatile("ld.acquire.gpu.global.u32 %0,[%1];" : "=r"(v) : "l"(p) : "memory"); return v; }
#define POLL_NS 200
template <int NS = POLL_NS> __device__ __forceinline__ void wait_flag(const Flag* p, unsigned v) {
    if (ld_acquire(p) >= v) return;
    unsigned x;
    int lim = 0;
    do {
        __nanosleep(NS);
        asm volatile("ld.relaxed.gpu.global.u32 %0,[%1];" : "=r"(x) : "l"(p) : "memory");
    } while (x < v && ++lim < SPIN_LIM);
    ld_acquire(p);
}
__device__ __forceinline__ void prefetch_l2(const void* p, int bytes) { asm volatile("cp.async.bulk.prefetch.L2.global [%0],%1;" ::"l"(p), "r"(bytes) : "memory"); }
__device__ __forceinline__ void red_release(Flag* p) { asm volatile("red.release.gpu.global.add.u32 [%0],1;" ::"l"(p) : "memory"); }
__device__ __forceinline__ void red_relaxed(Flag* p) { asm volatile("red.relaxed.gpu.global.add.u32 [%0],1;" ::"l"(p) : "memory"); }
__device__ __forceinline__ void red_h8(void* p, uint32_t a, uint32_t b, uint32_t c, uint32_t d) {
    asm volatile("red.relaxed.gpu.global.add.noftz.v4.f16x2 [%0],{%1,%2,%3,%4};" ::"l"(p), "r"(a), "r"(b), "r"(c), "r"(d) : "memory");
}
__device__ __forceinline__ float pow2_scale(float bound, int top, float* inv) {
    int e = (int)((__float_as_uint(bound) >> 23) & 0xff) - 126;
    int k = top - e;
    k = max(-100, min(100, k));
    *inv = __uint_as_float((uint32_t)(127 - k) << 23);
    return __uint_as_float((uint32_t)(127 + k) << 23);
}
__device__ __forceinline__ char* red_base() { return (char*)(((uintptr_t)g_redraw + 32767) & ~(uintptr_t)32767); }

__device__ __forceinline__ void setup_a(char* sm, const int b, const bf16* __restrict__ wr, const bf16* __restrict__ wi) {
    const int tid = threadIdx.x, lane = tid & 31;
    const uint32_t sb = smem_u32(sm);
    auto row_byte = [&](int q) { return ((b >> 2) + 32 * ((q >> 1) * 8 + 2 * (b & 3) + (q & 1))) * 642; };
#pragma unroll 1
    for (int r = tid >> 5; r < 32; r += 8) {
        const char* src = (const char*)(r < 16 ? wr : wi) + (row_byte(r & 15) & ~15);
        cp_async16(sb + r * 672 + lane * 16, src + lane * 16);
        if (lane < 9) cp_async16(sb + r * 672 + 512 + lane * 16, src + 512 + lane * 16);
    }
    ((uint4*)g_stat)[b * 256 + tid] = make_uint4(0, 0, 0, 0);
    if (tid < 2 * (NFLAG / 128)) ((uint4*)(g_flag + b * (NFLAG / 128) + (tid >> 1)))[tid & 1] = make_uint4(0, 0, 0, 0);
    if (tid < 12) {
        const int i = b * 12 + tid;
        const int f = ((i >> 4) & 3) * 8 + (i & 7), im = (i >> 3) & 1, part = (i >> 8) & 1;
        ((uint4*)g_ctab)[i] = cos_row8((float)(i < 1024 ? (i >> 7) * 80 * (i & 63) + ((i & 64) ? 480 : 0) : ((i >> 6) & 3) * 160 * f + (im == part ? 0 : im ? 160 : 480)),
                                       (float)(i < 1024 ? 10 * (i & 63) : 20 * f));
    }
    asm volatile("cp.async.wait_all;" ::: "memory");
    __syncthreads();
    const int q0 = (tid & 3) * 4;
    const char* rp[4];
#pragma unroll
    for (int u = 0; u < 4; u++) rp[u] = sm + (q0 + u) * 672 + (row_byte(q0 + u) & 15);
    uint32_t mx = 0;
#pragma unroll 2
    for (int c = tid >> 2; c < 321; c += 64) {
        uint32_t v[4];
#pragma unroll
        for (int u = 0; u < 4; u++) {
            v[u] = ((const unsigned short*)rp[u])[c] | ((uint32_t)((const unsigned short*)(rp[u] + 16 * 672))[c] << 16);
            mx = __vmaxu2(mx, v[u] & 0x7fff7fffu);
        }
        ((uint4*)g_Wf)[(size_t)c * 512 + b * 4 + ((tid ^ (b >> 1)) & 3)] = make_uint4(v[0], v[1], v[2], v[3]);
    }
    mx = __reduce_max_sync(~0u, max(mx & 0xffffu, mx >> 16));
    __syncthreads();
    if (lane == 0) ((uint32_t*)sm)[tid >> 5] = mx;
    __syncthreads();
    if (tid < 32) {
        mx = __reduce_max_sync(~0u, ((uint32_t*)sm)[lane & 7]);
        if (tid == 0) g_wmax[b] = __uint_as_float(mx << 16);
    }
}
__device__ __forceinline__ void setup_b(const int b, const bf16* __restrict__ mem0) {
    const int tid = threadIdx.x;
    uint4* z = (uint4*)red_base();
    if (b < 3) {
        const int w = tid >> 5, lane = tid & 31, p = b * 2 + ((w >> 1) & 1), odd = w & 1;
        uint32_t mx = 0;
#pragma unroll 4
        for (int i = lane; i < 640; i += 32) {
            const uint4 u = ((const uint4*)mem0)[i];
            mx = __vmaxu2(__vmaxu2(mx, u.x & 0x7fff7fffu), __vmaxu2(__vmaxu2(u.y & 0x7fff7fffu, u.z & 0x7fff7fffu), u.w & 0x7fff7fffu));
        }
        float inv, v[7];
        const float sc = pow2_scale(__uint_as_float(__reduce_max_sync(~0u, max(mx & 0xffffu, mx >> 16)) << 16), 14, &inv);
        if (tid == 0) g_invM0 = inv;
#pragma unroll
        for (int j = 0; j < 7; j++) {
            const int r = p * 56 + (j < 6 ? odd * 32 + (j >> 1) * 8 : 24) + (lane >> 2), mr = 2 * (lane & 3) + (j < 6 ? (j & 1) : odd);
            v[j] = r < 320 ? __bfloat162float(mem0[mr * 640 + (w >> 2) * 320 + r]) * sc : 0.f;
        }
        const int off = w * 2048 + (lane >> 4) * 1024 + ((lane >> 3) & 1) * 256 + (lane & 7) * 16 + (b == 2 ? (w >> 1) * 4096 + 128 : b * 16384);
        const uint4 u = make_uint4(pack_h(v[0], v[1]), pack_h(v[2], v[3]), pack_h(v[4], v[5]), pack_h(v[6], 32.f));
        z[off >> 4] = u; z[65536 + (off >> 4)] = u;
    }
}

#define SU_PAD 40960
constexpr int SU_SMEM = SU_PAD;
__global__ void __launch_bounds__(256, 4) k_setup(const bf16* __restrict__ wr, const bf16* __restrict__ wi, const bf16* __restrict__ mem0) {
    extern __shared__ __align__(1024) char sm[];
    TL(0);
    if (blockIdx.x >= 128) setup_b(blockIdx.x - 128, mem0);
    else setup_a(sm, blockIdx.x, wr, wi);
    __syncthreads();
    if (threadIdx.x == 0) red_release(g_ready);
    TL(1);
}
__device__ __forceinline__ float weight_scale(int h, int ty, float* inv) { return pow2_scale(__ldcg(g_wmx + h * 3 + ty), 6, inv); }

#define STR_(x) #x
#define STR(x) STR_(x)
#define RF_U 1
constexpr int RF_A = 22 * 2816, RF_X = RF_A + 22 * 1024, RF_BAR = RF_X + 64 * 1344, RF_SMEM = RF_BAR + 64;
__global__ void __cluster_dims__(2, 1, 1) __launch_bounds__(256, 2) k_rowf(const bf16* x, const int first) {
    extern __shared__ __align__(1024) char sm[];
    TL(first ? 2 : 16);
    const int tid = threadIdx.x, w = tid >> 5, lane = tid & 31, g = lane >> 2, t = lane & 3;
    if (blockIdx.x >= 128) { __nanosleep(2500); return; }
    const int a = blockIdx.x >> 2, gq = blockIdx.x & 3;
    const uint32_t sb = smem_u32(sm), mb = sb + RF_BAR + w * 8;
    if (lane == 0) {
        mbar_init(mb, 1);
        asm volatile("fence.mbarrier_init.release.cluster;" ::: "memory");
        mbar_expect(mb, 8 * 1280);
    }
    __syncwarp();
    asm volatile("barrier.cluster.arrive.relaxed.aligned;" ::: "memory");
#pragma unroll 1
    for (int ph = 0; ph < 2; ph++) {
        if (ph != first) {
            asm volatile("barrier.cluster.wait.aligned;" ::: "memory");
            pdl_wait();
            TL(first ? 3 : 17);
            if (lane < 4)
                asm volatile("cp.async.bulk.shared::cluster.global.mbarrier::complete_tx::bytes.multicast::cluster [%0],[%1],1280,[%2],%3;"
                             ::"r"(sb + RF_X + (w * 8 + (gq & 1) * 4 + lane) * 1344), "l"(x + (size_t)(a * 64 + w * 8 + (gq & 1) * 4 + lane) * 640), "r"(mb),
                             "h"((unsigned short)3) : "memory");
            __syncwarp();
            pdl_go();
        } else {
#pragma unroll 3
            for (int id = tid; id < 22 * 176; id += 256) {
                const int kg = id / 176, n = id - kg * 176;
                const float c = (float)(2 * n + (gq & 1));
                *(uint4*)(sm + id * 16) = cos_row8(fmaf((float)(kg * 8), c, (float)((gq & 2) * 80)), c, 0.03952847075210474f);
            }
        }
    }
    mbar_wait(mb, 0);
    const uint32_t row = sb + RF_X + (w * 8 + g) * 1344;
    float st[4][4] = {};
#pragma unroll 1
    for (int i = 0; i < 20; i += 4) {
        uint32_t u[4][4];
#pragma unroll
        for (int q = 0; q < 4; q++) lds128(u[q], row + (4 * (i + q) + t) * 16);
#pragma unroll
        for (int q = 0; q < 4; q++) {
            mma_bf(st[(q & 1) * 2], u[q][0], 0x3f803f80u, u[q][1], 0x3f803f80u, u[q][0], u[q][1]);
            mma_bf(st[(q & 1) * 2 + 1], u[q][2], 0x3f803f80u, u[q][3], 0x3f803f80u, u[q][2], u[q][3]);
        }
    }
#pragma unroll
    for (int q = 0; q < 4; q++) { st[0][q] += st[2][q]; st[1][q] += st[3][q]; }
    const float sq = __shfl_sync(~0u, (g & 1) ? st[0][1] + st[1][1] : st[0][0] + st[1][0], g * 4 + (g >> 1));
    const float mean = __shfl_sync(~0u, (g & 1) ? st[0][3] + st[1][3] : st[0][2] + st[1][2], g * 4 + (g >> 1)) * (1.f / 640.f);
    const float r = rsqrtf(fmaxf(fmaf(-mean, mean, sq * (1.f / 640.f)), 0.f) + 1e-5f), off = gq == 0 ? -4.f * mean * r : 0.f;
    const float r1 = (gq == 1 || gq == 2) ? -r : r, r2 = (gq & 1) ? -r : r, r3 = gq >= 2 ? -r : r;
    const uint32_t aa = sb + RF_A + w * 128 + g * 16;
    auto el = [&](int d) { unsigned short v; asm volatile("ld.shared.u16 %0,[%1];" : "=h"(v) : "r"(row + d * 2)); return __uint_as_float((uint32_t)v << 16); };
_Pragma(STR(unroll RF_U))
    for (int i = 0; i < 5; i++) {
        const int ch = t + 4 * i;
        uint32_t u[4][4];
        lds128(u[0], row + ch * 16); lds128(u[1], row + (39 - ch) * 16); lds128(u[2], row + (40 + ch) * 16); lds128(u[3], row + (79 - ch) * 16);
        const float nb0 = el(320 - 8 * ch), nb1 = el(ch ? 640 - 8 * ch : 0);
        float o[8];
#pragma unroll
        for (int q = 0; q < 8; q++) {
            const int m = (8 - q) >> 1;
            const float e0 = (q & 1) ? bf_hi(u[0][q >> 1]) : bf_lo(u[0][q >> 1]), e2 = (q & 1) ? bf_hi(u[2][q >> 1]) : bf_lo(u[2][q >> 1]);
            const float e1 = q == 0 ? nb0 : (q & 1) ? bf_hi(u[1][m & 3]) : bf_lo(u[1][m & 3]), e3 = q == 0 ? nb1 : (q & 1) ? bf_hi(u[3][m & 3]) : bf_lo(u[3][m & 3]);
            o[q] = fmaf(e3, r3, fmaf(e2, r2, fmaf(e1, r1, fmaf(e0, r, off))));
        }
        if (ch == 0) o[0] *= 0.5f;
        sts128(aa + ch * 1024, pack_h(o[0], o[1]), pack_h(o[2], o[3]), pack_h(o[4], o[5]), pack_h(o[6], o[7]));
    }
    if (t < 2) sts128(aa + (20 + t) * 1024, t == 0 ? pack_h(fmaf(el(480), r2, fmaf(el(160), r, 0.5f * off)), 0.f) : 0u, 0u, 0u, 0u);
    fence_async_smem();
    __syncthreads();
    const int wg = w >> 2;
    float acc[44];
    uint64_t da = mkdesc(sb + RF_A, 1024, 128, 0), db = mkdesc(sb + wg * 1408, 2816, 128, 0);
    wg_fence();
#pragma unroll 1
    for (int k = 0; k < 11; k++) { wg_n88_ss(acc, da, db, k); da += 128; db += 352; }
    wg_commit(); wg_wait<0>();
    const uint32_t stg = sb + RF_X + wg * 96 * 144;
#pragma unroll
    for (int j = 0; j < 12; j += 2) {
        const int m = lane >> 3, j1 = j < 10 ? j + 1 : j;
        stsm4t(stg + ((j + (m >> 1)) * 8 + (lane & 7)) * 144 + ((w & 3) * 16 + (m & 1) * 8) * 2, pack_h(acc[j * 4], acc[j * 4 + 1]),
               pack_h(acc[j * 4 + 2], acc[j * 4 + 3]), pack_h(acc[j1 * 4], acc[j1 * 4 + 1]), pack_h(acc[j1 * 4 + 2], acc[j1 * 4 + 3]));
    }
    bar_sync(1 + wg, 128);
#pragma unroll 3
    for (int rr = (tid & 127) >> 3; rr < 88; rr += 16) {
        const int ch = tid & 7, c = 2 * (wg * 88 + rr) + (gq & 1);
        if (c <= 320 - (gq >> 1) && (c | (gq ^ 2))) {
            uint32_t u[4];
            lds128(u, stg + rr * 144 + ch * 16);
            ((uint4*)g_UT)[((size_t)(c == 320 ? 1 : 2 * c + (gq >> 1)) * 32 + a) * 8 + (ch ^ (a & 7))] = make_uint4(u[0], u[1], u[2], u[3]);
        }
    }
    TL(first ? 4 : 18);
}

constexpr int GST = 4, GSTB = 32768 + 20480, GNC = 32;
constexpr int G_BAR = GST * GSTB + 3072;
#define GPACE 1100
#define GPACE2 650
__device__ __forceinline__ void oproj_load(const uint32_t sb, const int op, const int mb, const int nb, const int c0, const uint32_t pace) {
    const int by = op == 2 ? 20480 : 16384;
    const char* src = op == 2 ? (const char*)g_wot + (size_t)nb * GNC * 20480 : (const char*)g_O + (size_t)(2 * mb + op) * GNC * 16384;
    uint32_t t0 = clock32() - pace + op * (pace / 3);
#pragma unroll 1
    for (int c = c0; c < c0 + GNC; c++, src += by) {
        const int st = c % GST;
        if (c >= GST) mbar_wait(sb + G_BAR + (GST + st) * 8, ((c / GST) - 1) & 1);
        while (clock32() - t0 < pace) {}
        t0 = clock32();
        const int by_ = by;
        mbar_expect(sb + G_BAR + st * 8, by_);
        if (op == 2) bulk_g2s(sb + st * GSTB + 32768, src, by_, sb + G_BAR + st * 8);
        else bulk_g2s_last(sb + st * GSTB + op * 16384, src, by_, sb + G_BAR + st * 8);
    }
}
__device__ __forceinline__ void oproj_mma(const uint32_t sb, const int mb, const int nb, const int c0, const bf16* res, bf16* out) {
    const int w = threadIdx.x >> 5, lane = threadIdx.x & 31, wg = w >> 2;
    float acc[40];
    uint4 rv[5];
#pragma unroll 1
    for (int c = c0; c < c0 + GNC; c++) {
        const int st = c % GST;
        mbar_wait(sb + G_BAR + st * 8, (c / GST) & 1);
        const uint32_t d = sb + st * GSTB;
        wg_fence();
#pragma unroll
        for (int k = 0; k < 8; k++)
            wg_n80_ss(acc, mkdesc(d + wg * 16384 + k * 2048, 1024, 128, 0), mkdesc(d + 32768 + k * 2560, 1280, 128, 0), (c - c0) | k);
        wg_commit();
        if (c > c0) {
            wg_wait<1>();
            if (lane == 0) mbar_arrive(sb + G_BAR + (GST + (c - 1) % GST) * 8);
        }
    }
#pragma unroll
    for (int i = 0; i < 5; i++) {
        const int id = i * 32 + lane, r = id / 10;
        rv[i] = __ldcg((const uint4*)res + (size_t)(mb * 128 + w * 16 + r) * 80 + nb * 10 + id - r * 10);
    }
    wg_wait<0>();
    bar_sync(5, 256);
    const uint32_t stg = sb + (GST - 1) * GSTB + w * 16 * 176;
#pragma unroll
    for (int j = 0; j < 5; j++)
        stsm4(stg + (lane & 15) * 176 + (2 * j + (lane >> 4)) * 16, pack_bf(acc[j * 8], acc[j * 8 + 1]), pack_bf(acc[j * 8 + 2], acc[j * 8 + 3]),
              pack_bf(acc[j * 8 + 4], acc[j * 8 + 5]), pack_bf(acc[j * 8 + 6], acc[j * 8 + 7]));
    __syncwarp();
#pragma unroll
    for (int i = 0; i < 5; i++) {
        const int id = i * 32 + lane, r = id / 10, ch = id - r * 10;
        uint32_t y[4];
        lds128(y, stg + r * 176 + ch * 16);
        ((uint4*)out)[(size_t)(mb * 128 + w * 16 + r) * 80 + nb * 10 + ch] = add_bf8(rv[i], y);
    }
    fence_async_smem();
    __syncwarp();
    if (lane == 0) mbar_arrive(sb + G_BAR + (2 * GST - 1) * 8);
}

__global__ void __launch_bounds__(128, 4) k_col(const int first) {
    __shared__ __align__(1024) char sz[8192];
    __shared__ __align__(1024) char stab[24576];
    __shared__ __align__(1024) char swf[8192];
    __shared__ __align__(8) uint64_t bar[2];
    const int tid = threadIdx.x, wl = tid >> 5, lane = tid & 31, g = lane >> 2, t = lane & 3;
    const int c = blockIdx.x;
    TL(first ? 5 : 19);
    const bool realc = c == 0 || c == 320;
    const uint32_t z = smem_u32(sz), b2 = smem_u32(stab), a1 = b2 + 16384, wf = smem_u32(swf), mb = smem_u32(bar);
    if (tid == 0) { mbar_init(mb, 1); mbar_init(mb + 8, 1); fence_async_smem(); }
    if (realc) {
        for (int i = tid; i < 256; i += 128) sts128(z + 4096 + i * 16, 0, 0, 0, 0);
        fence_async_smem();
    }
    const int k1 = wl * 8 + g;
    float tc[16], ts[16];
#pragma unroll
    for (int j = 0; j < 16; j++) {
        const int p = ((j >> 1) * 8 + 2 * t + (j & 1)) * k1;
        __sincosf((float)(p - 1024) * 0.003067961575771282f, &ts[j], &tc[j]);
        ts[j] = -ts[j]; tc[j] = -tc[j];
    }
    if (first && tid == 32) { wait_flag<400>(g_ready, NSETUP); fence_async_glb(); }
    __syncthreads();
    if (tid == 32) {
        mbar_expect(mb + 8, 24576 + 8192);
        bulk_g2s(b2, g_ctab, 24576, mb + 8);
        bulk_g2s(wf, g_Wf + (size_t)c * 2048, 8192, mb + 8);
    }
    float inv;
    const float wsc = pow2_scale(wfilter_max(lane), 0, &inv) * (realc ? 0.0625f : 0.125f);
    pdl_wait();
    TL(first ? 6 : 20);
    if (tid == 0) {
        const int by = realc ? 4096 : 8192;
        mbar_expect(mb, by);
        bulk_g2s_last(z, (const char*)g_UT + (size_t)(c == 320 ? 1 : 2 * c) * 4096, by, mb);
    }
    pdl_go();
    mbar_wait(mb + 8, 0);
    mbar_wait(mb, 0);
    float d[64];
    uint32_t a[4][4];
    wg_fence();
#pragma unroll
    for (int ks = 0; ks < 4; ks++) wg_n64_ss_tb<0>(d, mkdesc(a1 + ks * 2048, 1024, 128, 0), mkdesc(z + ks * 2048, 1024, 1024, 1), ks);
    wg_commit(); wg_wait<0>();
    const float r32 = 0.17677669529663687f;
#pragma unroll
    for (int j = 0; j < 8; j++) {
        float yr[2], yi[2];
#pragma unroll
        for (int e = 0; e < 2; e++) {
            const float re = d[j * 4 + e] * r32, im = d[j * 4 + 2 + e] * r32, cc = tc[j * 2 + e], ss = ts[j * 2 + e];
            yr[e] = re * cc + im * ss; yi[e] = im * cc - re * ss;
        }
        a[j >> 1][(j & 1) * 2] = pack_h(yr[0], yr[1]); a[j >> 1][(j & 1) * 2 + 1] = pack_h(yi[0], yi[1]);
    }
    wg_fence();
#pragma unroll
    for (int ks = 0; ks < 4; ks++) wg_n128_rs(d, a[ks], mkdesc(b2 + ks * 4096, 2048, 128, 0), ks);
    wg_commit(); wg_wait<0>();
#pragma unroll
    for (int q = 0; q < 4; q++) {
        uint32_t wv[4];
        lds128(wv, wf + tid * 64 + ((q ^ (tid >> 1)) & 3) * 16);
#pragma unroll
        for (int jj = 0; jj < 2; jj++) {
            const int j = 2 * q + jj;
            float yr[2], yi[2];
#pragma unroll
            for (int e = 0; e < 2; e++) {
                const float xr = d[j * 4 + e] + d[32 + j * 4 + 2 + e], xi = d[j * 4 + 2 + e] - d[32 + j * 4 + e];
                const float fr = bf_lo(wv[jj * 2 + e]) * wsc, fi = bf_hi(wv[jj * 2 + e]) * wsc;
                yr[e] = xr * fr - xi * fi; yi[e] = xr * fi + xi * fr;
            }
            a[q][jj * 2] = pack_h(yr[0], yr[1]); a[q][jj * 2 + 1] = pack_h(yi[0], yi[1]);
        }
    }
    wg_fence();
#pragma unroll
    for (int ks = 0; ks < 4; ks++) wg_n128_rs(d, a[ks], mkdesc(b2 + ks * 4096, 2048, 128, 0), ks);
    wg_commit(); wg_wait<0>();
#pragma unroll
    for (int j = 0; j < 8; j++) {
        float yr[2], yi[2];
#pragma unroll
        for (int e = 0; e < 2; e++) {
            const float vr = (d[j * 4 + e] - d[32 + j * 4 + 2 + e]) * 0.125f, vi = (d[j * 4 + 2 + e] + d[32 + j * 4 + e]) * 0.125f;
            const float cc = tc[j * 2 + e], ss = ts[j * 2 + e];
            yr[e] = vr * cc - vi * ss; yi[e] = vi * cc + vr * ss;
        }
        a[j >> 1][(j & 1) * 2] = pack_h(yr[0], yr[1]); a[j >> 1][(j & 1) * 2 + 1] = pack_h(yi[0], yi[1]);
    }
    __syncthreads();
    const int mm = lane >> 3, rr = lane & 7;
    const uint32_t rowo = (wl * 16 + (mm & 1) * 8 + rr) * 128;
#pragma unroll
    for (int q = 0; q < 4; q++) stsm4(z + rowo + (((2 * q + (mm >> 1)) ^ rr) << 4), a[q][0], a[q][1], a[q][2], a[q][3]);
    fence_async_smem();
    __syncthreads();
    wg_fence();
#pragma unroll
    for (int ks = 0; ks < 4; ks++) wg_n64_ss_tb<1>(d, mkdesc(a1 + ks * 256, 128, 1024, 0), mkdesc(z + ks * 2048, 1024, 1024, 1), ks);
    wg_commit(); wg_wait<0>();
#pragma unroll
    for (int q = 0; q < 4; q++)
        stsm4(wf + rowo + (((2 * q + (mm >> 1)) ^ rr) << 4), pack_h(d[q * 8] * r32, d[q * 8 + 1] * r32), pack_h(d[q * 8 + 2] * r32, d[q * 8 + 3] * r32),
              pack_h(d[q * 8 + 4] * r32, d[q * 8 + 5] * r32), pack_h(d[q * 8 + 6] * r32, d[q * 8 + 7] * r32));
    __syncwarp();
    if (!(realc && wl >= 2)) {
        const int kk = c == 320 ? 320 : (c & 1) * 160 + (c >> 1) + (wl >> 1) * 320;
#pragma unroll
        for (int i = 0; i < 4; i++) {
            const int r = wl * 16 + i * 4 + (lane >> 3), ch = lane & 7;
            uint32_t v[4];
            lds128(v, wf + r * 128 + ((ch ^ (r & 7)) << 4));
            ((uint4*)g_YT)[((size_t)(r & 31) * 640 + kk) * 8 + (ch ^ (kk & 7))] = make_uint4(v[0], v[1], v[2], v[3]);
        }
    }
    __syncthreads();
    if (tid == 0) red_release(g_flag + F_X + (first ? 0 : 128) + 65);
    TL(first ? 7 : 21);
}

constexpr int O_XS = 0;
constexpr int O_MS = 81920;
constexpr int O_QKP = O_MS + 10752;
constexpr int O_VM = O_QKP + 4096;
constexpr int O_SC = O_VM + 4096;
constexpr int O_OS = O_SC + 1536;
constexpr int O_XCH = O_OS + 2048;
constexpr int O_SUM = O_XCH + 8192;
constexpr int O_MX = O_SUM + 256;
constexpr int O_STG = O_MS + 65536 - 8192;
static_assert(O_STG - 16384 >= O_MX + 1024, "shared-memory map");
constexpr int O_WO = O_STG + 16384;
constexpr int O_SCL = O_WO + 65536;
constexpr int O_BAR = O_SCL + 64;
constexpr int B_XF = O_BAR, B_S = O_BAR + 16, B_VX = O_BAR + 32, B_STG = O_BAR + 48, B_FREE = O_BAR + 72;
constexpr int T_FA = O_BAR + 96, T_EA = T_FA + 32, T_FB = T_EA + 32, T_EB = T_FB + 56, T_RED = T_EB + 32;
constexpr int O_WMX = O_BAR + 512, B_W = O_BAR + 64;
constexpr int O_LAST = (O_WMX + 192 + 1023) / 1024 * 1024;
constexpr int CH_SMEM = O_LAST + 8192;
static_assert(O_WO == 19 * 8192, "weight staging");
__device__ __forceinline__ uint32_t tail_b(int c) { return c % 7 < 4 ? O_XS + (c % 7) * 20480 : O_WO + (c % 7 - 4) * 20480; }
__device__ __forceinline__ int s_tx(int c) { return c == 2 ? 2 * 768 : 768 + 2048; }

#define NPERM 1
#define NWO0 1
#define NWO0B 4
#define NWO1 6
#define TDELAY 800
#define WDEPTH 6
#define RDELAY 580

#define STAMP(i)

#define NTA 23
#define NTB 26
template <int LO, int HI>
__device__ __forceinline__ void tok_issue(const uint32_t (&A0)[20][4], const uint32_t (&A1)[20][4], float (&b0)[16], float (&b1)[16], uint32_t xd,
                                          const uint32_t zero) {
    if (LO == 0) wg_fence();
    sfor<HI - LO>([&](auto I) {
        constexpr int i = LO + I;
        if constexpr (i < 20) wg_n32_x<i * 64, i>(b0, A0[i], xd); else wg_n32_x<(i - 20) * 64, i - 20>(b1, A1[i - 20], xd + zero);
        if constexpr (i == 19 || i == NTB - 1 || i == 39) wg_commit();
    });
}
__device__ __forceinline__ void tok_give(const float (&b0)[16], const uint32_t L16, const uint32_t xch0) {
    wg_wait<1>();
    sfor<2>([&](auto I) {
        constexpr int i = I;
        sts128_u<i * 512>(L16, xch0, pack_h(b0[8 * i], b0[8 * i + 1]), pack_h(b0[8 * i + 2], b0[8 * i + 3]), pack_h(b0[8 * i + 4], b0[8 * i + 5]),
                          pack_h(b0[8 * i + 6], b0[8 * i + 7]));
    });
}
__device__ __forceinline__ void tok_finish(float (&b1)[16], const uint32_t (&e)[2][4], const uint32_t L16, const uint32_t dst, const uint32_t idn) {
#pragma unroll
    for (int j = 0; j < 4; j++)
        asm volatile("mma.sync.aligned.m16n8k8.row.col.f32.f16.f16.f32 {%0,%1,%2,%3},{%4,%5},{%6},{%0,%1,%2,%3};"
                     : F4(b1, 4 * j) : "r"(e[j >> 1][(j & 1) * 2]), "r"(e[j >> 1][(j & 1) * 2 + 1]), "r"(idn));
    stsm4_u<0>(L16, dst, pack_bf(b1[0], b1[1]), pack_bf(b1[2], b1[3]), pack_bf(b1[4], b1[5]), pack_bf(b1[6], b1[7]));
    stsm4_u<512>(L16, dst, pack_bf(b1[8], b1[9]), pack_bf(b1[10], b1[11]), pack_bf(b1[12], b1[13]), pack_bf(b1[14], b1[15]));
}
__device__ __forceinline__ uint32_t uni(uint32_t v) { return __shfl_sync(~0u, v, 0); }
__device__ __forceinline__ uint32_t badd(uint32_t a, uint32_t b) { uint32_t r; asm("add.rn.bf16x2 %0,%1,%2;" : "=r"(r) : "r"(a), "r"(b)); return r; }
__device__ __forceinline__ uint32_t bmax(uint32_t a, uint32_t b) { uint32_t r; asm("max.bf16x2 %0,%1,%2;" : "=r"(r) : "r"(a), "r"(b)); return r; }
__device__ __forceinline__ uint32_t babsmax(uint32_t a, uint32_t b) { uint32_t r; asm("max.xorsign.abs.bf16x2 %0,%1,%2;" : "=r"(r) : "r"(a), "r"(b)); return r; }
__device__ __forceinline__ uint32_t habsmax(uint32_t a, uint32_t b) { uint32_t r; asm("max.xorsign.abs.f16x2 %0,%1,%2;" : "=r"(r) : "r"(a), "r"(b)); return r; }

template <int NPF>
__device__ __forceinline__ float mem_out(const uint32_t sb, const uint32_t L16, const uint32_t L8, uint32_t (&wo)[16][4], const uint32_t woa,
                                         char* dst, const bool odd) {
    bar_sync(2, 352);
    float a[4][4];
#pragma unroll
    for (int i = 0; i < 4; i++) a[i][0] = a[i][1] = a[i][2] = a[i][3] = 0.f;
    uint32_t ob[4][4], sm_[2], sc[2];
    sfor<8>([&](auto I) {
        constexpr int i = I;
        if constexpr (!(i & 1)) ldsm4t_u<O_OS + (i >> 1) * 512>(ob[i >> 1], L16, sb);
        if constexpr (i >= NPF) { ldsm4t(wo[i], woa + i * 1024); ldsm4t(wo[8 + i], (woa ^ 32) + i * 1024); }
    });
    lds64_u<O_SUM>(sm_, L8 & 24, sb); lds64(sc, sb + O_SCL);
#pragma unroll
    for (int i = 0; i < 8; i++) {
        mma_bf(a[i & 1], wo[i][0], wo[i][1], wo[i][2], wo[i][3], ob[i >> 1][(i & 1) * 2], ob[i >> 1][(i & 1) * 2 + 1]);
        mma_bf(a[2 + (i & 1)], wo[8 + i][0], wo[8 + i][1], wo[8 + i][2], wo[8 + i][3], ob[i >> 1][(i & 1) * 2], ob[i >> 1][(i & 1) * 2 + 1]);
    }
    const float f0 = rcp(__uint_as_float(sm_[0])) * __uint_as_float(sc[0]), f1 = rcp(__uint_as_float(sm_[1])) * __uint_as_float(sc[0]);
    red_h8(dst, pack_h((a[0][0] + a[1][0]) * f0, (a[0][1] + a[1][1]) * f1), pack_h((a[0][2] + a[1][2]) * f0, (a[0][3] + a[1][3]) * f1),
           pack_h((a[2][0] + a[3][0]) * f0, (a[2][1] + a[3][1]) * f1), pack_h(odd ? (a[2][3] + a[3][3]) * f1 : (a[2][2] + a[3][2]) * f0, 1.f));
    return __uint_as_float(sc[1]);
}

__device__ __forceinline__ void chain_mma(const uint32_t sb, const int c, const int h, const int layer, const uint32_t zero, const bf16* __restrict__ Wq,
                                          const bf16* __restrict__ Wk, const bf16* __restrict__ Wv, const bf16* __restrict__ Wo,
                                          const bf16* res, bf16* out) {
    int tid = read_tid(), lane = tid & 31;
    const int w = __shfl_sync(~0u, tid >> 5, 0), wg = w >> 2;
    [[maybe_unused]] const int cta = h * 3 + c;
    uint32_t A0[20][4], A1[20][4];
    const int t0 = (w & 3) + wg * 4, t1 = t0 ^ 4;
    float sl;
    {
        const int tl = tid & 127, r = tl >> 3, ch = tl & 7;
        const size_t so = (size_t)(wg * 320 + r) * 4096 + h * 128 + ch * 8;
        const bf16 *wa = (c == 2 ? Wv : Wq + c * 64) + so, *wb = (c == 2 ? Wv + 64 : Wk + c * 64) + so;
        const uint32_t ring = sb + wg * 4096;
        const uint32_t dst = ring + r * 128 + ((ch ^ r) & 7) * 16;
        const uint32_t src = ring + ((lane & 7) + (lane >> 4) * 8) * 128 + ((((w & 3) * 2 + ((lane >> 3) & 1)) ^ lane) & 7) * 16;
        const int q4 = lane & 3, gr = (c * 2 + ((w >> 1) & 1)) * 56 + (q4 == 3 ? 24 : (w & 1) * 32 + q4 * 8);
        const bf16* wo_ = Wo + (size_t)(h * 128 + (lane >> 2)) * 640 + wg * 320 + min(gr, 312);
        const uint32_t wdst = sb + O_WO + w * 8192 + (lane >> 2) * 64 + ((q4 ^ (lane >> 3)) & 3) * 16;
        auto issue = [&](int i) {
            if (i < 20) {
                const uint32_t d = dst + (i < 19 ? i * 8192 : O_LAST);
                cp_async16(d, wa + (size_t)i * 65536); cp_async16(d + 2048, wb + (size_t)i * 65536);
                if (i < 16) cp_async16(wdst + i * 512, wo_ + i * 5120, gr < 320 ? 16 : 0);
            }
            cp_commit();
        };
#pragma unroll 1
        for (int i = 0; i < WDEPTH; i++) issue(i);
        asm volatile("barrier.cluster.arrive.relaxed.aligned;" ::: "memory");
        float fa, fb;
        if (layer == 0) {
            uint32_t ma = 0, mb = 0;
#pragma unroll 1
            for (int i = 0; i < 20; i++) {
                issue(i + WDEPTH);
                cp_wait<WDEPTH>();
                const uint32_t d = dst + (i < 19 ? i * 8192 : O_LAST);
                uint32_t u[8];
                lds128(u, d); lds128(u + 4, d + 2048);
                ma = babsmax(babsmax(ma, babsmax(u[0], u[1])), babsmax(u[2], u[3])); mb = babsmax(babsmax(mb, babsmax(u[4], u[5])), babsmax(u[6], u[7]));
            }
            ma = __reduce_max_sync(~0u, max(ma & 0x7fffu, (ma >> 16) & 0x7fffu)); mb = __reduce_max_sync(~0u, max(mb & 0x7fffu, (mb >> 16) & 0x7fffu));
            asm volatile("barrier.cluster.wait.aligned;" ::: "memory");
            if (lane < 3)
                asm volatile("st.async.shared::cluster.mbarrier::complete_tx::bytes.v2.b32 [%0],{%1,%2},[%3];"
                             ::"r"(mapa(sb + O_WMX + (c * 8 + w) * 8, lane)), "r"(ma), "r"(mb), "r"(mapa(sb + B_W, lane)) : "memory");
            __syncwarp();
            {
                uint32_t off[4];
                float cs[4] = {0.f, 0.f, 0.f, 0.f};
#pragma unroll
                for (int q = 0; q < 4; q++) {
                    const int g_ = (c * 2 + ((w >> 1) & 1)) * 56 + (q == 3 ? 24 : (w & 1) * 32 + q * 8), col = wg * 320 + g_, nb = col / 80;
                    off[q] = g_ < 320 && !(q == 3 && (w & 1)) ? ((nb * 512 + h * 16) * 10 + (col - nb * 80) / 8) * 32 + lane : ~0u;
                }
                const uint32_t ta = sb + O_WO + w * 8192 + (lane & 7) * 64 + (((lane >> 3) ^ (lane >> 1)) & 3) * 16;
#pragma unroll 2
                for (int i = 0; i < 16; i++) {
                    uint32_t r[4];
                    ldsm4t(r, ta + i * 512);
#pragma unroll
                    for (int q = 0; q < 4; q++) {
                        if (off[q] != ~0u) ((uint32_t*)g_wot)[off[q] + i * 320] = r[q];
                        cs[q] += fabsf(bf_lo(r[q])) + fabsf(bf_hi(r[q]));
                    }
                }
                float cm = 0.f;
#pragma unroll
                for (int q = 0; q < 4; q++) {
                    cs[q] += __shfl_xor_sync(~0u, cs[q], 1); cs[q] += __shfl_xor_sync(~0u, cs[q], 2);
                    cm = fmaxf(cm, cs[q]);
                }
                const uint32_t n1 = __reduce_max_sync(~0u, __float_as_uint(cm));
                if (lane == 0) g_co[h * 32 + c * 8 + w] = __uint_as_float(n1);
            }
            mbar_wait(sb + B_W, 0);
            uint32_t v[2];
            lds64(v, sb + O_WMX + (lane < 24 ? lane : 0) * 8);
            const bool mine = (lane >> 3) < 3 && ((lane >> 4) == 1) == (c == 2);
            ma = __reduce_max_sync(~0u, mine ? v[0] : 0u); mb = __reduce_max_sync(~0u, mine ? v[1] : 0u);
            if (c == 2) ma = mb = max(ma, mb);
            fa = __uint_as_float(ma << 16); fb = __uint_as_float(mb << 16);
            if (tid == 0) {
                if (c != 1) g_wmx[h * 3 + c] = fa;
                if (c == 0) g_wmx[h * 3 + 1] = fb;
            }
        } else {
            fa = __ldcg(g_wmx + h * 3 + (c == 2 ? 2 : 0)); fb = __ldcg(g_wmx + h * 3 + (c == 2 ? 2 : 1));
            asm volatile("barrier.cluster.wait.aligned;" ::: "memory");
        }
        if (layer == TLL) TL(49);
        float ia, ib;
        const float sa = pow2_scale(fa, 6, &ia), sc_b = pow2_scale(fb, 6, &ib);
        sl = __uint_as_float(uni(__float_as_uint(ia * ib * (0.08838834764831845f * 1.4426950408889634f))));
        const uint32_t pa = pack_bf(sa, sa), pb = pack_bf(sc_b, sc_b);
        const int ahead = layer == 0 ? 20 : WDEPTH;
        auto convert = [&](int lo) {
#pragma unroll 1
            for (int i = lo; i < lo + 10; i++) {
                issue(i + ahead);
                cp_wait<WDEPTH>();
                const uint32_t d = dst + (i < 19 ? i * 8192 : O_LAST);
                uint32_t u[8];
                lds128(u, d); lds128(u + 4, d + 2048);
#pragma unroll
                for (int q = 0; q < 8; q++)
                    asm("{.reg .b32 m,l,u; mul.rn.bf16x2 m,%0,%1; shl.b32 l,m,16; and.b32 u,m,0xffff0000; cvt.rn.f16x2.f32 %0,u,l;}" : "+r"(u[q]) : "r"(q < 4 ? pa : pb));
                sts128(d, u[0], u[1], u[2], u[3]); sts128(d + 2048, u[4], u[5], u[6], u[7]);
            }
            bar_sync(6 + wg, 128);
        };
        const uint32_t s0 = src + wg * 2048, s1 = src + 2048 - wg * 2048;
        convert(0);
#pragma unroll
        for (int i = 0; i < 10; i++) { ldsm4t(A0[i], s0 + i * 8192); ldsm4t(A1[i], s1 + i * 8192); }
        if (layer == TLL) TL(50);
        convert(10);
#pragma unroll
        for (int i = 10; i < 20; i++) { ldsm4t(A0[i], s0 + (i < 19 ? i * 8192 : O_LAST)); ldsm4t(A1[i], s1 + (i < 19 ? i * 8192 : O_LAST)); }
        if (layer == TLL) TL(53);
        bar_sync(9, 256);
        if (tid == 0) red_release(g_flag + F_W + layer * 128);
        bar_sync(4, 288);
        asm volatile("barrier.cluster.arrive.relaxed.aligned;" ::: "memory");
    }
    const uint32_t idn = (lane >> 3) == (lane & 3) ? ((lane & 4) ? 0x3c000000u : 0x3c00u) : 0u;
    float invM = g_invM0;
    char* redp = red_base() + (size_t)layer * 32 * 32768 + w * 2048 + (lane >> 4) * 1024 + ((lane >> 3) & 1) * 256 + (lane & 7) * 16;
    const uint32_t ro2 = uni((w >> 1) * 4096 + 128), rown = uni(c == 2 ? ro2 : c * 16384);
    const uint32_t L16 = lane * 16, L8 = lane * 8, L4 = lane * 4;
    const uint32_t xch0 = uni(sb + O_XCH + t0 * 1024), xch1 = uni(sb + O_XCH + t1 * 1024);
    const uint32_t qo0 = uni(sb + O_QKP + (w & 3) * 1024 + (wg ? 768 : 0)), qp0 = uni(qo0 + (wg ? 128 : 256));
    const uint32_t qo1 = uni(sb + O_QKP + (w & 3) * 1024 + (wg ? 128 : 512)), qp1 = uni(qo1 + (wg ? 256 : 128));
    const uint32_t vo1 = uni(qo1 + (wg ? -128 : 256)), vp1 = uni(qp1 + (wg ? -128 : 256));
    const uint32_t msr = uni(sb + O_MS + wg * 5376);
    const uint32_t msw = uni(msr + ((w >> 1) & 1) * 896 + (w & 1) * 512), msh = uni(msr + ((w >> 1) & 1) * 896 + 384 + (w & 1) * 2);
    const uint32_t sco = uni(sb + O_SC + c * 768 + (w & 3) * 256);
    const uint32_t woa = sb + O_WO + w * 8192 + (lane >> 4) * 512 + (lane & 7) * 64 + (((lane >> 3) ^ (lane >> 1)) & 1) * 16 + ((lane >> 2) & 1) * 32;
    const uint32_t w512 = uni(sb + w * 512), w128 = uni(sb + w * 128);
    const uint32_t pd0 = uni(mapa(sb, c == 2 ? 0 : 2) - sb), pd1 = uni(mapa(sb, c == 1 ? 0 : 1) - sb);
    const bool scw = c < 2 && w >= 4 && w <= 6;
    uint32_t sn = uni(sb + O_STG + (c == 2 ? 8192 : 0) + t1 * 1024);
    uint32_t ka = uni(sb + (w == 6 ? O_QKP + 512 : O_STG + 4096 + (w & 1) * 512));
    uint32_t vs = uni(sb + O_VM + t1 * 256);
    uint32_t va = uni(sb + O_STG + 8192 + w * 2048), vr = uni(sb + O_VM + w * 512);
    const uint32_t sn2 = uni(2 * sn - 16384), ka2 = uni(2 * ka - (w == 6 ? 0 : 16384)), vs2 = uni(2 * vs + 2048), va2 = uni(2 * va - 16384),
                   vr2 = uni(2 * vr + 2048);
    uint32_t xd = uni((uint32_t)mkdesc(sb + O_XS + wg * 20480, 512, 128, 0));
    const uint32_t xd2 = uni(2 * xd + 2560);

    uint32_t wp[2 * NPERM + 1][4];
    sfor<NPERM>([&](auto I) { constexpr int i = I; ldsm4t(wp[2 * i], woa + i * 1024); ldsm4t(wp[2 * i + 1], (woa ^ 32) + i * 1024); });
    auto wo_fetch = [&](uint32_t (&wo)[16][4], auto I) {
        constexpr int i = I;
        if constexpr (i < NPERM) {
#pragma unroll
            for (int q = 0; q < 4; q++) { wo[i][q] = wp[2 * i][q]; wo[8 + i][q] = wp[2 * i + 1][q]; }
        } else { ldsm4t(wo[i], woa + i * 1024); ldsm4t(wo[8 + i], (woa ^ 32) + i * 1024); }
    };
    if (layer == TLL) TL(32);
    float b0[16], b1[16];
    mbar_wait(sb + B_XF, 0);
    if (layer == TLL) TL(33);
    tok_issue<0, NTB>(A0, A1, b0, b1, xd, zero);
    tok_give(b0, L16, xch0);
    tok_issue<NTB, 40>(A0, A1, b0, b1, xd, zero);
    bar_sync(4, 256);
    wg_wait<0>();
    {
        uint32_t e[2][4];
        lds128_u<0>(e[0], L16, xch1); lds128_u<512>(e[1], L16, xch1);
        tok_finish(b1, e, L16, sn, idn);
    }
    sn = sn2 - sn; xd = xd2 - xd;
    bar_sync(5, 288);
    asm volatile("barrier.cluster.wait.aligned;" ::: "memory");
    if (layer == TLL) TL(34);
    mbar_wait(sb + B_XF + 8, 0);
    if (layer == TLL) TL(35);
    tok_issue<0, NTA>(A0, A1, b0, b1, xd, zero);
    uint32_t tr = clock32() - RDELAY;

#pragma unroll 1
    for (int st = 0;; st++) {
        uint4 mv[3];
        asm volatile("{.reg .pred p; .reg .b32 t;\n"
                     "mov.b32 %0,0; mov.b32 %1,0; mov.b32 %2,0; mov.b32 %3,0; mov.b32 %4,0; mov.b32 %5,0; mov.b32 %6,0; mov.b32 %7,0;\n"
                     "mov.b32 %8,0; mov.b32 %9,0; mov.b32 %10,0; mov.b32 %11,0;\n"
                     "T_LOOP: mov.u32 t,%%clock; sub.u32 t,t,%14; setp.ge.u32 p,t,%15;\n"
                     "@p ld.relaxed.gpu.global.v4.u32 {%0,%1,%2,%3},[%12]; @p ld.relaxed.gpu.global.v4.u32 {%4,%5,%6,%7},[%12+16384];\n"
                     "@p ld.relaxed.gpu.global.v4.u32 {%8,%9,%10,%11},[%13];\n"
                     "@!p bra T_LOOP;}"
                     : "=r"(mv[0].x), "=r"(mv[0].y), "=r"(mv[0].z), "=r"(mv[0].w), "=r"(mv[1].x), "=r"(mv[1].y), "=r"(mv[1].z), "=r"(mv[1].w),
                       "=r"(mv[2].x), "=r"(mv[2].y), "=r"(mv[2].z), "=r"(mv[2].w)
                     : "l"(redp), "l"(redp + ro2), "r"(tr), "n"(RDELAY) : "memory");
        STAMP(10);
        tok_issue<NTA, NTB>(A0, A1, b0, b1, xd, zero);
        tok_give(b0, L16, xch0);
        tok_issue<NTB, 40>(A0, A1, b0, b1, xd, zero);
        xd = xd2 - xd;
        STAMP(9);
        if (zero >> 30) break;
        asm volatile("{.reg .pred p; .reg .b32 a,h,t,n; .reg .b16 l,u; .reg .b64 q;\n"
                     "add.u32 a,%12,%13; add.u32 h,%12,%14; mov.u32 n,0;\n"
                     "M_LOOP:\n .pragma \"nounroll\";\n"
                     "st.shared.b32 [a],%0; st.shared.b32 [a+128],%1; st.shared.b32 [a+256],%2; mov.b32 {l,u},%3; st.shared.b16 [h],l;\n"
                     "st.shared.b32 [a+1792],%4; st.shared.b32 [a+1920],%5; st.shared.b32 [a+2048],%6; mov.b32 {l,u},%7; st.shared.b16 [h+1792],l;\n"
                     "st.shared.b32 [a+3584],%8; st.shared.b32 [a+3712],%9; st.shared.b32 [a+3840],%10; mov.b32 {l,u},%11; st.shared.b16 [h+3584],l;\n"
                     "lop3.b32 t,%3,%7,0x50000000,0x7e; lop3.b32 t,t,%11,0x50000000,0xf6; setp.gt.u32 p,t,0xffff;\n"
                     "vote.sync.any.pred p,p,-1; add.u32 n,n,1; setp.lt.and.u32 p,n,%17,p; @!p bra M_DONE;\n"
                     "ld.relaxed.gpu.global.v4.u32 {%0,%1,%2,%3},[%15]; ld.relaxed.gpu.global.v4.u32 {%4,%5,%6,%7},[%15+16384];\n"
                     "cvt.u64.u32 q,%16; add.u64 q,q,%15; ld.relaxed.gpu.global.v4.u32 {%8,%9,%10,%11},[q];\n"
                     "bra M_LOOP;\n"
                     "M_DONE:}"
                     : "+r"(mv[0].x), "+r"(mv[0].y), "+r"(mv[0].z), "+r"(mv[0].w), "+r"(mv[1].x), "+r"(mv[1].y), "+r"(mv[1].z), "+r"(mv[1].w),
                       "+r"(mv[2].x), "+r"(mv[2].y), "+r"(mv[2].z), "+r"(mv[2].w)
                     : "r"(L4), "r"(msw), "r"(msh), "l"(redp), "r"(ro2), "n"(SPIN_LIM) : "memory");
        bar_sync(3, 256);
        STAMP(0);
        uint32_t e[2][4];
        float f1[4];
        {
            uint32_t b[10][4];
            float acc[4][4];
#pragma unroll
            for (int i = 0; i < 4; i++) acc[i][0] = acc[i][1] = acc[i][2] = acc[i][3] = 0.f;
            auto ld = [&](auto I) { constexpr int i = I; ldsm4t_u<i * 512>(b[i], L16, msr); };
            auto mm = [&](auto I) {
                constexpr int i = I;
                mma_f16(acc[0], A0[2 * i], b[i][0], b[i][1]); mma_f16(acc[2], A1[2 * i], b[i][0], b[i][1]);
                mma_f16(acc[1], A0[2 * i + 1], b[i][2], b[i][3]); mma_f16(acc[3], A1[2 * i + 1], b[i][2], b[i][3]);
            };
            ld(IC<0>()); ld(IC<1>()); ld(IC<2>()); ld(IC<3>());
            sts32_u<O_MX>(L4, w128,
                          habsmax(habsmax(habsmax(habsmax(mv[0].x, mv[0].y), habsmax(mv[0].z, mv[1].x)), habsmax(habsmax(mv[1].y, mv[1].z), mv[2].x)),
                                  habsmax(habsmax(mv[2].y, mv[2].z), habsmax(habsmax(mv[0].w, mv[1].w), mv[2].w) & 0xffffu)));
            wg_wait<0>();
            ld(IC<4>()); mm(IC<0>()); ld(IC<5>()); mm(IC<1>()); ld(IC<6>()); mm(IC<2>());
            ld(IC<7>()); mm(IC<3>()); ld(IC<8>()); mm(IC<4>()); ld(IC<9>()); mm(IC<5>());
            lds128_u<0>(e[0], L16, xch1); lds128_u<512>(e[1], L16, xch1);
            mm(IC<6>()); mm(IC<7>()); mm(IC<8>()); mm(IC<9>());
            const uint32_t u0 = pack_bf((acc[0][0] + acc[1][0]) * invM, (acc[0][1] + acc[1][1]) * invM);
            const uint32_t u1 = pack_bf((acc[0][2] + acc[1][2]) * invM, (acc[0][3] + acc[1][3]) * invM);
#pragma unroll
            for (int i = 0; i < 4; i++) f1[i] = (acc[2][i] + acc[3][i]) * invM;
            sts32_u<0>(L4, qo0, u0); sts32_u<0>(L4, qp0, u1); sts32_u<0>(L4, qo1, pack_bf(f1[0], f1[1])); sts32_u<0>(L4, qp1, pack_bf(f1[2], f1[3]));
        }
        STAMP(1);
        bar_sync(1, 320);
        if (__builtin_expect(scw, 1)) {
            float a[4][4];
#pragma unroll
            for (int i = 0; i < 4; i++) a[i][0] = a[i][1] = a[i][2] = a[i][3] = 0.f;
            uint32_t q[4][4], k[4][4];
            sfor<4>([&](auto I) {
                constexpr int i = I;
                ldsm4t_u<O_QKP + i * 1024>(q[i], L16, sb); ldsm4t_u<i * 1024>(k[i], L16, ka);
            });
#pragma unroll
            for (int i = 0; i < 4; i++) {
                mma_bf(a[i & 1], q[i][0], q[i][1], q[i][2], q[i][3], k[i][0], k[i][1]);
                mma_bf(a[2 + (i & 1)], q[i][0], q[i][1], q[i][2], q[i][3], k[i][2], k[i][3]);
            }
            const float mk = w == 6 ? 1.f : 0.f;
            const float x0 = (a[0][0] + a[0][2]) + (a[1][0] + a[1][2]), x1 = (a[0][1] + a[0][3]) + (a[1][1] + a[1][3]);
            const float y0 = (a[2][0] + a[2][2]) + (a[3][0] + a[3][2]), y1 = (a[2][1] + a[2][3]) + (a[3][1] + a[3][3]);
            st_share2(L8, sco, sb + B_S, pd0, pd1, pack_bf(fmaf(y0, mk, x0) * sl, fmaf(y1, mk, x1) * sl), pack_bf(y0 * sl, y1 * sl));
        }
        if (c == 2) {
            const uint32_t x = lds32_u<0>(L4, vo1), y = lds32_u<0>(L4, vp1);
            st_share2(L8, vs, sb + B_S, pd0, pd1, pack_bf(f1[0] + bf_lo(x), f1[1] + bf_hi(x)), pack_bf(f1[2] + bf_lo(y), f1[3] + bf_hi(y)));
        }
        STAMP(3);
        if (st == NSEG - 1) break;
        tok_finish(b1, e, L16, sn, idn);
        redp += (st & 1) ? 32768 - 512 : 512;
        if (wg == 0) {
            uint32_t wo[16][4], vx[2][2][4], vm[2][2];
            ldsm4_u<0>(vx[0][0], L16, va); ldsm4_u<512>(vx[0][1], L16, va); ldsm4_u<1024>(vx[1][0], L16, va); ldsm4_u<1536>(vx[1][1], L16, va);
            sfor<NWO0>([&](auto I) { wo_fetch(wo, I); });
            mbar_wait(sb + B_S, st & 1);
            STAMP(4);
            uint32_t s[5];
            {
                uint32_t p[2][5];
                sfor<2>([&](auto R) {
                    constexpr int r = R;
                    lds64_u<O_SC + r * 768>(p[r], L8, sb); lds64_u<O_SC + r * 768 + 256>(p[r] + 2, L8, sb); p[r][4] = lds32_u<O_SC + r * 768 + 512>(L8, sb);
                });
#pragma unroll
                for (int j = 0; j < 5; j++) s[j] = badd(p[0][j], p[1][j]);
            }
            lds64_u<0>(vm[0], L8, vr); lds64_u<256>(vm[1], L8, vr);
            uint32_t mm = bmax(bmax(bmax(s[0], s[1]), bmax(s[2], s[3])), s[4]);
            mm = bmax(bmax(mm, __shfl_xor_sync(~0u, mm, 1)), bmax(__shfl_xor_sync(~0u, mm, 2), __shfl_xor_sync(~0u, mm, 3)));
            const float m = fmaxf(bf_lo(mm), bf_hi(mm));
            float o0[4] = {0.f, 0.f, 0.f, 0.f}, o1[4] = {0.f, 0.f, 0.f, 0.f}, d[10];
#pragma unroll
            for (int j = 0; j < 5; j++) { d[2 * j] = bf_lo(s[j]) - m; d[2 * j + 1] = bf_hi(s[j]) - m; }
#pragma unroll
            for (int j = 0; j < 10; j++) d[(j + 8) % 10] = ex2(d[(j + 8) % 10]);
            float sum = ((d[8] + d[9]) + (d[0] + d[1])) + ((d[2] + d[3]) + (d[4] + d[5])) + (d[6] + d[7]);
            const uint32_t p4 = pack_bf(d[8], d[9]), p0 = pack_bf(d[0], d[1]), p1 = pack_bf(d[2], d[3]), p2 = pack_bf(d[4], d[5]), p3 = pack_bf(d[6], d[7]);
            mma_bf8(o0, vm[0][0], vm[0][1], p4);
            mma_bf8(o1, vm[1][0], vm[1][1], p4);
            mma_bf(o0, vx[0][0][0], vx[0][0][1], vx[0][0][2], vx[0][0][3], p0, p1);
            mma_bf(o1, vx[1][0][0], vx[1][0][1], vx[1][0][2], vx[1][0][3], p0, p1);
            mma_bf(o0, vx[0][1][0], vx[0][1][1], vx[0][1][2], vx[0][1][3], p2, p3);
            mma_bf(o1, vx[1][1][0], vx[1][1][1], vx[1][1][2], vx[1][1][3], p2, p3);
            sfor<NWO0B - NWO0>([&](auto I) { constexpr int i = I; wo_fetch(wo, IC<NWO0 + i>()); });
            sum += __shfl_xor_sync(~0u, sum, 1);
            sum += __shfl_xor_sync(~0u, sum, 2);
            sts32_u<O_OS>(L4, w512, pack_bf(o0[0], o0[1])); sts32_u<O_OS + 128>(L4, w512, pack_bf(o0[2], o0[3]));
            sts32_u<O_OS + 256>(L4, w512, pack_bf(o1[0], o1[1])); sts32_u<O_OS + 384>(L4, w512, pack_bf(o1[2], o1[3]));
            sts32_u<O_SUM>(lane & 28, sb, __float_as_uint(sum));
            STAMP(5);
            invM = mem_out<NWO0B>(sb, L16, L8, wo, woa, redp + rown, w & 1);
            tr = clock32();

        } else {
            uint32_t wo[16][4];
            sfor<NWO1>([&](auto I) { wo_fetch(wo, I); });
            invM = mem_out<NWO1>(sb, L16, L8, wo, woa, redp + rown, w & 1);
            tr = clock32();

        }
        STAMP(7);
        tok_issue<0, NTA>(A0, A1, b0, b1, xd, zero);
        sn = sn2 - sn; ka = ka2 - ka; vs = vs2 - vs; va = va2 - va; vr = vr2 - vr;
        STAMP(8);
    }
    if (layer == TLL) TL(40);
    bar_arrive(8, 320);
    tid = read_tid(); lane = tid & 31;
    float acc[40];
    const int nc = c == 2 ? 10 : 11;
#pragma unroll 1
    for (int k = 0; k < nc; k++) {
        mbar_wait(sb + T_FB + (k % 7) * 8, k >= 7);
        mbar_wait(sb + T_FA + (k & 3) * 8, (k >> 2) & 1);
        if (layer == TLL && k == 0) TL(41);
        const uint64_t da = mkdesc(sb + O_MS + (k & 3) * 16384 + wg * 8192, 1024, 128, 0), db = mkdesc(sb + tail_b(k) + wg * 10240, 1280, 128, 0);
        wg_fence();
#pragma unroll
        for (int q = 0; q < 4; q++) wg_n80_ss(acc, da + q * 128, db + q * 160, k | q);
        wg_commit();
        if (k > 0) {
            wg_wait<1>();
            if (lane == 0) { mbar_arrive(sb + T_EA + ((k - 1) & 3) * 8); if (k <= 4) mbar_arrive(sb + T_EB + (k - 1) * 8); }
        }
    }
    if (layer == TLL) TL(52);
    const int mb = 28 + (h >> 3), nj = c == 2 ? 1 : 2;
    uint32_t rv[2][2];
    const size_t go = ((size_t)(mb * 64 + (w & 3) * 16 + (lane >> 2)) * 640 + (h & 7) * 80 + (wg * 5 + c * 2) * 8 + (lane & 3) * 2) >> 1;
#pragma unroll
    for (int u = 0; u < 4; u++) rv[u >> 1][u & 1] = (u >> 1) < nj ? __ldcg((const uint32_t*)res + go + (u >> 1) * 4 + (u & 1) * 2560) : 0u;
    wg_wait<0>();
    asm volatile("barrier.cluster.arrive.relaxed.aligned; barrier.cluster.wait.aligned;" ::: "memory");
    const uint32_t ra = sb + O_XS + tid * 16, rb = sb + O_MS + tid * 16;
#pragma unroll
    for (int j = 0; j < 5; j++) {
        const float* q = acc + 4 * j;
        sts128(rb + j * 4096, __float_as_uint(wg ? q[0] : q[20]), __float_as_uint(wg ? q[1] : q[21]), __float_as_uint(wg ? q[2] : q[22]), __float_as_uint(wg ? q[3] : q[23]));
    }
    bar_sync(4, 256);
#pragma unroll
    for (int j = 0; j < 5; j++) {
        const float* q = acc + 4 * j;
        uint32_t p[4];
        lds128(p, sb + O_MS + (tid ^ 128) * 16 + j * 4096);
        asm volatile("st.async.shared::cluster.mbarrier::complete_tx::bytes.v4.f32 [%0],{%1,%2,%3,%4},[%5];" ::"r"(mapa(ra + c * 8192 + (j & 1) * 4096, j >> 1)),
                     "f"((wg ? q[20] : q[0]) + __uint_as_float(p[0])), "f"((wg ? q[21] : q[1]) + __uint_as_float(p[1])),
                     "f"((wg ? q[22] : q[2]) + __uint_as_float(p[2])), "f"((wg ? q[23] : q[3]) + __uint_as_float(p[3])), "r"(mapa(sb + T_RED, j >> 1)) : "memory");
    }
    mbar_wait(sb + T_RED, 0);
#pragma unroll 1
    for (int u = 0; u < nj; u++) {
        uint32_t p[3][4];
#pragma unroll
        for (int q = 0; q < 3; q++) lds128(p[q], ra + q * 8192 + u * 4096);
        float y[4];
#pragma unroll
        for (int i = 0; i < 4; i++) y[i] = __uint_as_float(p[0][i]) + __uint_as_float(p[1][i]) + __uint_as_float(p[2][i]);
        ((uint32_t*)out)[go + u * 4] = bfma(pack_bf(y[0], y[1]), 0x3f803f80u, u ? rv[1][0] : rv[0][0]);
        ((uint32_t*)out)[go + u * 4 + 2560] = bfma(pack_bf(y[2], y[3]), 0x3f803f80u, u ? rv[1][1] : rv[0][1]);
    }
    TL(layer == 0 ? 15 : 29);
    asm volatile("barrier.cluster.arrive.relaxed.aligned; barrier.cluster.wait.aligned;" ::: "memory");
}

__device__ __forceinline__ void tail_load_b(const uint32_t sb, const int h, const int c, const int k) {
    mbar_expect(sb + T_FB + (k % 7) * 8, 20480);
    bulk_g2s(sb + tail_b(k), (const char*)g_wot + (size_t)((h & 7) * GNC + c * 11 + k) * 20480, 20480, sb + T_FB + (k % 7) * 8);
}
__device__ __forceinline__ void chain_aux(const uint32_t sb, const int c, const int h, const int layer, const int nact) {
    const int tid = read_tid(), w = __shfl_sync(~0u, tid >> 5, 0), lane = tid & 31;
    if (w == 8) {
        mbar_init(sb + O_BAR + lane * 8, lane == 2 ? (c == 2 ? 9 : 4) : (lane >= 16 && lane < 20) || (lane >= 27 && lane < 31) ? 8 : 1);
        asm volatile("fence.mbarrier_init.release.cluster;" ::: "memory");
        fence_async_smem();
        __syncwarp();
    }
    {
        uint4* z = (uint4*)red_base() + layer * 65536;
#pragma unroll 1
        for (int i = blockIdx.x * 128 + tid - 256; i < 65536; i += 96 * 128)
            if (i >= 2048 || (i & 32)) z[i] = make_uint4(0, 0, 0, 0);
    }
    if (w == 8 && lane == 0) {
        mbar_expect(sb + B_S, s_tx(c));
        mbar_expect(sb + B_W, 192);
        mbar_expect(sb + T_RED, (c == 2 ? 1 : 2) * 3 * 4096);
        if (layer == 1) prefetch_l2(red_base() + 32 * 32768 + blockIdx.x * 1024, 1024);
        if (layer == 0) wait_flag<400>(g_ready, NSETUP);
    }
    __syncwarp();
    cluster_sync_full();
    asm volatile("barrier.cluster.arrive.relaxed.aligned;" ::: "memory");
    pdl_wait();
    Flag* flag = g_flag + layer * NSEG * 32 + h;
    const Flag* xflag = g_flag + F_X + layer * 128;
    char* const it0 = g_item + (size_t)h * 32768;
    if (w == 8) {
#pragma unroll 1
        for (int n = 0; n < 3; n++) {
            wait_flag<100>(xflag + (n >> 1), 4);
            fence_async_glb();
            if (n == 0) { bar_sync(4, 288); fence_async_smem(); }
            if (lane == 0 && n < 2) {
                mbar_expect(sb + B_XF + n * 8, 40960);
                bulk_g2s(sb + O_XS + n * 40960, (const char*)g_xn + n * 40960, 40960, sb + B_XF + n * 8);
            }
            __syncwarp();
        }
#pragma unroll 1
        for (int n = 0; n < NSEG; n++) {
            const int np = n & 1;
            if (n == 0) { wait_flag<100>(g_flag + F_W + layer * 128, 96); bar_sync(5, 288); } else bar_sync(2, 352);
            if (n == 1) TL(12 + layer * 14);
            if (n == 63) TL(13 + layer * 14);
            if (lane == 0 && n == NSEG - 1) mbar_arrive(sb + B_STG + 8);
            if (lane == 0 && n < NSEG - 1) {
                const uint32_t vs = sb + O_STG + 8192 - np * 16384, vb = sb + B_VX + np * 8;
                if (c == 2) {
                    fence_async_smem();
                    bulk_s2s(mapa(vs, 0), vs, 8192, mapa(vb, 0));
                    bulk_s2s(mapa(vs, 1), vs, 8192, mapa(vb, 1));
                } else mbar_expect(vb, 8192);
                if (n == 0) { mbar_expect(sb + B_XF, 40960); bulk_g2s(sb + O_XS, (const char*)g_xn + 2 * 40960, 40960, sb + B_XF); }
                if (n == h * 3 + c && !np && n + 6 < NSEG) prefetch_l2(red_base() + (size_t)(layer * 32 + (n >> 1) + 3) * 32768, 32768);
            }
            __syncwarp();
        }
    } else if (w == 11) {
        float cvo;
        {
            auto max8 = [&](const float* p) {
                const float4 u = ((const float4*)p)[0], v = ((const float4*)p)[1];
                return fmaxf(fmaxf(fmaxf(u.x, u.y), fmaxf(u.z, u.w)), fmaxf(fmaxf(v.x, v.y), fmaxf(v.z, v.w)));
            };
            wait_flag<300>(g_flag + F_W + layer * 128, 96);
            const float* pc = g_co + lane * 32;
            float a = 640.f * __ldcg(g_wmx + lane * 3 + 2), o = fmaxf(fmaxf(max8(pc), max8(pc + 8)), max8(pc + 16));
#pragma unroll 1
            for (int s = 16; s; s >>= 1) { a = fmaxf(a, __shfl_xor_sync(~0u, a, s)); o += __shfl_xor_sync(~0u, o, s); }
            cvo = a * o * 2.f;
        }
        float invM = g_invM0;
        float iv;
        weight_scale(h, 2, &iv);
        const uint32_t L16 = sb + lane * 16 + O_MX;
#pragma unroll 1
        for (int st = 0; st < NSEG; st++) {
            bar_sync(1, 320);
            if (st == NSEG - 1) break;
            if (lane == 0) mbar_arrive(sb + B_STG + (st & 1) * 8);
            uint32_t u[2][4];
            lds128(u[0], L16); lds128(u[1], L16 + 512);
            uint32_t mx = habsmax(habsmax(habsmax(u[0][0], u[0][1]), habsmax(u[0][2], u[0][3])), habsmax(habsmax(u[1][0], u[1][1]), habsmax(u[1][2], u[1][3])));
            mx = __reduce_max_sync(~0u, max(mx & 0x7fffu, (mx >> 16) & 0x7fffu));
            const float bound = fmaxf(__half2float(__ushort_as_half((unsigned short)mx)) * invM, 25.5f) * cvo;
            const float sc = pow2_scale(bound, 15, &invM);
            sts64(sb + O_SCL, __float_as_uint(sc * iv), __float_as_uint(invM));
            bar_arrive(2, 352);
        }
    } else if (w == 10) {
        if (lane == 0) {
#pragma unroll 1
            for (int n = 0; n < NSEG; n++) {
                mbar_sleep(sb + B_STG + (n & 1) * 8, (n >> 1) & 1);
                fence_async_smem();
                const uint32_t stg = sb + O_STG - (n & 1) * 16384;
                char* it = it0 + (size_t)(n % RING) * 32 * 32768;
                bulk_s2g(it + c * 8192, stg + (c == 2 ? 8192 : 0), 8192);
                bulk_commit();
                if (n + 1 >= RING && n + 1 < NSEG) wait_flag(flag - (RING - 1) * 32, 7);
                bulk_wait0();
                mbar_arrive(sb + B_FREE + (n & 1) * 8);
                fence_async_glb();
                red_relaxed(flag);
                flag += 32;
            }
        }
    } else {
        bool allx = false;
#pragma unroll 1
        for (int st = 0; st < NSEG; st++) {
            const int par = st & 1;
            char* const it = it0 + (size_t)(st % RING) * 32 * 32768;
            if (lane == 0 && !allx && st + 3 < NSEG) {
                allx = ld_acquire(xflag + 64) >= nact;
                if (!allx) wait_flag(xflag + ((st + 3) >> 1), 4);
                fence_async_glb();
            }
            __syncwarp();
            if (st < NSEG - 1 && c < 2) mbar_sleep(sb + B_VX + par * 8, (st >> 1) & 1);
            if (st < NSEG - 2) mbar_sleep(sb + B_XF + par * 8, ((st >> 1) + 1) & 1);
            bar_sync(1, 320);
            if (lane == 0 && st + 3 < NSEG) {
                mbar_expect(sb + B_XF + (par ^ 1) * 8, 40960);
                bulk_g2s_last(sb + O_XS + (par ^ 1) * 40960, (const char*)g_xn + (size_t)(st + 3) * 40960, 40960, sb + B_XF + (par ^ 1) * 8);
            } else if (lane == 0 && st < NSEG - 1) {
                tail_load_b(sb, h, c, (par ^ 1) * 2); tail_load_b(sb, h, c, (par ^ 1) * 2 + 1);
            }
            __syncwarp();
            if (lane == 0 && c < 2) {
                fence_async_smem();
#pragma unroll 1
                for (int i = 0; i < 4; i++) bulk_s2g(it + 24576 + (c * 4 + i) * 512, sb + O_QKP + i * 1024 + 512, 512);
                bulk_commit();
                asm volatile("cp.async.bulk.wait_group.read 0;" ::: "memory");
            }
            __syncwarp();
            if (st < NSEG - 1) bar_arrive(2, 352);
            mbar_sleep(sb + B_S, par);
            __syncwarp();
            if (lane == 0) {
                if (st < NSEG - 1) mbar_expect(sb + B_S, s_tx(c));
                if (c == 2) { fence_async_smem(); bulk_s2g(it + 28672, sb + O_VM + par * 2048, 2048); bulk_commit(); }
                if (st == NSEG - 1) asm volatile("cp.async.bulk.wait_group.read 0;" ::: "memory");
            }
            __syncwarp();
            if (st == NSEG - 1) bar_arrive(8, 320);
            if (lane == 0) { bulk_wait0(); fence_async_glb(); red_relaxed(flag); }
            __syncwarp();
            mbar_sleep(sb + B_FREE + par * 8, (st >> 1) & 1);
            flag += 32;
        }
    }
    __syncwarp();
    const int nc = c == 2 ? 10 : 11;
    if (w == 10) {
        bar_sync(8, 320);
        if (lane == 0) {
            if (layer == 1 && blockIdx.x == 0) g_ready[0].v = 0;
            fence_async_smem();
            __nanosleep(TDELAY);
            wait_flag(xflag + 64, nact);
            wait_flag<50>(g_flag + F_O + layer * 32 + 28 + (h >> 3), 64);
            fence_async_glb();
#pragma unroll 1
            for (int k = 0; k < nc; k++) {
                if (k >= 4) mbar_sleep(sb + T_EA + (k & 3) * 8, ((k >> 2) - 1) & 1);
                mbar_expect(sb + T_FA + (k & 3) * 8, 16384);
                bulk_g2s_last(sb + O_MS + (k & 3) * 16384, (const char*)g_O + (size_t)((28 + (h >> 3)) * GNC + c * 11 + k) * 16384, 16384, sb + T_FA + (k & 3) * 8);
            }
        }
    } else if (w == 9 && lane == 0) {
        __nanosleep(TDELAY);
#pragma unroll 1
        for (int k = 4; k < nc; k++) {
            if (k >= 7) mbar_sleep(sb + T_EB + (k - 7) * 8, 0);
            tail_load_b(sb, h, c, k);
        }
    }
    __syncwarp();
    asm volatile("barrier.cluster.wait.aligned;" ::: "memory");
    asm volatile("barrier.cluster.arrive.relaxed.aligned; barrier.cluster.wait.aligned;" ::: "memory");
    asm volatile("barrier.cluster.arrive.relaxed.aligned; barrier.cluster.wait.aligned;" ::: "memory");
}

constexpr int RI_A = 0, RI_TAB = 81920, RI_STG = RI_TAB + 82 * 768;
constexpr int RI_RES = RI_STG + 25600, RI_ST = RI_RES + 2 * 64 * 336;
constexpr int HB_A = G_BAR + 64, HB_AFREE = HB_A + 32, HB_LN = HB_A + 40, HB_FULL = HB_A + 64, HB_DONE = HB_FULL + 48, HB_FREE = HB_DONE + 48;
constexpr int HP_SMEM = HB_FREE + 48;
static_assert(G_BAR >= RI_ST + 2048, "helper shared-memory map");
#define IDL 280
#define ITEM_NS 60
#define PFW_AT 28
#define PFW_NS 150
__device__ __forceinline__ void helper_aux(const uint32_t sb, const int j, const int nh, const int na, const int nbh, const int layer, const bf16* Wq,
                                           const bf16* Wk, const bf16* Wv, const bf16* Wo) {
    const int w = threadIdx.x >> 5, lane = threadIdx.x & 31, p = w - 8;
    if (lane == 0 && j < (nh & ~3)) {
        int n = 0;
        for (int a = j >> 2; a < 32; a += nh >> 2, n++) {
            if (n == 0) continue;
            mbar_wait(sb + HB_AFREE, (n - 1) & 1);
            mbar_expect(sb + HB_A + p * 8, 20480);
            bulk_g2s_last(sb + RI_A + p * 20480, (const char*)g_YT + (size_t)a * 81920 + p * 20480, 20480, sb + HB_A + p * 8);
            if (p == 0) { mbar_wait(sb + HB_LN, (n - 1) & 1); red_release(g_flag + F_X + layer * 128 + a - (nh >> 2)); }
        }
        if (p == 0) { mbar_wait(sb + HB_LN, (n - 1) & 1); red_release(g_flag + F_X + layer * 128 + (j >> 2) + (n - 1) * (nh >> 2)); }
    }
    __syncwarp();
    if (layer == 0 && w == 8 && lane == 0) wait_flag<400>(g_flag + F_W, 96);
    __syncwarp();
    bar_sync(3, 384);
    if (p == 3 && lane == 0 && j < (nh & ~3)) red_release(g_flag + F_X + layer * 128 + 64);
    fence_async_smem();
    Flag* oflag = g_flag + F_O + layer * 32;
    if (j < na) {
        int sl = p & 1, ph = 1;
        for (int idx = j + (p & 1) * na; idx < NSEG * 32 && p >= 2 && lane == 0; idx += 2 * na) {
            mbar_wait(sb + HB_DONE + sl * 8, ph ^ 1);
            mbar_arrive(sb + HB_FREE + sl * 8);
            red_release(oflag + (idx >> 6));
            atomicAdd(&g_flag[layer * NSEG * 32 + idx].v, 1u);
            sl += 2;
            if (sl >= 6) { sl -= 6; ph ^= 1; }
        }
        for (int idx = j + p * na; idx < NSEG * 32 && p < 2 && lane == 0; idx += 2 * na) {
            mbar_wait(sb + HB_FREE + sl * 8, ph);
            wait_flag<ITEM_NS>(g_flag + layer * NSEG * 32 + idx, 6);
            fence_async_glb();
            if (idx < (NSEG - 2) * 32) __nanosleep(IDL);
            mbar_expect(sb + HB_FULL + sl * 8, 30720);
            bulk_g2s(sb + sl * 30720, g_item + (size_t)(idx % (RING * 32)) * 32768, 30720, sb + HB_FULL + sl * 8);
            sl += 2;
            if (sl >= 6) { sl -= 6; ph ^= 1; }
        }
    } else if (lane == 0 && p == 3) {
        if (layer == 0) {
            wait_flag<1000>(oflag + PFW_AT, 64);
            const int np = nh - na;
#pragma unroll 1
            for (int i = j - na; i < 1280; i += np) {
                const bf16* W = i < 320 ? Wq : i < 640 ? Wk : i < 960 ? Wv : Wo;
                prefetch_l2((const char*)W + (size_t)(i % 320) * 16384, 16384);
                __nanosleep(PFW_NS);
            }
#pragma unroll 1
            for (int i = j - na; i < 205; i += np) {
                const char* p_ = i < 160 ? (const char*)g_Wf + i * 16384 : i < 165 ? (const char*)g_stat + (i - 144) * 16384
                               : i < 167 ? (const char*)g_ctab + (i - 165) * 8192 : (const char*)(g_flag + NFLAG) - (i - 166) * 16384;
                prefetch_l2(p_, 16384);
                __nanosleep(PFW_NS);
            }
        }
    } else if (lane == 0) {
        if (p == 2) wait_flag<500>(g_flag + F_X + layer * 128 + 64, nh & ~3);
        int c0 = 0;
        for (int mb = (j - na) >> 3; mb < nbh; mb += (nh - na) >> 3, c0 += GNC) {
            if (p < 2) wait_flag<300>(oflag + 2 * mb + p, 64);
            fence_async_glb();
            oproj_load(sb, p, mb, (j - na) & 7, c0, nh - na < 24 ? 0 : mb == nbh - 1 ? GPACE2 : GPACE);
        }
    }
}
__device__ __forceinline__ void helper_mma(char* sm, const int jh, const int nh, const int na, const int nbh, const int layer, const bf16* res, bf16* x,
                                           bf16* out) {
    const uint32_t sb = smem_u32(sm);
    const int tid = threadIdx.x, w = tid >> 5, lane = tid & 31, g = lane >> 2, t = lane & 3;
    const bool act = jh < (nh & ~3);
    const int j4 = jh & 3;
    const int fr = tid & 63, rg = w >> 1;
    auto chunk0 = [&](int u) { return u == 0 ? 5 * j4 : u == 1 ? 75 - 5 * j4 : u == 2 ? 40 + 5 * j4 : 35 - 5 * j4; };
    const int gr = tid / 20, gq_ = tid - gr * 20, go = gr * 80 + chunk0(gq_ / 5) + gq_ % 5;
    const uint32_t gs = sb + RI_RES + gr * 336 + gq_ * 16;
    auto residual = [&](int a, int n) {
#pragma unroll 1
        for (int r = 0; r < 64 - gr && tid < 240 && a < 32; r += 12) cp_async16(gs + (n & 1) * 21504 + r * 336, (const uint4*)res + (a * 64 + r) * 80 + go);
        cp_commit();
    };
    if (act) {
        if (tid < 240) {
            const int k0 = tid / 48, n = tid - k0 * 48;
            const float d = (float)(40 * j4 + n), amp = 2.f * 0.03952847075210474f;
#pragma unroll 4
            for (int u = 0; u < 16; u++)
                *(uint4*)(sm + RI_TAB + (tid + u * 240) * 16) = cos_row8(fmaf((float)((k0 + (u & 3) * 5) * 16 + ((u >> 2) & 1)), d, (float)((u & 8) * 20)), 2.f * d, amp);
            if (tid < 96) *(uint4*)(sm + RI_TAB + (3840 + tid) * 16) = make_uint4(k0 == 0 ? pack_h((n & 1) ? -amp : amp, 0.f) : 0u, 0, 0, 0);
        }
        fence_async_smem();
        residual(jh >> 2, 0);
    }
    bar_sync(1, 384);
    if (layer == TLL) TL(36);
    if (act) {
        const float4 wm = ((const float4*)g_wmax)[lane];
        const int wg = w >> 2;
        int n = 0;
#pragma unroll 1
        for (int a = jh >> 2; a < 32; a += nh >> 2, n++) {
            float acc[2][24];
            uint64_t da = mkdesc(sb + RI_A + wg * 40960, 1024, 1024, 1), db = mkdesc(sb + RI_TAB + wg * 30720, 768, 128, 0);
#pragma unroll
            for (int gq = 0; gq < 2; gq++) {
                mbar_wait(sb + HB_A + (wg * 2 + gq) * 8, n & 1);
                if (layer == TLL && n == TLN && gq == 0) TL(45);
                wg_fence();
#pragma unroll 5
                for (int k = 0; k < 10; k++) { wg_n48_ss_ta(acc[gq], da, db, k); da += 128; db += 96; }
                wg_commit();
            }
            if (wg == 0) {
                mbar_wait(sb + HB_A + 16, n & 1);
                wg_fence();
                wg_n48_ss_ta(acc[0], da, db + 20 * 96, 1);
                wg_commit();
            }
            float inv;
            pow2_scale(__uint_as_float(__reduce_max_sync(~0u, __float_as_uint(fmaxf(fmaxf(wm.x, wm.y), fmaxf(wm.z, wm.w))))), 0, &inv);
            const uint32_t ysc = pack_bf(inv, inv);
            wg_wait<0>();
            if (layer == TLL && n == TLN) TL(46);
            if (lane == 0) mbar_arrive(sb + HB_AFREE);
            const uint32_t ad = sb + RI_STG + ((w & 3) * 16 + (lane & 15)) * 400 + (lane >> 4) * 96 + wg * 192;
#pragma unroll
            for (int q = 0; q < 6; q++) {
                const float *e = acc[0] + q * 4, *o = acc[1] + q * 4;
                stsm4(ad + q * 16, pack_h(e[0] + o[0], e[1] + o[1]), pack_h(e[2] + o[2], e[3] + o[3]), pack_h(e[0] - o[0], e[1] - o[1]), pack_h(e[2] - o[2], e[3] - o[3]));
            }
            cp_wait<0>();
            bar_sync(4, 256);
            const uint32_t xa = sb + RI_RES + (n & 1) * 21504 + fr * 336 + rg * 80, sg = (rg & 1) ? 0xbc00bc00u : 0x3c003c00u;
            float sum = 0.f, sq = 0.f;
            uint32_t ya = sb + RI_STG + fr * 400 + (rg >> 1) * 96 + ((rg & 1) ? 64 : 0), carry;
            asm("fma.rn.f16x2 %0,%1,%2,%3;" : "=r"(carry) : "r"(lds32(ya + 208)), "r"(sg), "r"(lds32(ya + 16)));
#pragma unroll 1
            for (int ch = 0; ch < 5; ch++, ya += (rg & 1) ? -16 : 16) {
                uint32_t y[4], z[4], xr[4];
                lds128(y, ya); lds128(z, ya + 192); lds128(xr, xa + ch * 16);
#pragma unroll
                for (int q = 0; q < 4; q++) asm("fma.rn.f16x2 %0,%1,%2,%0;" : "+r"(y[q]) : "r"(z[q]), "r"(sg));
                if (rg & 1) {
                    const uint32_t y0 = y[0], y1 = y[1];
                    y[0] = __byte_perm(carry, y[3], 0x7610); y[1] = __byte_perm(y[3], y[2], 0x7610);
                    y[3] = __byte_perm(y1, y0, 0x7610); y[2] = __byte_perm(y[2], y1, 0x7610);
                    carry = y0;
                }
#pragma unroll
                for (int q = 0; q < 4; q++) {
                    const float2 yf = __half22float2(*(const __half2*)&y[q]);
                    xr[q] = bfma(pack_bf(yf.x, yf.y), ysc, xr[q]);
                    const float e = bf_lo(xr[q]), f = bf_hi(xr[q]);
                    sum += e + f; sq = fmaf(e, e, fmaf(f, f, sq));
                }
                sts128(xa + ch * 16, xr[0], xr[1], xr[2], xr[3]);
            }
            uint2* stat = g_stat + (size_t)(layer * 32 + a) * 1024 + rg * 64 + fr;
            asm volatile("st.relaxed.gpu.global.v2.u32 [%0],{%1,%2};" ::"l"(stat + j4 * 256), "r"(__float_as_uint(sum)), "r"(__float_as_uint(sq) | 0x80000000u) : "memory");
            if (layer == TLL && n == TLN) TL(47);
            uint32_t s0[3], s1[3];
            int lim = 0;
            do {
#pragma unroll
                for (int q = 0; q < 3; q++)
                    asm volatile("ld.relaxed.gpu.global.v2.u32 {%0,%1},[%2];" : "=r"(s0[q]), "=r"(s1[q]) : "l"(stat + ((j4 + 1 + q) & 3) * 256) : "memory");
            } while (__any_sync(~0u, (int)(s1[0] & s1[1] & s1[2]) >= 0) && ++lim < SPIN_LIM);
#pragma unroll
            for (int q = 0; q < 3; q++) { sum += __uint_as_float(s0[q]); sq -= __uint_as_float(s1[q]); }
            sts64(sb + RI_ST + tid * 8, __float_as_uint(sum), __float_as_uint(sq));
            bar_sync(4, 256);
            if (layer == TLL && n == TLN) TL(48);
#pragma unroll
            for (int q = 1; q < 4; q++) {
                uint32_t st2[2];
                lds64(st2, sb + RI_ST + ((tid + q * 64) & 255) * 8);
                sum += __uint_as_float(st2[0]); sq += __uint_as_float(st2[1]);
            }
            const float mean = sum * (1.f / 640.f), r = rsqrtf(fmaxf(fmaf(-mean, mean, sq * (1.f / 640.f)), 0.f) + 1e-5f), off = -mean * r;
            uint4* dst = (uint4*)g_xn + ((size_t)(2 * a + (w & 1)) * 80 + chunk0(rg)) * 32 + lane;
#pragma unroll
            for (int i = 0; i < 5; i++) {
                uint32_t u[4];
                lds128(u, xa + i * 16);
                dst[i * 32] = make_uint4(pack_h(fmaf(bf_lo(u[0]), r, off), fmaf(bf_hi(u[0]), r, off)), pack_h(fmaf(bf_lo(u[1]), r, off), fmaf(bf_hi(u[1]), r, off)),
                                         pack_h(fmaf(bf_lo(u[2]), r, off), fmaf(bf_hi(u[2]), r, off)), pack_h(fmaf(bf_lo(u[3]), r, off), fmaf(bf_hi(u[3]), r, off)));
            }
            __syncwarp();
            if (lane == 0) mbar_arrive(sb + HB_LN);
            if (layer == TLL) TL(37);
            if (layer == TLL && n == TLN) TL(44);
            residual(a + (nh >> 2), n + 1);
#pragma unroll 2
            for (int rr = 0; rr < 64 - gr && tid < 240; rr += 12) {
                uint32_t v[4];
                lds128(v, gs + (n & 1) * 21504 + rr * 336);
                ((uint4*)x)[(a * 64 + rr) * 80 + go] = make_uint4(v[0], v[1], v[2], v[3]);
            }
        }
    }
    bar_sync(3, 384);
    if (layer == TLL) TL(38);
    if (jh >= na) {
        int c0 = 0;
#pragma unroll 1
        for (int mb = (jh - na) >> 3; mb < nbh; mb += (nh - na) >> 3, c0 += GNC) oproj_mma(sb, mb, (jh - na) & 7, c0, x, out);
        if (layer == TLL) TL(42);
        return;
    }
    const int p = w >> 1, mi = w & 1;
    int slot = p, ph = 0;
    for (int idx = jh + p * na; idx < NSEG * 32; idx += 4 * na) {
        const uint32_t it = sb + slot * 30720 + lane * 16;
        float iq, ik, iv;
        weight_scale(idx & 31, 0, &iq); weight_scale(idx & 31, 1, &ik); weight_scale(idx & 31, 2, &iv);
        bar_sync(6 + p, 64);
        mbar_wait(sb + HB_DONE + slot * 8, ph ^ 1);
        mbar_wait(sb + HB_FULL + slot * 8, ph);
        if (layer == TLL && idx >= 63 * 32) TL(55);
        float s[6][4];
#pragma unroll
        for (int i = 0; i < 6; i++) s[i][0] = s[i][1] = s[i][2] = s[i][3] = 0.f;
#pragma unroll
        for (int e = 0; e < 8; e++) {
            uint32_t q[4], k[4];
            ldsm4t(q, it + (e >> 2) * 8192 + (e & 3) * 1024 + mi * 512);
            ldsm4t(k, it + 24576 + e * 512);
            mma_bf(s[4], q[0], q[2], q[1], q[3], k[0], k[1]);
            mma_bf(s[5], q[0], q[2], q[1], q[3], k[2], k[3]);
            ldsm4t(k, it + (e >> 2) * 8192 + 4096 + (e & 3) * 1024);
            mma_bf(s[0], q[0], q[2], q[1], q[3], k[0], k[1]);
            mma_bf(s[1], q[0], q[2], q[1], q[3], k[2], k[3]);
            if (mi) {
                ldsm4t(k, it + (e >> 2) * 8192 + 4096 + (e & 3) * 1024 + 512);
                mma_bf(s[2], q[0], q[2], q[1], q[3], k[0], k[1]);
                mma_bf(s[3], q[0], q[2], q[1], q[3], k[2], k[3]);
            }
        }
#pragma unroll
        for (int q = 0; q < 4; q++) s[4][q] += s[5][q];
        const int seg = idx >> 5, h = idx & 31;
        const float sl = iq * ik * (0.08838834764831845f * 1.4426950408889634f);
        float mx[2] = {-3.0e38f, -3.0e38f};
#pragma unroll
        for (int i = 0; i < 5; i++)
#pragma unroll
            for (int q = 0; q < 4; q++) {
                const bool ok = i == 4 || (i * 8 + 2 * t + (q & 1)) <= (mi * 16 + g + (q >> 1) * 8);
                s[i][q] = ok ? s[i][q] * sl : -1.0e9f * 1.4426950408889634f;
                mx[q >> 1] = fmaxf(mx[q >> 1], s[i][q]);
            }
        float sum[2] = {0.f, 0.f};
#pragma unroll
        for (int r = 0; r < 2; r++) {
            mx[r] = fmaxf(mx[r], __shfl_xor_sync(~0u, mx[r], 1));
            mx[r] = fmaxf(mx[r], __shfl_xor_sync(~0u, mx[r], 2));
        }
#pragma unroll
        for (int i = 0; i < 5; i++)
#pragma unroll
            for (int q = 0; q < 4; q++) { s[i][q] = ex2(s[i][q] - mx[q >> 1]); sum[q >> 1] += s[i][q]; }
#pragma unroll
        for (int r = 0; r < 2; r++) {
            sum[r] += __shfl_xor_sync(~0u, sum[r], 1);
            sum[r] += __shfl_xor_sync(~0u, sum[r], 2);
            sum[r] = iv * rcp(sum[r]);
        }
        uint32_t pp[5][2];
#pragma unroll
        for (int i = 0; i < 5; i++) { pp[i][0] = pack_bf(s[i][0] * sum[0], s[i][1] * sum[0]); pp[i][1] = pack_bf(s[i][2] * sum[1], s[i][3] * sum[1]); }
        uint32_t* o = (uint32_t*)g_O + (((size_t)(seg >> 1) * 512 + h * 16) * 8 + (seg & 1) * 4 + mi * 2) * 32 + lane;
#pragma unroll
        for (int e = 0; e < 8; e++) {
            float o0[4] = {0.f, 0.f, 0.f, 0.f}, o1[4] = {0.f, 0.f, 0.f, 0.f};
            uint32_t v[4];
            lds64(v, it - lane * 8 + 28672 + e * 256);
            mma_bf8(o0, pp[4][0], pp[4][1], v[0]);
            mma_bf8(o1, pp[4][0], pp[4][1], v[1]);
            ldsm4(v, it + 16384 + e * 1024);
            mma_bf(o0, pp[0][0], pp[0][1], pp[1][0], pp[1][1], v[0], v[2]);
            mma_bf(o1, pp[0][0], pp[0][1], pp[1][0], pp[1][1], v[1], v[3]);
            ldsm4(v, it + 16384 + e * 1024 + 512);
            mma_bf(o0, pp[2][0], pp[2][1], pp[3][0], pp[3][1], v[0], v[2]);
            mma_bf(o1, pp[2][0], pp[2][1], pp[3][0], pp[3][1], v[1], v[3]);
            o[(2 * e) * 256] = pack_bf(o0[0], o0[1]); o[(2 * e) * 256 + 32] = pack_bf(o0[2], o0[3]);
            o[(2 * e + 1) * 256] = pack_bf(o1[0], o1[1]); o[(2 * e + 1) * 256 + 32] = pack_bf(o1[2], o1[3]);
        }
        __syncwarp();
        if (lane == 0) mbar_arrive(sb + HB_DONE + slot * 8);
        slot += 4;
        if (slot >= 6) { slot -= 6; ph ^= 1; }
    }
    if (layer == TLL) TL(39);
}

__global__ void __cluster_dims__(3, 1, 1) __launch_bounds__(384, 1)
k_chain(const int layer, const int nact, const uint32_t zero, const bf16* __restrict__ Wq, const bf16* __restrict__ Wk, const bf16* __restrict__ Wv,
        const bf16* __restrict__ Wo, const bf16* res, bf16* out) {
    extern __shared__ __align__(1024) char sm[];
    const uint32_t sb = smem_u32(sm);
    const int b = blockIdx.x, h = b / 3, c = b - h * 3;
    pdl_go();
    if (threadIdx.x >= 256) {
        asm volatile("setmaxnreg.dec.sync.aligned.u32 24;");
        TL(11 + layer * 14);
        chain_aux(sb, c, h, layer, nact);
    } else {
        asm volatile("setmaxnreg.inc.sync.aligned.u32 240;");
        chain_mma(sb, c, h, layer, zero, Wq, Wk, Wv, Wo, res, out);
    }
}
__global__ void __launch_bounds__(384, 1) k_help(const bf16* res, bf16* x, bf16* out, const int layer, const int na, const int nbh, const int zero, const bf16* Wq,
                                                  const bf16* Wk, const bf16* Wv, const bf16* Wo) {
    extern __shared__ __align__(1024) char sm[];
    if (layer == TLL) TL(51);
    if (threadIdx.x >= 256) {
        const uint32_t sb = smem_u32(sm);
        const int p = (threadIdx.x >> 5) - 8, i = (threadIdx.x & 31) * 4 + p;
        if (i < 34) mbar_init(sb + G_BAR + i * 8, i < 4 ? 3 : i < 8 || i == 12 || i == 13 ? 8 : i >= 22 && i < 28 ? 2 : 1);
        fence_async_smem();
        wait_flag<100>(g_flag + F_X + layer * 128 + 65, 321);
        fence_async_glb();
        if (i == 8 + p && blockIdx.x < (gridDim.x & ~3)) {
            mbar_expect(sb + HB_A + p * 8, 20480);
            bulk_g2s(sb + RI_A + p * 20480, (const char*)g_YT + (size_t)(blockIdx.x >> 2) * 81920 + p * 20480, 20480, sb + HB_A + p * 8);
        }
        __syncwarp();
        bar_sync(2, 128);
        bar_arrive(1, 384);
    }
    if (threadIdx.x + zero >= 256) helper_aux(smem_u32(sm), blockIdx.x, gridDim.x, na, nbh, layer, Wq, Wk, Wv, Wo);
    else helper_mma(sm, blockIdx.x, gridDim.x, na, nbh, layer, res, x, out);
    __syncwarp();
    pdl_go();
    if (blockIdx.x == 0) pdl_wait();
}

#define COL_PAD 15872
template <class... P, class... A>
void launch_pdl(void (*k)(P...), int grid, int block, int smem, cudaStream_t st, A... args) {
    cudaLaunchConfig_t cfg = {};
    cfg.gridDim = dim3(grid); cfg.blockDim = dim3(block); cfg.dynamicSmemBytes = smem; cfg.stream = st;
    cudaLaunchAttribute at[1];
    at[0].id = cudaLaunchAttributeProgrammaticStreamSerialization; at[0].val.programmaticStreamSerializationAllowed = 1;
    cfg.attrs = at;
    cfg.numAttrs = 1;
    cudaLaunchKernelEx(&cfg, k, args...);
}

}

extern "C" void kernel_launch(void* const* d_in, const int* in_sizes, int n_in, void* d_out, int out_size) {
    const bf16* x = (const bf16*)d_in[0];
    const bf16* wr = (const bf16*)d_in[1];
    const bf16* wi = (const bf16*)d_in[2];
    const bf16* mem0 = (const bf16*)d_in[4];
    const bf16* Wq = (const bf16*)d_in[5];
    const bf16* Wk = (const bf16*)d_in[6];
    const bf16* Wv = (const bf16*)d_in[7];
    const bf16* Wo = (const bf16*)d_in[8];
    bf16* out = (bf16*)d_out;
    static int nhelp = 0;
    static bf16 *xa, *xb;
    static cudaStream_t s1;
    static cudaEvent_t ev_fork, ev_join;
    if (!nhelp) {
        cudaStreamCreateWithFlags(&s1, cudaStreamNonBlocking);
        cudaEventCreateWithFlags(&ev_fork, cudaEventDisableTiming);
        cudaEventCreateWithFlags(&ev_join, cudaEventDisableTiming);
        cudaFuncSetAttribute(k_setup, cudaFuncAttributeMaxDynamicSharedMemorySize, SU_SMEM);
        cudaFuncSetAttribute(k_rowf, cudaFuncAttributeMaxDynamicSharedMemorySize, RF_SMEM);
        cudaFuncSetAttribute(k_col, cudaFuncAttributeMaxDynamicSharedMemorySize, COL_PAD);
        cudaFuncSetAttribute(k_chain, cudaFuncAttributeMaxDynamicSharedMemorySize, CH_SMEM);
        cudaFuncSetAttribute(k_setup, cudaFuncAttributePreferredSharedMemoryCarveout, 100);
        cudaFuncSetAttribute(k_rowf, cudaFuncAttributePreferredSharedMemoryCarveout, 100);
        cudaFuncSetAttribute(k_col, cudaFuncAttributePreferredSharedMemoryCarveout, 100);
        cudaFuncSetAttribute(k_chain, cudaFuncAttributePreferredSharedMemoryCarveout, 100);
        cudaFuncSetAttribute(k_help, cudaFuncAttributeMaxDynamicSharedMemorySize, HP_SMEM);
        cudaFuncSetAttribute(k_help, cudaFuncAttributePreferredSharedMemoryCarveout, 100);
        int dev = 0, sms = 0;
        cudaGetDevice(&dev);
        cudaDeviceGetAttribute(&sms, cudaDevAttrMultiProcessorCount, dev);
        nhelp = sms - 96 < 12 ? 12 : sms - 96;
        cudaGetSymbolAddress((void**)&xa, g_xa);
        cudaGetSymbolAddress((void**)&xb, g_xb);
    }
    const int na = nhelp - (nhelp >= 36 ? 24 : nhelp >= 28 ? 16 : 8), nbh = 14;
    cudaStream_t s0 = cudaStreamPerThread;
    cudaEventRecord(ev_fork, s0);
    cudaStreamWaitEvent(s1, ev_fork, 0);
    k_rowf<<<(96 + nhelp) & ~1, 256, RF_SMEM, s0>>>(x, 1);
    k_setup<<<NSETUP, 256, SU_SMEM, s1>>>(wr, wi, mem0);
    cudaEventRecord(ev_join, s1);
#define NLAYER 2
    for (int l = 0; l < NLAYER; l++) {
        const bf16* xin = l == 0 ? x : xb;
        if (l == 1) launch_pdl(k_rowf, 128, 256, RF_SMEM, s0, xin, 0);
        launch_pdl(k_col, 321, 128, l == 0 ? 0 : COL_PAD, s0, (int)(l == 0));
        launch_pdl(k_chain, 96, 384, CH_SMEM, s0, l, nhelp & ~3, 0u, Wq, Wk, Wv, Wo, (const bf16*)xa, l == 0 ? xb : out);
        launch_pdl(k_help, nhelp, 384, HP_SMEM, s0, xin, xa, l == 0 ? xb : out, l, na, nbh, 0, Wq, Wk, Wv, Wo);
    }
    cudaStreamWaitEvent(s0, ev_join, 0);
}
```

```cpp
#include <cuda_runtime.h>
#include <cuda_bf16.h>
#include <cuda_fp16.h>
#include <stdint.h>
#include <string.h>

namespace {

typedef __nv_bfloat16 bf16;
constexpr int S_ = 2048, D_ = 640, NSEG = 64;
constexpr int SPIN_LIM = 1 << 13;

__device__ float                  g_wmx[96];
__device__ __align__(1024) bf16   g_wot[4096 * 640];
__device__ __align__(16) float    g_co[1024];
__device__ __align__(256) uint2   g_stat[2 * 32 * 16 * 64];
__device__ float                  g_invM0;
__device__ __align__(16) float    g_wmax[128];
__device__ __align__(1024) char   g_redraw[65 * 32768];
constexpr int F_X = 2 * NSEG * 32, F_O = F_X + 2 * 128, NFLAG = F_O + 128, RING = 8;
constexpr int F_W = F_X + 66;
constexpr int NSETUP = 131;
struct __align__(256) Flag { unsigned v; };
__device__ Flag                   g_flag[NFLAG];
__device__ Flag                   g_ready[1];
__device__ __align__(1024) char   g_item[RING * 32 * 32768];
__device__ __align__(1024) bf16   g_O[S_ * 4096];
__device__ __align__(1024) __half g_xn[S_ * D_];
__device__ __align__(1024) bf16   g_xa[S_ * D_];
__device__ __align__(1024) bf16   g_xb[S_ * D_];
__device__ __align__(1024) __half g_UT[D_ * S_];
__device__ __align__(1024) __half g_YT[D_ * S_];
__device__ __align__(1024) __half g_ctab[64 * 128 + 64 * 64];
__device__ __align__(1024) uint32_t g_Wf[321 * 2048];

#define TL(i)
#define TLN 0
#define TLL 1
#define CK(i)
__device__ __forceinline__ uint32_t smem_u32(const void* p) { return (uint32_t)__cvta_generic_to_shared(p); }
__device__ __forceinline__ uint32_t mapa(uint32_t a, uint32_t r) { uint32_t o; asm("mapa.shared::cluster.u32 %0,%1,%2;" : "=r"(o) : "r"(a), "r"(r)); return o; }
__device__ __forceinline__ void mbar_init(uint32_t a, int c) { asm volatile("mbarrier.init.shared::cta.b64 [%0],%1;" ::"r"(a), "r"(c) : "memory"); }
__device__ __forceinline__ void mbar_expect(uint32_t a, int bytes) { asm volatile("mbarrier.arrive.expect_tx.shared::cta.b64 _,[%0],%1;" ::"r"(a), "r"(bytes) : "memory"); }
__device__ __forceinline__ void mbar_arrive(uint32_t a) { asm volatile("mbarrier.arrive.shared::cta.b64 _,[%0];" ::"r"(a) : "memory"); }
__device__ __forceinline__ bool mbar_try(uint32_t a, uint32_t par) {
    uint32_t p;
    asm volatile("{.reg .pred q; mbarrier.try_wait.parity.shared::cta.b64 q,[%1],%2; selp.u32 %0,1,0,q;}" : "=r"(p) : "r"(a), "r"(par) : "memory");
    return p;
}
__device__ __forceinline__ void mbar_wait(uint32_t a, uint32_t par) {
    if (!mbar_try(a, par)) {
        int lim = 0;
        while (!mbar_try(a, par) && ++lim < SPIN_LIM) {}
    }
}
__device__ __forceinline__ void mbar_sleep(uint32_t a, uint32_t par) {
    asm volatile("{.reg .pred q; .reg .u32 n; mov.u32 n,0;\n"
                 "W_LOOP: mbarrier.try_wait.parity.shared::cta.b64 q,[%0],%1,%2; add.u32 n,n,1; setp.lt.and.u32 q,n,%3,!q; @q bra W_LOOP;}"
                 ::"r"(a), "r"(par), "n"(20000), "n"(SPIN_LIM) : "memory");
}
__device__ __forceinline__ void bar_arrive(int id, int n) { asm volatile("bar.arrive %0,%1;" ::"r"(id), "r"(n) : "memory"); }
__device__ __forceinline__ uint32_t clock32() { uint32_t c; asm volatile("mov.u32 %0,%%clock;" : "=r"(c)); return c; }
__device__ __forceinline__ uint32_t read_tid() { uint32_t v; asm volatile("mov.u32 %0,%%tid.x;" : "=r"(v)); return v; }
__device__ __forceinline__ void bar_sync(int id, int n) { asm volatile("bar.sync %0,%1;" ::"r"(id), "r"(n) : "memory"); }
__device__ __forceinline__ void fence_async_smem() { asm volatile("fence.proxy.async.shared::cta;" ::: "memory"); }
__device__ __forceinline__ void fence_async_glb() { asm volatile("fence.proxy.async.global;" ::: "memory"); }
__device__ __forceinline__ void cluster_sync_full() { asm volatile("barrier.cluster.arrive.aligned; barrier.cluster.wait.aligned;" ::: "memory"); }
__device__ __forceinline__ void bulk_g2s(uint32_t dst, const void* src, int bytes, uint32_t mb) {
    asm volatile("cp.async.bulk.shared::cluster.global.mbarrier::complete_tx::bytes [%0],[%1],%2,[%3];" ::"r"(dst), "l"(src), "r"(bytes), "r"(mb) : "memory");
}
__device__ __forceinline__ void bulk_g2s_last(uint32_t dst, const void* src, int bytes, uint32_t mb) {
    asm volatile("{.reg .b64 p; createpolicy.fractional.L2::evict_first.b64 p, 1.0;\n"
                 "cp.async.bulk.shared::cluster.global.mbarrier::complete_tx::bytes.L2::cache_hint [%0],[%1],%2,[%3],p;}"
                 ::"r"(dst), "l"(src), "r"(bytes), "r"(mb) : "memory");
}
__device__ __forceinline__ void bulk_s2s(uint32_t dst, uint32_t src, int bytes, uint32_t mb) {
    asm volatile("cp.async.bulk.shared::cluster.shared::cta.mbarrier::complete_tx::bytes [%0],[%1],%2,[%3];" ::"r"(dst), "r"(src), "r"(bytes), "r"(mb) : "memory");
}
__device__ __forceinline__ void bulk_s2g(void* dst, uint32_t src, int bytes) {
    asm volatile("cp.async.bulk.global.shared::cta.bulk_group [%0],[%1],%2;" ::"l"(dst), "r"(src), "r"(bytes) : "memory");
}
__device__ __forceinline__ void cp_async16(uint32_t dst, const void* src, uint32_t bytes = 16) {
    asm volatile("cp.async.cg.shared.global [%0],[%1],16,%2;" ::"r"(dst), "l"(src), "r"(bytes) : "memory");
}
__device__ __forceinline__ void cp_commit() { asm volatile("cp.async.commit_group;" ::: "memory"); }
template <int N> __device__ __forceinline__ void cp_wait() { asm volatile("cp.async.wait_group %0;" ::"n"(N) : "memory"); }
__device__ __forceinline__ void bulk_commit() { asm volatile("cp.async.bulk.commit_group;" ::: "memory"); }
__device__ __forceinline__ void bulk_wait0() { asm volatile("cp.async.bulk.wait_group 0;" ::: "memory"); }
__device__ __forceinline__ void ldsm4(uint32_t* r, uint32_t a) {
    asm volatile("ldmatrix.sync.aligned.m8n8.x4.shared.b16 {%0,%1,%2,%3},[%4];" : "=r"(r[0]), "=r"(r[1]), "=r"(r[2]), "=r"(r[3]) : "r"(a) : "memory");
}
__device__ __forceinline__ void ldsm4t(uint32_t* r, uint32_t a) {
    asm volatile("ldmatrix.sync.aligned.m8n8.x4.trans.shared.b16 {%0,%1,%2,%3},[%4];" : "=r"(r[0]), "=r"(r[1]), "=r"(r[2]), "=r"(r[3]) : "r"(a) : "memory");
}
__device__ __forceinline__ void stsm4(uint32_t a, uint32_t r0, uint32_t r1, uint32_t r2, uint32_t r3) {
    asm volatile("stmatrix.sync.aligned.m8n8.x4.shared.b16 [%0],{%1,%2,%3,%4};" ::"r"(a), "r"(r0), "r"(r1), "r"(r2), "r"(r3) : "memory");
}
__device__ __forceinline__ void stsm4t(uint32_t a, uint32_t r0, uint32_t r1, uint32_t r2, uint32_t r3) {
    asm volatile("stmatrix.sync.aligned.m8n8.x4.trans.shared.b16 [%0],{%1,%2,%3,%4};" ::"r"(a), "r"(r0), "r"(r1), "r"(r2), "r"(r3) : "memory");
}
__device__ __forceinline__ void lds128(uint32_t* r, uint32_t a) {
    asm volatile("ld.shared.v4.b32 {%0,%1,%2,%3},[%4];" : "=r"(r[0]), "=r"(r[1]), "=r"(r[2]), "=r"(r[3]) : "r"(a) : "memory");
}
__device__ __forceinline__ void lds64(uint32_t* r, uint32_t a) {
    asm volatile("ld.shared.v2.b32 {%0,%1},[%2];" : "=r"(r[0]), "=r"(r[1]) : "r"(a) : "memory");
}
__device__ __forceinline__ uint32_t lds32(uint32_t a) { uint32_t v; asm volatile("ld.shared.b32 %0,[%1];" : "=r"(v) : "r"(a) : "memory"); return v; }
__device__ __forceinline__ void sts128(uint32_t a, uint32_t r0, uint32_t r1, uint32_t r2, uint32_t r3) {
    asm volatile("st.shared.v4.b32 [%0],{%1,%2,%3,%4};" ::"r"(a), "r"(r0), "r"(r1), "r"(r2), "r"(r3) : "memory");
}
__device__ __forceinline__ void sts64(uint32_t a, uint32_t v0, uint32_t v1) { asm volatile("st.shared.v2.b32 [%0],{%1,%2};" ::"r"(a), "r"(v0), "r"(v1) : "memory"); }
[[maybe_unused]] __device__ __forceinline__ void sts32(uint32_t a, uint32_t v) { asm volatile("st.shared.b32 [%0],%1;" ::"r"(a), "r"(v) : "memory"); }
#define AU_(op) "{.reg .u32 t; add.u32 t,%4,%5; " op " {%0,%1,%2,%3},[t+%6];}"
template <int I> __device__ __forceinline__ void ldsm4_u(uint32_t* r, uint32_t a, uint32_t u) {
    asm volatile(AU_("ldmatrix.sync.aligned.m8n8.x4.shared.b16") : "=r"(r[0]), "=r"(r[1]), "=r"(r[2]), "=r"(r[3]) : "r"(a), "r"(u), "n"(I) : "memory");
}
template <int I> __device__ __forceinline__ void ldsm4t_u(uint32_t* r, uint32_t a, uint32_t u) {
    asm volatile(AU_("ldmatrix.sync.aligned.m8n8.x4.trans.shared.b16") : "=r"(r[0]), "=r"(r[1]), "=r"(r[2]), "=r"(r[3]) : "r"(a), "r"(u), "n"(I) : "memory");
}
template <int I> __device__ __forceinline__ void lds128_u(uint32_t* r, uint32_t a, uint32_t u) {
    asm volatile(AU_("ld.shared.v4.b32") : "=r"(r[0]), "=r"(r[1]), "=r"(r[2]), "=r"(r[3]) : "r"(a), "r"(u), "n"(I) : "memory");
}
template <int I> __device__ __forceinline__ void lds64_u(uint32_t* r, uint32_t a, uint32_t u) {
    asm volatile("{.reg .u32 t; add.u32 t,%2,%3; ld.shared.v2.b32 {%0,%1},[t+%4];}" : "=r"(r[0]), "=r"(r[1]) : "r"(a), "r"(u), "n"(I) : "memory");
}
template <int I> __device__ __forceinline__ uint32_t lds32_u(uint32_t a, uint32_t u) {
    uint32_t v;
    asm volatile("{.reg .u32 t; add.u32 t,%1,%2; ld.shared.b32 %0,[t+%3];}" : "=r"(v) : "r"(a), "r"(u), "n"(I) : "memory");
    return v;
}
template <int I> __device__ __forceinline__ void sts64_u(uint32_t a, uint32_t u, uint32_t v0, uint32_t v1) {
    asm volatile("{.reg .u32 t; add.u32 t,%0,%1; st.shared.v2.b32 [t+%2],{%3,%4};}" ::"r"(a), "r"(u), "n"(I), "r"(v0), "r"(v1) : "memory");
}
template <int I> __device__ __forceinline__ void sts32_u(uint32_t a, uint32_t u, uint32_t v) {
    asm volatile("{.reg .u32 t; add.u32 t,%0,%1; st.shared.b32 [t+%2],%3;}" ::"r"(a), "r"(u), "n"(I), "r"(v) : "memory");
}
template <int I> __device__ __forceinline__ void sts16_u(uint32_t a, uint32_t u, uint32_t v) {
    asm volatile("{.reg .u32 t; add.u32 t,%0,%1; st.shared.b16 [t+%2],%3;}" ::"r"(a), "r"(u), "n"(I), "h"((unsigned short)v) : "memory");
}
template <int I> __device__ __forceinline__ void sts128_u(uint32_t a, uint32_t u, uint32_t r0, uint32_t r1, uint32_t r2, uint32_t r3) {
    asm volatile("{.reg .u32 t; add.u32 t,%0,%1; st.shared.v4.b32 [t+%2],{%3,%4,%5,%6};}" ::"r"(a), "r"(u), "n"(I), "r"(r0), "r"(r1), "r"(r2), "r"(r3) : "memory");
}
template <int I> __device__ __forceinline__ void stsm4_u(uint32_t a, uint32_t u, uint32_t r0, uint32_t r1, uint32_t r2, uint32_t r3) {
    asm volatile("{.reg .u32 t; add.u32 t,%0,%1; stmatrix.sync.aligned.m8n8.x4.shared.b16 [t+%2],{%3,%4,%5,%6};}"
                 ::"r"(a), "r"(u), "n"(I), "r"(r0), "r"(r1), "r"(r2), "r"(r3) : "memory");
}
__device__ __forceinline__ void st_share2(uint32_t a, uint32_t u, uint32_t mb, uint32_t d0, uint32_t d1, uint32_t v0, uint32_t v1) {
    asm volatile("{.reg .pred p; .reg .u32 t,x,y; add.u32 t,%0,%1;\n"
                 "add.u32 x,t,%3; add.u32 y,%2,%3; st.async.shared::cluster.mbarrier::complete_tx::bytes.v2.b32 [x],{%5,%6},[y];\n"
                 "add.u32 x,t,%4; add.u32 y,%2,%4; st.async.shared::cluster.mbarrier::complete_tx::bytes.v2.b32 [x],{%5,%6},[y];\n"
                 "st.shared.v2.b32 [t],{%5,%6}; bar.warp.sync -1; setp.eq.u32 p,%0,0; @p mbarrier.arrive.shared::cta.b64 _,[%2];}"
                 ::"r"(a), "r"(u), "r"(mb), "r"(d0), "r"(d1), "r"(v0), "r"(v1) : "memory");
}
template <int V> struct IC { __host__ __device__ constexpr operator int() const { return V; } };
template <int N, class F> __device__ __forceinline__ void sfor(F f) {
    if constexpr (N > 0) { sfor<N - 1>(f); f(IC<N - 1>()); }
}
__device__ __forceinline__ void mma_f16(float* d, const uint32_t* a, uint32_t b0, uint32_t b1) {
    asm volatile("mma.sync.aligned.m16n8k16.row.col.f32.f16.f16.f32 {%0,%1,%2,%3},{%4,%5,%6,%7},{%8,%9},{%0,%1,%2,%3};"
                 : "+f"(d[0]), "+f"(d[1]), "+f"(d[2]), "+f"(d[3]) : "r"(a[0]), "r"(a[1]), "r"(a[2]), "r"(a[3]), "r"(b0), "r"(b1));
}
__device__ __forceinline__ void mma_bf(float* d, uint32_t a0, uint32_t a1, uint32_t a2, uint32_t a3, uint32_t b0, uint32_t b1) {
    asm volatile("mma.sync.aligned.m16n8k16.row.col.f32.bf16.bf16.f32 {%0,%1,%2,%3},{%4,%5,%6,%7},{%8,%9},{%0,%1,%2,%3};"
                 : "+f"(d[0]), "+f"(d[1]), "+f"(d[2]), "+f"(d[3]) : "r"(a0), "r"(a1), "r"(a2), "r"(a3), "r"(b0), "r"(b1));
}
__device__ __forceinline__ void mma_bf8(float* d, uint32_t a0, uint32_t a1, uint32_t b0) {
    asm volatile("mma.sync.aligned.m16n8k8.row.col.f32.bf16.bf16.f32 {%0,%1,%2,%3},{%4,%5},{%6},{%0,%1,%2,%3};"
                 : "+f"(d[0]), "+f"(d[1]), "+f"(d[2]), "+f"(d[3]) : "r"(a0), "r"(a1), "r"(b0));
}
__device__ __forceinline__ uint32_t pack_bf(float lo, float hi) { uint32_t r; asm("cvt.rn.bf16x2.f32 %0,%1,%2;" : "=r"(r) : "f"(hi), "f"(lo)); return r; }
__device__ __forceinline__ uint32_t pack_h(float lo, float hi) { uint32_t r; asm("cvt.rn.f16x2.f32 %0,%1,%2;" : "=r"(r) : "f"(hi), "f"(lo)); return r; }
__device__ __forceinline__ float bf_lo(uint32_t v) { return __uint_as_float(v << 16); }
__device__ __forceinline__ float bf_hi(uint32_t v) { return __uint_as_float(v & 0xffff0000u); }
__device__ __forceinline__ uint32_t bfma(uint32_t a, uint32_t b, uint32_t c) { uint32_t r; asm("fma.rn.bf16x2 %0,%1,%2,%3;" : "=r"(r) : "r"(a), "r"(b), "r"(c)); return r; }
__device__ __forceinline__ uint4 add_bf8(const uint4 x, const uint32_t* y, const uint32_t k = 0x3f803f80u) {
    return make_uint4(bfma(y[0], k, x.x), bfma(y[1], k, x.y), bfma(y[2], k, x.z), bfma(y[3], k, x.w));
}
__device__ __forceinline__ float ex2(float x) { float r; asm("ex2.approx.ftz.f32 %0,%1;" : "=f"(r) : "f"(x)); return r; }
__device__ __forceinline__ float rcp(float x) { float r; asm("rcp.approx.ftz.f32 %0,%1;" : "=f"(r) : "f"(x)); return r; }
__device__ __forceinline__ void wg_fence() { asm volatile("wgmma.fence.sync.aligned;" ::: "memory"); }
__device__ __forceinline__ void wg_commit() { asm volatile("wgmma.commit_group.sync.aligned;" ::: "memory"); }
template <int N> __device__ __forceinline__ void wg_wait() { asm volatile("wgmma.wait_group.sync.aligned %0;" ::"n"(N) : "memory"); }
__device__ __forceinline__ uint64_t mkdesc(uint32_t a, uint32_t lbo, uint32_t sbo, uint32_t sw) {
    return (uint64_t)((a & 0x3FFFF) >> 4) | ((uint64_t)(lbo >> 4) << 16) | ((uint64_t)(sbo >> 4) << 32) | ((uint64_t)sw << 62);
}
#define F4(d, i) "+f"(d[i]), "+f"(d[i + 1]), "+f"(d[i + 2]), "+f"(d[i + 3])
#define F8(d, i) F4(d, i), F4(d, i + 4)
#define F16(d, i) F8(d, i), F8(d, i + 8)
template <int OFF, int SC> __device__ __forceinline__ void wg_n32_x(float* d, const uint32_t* a, uint32_t lo) {
    asm volatile("{.reg .pred p; .reg .b32 l; .reg .b64 q; setp.ne.b32 p,%22,0; add.u32 l,%20,%21; mov.b64 q,{l,8};\n"
                 "wgmma.mma_async.sync.aligned.m64n32k16.f32.f16.f16 "
                 "{%0,%1,%2,%3,%4,%5,%6,%7,%8,%9,%10,%11,%12,%13,%14,%15},{%16,%17,%18,%19},q,p,1,1,0;}"
                 : F16(d, 0) : "r"(a[0]), "r"(a[1]), "r"(a[2]), "r"(a[3]), "r"(lo), "n"(OFF), "n"(SC));
}
__device__ __forceinline__ void wg_n128_rs(float* d, const uint32_t* a, uint64_t db, int sc) {
    asm volatile("{.reg .pred p; setp.ne.b32 p,%69,0; wgmma.mma_async.sync.aligned.m64n128k16.f32.f16.f16 "
                 "{%0,%1,%2,%3,%4,%5,%6,%7,%8,%9,%10,%11,%12,%13,%14,%15,%16,%17,%18,%19,%20,%21,%22,%23,%24,%25,%26,%27,%28,%29,%30,%31,"
                 "%32,%33,%34,%35,%36,%37,%38,%39,%40,%41,%42,%43,%44,%45,%46,%47,%48,%49,%50,%51,%52,%53,%54,%55,%56,%57,%58,%59,%60,%61,%62,%63},"
                 "{%64,%65,%66,%67},%68,p,1,1,0;}"
                 : F16(d, 0), F16(d, 16), F16(d, 32), F16(d, 48) : "r"(a[0]), "r"(a[1]), "r"(a[2]), "r"(a[3]), "l"(db), "r"(sc));
}
#define N80_REGS "{%0,%1,%2,%3,%4,%5,%6,%7,%8,%9,%10,%11,%12,%13,%14,%15,%16,%17,%18,%19,%20,%21,%22,%23,%24,%25,%26,%27,%28,%29,%30,%31,%32,%33,%34,%35,%36,%37,%38,%39}"
__device__ __forceinline__ void wg_n80_ss(float* d, uint64_t da, uint64_t db, int sc) {
    asm volatile("{.reg .pred p; setp.ne.b32 p,%42,0; wgmma.mma_async.sync.aligned.m64n80k16.f32.bf16.bf16 " N80_REGS ",%40,%41,p,1,1,0,0;}"
                 : F16(d, 0), F16(d, 16), F8(d, 32) : "l"(da), "l"(db), "r"(sc));
}
__device__ __forceinline__ void wg_n88_ss(float* d, uint64_t da, uint64_t db, int sc) {
    asm volatile("{.reg .pred p; setp.ne.b32 p,%46,0; wgmma.mma_async.sync.aligned.m64n88k16.f32.f16.f16 "
                 "{%0,%1,%2,%3,%4,%5,%6,%7,%8,%9,%10,%11,%12,%13,%14,%15,%16,%17,%18,%19,%20,%21,%22,%23,%24,%25,%26,%27,%28,%29,%30,%31,"
                 "%32,%33,%34,%35,%36,%37,%38,%39,%40,%41,%42,%43},%44,%45,p,1,1,0,0;}"
                 : F16(d, 0), F16(d, 16), F8(d, 32), F4(d, 40) : "l"(da), "l"(db), "r"(sc));
}
__device__ __forceinline__ void wg_n48_ss_ta(float* d, uint64_t da, uint64_t db, int sc) {
    asm volatile("{.reg .pred p; setp.ne.b32 p,%26,0; wgmma.mma_async.sync.aligned.m64n48k16.f32.f16.f16 "
                 "{%0,%1,%2,%3,%4,%5,%6,%7,%8,%9,%10,%11,%12,%13,%14,%15,%16,%17,%18,%19,%20,%21,%22,%23},%24,%25,p,1,1,1,0;}"
                 : F16(d, 0), F8(d, 16) : "l"(da), "l"(db), "r"(sc));
}
template <int TA> __device__ __forceinline__ void wg_n64_ss_tb(float* d, uint64_t da, uint64_t db, int sc) {
    asm volatile("{.reg .pred p; setp.ne.b32 p,%34,0; wgmma.mma_async.sync.aligned.m64n64k16.f32.f16.f16 "
                 "{%0,%1,%2,%3,%4,%5,%6,%7,%8,%9,%10,%11,%12,%13,%14,%15,%16,%17,%18,%19,%20,%21,%22,%23,%24,%25,%26,%27,%28,%29,%30,%31},"
                 "%32,%33,p,1,1,%35,1;}"
                 : F16(d, 0), F16(d, 16) : "l"(da), "l"(db), "r"(sc), "n"(TA));
}
__device__ __forceinline__ void pdl_wait() { asm volatile("griddepcontrol.wait;" ::: "memory"); }
__device__ __forceinline__ void pdl_go() { asm volatile("griddepcontrol.launch_dependents;" ::: "memory"); }
__device__ __forceinline__ float cos640(float p) {
    const float q = fmaf(p, 0.0015625f, 12582912.f) - 12582912.f;
    return __cosf(fmaf(q, -640.f, p) * 0.009817477042468103f);
}
__device__ __forceinline__ uint4 cos_row8(float p0, float step, float amp = 1.f) {
    float v[8];
    const float k = 2.f * cos640(step);
    v[0] = amp * cos640(p0); v[1] = amp * cos640(p0 + step);
#pragma unroll
    for (int i = 2; i < 8; i++) v[i] = fmaf(k, v[i - 1], -v[i - 2]);
    return make_uint4(pack_h(v[0], v[1]), pack_h(v[2], v[3]), pack_h(v[4], v[5]), pack_h(v[6], v[7]));
}
__device__ __forceinline__ float wfilter_max(int lane) {
    float m = fmaxf(fmaxf(g_wmax[lane], g_wmax[lane + 32]), fmaxf(g_wmax[lane + 64], g_wmax[lane + 96]));
    return __uint_as_float(__reduce_max_sync(~0u, __float_as_uint(m)));
}
__device__ __forceinline__ unsigned ld_acquire(const Flag* p) { unsigned v; asm volatile("ld.acquire.gpu.global.u32 %0,[%1];" : "=r"(v) : "l"(p) : "memory"); return v; }
#define POLL_NS 200
template <int NS = POLL_NS> __device__ __forceinline__ void wait_flag(const Flag* p, unsigned v) {
    if (ld_acquire(p) >= v) return;
    unsigned x;
    int lim = 0;
    do {
        __nanosleep(NS);
        asm volatile("ld.relaxed.gpu.global.u32 %0,[%1];" : "=r"(x) : "l"(p) : "memory");
    } while (x < v && ++lim < SPIN_LIM);
    ld_acquire(p);
}
__device__ __forceinline__ void prefetch_l2(const void* p, int bytes) { asm volatile("cp.async.bulk.prefetch.L2.global [%0],%1;" ::"l"(p), "r"(bytes) : "memory"); }
__device__ __forceinline__ void red_release(Flag* p) { asm volatile("red.release.gpu.global.add.u32 [%0],1;" ::"l"(p) : "memory"); }
__device__ __forceinline__ void red_relaxed(Flag* p) { asm volatile("red.relaxed.gpu.global.add.u32 [%0],1;" ::"l"(p) : "memory"); }
__device__ __forceinline__ void red_h8(void* p, uint32_t a, uint32_t b, uint32_t c, uint32_t d) {
    asm volatile("red.relaxed.gpu.global.add.noftz.v4.f16x2 [%0],{%1,%2,%3,%4};" ::"l"(p), "r"(a), "r"(b), "r"(c), "r"(d) : "memory");
}
__device__ __forceinline__ float pow2_scale(float bound, int top, float* inv) {
    int e = (int)((__float_as_uint(bound) >> 23) & 0xff) - 126;
    int k = top - e;
    k = max(-100, min(100, k));
    *inv = __uint_as_float((uint32_t)(127 - k) << 23);
    return __uint_as_float((uint32_t)(127 + k) << 23);
}
__device__ __forceinline__ char* red_base() { return (char*)(((uintptr_t)g_redraw + 32767) & ~(uintptr_t)32767); }

__device__ __forceinline__ void setup_a(char* sm, const int b, const bf16* __restrict__ wr, const bf16* __restrict__ wi) {
    const int tid = threadIdx.x, lane = tid & 31;
    const uint32_t sb = smem_u32(sm);
    auto row_byte = [&](int q) { return ((b >> 2) + 32 * ((q >> 1) * 8 + 2 * (b & 3) + (q & 1))) * 642; };
#pragma unroll 1
    for (int r = tid >> 5; r < 32; r += 8) {
        const char* src = (const char*)(r < 16 ? wr : wi) + (row_byte(r & 15) & ~15);
        cp_async16(sb + r * 672 + lane * 16, src + lane * 16);
        if (lane < 9) cp_async16(sb + r * 672 + 512 + lane * 16, src + 512 + lane * 16);
    }
    ((uint4*)g_stat)[b * 256 + tid] = make_uint4(0, 0, 0, 0);
    if (tid < 2 * (NFLAG / 128)) ((uint4*)(g_flag + b * (NFLAG / 128) + (tid >> 1)))[tid & 1] = make_uint4(0, 0, 0, 0);
    if (tid < 12) {
        const int i = b * 12 + tid;
        const int f = ((i >> 4) & 3) * 8 + (i & 7), im = (i >> 3) & 1, part = (i >> 8) & 1;
        ((uint4*)g_ctab)[i] = cos_row8((float)(i < 1024 ? (i >> 7) * 80 * (i & 63) + ((i & 64) ? 480 : 0) : ((i >> 6) & 3) * 160 * f + (im == part ? 0 : im ? 160 : 480)),
                                       (float)(i < 1024 ? 10 * (i & 63) : 20 * f));
    }
    asm volatile("cp.async.wait_all;" ::: "memory");
    __syncthreads();
    const int q0 = (tid & 3) * 4;
    const char* rp[4];
#pragma unroll
    for (int u = 0; u < 4; u++) rp[u] = sm + (q0 + u) * 672 + (row_byte(q0 + u) & 15);
    uint32_t mx = 0;
#pragma unroll 2
    for (int c = tid >> 2; c < 321; c += 64) {
        uint32_t v[4];
#pragma unroll
        for (int u = 0; u < 4; u++) {
            v[u] = ((const unsigned short*)rp[u])[c] | ((uint32_t)((const unsigned short*)(rp[u] + 16 * 672))[c] << 16);
            mx = __vmaxu2(mx, v[u] & 0x7fff7fffu);
        }
        ((uint4*)g_Wf)[(size_t)c * 512 + b * 4 + ((tid ^ (b >> 1)) & 3)] = make_uint4(v[0], v[1], v[2], v[3]);
    }
    mx = __reduce_max_sync(~0u, max(mx & 0xffffu, mx >> 16));
    __syncthreads();
    if (lane == 0) ((uint32_t*)sm)[tid >> 5] = mx;
    __syncthreads();
    if (tid < 32) {
        mx = __reduce_max_sync(~0u, ((uint32_t*)sm)[lane & 7]);
        if (tid == 0) g_wmax[b] = __uint_as_float(mx << 16);
    }
}
__device__ __forceinline__ void setup_b(const int b, const bf16* __restrict__ mem0) {
    const int tid = threadIdx.x;
    uint4* z = (uint4*)red_base();
    if (b < 3) {
        const int w = tid >> 5, lane = tid & 31, p = b * 2 + ((w >> 1) & 1), odd = w & 1;
        uint32_t mx = 0;
#pragma unroll 4
        for (int i = lane; i < 640; i += 32) {
            const uint4 u = ((const uint4*)mem0)[i];
            mx = __vmaxu2(__vmaxu2(mx, u.x & 0x7fff7fffu), __vmaxu2(__vmaxu2(u.y & 0x7fff7fffu, u.z & 0x7fff7fffu), u.w & 0x7fff7fffu));
        }
        float inv, v[7];
        const float sc = pow2_scale(__uint_as_float(__reduce_max_sync(~0u, max(mx & 0xffffu, mx >> 16)) << 16), 14, &inv);
        if (tid == 0) g_invM0 = inv;
#pragma unroll
        for (int j = 0; j < 7; j++) {
            const int r = p * 56 + (j < 6 ? odd * 32 + (j >> 1) * 8 : 24) + (lane >> 2), mr = 2 * (lane & 3) + (j < 6 ? (j & 1) : odd);
            v[j] = r < 320 ? __bfloat162float(mem0[mr * 640 + (w >> 2) * 320 + r]) * sc : 0.f;
        }
        const int off = w * 2048 + (lane >> 4) * 1024 + ((lane >> 3) & 1) * 256 + (lane & 7) * 16 + (b == 2 ? (w >> 1) * 4096 + 128 : b * 16384);
        const uint4 u = make_uint4(pack_h(v[0], v[1]), pack_h(v[2], v[3]), pack_h(v[4], v[5]), pack_h(v[6], 32.f));
        z[off >> 4] = u; z[65536 + (off >> 4)] = u;
    }
}

#define SU_PAD 40960
constexpr int SU_SMEM = SU_PAD;
__global__ void __launch_bounds__(256, 4) k_setup(const bf16* __restrict__ wr, const bf16* __restrict__ wi, const bf16* __restrict__ mem0) {
    extern __shared__ __align__(1024) char sm[];
    TL(0);
    if (blockIdx.x >= 128) setup_b(blockIdx.x - 128, mem0);
    else setup_a(sm, blockIdx.x, wr, wi);
    __syncthreads();
    if (threadIdx.x == 0) red_release(g_ready);
    TL(1);
}
__device__ __forceinline__ float weight_scale(int h, int ty, float* inv) { return pow2_scale(__ldcg(g_wmx + h * 3 + ty), 6, inv); }

#define STR_(x) #x
#define STR(x) STR_(x)
#define RF_U 1
constexpr int RF_A = 22 * 2816, RF_X = RF_A + 22 * 1024, RF_BAR = RF_X + 64 * 1344, RF_SMEM = RF_BAR + 64;
__global__ void __cluster_dims__(2, 1, 1) __launch_bounds__(256, 2) k_rowf(const bf16* x, const int first) {
    extern __shared__ __align__(1024) char sm[];
    TL(first ? 2 : 16);
    const int tid = threadIdx.x, w = tid >> 5, lane = tid & 31, g = lane >> 2, t = lane & 3;
    if (blockIdx.x >= 128) { __nanosleep(2500); return; }
    const int a = blockIdx.x >> 2, gq = blockIdx.x & 3;
    const uint32_t sb = smem_u32(sm), mb = sb + RF_BAR + w * 8;
    if (lane == 0) {
        mbar_init(mb, 1);
        asm volatile("fence.mbarrier_init.release.cluster;" ::: "memory");
        mbar_expect(mb, 8 * 1280);
    }
    __syncwarp();
    asm volatile("barrier.cluster.arrive.relaxed.aligned;" ::: "memory");
#pragma unroll 1
    for (int ph = 0; ph < 2; ph++) {
        if (ph != first) {
            asm volatile("barrier.cluster.wait.aligned;" ::: "memory");
            pdl_wait();
            TL(first ? 3 : 17);
            if (lane < 4)
                asm volatile("cp.async.bulk.shared::cluster.global.mbarrier::complete_tx::bytes.multicast::cluster [%0],[%1],1280,[%2],%3;"
                             ::"r"(sb + RF_X + (w * 8 + (gq & 1) * 4 + lane) * 1344), "l"(x + (size_t)(a * 64 + w * 8 + (gq & 1) * 4 + lane) * 640), "r"(mb),
                             "h"((unsigned short)3) : "memory");
            __syncwarp();
            pdl_go();
        } else {
#pragma unroll 3
            for (int id = tid; id < 22 * 176; id += 256) {
                const int kg = id / 176, n = id - kg * 176;
                const float c = (float)(2 * n + (gq & 1));
                *(uint4*)(sm + id * 16) = cos_row8(fmaf((float)(kg * 8), c, (float)((gq & 2) * 80)), c, 0.03952847075210474f);
            }
        }
    }
    mbar_wait(mb, 0);
    const uint32_t row = sb + RF_X + (w * 8 + g) * 1344;
    float st[4][4] = {};
#pragma unroll 1
    for (int i = 0; i < 20; i += 4) {
        uint32_t u[4][4];
#pragma unroll
        for (int q = 0; q < 4; q++) lds128(u[q], row + (4 * (i + q) + t) * 16);
#pragma unroll
        for (int q = 0; q < 4; q++) {
            mma_bf(st[(q & 1) * 2], u[q][0], 0x3f803f80u, u[q][1], 0x3f803f80u, u[q][0], u[q][1]);
            mma_bf(st[(q & 1) * 2 + 1], u[q][2], 0x3f803f80u, u[q][3], 0x3f803f80u, u[q][2], u[q][3]);
        }
    }
#pragma unroll
    for (int q = 0; q < 4; q++) { st[0][q] += st[2][q]; st[1][q] += st[3][q]; }
    const float sq = __shfl_sync(~0u, (g & 1) ? st[0][1] + st[1][1] : st[0][0] + st[1][0], g * 4 + (g >> 1));
    const float mean = __shfl_sync(~0u, (g & 1) ? st[0][3] + st[1][3] : st[0][2] + st[1][2], g * 4 + (g >> 1)) * (1.f / 640.f);
    const float r = rsqrtf(fmaxf(fmaf(-mean, mean, sq * (1.f / 640.f)), 0.f) + 1e-5f), off = gq == 0 ? -4.f * mean * r : 0.f;
    const float r1 = (gq == 1 || gq == 2) ? -r : r, r2 = (gq & 1) ? -r : r, r3 = gq >= 2 ? -r : r;
    const uint32_t aa = sb + RF_A + w * 128 + g * 16;
    auto el = [&](int d) { unsigned short v; asm volatile("ld.shared.u16 %0,[%1];" : "=h"(v) : "r"(row + d * 2)); return __uint_as_float((uint32_t)v << 16); };
_Pragma(STR(unroll RF_U))
    for (int i = 0; i < 5; i++) {
        const int ch = t + 4 * i;
        uint32_t u[4][4];
        lds128(u[0], row + ch * 16); lds128(u[1], row + (39 - ch) * 16); lds128(u[2], row + (40 + ch) * 16); lds128(u[3], row + (79 - ch) * 16);
        const float nb0 = el(320 - 8 * ch), nb1 = el(ch ? 640 - 8 * ch : 0);
        float o[8];
#pragma unroll
        for (int q = 0; q < 8; q++) {
            const int m = (8 - q) >> 1;
            const float e0 = (q & 1) ? bf_hi(u[0][q >> 1]) : bf_lo(u[0][q >> 1]), e2 = (q & 1) ? bf_hi(u[2][q >> 1]) : bf_lo(u[2][q >> 1]);
            const float e1 = q == 0 ? nb0 : (q & 1) ? bf_hi(u[1][m & 3]) : bf_lo(u[1][m & 3]), e3 = q == 0 ? nb1 : (q & 1) ? bf_hi(u[3][m & 3]) : bf_lo(u[3][m & 3]);
            o[q] = fmaf(e3, r3, fmaf(e2, r2, fmaf(e1, r1, fmaf(e0, r, off))));
        }
        if (ch == 0) o[0] *= 0.5f;
        sts128(aa + ch * 1024, pack_h(o[0], o[1]), pack_h(o[2], o[3]), pack_h(o[4], o[5]), pack_h(o[6], o[7]));
    }
    if (t < 2) sts128(aa + (20 + t) * 1024, t == 0 ? pack_h(fmaf(el(480), r2, fmaf(el(160), r, 0.5f * off)), 0.f) : 0u, 0u, 0u, 0u);
    fence_async_smem();
    __syncthreads();
    const int wg = w >> 2;
    float acc[44];
    uint64_t da = mkdesc(sb + RF_A, 1024, 128, 0), db = mkdesc(sb + wg * 1408, 2816, 128, 0);
    wg_fence();
#pragma unroll 1
    for (int k = 0; k < 11; k++) { wg_n88_ss(acc, da, db, k); da += 128; db += 352; }
    wg_commit(); wg_wait<0>();
    const uint32_t stg = sb + RF_X + wg * 96 * 144;
#pragma unroll
    for (int j = 0; j < 12; j += 2) {
        const int m = lane >> 3, j1 = j < 10 ? j + 1 : j;
        stsm4t(stg + ((j + (m >> 1)) * 8 + (lane & 7)) * 144 + ((w & 3) * 16 + (m & 1) * 8) * 2, pack_h(acc[j * 4], acc[j * 4 + 1]),
               pack_h(acc[j * 4 + 2], acc[j * 4 + 3]), pack_h(acc[j1 * 4], acc[j1 * 4 + 1]), pack_h(acc[j1 * 4 + 2], acc[j1 * 4 + 3]));
    }
    bar_sync(1 + wg, 128);
#pragma unroll 3
    for (int rr = (tid & 127) >> 3; rr < 88; rr += 16) {
        const int ch = tid & 7, c = 2 * (wg * 88 + rr) + (gq & 1);
        if (c <= 320 - (gq >> 1) && (c | (gq ^ 2))) {
            uint32_t u[4];
            lds128(u, stg + rr * 144 + ch * 16);
            ((uint4*)g_UT)[((size_t)(c == 320 ? 1 : 2 * c + (gq >> 1)) * 32 + a) * 8 + (ch ^ (a & 7))] = make_uint4(u[0], u[1], u[2], u[3]);
        }
    }
    TL(first ? 4 : 18);
}

constexpr int GST = 4, GSTB = 32768 + 20480, GNC = 32;
constexpr int G_BAR = GST * GSTB + 3072;
#define GPACE 1100
#define GPACE2 650
__device__ __forceinline__ void oproj_load(const uint32_t sb, const int op, const int mb, const int nb, const int c0, const uint32_t pace) {
    const int by = op == 2 ? 20480 : 16384;
    const char* src = op == 2 ? (const char*)g_wot + (size_t)nb * GNC * 20480 : (const char*)g_O + (size_t)(2 * mb + op) * GNC * 16384;
    uint32_t t0 = clock32() - pace + op * (pace / 3);
#pragma unroll 1
    for (int c = c0; c < c0 + GNC; c++, src += by) {
        const int st = c % GST;
        if (c >= GST) mbar_wait(sb + G_BAR + (GST + st) * 8, ((c / GST) - 1) & 1);
        while (clock32() - t0 < pace) {}
        t0 = clock32();
        const int by_ = by;
        mbar_expect(sb + G_BAR + st * 8, by_);
        if (op == 2) bulk_g2s(sb + st * GSTB + 32768, src, by_, sb + G_BAR + st * 8);
        else bulk_g2s_last(sb + st * GSTB + op * 16384, src, by_, sb + G_BAR + st * 8);
    }
}
__device__ __forceinline__ void oproj_mma(const uint32_t sb, const int mb, const int nb, const int c0, const bf16* res, bf16* out) {
    const int w = threadIdx.x >> 5, lane = threadIdx.x & 31, wg = w >> 2;
    float acc[40];
    uint4 rv[5];
#pragma unroll 1
    for (int c = c0; c < c0 + GNC; c++) {
        const int st = c % GST;
        mbar_wait(sb + G_BAR + st * 8, (c / GST) & 1);
        const uint32_t d = sb + st * GSTB;
        wg_fence();
#pragma unroll
        for (int k = 0; k < 8; k++)
            wg_n80_ss(acc, mkdesc(d + wg * 16384 + k * 2048, 1024, 128, 0), mkdesc(d + 32768 + k * 2560, 1280, 128, 0), (c - c0) | k);
        wg_commit();
        if (c > c0) {
            wg_wait<1>();
            if (lane == 0) mbar_arrive(sb + G_BAR + (GST + (c - 1) % GST) * 8);
        }
    }
#pragma unroll
    for (int i = 0; i < 5; i++) {
        const int id = i * 32 + lane, r = id / 10;
        rv[i] = __ldcg((const uint4*)res + (size_t)(mb * 128 + w * 16 + r) * 80 + nb * 10 + id - r * 10);
    }
    wg_wait<0>();
    bar_sync(5, 256);
    const uint32_t stg = sb + (GST - 1) * GSTB + w * 16 * 176;
#pragma unroll
    for (int j = 0; j < 5; j++)
        stsm4(stg + (lane & 15) * 176 + (2 * j + (lane >> 4)) * 16, pack_bf(acc[j * 8], acc[j * 8 + 1]), pack_bf(acc[j * 8 + 2], acc[j * 8 + 3]),
              pack_bf(acc[j * 8 + 4], acc[j * 8 + 5]), pack_bf(acc[j * 8 + 6], acc[j * 8 + 7]));
    __syncwarp();
#pragma unroll
    for (int i = 0; i < 5; i++) {
        const int id = i * 32 + lane, r = id / 10, ch = id - r * 10;
        uint32_t y[4];
        lds128(y, stg + r * 176 + ch * 16);
        ((uint4*)out)[(size_t)(mb * 128 + w * 16 + r) * 80 + nb * 10 + ch] = add_bf8(rv[i], y);
    }
    fence_async_smem();
    __syncwarp();
    if (lane == 0) mbar_arrive(sb + G_BAR + (2 * GST - 1) * 8);
}

__global__ void __launch_bounds__(128, 4) k_col(const int first) {
    __shared__ __align__(1024) char sz[8192];
    __shared__ __align__(1024) char stab[24576];
    __shared__ __align__(1024) char swf[8192];
    __shared__ __align__(8) uint64_t bar[2];
    const int tid = threadIdx.x, wl = tid >> 5, lane = tid & 31, g = lane >> 2, t = lane & 3;
    const int c = blockIdx.x;
    TL(first ? 5 : 19);
    const bool realc = c == 0 || c == 320;
    const uint32_t z = smem_u32(sz), b2 = smem_u32(stab), a1 = b2 + 16384, wf = smem_u32(swf), mb = smem_u32(bar);
    if (tid == 0) { mbar_init(mb, 1); mbar_init(mb + 8, 1); fence_async_smem(); }
    if (realc) {
        for (int i = tid; i < 256; i += 128) sts128(z + 4096 + i * 16, 0, 0, 0, 0);
        fence_async_smem();
    }
    const int k1 = wl * 8 + g;
    float tc[16], ts[16];
#pragma unroll
    for (int j = 0; j < 16; j++) {
        const int p = ((j >> 1) * 8 + 2 * t + (j & 1)) * k1;
        __sincosf((float)(p - 1024) * 0.003067961575771282f, &ts[j], &tc[j]);
        ts[j] = -ts[j]; tc[j] = -tc[j];
    }
    if (first && tid == 32) { wait_flag<400>(g_ready, NSETUP); fence_async_glb(); }
    __syncthreads();
    if (tid == 32) {
        mbar_expect(mb + 8, 24576 + 8192);
        bulk_g2s(b2, g_ctab, 24576, mb + 8);
        bulk_g2s(wf, g_Wf + (size_t)c * 2048, 8192, mb + 8);
    }
    float inv;
    const float wsc = pow2_scale(wfilter_max(lane), 0, &inv) * (realc ? 0.0625f : 0.125f);
    pdl_wait();
    TL(first ? 6 : 20);
    if (tid == 0) {
        const int by = realc ? 4096 : 8192;
        mbar_expect(mb, by);
        bulk_g2s_last(z, (const char*)g_UT + (size_t)(c == 320 ? 1 : 2 * c) * 4096, by, mb);
    }
    pdl_go();
    mbar_wait(mb + 8, 0);
    mbar_wait(mb, 0);
    float d[64];
    uint32_t a[4][4];
    wg_fence();
#pragma unroll
    for (int ks = 0; ks < 4; ks++) wg_n64_ss_tb<0>(d, mkdesc(a1 + ks * 2048, 1024, 128, 0), mkdesc(z + ks * 2048, 1024, 1024, 1), ks);
    wg_commit(); wg_wait<0>();
    const float r32 = 0.17677669529663687f;
#pragma unroll
    for (int j = 0; j < 8; j++) {
        float yr[2], yi[2];
#pragma unroll
        for (int e = 0; e < 2; e++) {
            const float re = d[j * 4 + e] * r32, im = d[j * 4 + 2 + e] * r32, cc = tc[j * 2 + e], ss = ts[j * 2 + e];
            yr[e] = re * cc + im * ss; yi[e] = im * cc - re * ss;
        }
        a[j >> 1][(j & 1) * 2] = pack_h(yr[0], yr[1]); a[j >> 1][(j & 1) * 2 + 1] = pack_h(yi[0], yi[1]);
    }
    wg_fence();
#pragma unroll
    for (int ks = 0; ks < 4; ks++) wg_n128_rs(d, a[ks], mkdesc(b2 + ks * 4096, 2048, 128, 0), ks);
    wg_commit(); wg_wait<0>();
#pragma unroll
    for (int q = 0; q < 4; q++) {
        uint32_t wv[4];
        lds128(wv, wf + tid * 64 + ((q ^ (tid >> 1)) & 3) * 16);
#pragma unroll
        for (int jj = 0; jj < 2; jj++) {
            const int j = 2 * q + jj;
            float yr[2], yi[2];
#pragma unroll
            for (int e = 0; e < 2; e++) {
                const float xr = d[j * 4 + e] + d[32 + j * 4 + 2 + e], xi = d[j * 4 + 2 + e] - d[32 + j * 4 + e];
                const float fr = bf_lo(wv[jj * 2 + e]) * wsc, fi = bf_hi(wv[jj * 2 + e]) * wsc;
                yr[e] = xr * fr - xi * fi; yi[e] = xr * fi + xi * fr;
            }
            a[q][jj * 2] = pack_h(yr[0], yr[1]); a[q][jj * 2 + 1] = pack_h(yi[0], yi[1]);
        }
    }
    wg_fence();
#pragma unroll
    for (int ks = 0; ks < 4; ks++) wg_n128_rs(d, a[ks], mkdesc(b2 + ks * 4096, 2048, 128, 0), ks);
    wg_commit(); wg_wait<0>();
#pragma unroll
    for (int j = 0; j < 8; j++) {
        float yr[2], yi[2];
#pragma unroll
        for (int e = 0; e < 2; e++) {
            const float vr = (d[j * 4 + e] - d[32 + j * 4 + 2 + e]) * 0.125f, vi = (d[j * 4 + 2 + e] + d[32 + j * 4 + e]) * 0.125f;
            const float cc = tc[j * 2 + e], ss = ts[j * 2 + e];
            yr[e] = vr * cc - vi * ss; yi[e] = vi * cc + vr * ss;
        }
        a[j >> 1][(j & 1) * 2] = pack_h(yr[0], yr[1]); a[j >> 1][(j & 1) * 2 + 1] = pack_h(yi[0], yi[1]);
    }
    __syncthreads();
    const int mm = lane >> 3, rr = lane & 7;
    const uint32_t rowo = (wl * 16 + (mm & 1) * 8 + rr) * 128;
#pragma unroll
    for (int q = 0; q < 4; q++) stsm4(z + rowo + (((2 * q + (mm >> 1)) ^ rr) << 4), a[q][0], a[q][1], a[q][2], a[q][3]);
    fence_async_smem();
    __syncthreads();
    wg_fence();
#pragma unroll
    for (int ks = 0; ks < 4; ks++) wg_n64_ss_tb<1>(d, mkdesc(a1 + ks * 256, 128, 1024, 0), mkdesc(z + ks * 2048, 1024, 1024, 1), ks);
    wg_commit(); wg_wait<0>();
#pragma unroll
    for (int q = 0; q < 4; q++)
        stsm4(wf + rowo + (((2 * q + (mm >> 1)) ^ rr) << 4), pack_h(d[q * 8] * r32, d[q * 8 + 1] * r32), pack_h(d[q * 8 + 2] * r32, d[q * 8 + 3] * r32),
              pack_h(d[q * 8 + 4] * r32, d[q * 8 + 5] * r32), pack_h(d[q * 8 + 6] * r32, d[q * 8 + 7] * r32));
    __syncwarp();
    if (!(realc && wl >= 2)) {
        const int kk = c == 320 ? 320 : (c & 1) * 160 + (c >> 1) + (wl >> 1) * 320;
#pragma unroll
        for (int i = 0; i < 4; i++) {
            const int r = wl * 16 + i * 4 + (lane >> 3), ch = lane & 7;
            uint32_t v[4];
            lds128(v, wf + r * 128 + ((ch ^ (r & 7)) << 4));
            ((uint4*)g_YT)[((size_t)(r & 31) * 640 + kk) * 8 + (ch ^ (kk & 7))] = make_uint4(v[0], v[1], v[2], v[3]);
        }
    }
    TL(first ? 7 : 21);
}

constexpr int O_XS = 0;
constexpr int O_MS = 81920;
constexpr int O_QKP = O_MS + 10752;
constexpr int O_VM = O_QKP + 4096;
constexpr int O_SC = O_VM + 4096;
constexpr int O_OS = O_SC + 1536;
constexpr int O_XCH = O_OS + 2048;
constexpr int O_SUM = O_XCH + 8192;
constexpr int O_MX = O_SUM + 256;
constexpr int O_STG = O_MS + 65536 - 8192;
static_assert(O_STG - 16384 >= O_MX + 1024, "shared-memory map");
constexpr int O_WO = O_STG + 16384;
constexpr int O_SCL = O_WO + 65536;
constexpr int O_BAR = O_SCL + 64;
constexpr int B_XF = O_BAR, B_S = O_BAR + 16, B_VX = O_BAR + 32, B_STG = O_BAR + 48, B_FREE = O_BAR + 72;
constexpr int T_FA = O_BAR + 96, T_EA = T_FA + 32, T_FB = T_EA + 32, T_EB = T_FB + 56, T_RED = T_EB + 32;
constexpr int O_WMX = O_BAR + 512, B_W = O_BAR + 64;
constexpr int O_LAST = (O_WMX + 192 + 1023) / 1024 * 1024;
constexpr int CH_SMEM = O_LAST + 8192;
static_assert(O_WO == 19 * 8192, "weight staging");
__device__ __forceinline__ uint32_t tail_b(int c) { return c % 7 < 4 ? O_XS + (c % 7) * 20480 : O_WO + (c % 7 - 4) * 20480; }
__device__ __forceinline__ int s_tx(int c) { return c == 2 ? 2 * 768 : 768 + 2048; }

#define NPERM 1
#define NWO0 1
#define NWO0B 4
#define NWO1 6
#define TDELAY 800
#define WDEPTH 6
#define RDELAY 580

#define STAMP(i)

#define NTA 23
#define NTB 26
template <int LO, int HI>
__device__ __forceinline__ void tok_issue(const uint32_t (&A0)[20][4], const uint32_t (&A1)[20][4], float (&b0)[16], float (&b1)[16], uint32_t xd,
                                          const uint32_t zero) {
    if (LO == 0) wg_fence();
    sfor<HI - LO>([&](auto I) {
        constexpr int i = LO + I;
        if constexpr (i < 20) wg_n32_x<i * 64, i>(b0, A0[i], xd); else wg_n32_x<(i - 20) * 64, i - 20>(b1, A1[i - 20], xd + zero);
        if constexpr (i == 19 || i == NTB - 1 || i == 39) wg_commit();
    });
}
__device__ __forceinline__ void tok_give(const float (&b0)[16], const uint32_t L16, const uint32_t xch0) {
    wg_wait<1>();
    sfor<2>([&](auto I) {
        constexpr int i = I;
        sts128_u<i * 512>(L16, xch0, pack_h(b0[8 * i], b0[8 * i + 1]), pack_h(b0[8 * i + 2], b0[8 * i + 3]), pack_h(b0[8 * i + 4], b0[8 * i + 5]),
                          pack_h(b0[8 * i + 6], b0[8 * i + 7]));
    });
}
__device__ __forceinline__ void tok_finish(float (&b1)[16], const uint32_t (&e)[2][4], const uint32_t L16, const uint32_t dst, const uint32_t idn) {
#pragma unroll
    for (int j = 0; j < 4; j++)
        asm volatile("mma.sync.aligned.m16n8k8.row.col.f32.f16.f16.f32 {%0,%1,%2,%3},{%4,%5},{%6},{%0,%1,%2,%3};"
                     : F4(b1, 4 * j) : "r"(e[j >> 1][(j & 1) * 2]), "r"(e[j >> 1][(j & 1) * 2 + 1]), "r"(idn));
    stsm4_u<0>(L16, dst, pack_bf(b1[0], b1[1]), pack_bf(b1[2], b1[3]), pack_bf(b1[4], b1[5]), pack_bf(b1[6], b1[7]));
    stsm4_u<512>(L16, dst, pack_bf(b1[8], b1[9]), pack_bf(b1[10], b1[11]), pack_bf(b1[12], b1[13]), pack_bf(b1[14], b1[15]));
}
__device__ __forceinline__ uint32_t uni(uint32_t v) { return __shfl_sync(~0u, v, 0); }
__device__ __forceinline__ uint32_t badd(uint32_t a, uint32_t b) { uint32_t r; asm("add.rn.bf16x2 %0,%1,%2;" : "=r"(r) : "r"(a), "r"(b)); return r; }
__device__ __forceinline__ uint32_t bmax(uint32_t a, uint32_t b) { uint32_t r; asm("max.bf16x2 %0,%1,%2;" : "=r"(r) : "r"(a), "r"(b)); return r; }
__device__ __forceinline__ uint32_t babsmax(uint32_t a, uint32_t b) { uint32_t r; asm("max.xorsign.abs.bf16x2 %0,%1,%2;" : "=r"(r) : "r"(a), "r"(b)); return r; }
__device__ __forceinline__ uint32_t habsmax(uint32_t a, uint32_t b) { uint32_t r; asm("max.xorsign.abs.f16x2 %0,%1,%2;" : "=r"(r) : "r"(a), "r"(b)); return r; }

template <int NPF>
__device__ __forceinline__ float mem_out(const uint32_t sb, const uint32_t L16, const uint32_t L8, uint32_t (&wo)[16][4], const uint32_t woa,
                                         char* dst, const bool odd) {
    bar_sync(2, 352);
    float a[4][4];
#pragma unroll
    for (int i = 0; i < 4; i++) a[i][0] = a[i][1] = a[i][2] = a[i][3] = 0.f;
    uint32_t ob[4][4], sm_[2], sc[2];
    sfor<8>([&](auto I) {
        constexpr int i = I;
        if constexpr (!(i & 1)) ldsm4t_u<O_OS + (i >> 1) * 512>(ob[i >> 1], L16, sb);
        if constexpr (i >= NPF) { ldsm4t(wo[i], woa + i * 1024); ldsm4t(wo[8 + i], (woa ^ 32) + i * 1024); }
    });
    lds64_u<O_SUM>(sm_, L8 & 24, sb); lds64(sc, sb + O_SCL);
#pragma unroll
    for (int i = 0; i < 8; i++) {
        mma_bf(a[i & 1], wo[i][0], wo[i][1], wo[i][2], wo[i][3], ob[i >> 1][(i & 1) * 2], ob[i >> 1][(i & 1) * 2 + 1]);
        mma_bf(a[2 + (i & 1)], wo[8 + i][0], wo[8 + i][1], wo[8 + i][2], wo[8 + i][3], ob[i >> 1][(i & 1) * 2], ob[i >> 1][(i & 1) * 2 + 1]);
    }
    const float f0 = rcp(__uint_as_float(sm_[0])) * __uint_as_float(sc[0]), f1 = rcp(__uint_as_float(sm_[1])) * __uint_as_float(sc[0]);
    red_h8(dst, pack_h((a[0][0] + a[1][0]) * f0, (a[0][1] + a[1][1]) * f1), pack_h((a[0][2] + a[1][2]) * f0, (a[0][3] + a[1][3]) * f1),
           pack_h((a[2][0] + a[3][0]) * f0, (a[2][1] + a[3][1]) * f1), pack_h(odd ? (a[2][3] + a[3][3]) * f1 : (a[2][2] + a[3][2]) * f0, 1.f));
    return __uint_as_float(sc[1]);
}

__device__ __forceinline__ void chain_mma(const uint32_t sb, const int c, const int h, const int layer, const uint32_t zero, const bf16* __restrict__ Wq,
                                          const bf16* __restrict__ Wk, const bf16* __restrict__ Wv, const bf16* __restrict__ Wo,
                                          const bf16* res, bf16* out) {
    int tid = read_tid(), lane = tid & 31;
    const int w = __shfl_sync(~0u, tid >> 5, 0), wg = w >> 2;
    [[maybe_unused]] const int cta = h * 3 + c;
    uint32_t A0[20][4], A1[20][4];
    const int t0 = (w & 3) + wg * 4, t1 = t0 ^ 4;
    float sl;
    {
        const int tl = tid & 127, r = tl >> 3, ch = tl & 7;
        const size_t so = (size_t)(wg * 320 + r) * 4096 + h * 128 + ch * 8;
        const bf16 *wa = (c == 2 ? Wv : Wq + c * 64) + so, *wb = (c == 2 ? Wv + 64 : Wk + c * 64) + so;
        const uint32_t ring = sb + wg * 4096;
        const uint32_t dst = ring + r * 128 + ((ch ^ r) & 7) * 16;
        const uint32_t src = ring + ((lane & 7) + (lane >> 4) * 8) * 128 + ((((w & 3) * 2 + ((lane >> 3) & 1)) ^ lane) & 7) * 16;
        const int q4 = lane & 3, gr = (c * 2 + ((w >> 1) & 1)) * 56 + (q4 == 3 ? 24 : (w & 1) * 32 + q4 * 8);
        const bf16* wo_ = Wo + (size_t)(h * 128 + (lane >> 2)) * 640 + wg * 320 + min(gr, 312);
        const uint32_t wdst = sb + O_WO + w * 8192 + (lane >> 2) * 64 + ((q4 ^ (lane >> 3)) & 3) * 16;
        auto issue = [&](int i) {
            if (i < 20) {
                const uint32_t d = dst + (i < 19 ? i * 8192 : O_LAST);
                cp_async16(d, wa + (size_t)i * 65536); cp_async16(d + 2048, wb + (size_t)i * 65536);
                if (i < 16) cp_async16(wdst + i * 512, wo_ + i * 5120, gr < 320 ? 16 : 0);
            }
            cp_commit();
        };
#pragma unroll 1
        for (int i = 0; i < WDEPTH; i++) issue(i);
        asm volatile("barrier.cluster.arrive.relaxed.aligned;" ::: "memory");
        float fa, fb;
        if (layer == 0) {
            uint32_t ma = 0, mb = 0;
#pragma unroll 1
            for (int i = 0; i < 20; i++) {
                issue(i + WDEPTH);
                cp_wait<WDEPTH>();
                const uint32_t d = dst + (i < 19 ? i * 8192 : O_LAST);
                uint32_t u[8];
                lds128(u, d); lds128(u + 4, d + 2048);
                ma = babsmax(babsmax(ma, babsmax(u[0], u[1])), babsmax(u[2], u[3])); mb = babsmax(babsmax(mb, babsmax(u[4], u[5])), babsmax(u[6], u[7]));
            }
            ma = __reduce_max_sync(~0u, max(ma & 0x7fffu, (ma >> 16) & 0x7fffu)); mb = __reduce_max_sync(~0u, max(mb & 0x7fffu, (mb >> 16) & 0x7fffu));
            asm volatile("barrier.cluster.wait.aligned;" ::: "memory");
            if (lane < 3)
                asm volatile("st.async.shared::cluster.mbarrier::complete_tx::bytes.v2.b32 [%0],{%1,%2},[%3];"
                             ::"r"(mapa(sb + O_WMX + (c * 8 + w) * 8, lane)), "r"(ma), "r"(mb), "r"(mapa(sb + B_W, lane)) : "memory");
            __syncwarp();
            {
                uint32_t off[4];
                float cs[4] = {0.f, 0.f, 0.f, 0.f};
#pragma unroll
                for (int q = 0; q < 4; q++) {
                    const int g_ = (c * 2 + ((w >> 1) & 1)) * 56 + (q == 3 ? 24 : (w & 1) * 32 + q * 8), col = wg * 320 + g_, nb = col / 80;
                    off[q] = g_ < 320 && !(q == 3 && (w & 1)) ? ((nb * 512 + h * 16) * 10 + (col - nb * 80) / 8) * 32 + lane : ~0u;
                }
                const uint32_t ta = sb + O_WO + w * 8192 + (lane & 7) * 64 + (((lane >> 3) ^ (lane >> 1)) & 3) * 16;
#pragma unroll 2
                for (int i = 0; i < 16; i++) {
                    uint32_t r[4];
                    ldsm4t(r, ta + i * 512);
#pragma unroll
                    for (int q = 0; q < 4; q++) {
                        if (off[q] != ~0u) ((uint32_t*)g_wot)[off[q] + i * 320] = r[q];
                        cs[q] += fabsf(bf_lo(r[q])) + fabsf(bf_hi(r[q]));
                    }
                }
                float cm = 0.f;
#pragma unroll
                for (int q = 0; q < 4; q++) {
                    cs[q] += __shfl_xor_sync(~0u, cs[q], 1); cs[q] += __shfl_xor_sync(~0u, cs[q], 2);
                    cm = fmaxf(cm, cs[q]);
                }
                const uint32_t n1 = __reduce_max_sync(~0u, __float_as_uint(cm));
                if (lane == 0) g_co[h * 32 + c * 8 + w] = __uint_as_float(n1);
            }
            mbar_wait(sb + B_W, 0);
            uint32_t v[2];
            lds64(v, sb + O_WMX + (lane < 24 ? lane : 0) * 8);
            const bool mine = (lane >> 3) < 3 && ((lane >> 4) == 1) == (c == 2);
            ma = __reduce_max_sync(~0u, mine ? v[0] : 0u); mb = __reduce_max_sync(~0u, mine ? v[1] : 0u);
            if (c == 2) ma = mb = max(ma, mb);
            fa = __uint_as_float(ma << 16); fb = __uint_as_float(mb << 16);
            if (tid == 0) {
                if (c != 1) g_wmx[h * 3 + c] = fa;
                if (c == 0) g_wmx[h * 3 + 1] = fb;
            }
        } else {
            fa = __ldcg(g_wmx + h * 3 + (c == 2 ? 2 : 0)); fb = __ldcg(g_wmx + h * 3 + (c == 2 ? 2 : 1));
            asm volatile("barrier.cluster.wait.aligned;" ::: "memory");
        }
        if (layer == TLL) TL(49);
        float ia, ib;
        const float sa = pow2_scale(fa, 6, &ia), sc_b = pow2_scale(fb, 6, &ib);
        sl = __uint_as_float(uni(__float_as_uint(ia * ib * (0.08838834764831845f * 1.4426950408889634f))));
        const uint32_t pa = pack_bf(sa, sa), pb = pack_bf(sc_b, sc_b);
        const int ahead = layer == 0 ? 20 : WDEPTH;
        auto convert = [&](int lo) {
#pragma unroll 1
            for (int i = lo; i < lo + 10; i++) {
                issue(i + ahead);
                cp_wait<WDEPTH>();
                const uint32_t d = dst + (i < 19 ? i * 8192 : O_LAST);
                uint32_t u[8];
                lds128(u, d); lds128(u + 4, d + 2048);
#pragma unroll
                for (int q = 0; q < 8; q++)
                    asm("{.reg .b32 m,l,u; mul.rn.bf16x2 m,%0,%1; shl.b32 l,m,16; and.b32 u,m,0xffff0000; cvt.rn.f16x2.f32 %0,u,l;}" : "+r"(u[q]) : "r"(q < 4 ? pa : pb));
                sts128(d, u[0], u[1], u[2], u[3]); sts128(d + 2048, u[4], u[5], u[6], u[7]);
            }
            bar_sync(6 + wg, 128);
        };
        const uint32_t s0 = src + wg * 2048, s1 = src + 2048 - wg * 2048;
        convert(0);
#pragma unroll
        for (int i = 0; i < 10; i++) { ldsm4t(A0[i], s0 + i * 8192); ldsm4t(A1[i], s1 + i * 8192); }
        if (layer == TLL) TL(50);
        convert(10);
#pragma unroll
        for (int i = 10; i < 20; i++) { ldsm4t(A0[i], s0 + (i < 19 ? i * 8192 : O_LAST)); ldsm4t(A1[i], s1 + (i < 19 ? i * 8192 : O_LAST)); }
        if (layer == TLL) TL(53);
        bar_arrive(9, 288);
        bar_sync(4, 288);
        asm volatile("barrier.cluster.arrive.relaxed.aligned;" ::: "memory");
    }
    const uint32_t idn = (lane >> 3) == (lane & 3) ? ((lane & 4) ? 0x3c000000u : 0x3c00u) : 0u;
    float invM = g_invM0;
    char* redp = red_base() + (size_t)layer * 32 * 32768 + w * 2048 + (lane >> 4) * 1024 + ((lane >> 3) & 1) * 256 + (lane & 7) * 16;
    const uint32_t ro2 = uni((w >> 1) * 4096 + 128), rown = uni(c == 2 ? ro2 : c * 16384);
    const uint32_t L16 = lane * 16, L8 = lane * 8, L4 = lane * 4;
    const uint32_t xch0 = uni(sb + O_XCH + t0 * 1024), xch1 = uni(sb + O_XCH + t1 * 1024);
    const uint32_t qo0 = uni(sb + O_QKP + (w & 3) * 1024 + (wg ? 768 : 0)), qp0 = uni(qo0 + (wg ? 128 : 256));
    const uint32_t qo1 = uni(sb + O_QKP + (w & 3) * 1024 + (wg ? 128 : 512)), qp1 = uni(qo1 + (wg ? 256 : 128));
    const uint32_t vo1 = uni(qo1 + (wg ? -128 : 256)), vp1 = uni(qp1 + (wg ? -128 : 256));
    const uint32_t msr = uni(sb + O_MS + wg * 5376);
    const uint32_t msw = uni(msr + ((w >> 1) & 1) * 896 + (w & 1) * 512), msh = uni(msr + ((w >> 1) & 1) * 896 + 384 + (w & 1) * 2);
    const uint32_t sco = uni(sb + O_SC + c * 768 + (w & 3) * 256);
    const uint32_t woa = sb + O_WO + w * 8192 + (lane >> 4) * 512 + (lane & 7) * 64 + (((lane >> 3) ^ (lane >> 1)) & 1) * 16 + ((lane >> 2) & 1) * 32;
    const uint32_t w512 = uni(sb + w * 512), w128 = uni(sb + w * 128);
    const uint32_t pd0 = uni(mapa(sb, c == 2 ? 0 : 2) - sb), pd1 = uni(mapa(sb, c == 1 ? 0 : 1) - sb);
    const bool scw = c < 2 && w >= 4 && w <= 6;
    uint32_t sn = uni(sb + O_STG + (c == 2 ? 8192 : 0) + t1 * 1024);
    uint32_t ka = uni(sb + (w == 6 ? O_QKP + 512 : O_STG + 4096 + (w & 1) * 512));
    uint32_t vs = uni(sb + O_VM + t1 * 256);
    uint32_t va = uni(sb + O_STG + 8192 + w * 2048), vr = uni(sb + O_VM + w * 512);
    const uint32_t sn2 = uni(2 * sn - 16384), ka2 = uni(2 * ka - (w == 6 ? 0 : 16384)), vs2 = uni(2 * vs + 2048), va2 = uni(2 * va - 16384),
                   vr2 = uni(2 * vr + 2048);
    uint32_t xd = uni((uint32_t)mkdesc(sb + O_XS + wg * 20480, 512, 128, 0));
    const uint32_t xd2 = uni(2 * xd + 2560);

    uint32_t wp[2 * NPERM + 1][4];
    sfor<NPERM>([&](auto I) { constexpr int i = I; ldsm4t(wp[2 * i], woa + i * 1024); ldsm4t(wp[2 * i + 1], (woa ^ 32) + i * 1024); });
    auto wo_fetch = [&](uint32_t (&wo)[16][4], auto I) {
        constexpr int i = I;
        if constexpr (i < NPERM) {
#pragma unroll
            for (int q = 0; q < 4; q++) { wo[i][q] = wp[2 * i][q]; wo[8 + i][q] = wp[2 * i + 1][q]; }
        } else { ldsm4t(wo[i], woa + i * 1024); ldsm4t(wo[8 + i], (woa ^ 32) + i * 1024); }
    };
    if (layer == TLL) TL(32);
    float b0[16], b1[16];
    mbar_wait(sb + B_XF, 0);
    if (layer == TLL) TL(33);
    tok_issue<0, NTB>(A0, A1, b0, b1, xd, zero);
    tok_give(b0, L16, xch0);
    tok_issue<NTB, 40>(A0, A1, b0, b1, xd, zero);
    bar_sync(4, 256);
    wg_wait<0>();
    {
        uint32_t e[2][4];
        lds128_u<0>(e[0], L16, xch1); lds128_u<512>(e[1], L16, xch1);
        tok_finish(b1, e, L16, sn, idn);
    }
    sn = sn2 - sn; xd = xd2 - xd;
    bar_sync(5, 288);
    asm volatile("barrier.cluster.wait.aligned;" ::: "memory");
    if (layer == TLL) TL(34);
    mbar_wait(sb + B_XF + 8, 0);
    if (layer == TLL) TL(35);
    tok_issue<0, NTA>(A0, A1, b0, b1, xd, zero);
    uint32_t tr = clock32() - RDELAY;

#pragma unroll 1
    for (int st = 0;; st++) {
        uint4 mv[3];
        asm volatile("{.reg .pred p; .reg .b32 t;\n"
                     "mov.b32 %0,0; mov.b32 %1,0; mov.b32 %2,0; mov.b32 %3,0; mov.b32 %4,0; mov.b32 %5,0; mov.b32 %6,0; mov.b32 %7,0;\n"
                     "mov.b32 %8,0; mov.b32 %9,0; mov.b32 %10,0; mov.b32 %11,0;\n"
                     "T_LOOP: mov.u32 t,%%clock; sub.u32 t,t,%14; setp.ge.u32 p,t,%15;\n"
                     "@p ld.relaxed.gpu.global.v4.u32 {%0,%1,%2,%3},[%12]; @p ld.relaxed.gpu.global.v4.u32 {%4,%5,%6,%7},[%12+16384];\n"
                     "@p ld.relaxed.gpu.global.v4.u32 {%8,%9,%10,%11},[%13];\n"
                     "@!p bra T_LOOP;}"
                     : "=r"(mv[0].x), "=r"(mv[0].y), "=r"(mv[0].z), "=r"(mv[0].w), "=r"(mv[1].x), "=r"(mv[1].y), "=r"(mv[1].z), "=r"(mv[1].w),
                       "=r"(mv[2].x), "=r"(mv[2].y), "=r"(mv[2].z), "=r"(mv[2].w)
                     : "l"(redp), "l"(redp + ro2), "r"(tr), "n"(RDELAY) : "memory");
        STAMP(10);
        tok_issue<NTA, NTB>(A0, A1, b0, b1, xd, zero);
        tok_give(b0, L16, xch0);
        tok_issue<NTB, 40>(A0, A1, b0, b1, xd, zero);
        xd = xd2 - xd;
        STAMP(9);
        if (zero >> 30) break;
        asm volatile("{.reg .pred p; .reg .b32 a,h,t,n; .reg .b16 l,u; .reg .b64 q;\n"
                     "add.u32 a,%12,%13; add.u32 h,%12,%14; mov.u32 n,0;\n"
                     "M_LOOP:\n .pragma \"nounroll\";\n"
                     "st.shared.b32 [a],%0; st.shared.b32 [a+128],%1; st.shared.b32 [a+256],%2; mov.b32 {l,u},%3; st.shared.b16 [h],l;\n"
                     "st.shared.b32 [a+1792],%4; st.shared.b32 [a+1920],%5; st.shared.b32 [a+2048],%6; mov.b32 {l,u},%7; st.shared.b16 [h+1792],l;\n"
                     "st.shared.b32 [a+3584],%8; st.shared.b32 [a+3712],%9; st.shared.b32 [a+3840],%10; mov.b32 {l,u},%11; st.shared.b16 [h+3584],l;\n"
                     "lop3.b32 t,%3,%7,0x50000000,0x7e; lop3.b32 t,t,%11,0x50000000,0xf6; setp.gt.u32 p,t,0xffff;\n"
                     "vote.sync.any.pred p,p,-1; add.u32 n,n,1; setp.lt.and.u32 p,n,%17,p; @!p bra M_DONE;\n"
                     "ld.relaxed.gpu.global.v4.u32 {%0,%1,%2,%3},[%15]; ld.relaxed.gpu.global.v4.u32 {%4,%5,%6,%7},[%15+16384];\n"
                     "cvt.u64.u32 q,%16; add.u64 q,q,%15; ld.relaxed.gpu.global.v4.u32 {%8,%9,%10,%11},[q];\n"
                     "bra M_LOOP;\n"
                     "M_DONE:}"
                     : "+r"(mv[0].x), "+r"(mv[0].y), "+r"(mv[0].z), "+r"(mv[0].w), "+r"(mv[1].x), "+r"(mv[1].y), "+r"(mv[1].z), "+r"(mv[1].w),
                       "+r"(mv[2].x), "+r"(mv[2].y), "+r"(mv[2].z), "+r"(mv[2].w)
                     : "r"(L4), "r"(msw), "r"(msh), "l"(redp), "r"(ro2), "n"(SPIN_LIM) : "memory");
        bar_sync(3, 256);
        STAMP(0);
        uint32_t e[2][4];
        float f1[4];
        {
            uint32_t b[10][4];
            float acc[4][4];
#pragma unroll
            for (int i = 0; i < 4; i++) acc[i][0] = acc[i][1] = acc[i][2] = acc[i][3] = 0.f;
            auto ld = [&](auto I) { constexpr int i = I; ldsm4t_u<i * 512>(b[i], L16, msr); };
            auto mm = [&](auto I) {
                constexpr int i = I;
                mma_f16(acc[0], A0[2 * i], b[i][0], b[i][1]); mma_f16(acc[2], A1[2 * i], b[i][0], b[i][1]);
                mma_f16(acc[1], A0[2 * i + 1], b[i][2], b[i][3]); mma_f16(acc[3], A1[2 * i + 1], b[i][2], b[i][3]);
            };
            ld(IC<0>()); ld(IC<1>()); ld(IC<2>()); ld(IC<3>());
            sts32_u<O_MX>(L4, w128,
                          habsmax(habsmax(habsmax(habsmax(mv[0].x, mv[0].y), habsmax(mv[0].z, mv[1].x)), habsmax(habsmax(mv[1].y, mv[1].z), mv[2].x)),
                                  habsmax(habsmax(mv[2].y, mv[2].z), habsmax(habsmax(mv[0].w, mv[1].w), mv[2].w) & 0xffffu)));
            wg_wait<0>();
            ld(IC<4>()); mm(IC<0>()); ld(IC<5>()); mm(IC<1>()); ld(IC<6>()); mm(IC<2>());
            ld(IC<7>()); mm(IC<3>()); ld(IC<8>()); mm(IC<4>()); ld(IC<9>()); mm(IC<5>());
            lds128_u<0>(e[0], L16, xch1); lds128_u<512>(e[1], L16, xch1);
            mm(IC<6>()); mm(IC<7>()); mm(IC<8>()); mm(IC<9>());
            const uint32_t u0 = pack_bf((acc[0][0] + acc[1][0]) * invM, (acc[0][1] + acc[1][1]) * invM);
            const uint32_t u1 = pack_bf((acc[0][2] + acc[1][2]) * invM, (acc[0][3] + acc[1][3]) * invM);
#pragma unroll
            for (int i = 0; i < 4; i++) f1[i] = (acc[2][i] + acc[3][i]) * invM;
            sts32_u<0>(L4, qo0, u0); sts32_u<0>(L4, qp0, u1); sts32_u<0>(L4, qo1, pack_bf(f1[0], f1[1])); sts32_u<0>(L4, qp1, pack_bf(f1[2], f1[3]));
        }
        STAMP(1);
        bar_sync(1, 320);
        if (__builtin_expect(scw, 1)) {
            float a[4][4];
#pragma unroll
            for (int i = 0; i < 4; i++) a[i][0] = a[i][1] = a[i][2] = a[i][3] = 0.f;
            uint32_t q[4][4], k[4][4];
            sfor<4>([&](auto I) {
                constexpr int i = I;
                ldsm4t_u<O_QKP + i * 1024>(q[i], L16, sb); ldsm4t_u<i * 1024>(k[i], L16, ka);
            });
#pragma unroll
            for (int i = 0; i < 4; i++) {
                mma_bf(a[i & 1], q[i][0], q[i][1], q[i][2], q[i][3], k[i][0], k[i][1]);
                mma_bf(a[2 + (i & 1)], q[i][0], q[i][1], q[i][2], q[i][3], k[i][2], k[i][3]);
            }
            const float mk = w == 6 ? 1.f : 0.f;
            const float x0 = (a[0][0] + a[0][2]) + (a[1][0] + a[1][2]), x1 = (a[0][1] + a[0][3]) + (a[1][1] + a[1][3]);
            const float y0 = (a[2][0] + a[2][2]) + (a[3][0] + a[3][2]), y1 = (a[2][1] + a[2][3]) + (a[3][1] + a[3][3]);
            st_share2(L8, sco, sb + B_S, pd0, pd1, pack_bf(fmaf(y0, mk, x0) * sl, fmaf(y1, mk, x1) * sl), pack_bf(y0 * sl, y1 * sl));
        }
        if (c == 2) {
            const uint32_t x = lds32_u<0>(L4, vo1), y = lds32_u<0>(L4, vp1);
            st_share2(L8, vs, sb + B_S, pd0, pd1, pack_bf(f1[0] + bf_lo(x), f1[1] + bf_hi(x)), pack_bf(f1[2] + bf_lo(y), f1[3] + bf_hi(y)));
        }
        STAMP(3);
        if (st == NSEG - 1) break;
        tok_finish(b1, e, L16, sn, idn);
        redp += (st & 1) ? 32768 - 512 : 512;
        if (wg == 0) {
            uint32_t wo[16][4], vx[2][2][4], vm[2][2];
            ldsm4_u<0>(vx[0][0], L16, va); ldsm4_u<512>(vx[0][1], L16, va); ldsm4_u<1024>(vx[1][0], L16, va); ldsm4_u<1536>(vx[1][1], L16, va);
            sfor<NWO0>([&](auto I) { wo_fetch(wo, I); });
            mbar_wait(sb + B_S, st & 1);
            STAMP(4);
            uint32_t s[5];
            {
                uint32_t p[2][5];
                sfor<2>([&](auto R) {
                    constexpr int r = R;
                    lds64_u<O_SC + r * 768>(p[r], L8, sb); lds64_u<O_SC + r * 768 + 256>(p[r] + 2, L8, sb); p[r][4] = lds32_u<O_SC + r * 768 + 512>(L8, sb);
                });
#pragma unroll
                for (int j = 0; j < 5; j++) s[j] = badd(p[0][j], p[1][j]);
            }
            lds64_u<0>(vm[0], L8, vr); lds64_u<256>(vm[1], L8, vr);
            uint32_t mm = bmax(bmax(bmax(s[0], s[1]), bmax(s[2], s[3])), s[4]);
            mm = bmax(bmax(mm, __shfl_xor_sync(~0u, mm, 1)), bmax(__shfl_xor_sync(~0u, mm, 2), __shfl_xor_sync(~0u, mm, 3)));
            const float m = fmaxf(bf_lo(mm), bf_hi(mm));
            float o0[4] = {0.f, 0.f, 0.f, 0.f}, o1[4] = {0.f, 0.f, 0.f, 0.f}, d[10];
#pragma unroll
            for (int j = 0; j < 5; j++) { d[2 * j] = bf_lo(s[j]) - m; d[2 * j + 1] = bf_hi(s[j]) - m; }
#pragma unroll
            for (int j = 0; j < 10; j++) d[(j + 8) % 10] = ex2(d[(j + 8) % 10]);
            float sum = ((d[8] + d[9]) + (d[0] + d[1])) + ((d[2] + d[3]) + (d[4] + d[5])) + (d[6] + d[7]);
            const uint32_t p4 = pack_bf(d[8], d[9]), p0 = pack_bf(d[0], d[1]), p1 = pack_bf(d[2], d[3]), p2 = pack_bf(d[4], d[5]), p3 = pack_bf(d[6], d[7]);
            mma_bf8(o0, vm[0][0], vm[0][1], p4);
            mma_bf8(o1, vm[1][0], vm[1][1], p4);
            mma_bf(o0, vx[0][0][0], vx[0][0][1], vx[0][0][2], vx[0][0][3], p0, p1);
            mma_bf(o1, vx[1][0][0], vx[1][0][1], vx[1][0][2], vx[1][0][3], p0, p1);
            mma_bf(o0, vx[0][1][0], vx[0][1][1], vx[0][1][2], vx[0][1][3], p2, p3);
            mma_bf(o1, vx[1][1][0], vx[1][1][1], vx[1][1][2], vx[1][1][3], p2, p3);
            sfor<NWO0B - NWO0>([&](auto I) { constexpr int i = I; wo_fetch(wo, IC<NWO0 + i>()); });
            sum += __shfl_xor_sync(~0u, sum, 1);
            sum += __shfl_xor_sync(~0u, sum, 2);
            sts32_u<O_OS>(L4, w512, pack_bf(o0[0], o0[1])); sts32_u<O_OS + 128>(L4, w512, pack_bf(o0[2], o0[3]));
            sts32_u<O_OS + 256>(L4, w512, pack_bf(o1[0], o1[1])); sts32_u<O_OS + 384>(L4, w512, pack_bf(o1[2], o1[3]));
            sts32_u<O_SUM>(lane & 28, sb, __float_as_uint(sum));
            STAMP(5);
            invM = mem_out<NWO0B>(sb, L16, L8, wo, woa, redp + rown, w & 1);
            tr = clock32();

        } else {
            uint32_t wo[16][4];
            sfor<NWO1>([&](auto I) { wo_fetch(wo, I); });
            invM = mem_out<NWO1>(sb, L16, L8, wo, woa, redp + rown, w & 1);
            tr = clock32();

        }
        STAMP(7);
        tok_issue<0, NTA>(A0, A1, b0, b1, xd, zero);
        sn = sn2 - sn; ka = ka2 - ka; vs = vs2 - vs; va = va2 - va; vr = vr2 - vr;
        STAMP(8);
    }
    if (layer == TLL) TL(40);
    bar_arrive(8, 320);
    tid = read_tid(); lane = tid & 31;
    float acc[40];
    const int nc = c == 2 ? 10 : 11;
    const int mb = 28 + (h >> 3), nj = c == 2 ? 1 : 2;
    uint32_t rv[2][2];
    const size_t go = ((size_t)(mb * 64 + (w & 3) * 16 + (lane >> 2)) * 640 + (h & 7) * 80 + (wg * 5 + c * 2) * 8 + (lane & 3) * 2) >> 1;
#pragma unroll
    for (int u = 0; u < 4; u++) rv[u >> 1][u & 1] = (u >> 1) < nj ? __ldcg((const uint32_t*)res + go + (u >> 1) * 4 + (u & 1) * 2560) : 0u;
#pragma unroll 1
    for (int k = 0; k < nc; k++) {
        mbar_wait(sb + T_FB + (k % 7) * 8, k >= 7);
        mbar_wait(sb + T_FA + (k & 3) * 8, (k >> 2) & 1);
        if (layer == TLL && k == 0) TL(41);
        const uint64_t da = mkdesc(sb + O_MS + (k & 3) * 16384 + wg * 8192, 1024, 128, 0), db = mkdesc(sb + tail_b(k) + wg * 10240, 1280, 128, 0);
        wg_fence();
#pragma unroll
        for (int q = 0; q < 4; q++) wg_n80_ss(acc, da + q * 128, db + q * 160, k | q);
        wg_commit();
        if (k > 0) {
            wg_wait<1>();
            if (lane == 0) { mbar_arrive(sb + T_EA + ((k - 1) & 3) * 8); if (k <= 4) mbar_arrive(sb + T_EB + (k - 1) * 8); }
        }
    }
    if (layer == TLL) TL(52);
    wg_wait<0>();
    asm volatile("barrier.cluster.arrive.relaxed.aligned; barrier.cluster.wait.aligned;" ::: "memory");
    const uint32_t ra = sb + O_XS + tid * 16, rb = sb + O_MS + tid * 16;
#pragma unroll
    for (int j = 0; j < 5; j++) {
        const float* q = acc + 4 * j;
        sts128(rb + j * 4096, __float_as_uint(wg ? q[0] : q[20]), __float_as_uint(wg ? q[1] : q[21]), __float_as_uint(wg ? q[2] : q[22]), __float_as_uint(wg ? q[3] : q[23]));
    }
    bar_sync(4, 256);
#pragma unroll
    for (int j = 0; j < 5; j++) {
        const float* q = acc + 4 * j;
        uint32_t p[4];
        lds128(p, sb + O_MS + (tid ^ 128) * 16 + j * 4096);
        asm volatile("st.async.shared::cluster.mbarrier::complete_tx::bytes.v4.f32 [%0],{%1,%2,%3,%4},[%5];" ::"r"(mapa(ra + c * 8192 + (j & 1) * 4096, j >> 1)),
                     "f"((wg ? q[20] : q[0]) + __uint_as_float(p[0])), "f"((wg ? q[21] : q[1]) + __uint_as_float(p[1])),
                     "f"((wg ? q[22] : q[2]) + __uint_as_float(p[2])), "f"((wg ? q[23] : q[3]) + __uint_as_float(p[3])), "r"(mapa(sb + T_RED, j >> 1)) : "memory");
    }
    mbar_wait(sb + T_RED, 0);
#pragma unroll 1
    for (int u = 0; u < nj; u++) {
        uint32_t p[3][4];
#pragma unroll
        for (int q = 0; q < 3; q++) lds128(p[q], ra + q * 8192 + u * 4096);
        float y[4];
#pragma unroll
        for (int i = 0; i < 4; i++) y[i] = __uint_as_float(p[0][i]) + __uint_as_float(p[1][i]) + __uint_as_float(p[2][i]);
        ((uint32_t*)out)[go + u * 4] = bfma(pack_bf(y[0], y[1]), 0x3f803f80u, u ? rv[1][0] : rv[0][0]);
        ((uint32_t*)out)[go + u * 4 + 2560] = bfma(pack_bf(y[2], y[3]), 0x3f803f80u, u ? rv[1][1] : rv[0][1]);
    }
    TL(layer == 0 ? 15 : 29);
    asm volatile("barrier.cluster.arrive.relaxed.aligned; barrier.cluster.wait.aligned;" ::: "memory");
}

__device__ __forceinline__ void tail_load_b(const uint32_t sb, const int h, const int c, const int k) {
    mbar_expect(sb + T_FB + (k % 7) * 8, 20480);
    bulk_g2s(sb + tail_b(k), (const char*)g_wot + (size_t)((h & 7) * GNC + c * 11 + k) * 20480, 20480, sb + T_FB + (k % 7) * 8);
}
__device__ __forceinline__ void chain_aux(const uint32_t sb, const int c, const int h, const int layer, const int nact) {
    const int tid = read_tid(), w = __shfl_sync(~0u, tid >> 5, 0), lane = tid & 31;
    if (w == 8) {
        mbar_init(sb + O_BAR + lane * 8, lane == 2 ? (c == 2 ? 9 : 4) : (lane >= 16 && lane < 20) || (lane >= 27 && lane < 31) ? 8 : 1);
        asm volatile("fence.mbarrier_init.release.cluster;" ::: "memory");
        fence_async_smem();
        __syncwarp();
    }
    {
        uint4* z = (uint4*)red_base() + layer * 65536;
#pragma unroll 1
        for (int i = blockIdx.x * 128 + tid - 256; i < 65536; i += 96 * 128)
            if (i >= 2048 || (i & 32)) z[i] = make_uint4(0, 0, 0, 0);
    }
    if (w == 8 && lane == 0) {
        mbar_expect(sb + B_S, s_tx(c));
        mbar_expect(sb + B_W, 192);
        mbar_expect(sb + T_RED, (c == 2 ? 1 : 2) * 3 * 4096);
        if (layer == 1) prefetch_l2(red_base() + 32 * 32768 + blockIdx.x * 1024, 1024);
        if (layer == 0) wait_flag<400>(g_ready, NSETUP);
    }
    __syncwarp();
    cluster_sync_full();
    asm volatile("barrier.cluster.arrive.relaxed.aligned;" ::: "memory");
    pdl_wait();
    if (w == 11 && lane == 0) red_relaxed(g_flag + F_X + layer * 128 + 65);
    Flag* flag = g_flag + layer * NSEG * 32 + h;
    const Flag* xflag = g_flag + F_X + layer * 128;
    char* const it0 = g_item + (size_t)h * 32768;
    if (w == 8) {
#pragma unroll 1
        for (int n = 0; n < 3; n++) {
            wait_flag<100>(xflag + (n >> 1), 4);
            fence_async_glb();
            if (n == 0) { bar_sync(4, 288); fence_async_smem(); }
            if (lane == 0 && n < 2) {
                mbar_expect(sb + B_XF + n * 8, 40960);
                bulk_g2s(sb + O_XS + n * 40960, (const char*)g_xn + n * 40960, 40960, sb + B_XF + n * 8);
            }
            __syncwarp();
        }
#pragma unroll 1
        for (int n = 0; n < NSEG; n++) {
            const int np = n & 1;
            if (n == 0) { wait_flag<100>(g_flag + F_W + layer * 128, 96); bar_sync(5, 288); } else bar_sync(2, 352);
            if (n == 1) TL(12 + layer * 14);
            if (n == 63) TL(13 + layer * 14);
            if (lane == 0 && n == NSEG - 1) mbar_arrive(sb + B_STG + 8);
            if (lane == 0 && n < NSEG - 1) {
                const uint32_t vs = sb + O_STG + 8192 - np * 16384, vb = sb + B_VX + np * 8;
                if (c == 2) {
                    fence_async_smem();
                    bulk_s2s(mapa(vs, 0), vs, 8192, mapa(vb, 0));
                    bulk_s2s(mapa(vs, 1), vs, 8192, mapa(vb, 1));
                } else mbar_expect(vb, 8192);
                if (n == 0) { mbar_expect(sb + B_XF, 40960); bulk_g2s(sb + O_XS, (const char*)g_xn + 2 * 40960, 40960, sb + B_XF); }
                if (n == h * 3 + c && !np && n + 6 < NSEG) prefetch_l2(red_base() + (size_t)(layer * 32 + (n >> 1) + 3) * 32768, 32768);
            }
            __syncwarp();
        }
    } else if (w == 11) {
        float cvo;
        {
            auto max8 = [&](const float* p) {
                const float4 u = ((const float4*)p)[0], v = ((const float4*)p)[1];
                return fmaxf(fmaxf(fmaxf(u.x, u.y), fmaxf(u.z, u.w)), fmaxf(fmaxf(v.x, v.y), fmaxf(v.z, v.w)));
            };
            wait_flag<300>(g_flag + F_W + layer * 128, 96);
            const float* pc = g_co + lane * 32;
            float a = 640.f * __ldcg(g_wmx + lane * 3 + 2), o = fmaxf(fmaxf(max8(pc), max8(pc + 8)), max8(pc + 16));
#pragma unroll 1
            for (int s = 16; s; s >>= 1) { a = fmaxf(a, __shfl_xor_sync(~0u, a, s)); o += __shfl_xor_sync(~0u, o, s); }
            cvo = a * o * 2.f;
        }
        float invM = g_invM0;
        float iv;
        weight_scale(h, 2, &iv);
        const uint32_t L16 = sb + lane * 16 + O_MX;
#pragma unroll 1
        for (int st = 0; st < NSEG; st++) {
            bar_sync(1, 320);
            if (st == NSEG - 1) break;
            if (lane == 0) mbar_arrive(sb + B_STG + (st & 1) * 8);
            uint32_t u[2][4];
            lds128(u[0], L16); lds128(u[1], L16 + 512);
            uint32_t mx = habsmax(habsmax(habsmax(u[0][0], u[0][1]), habsmax(u[0][2], u[0][3])), habsmax(habsmax(u[1][0], u[1][1]), habsmax(u[1][2], u[1][3])));
            mx = __reduce_max_sync(~0u, max(mx & 0x7fffu, (mx >> 16) & 0x7fffu));
            const float bound = fmaxf(__half2float(__ushort_as_half((unsigned short)mx)) * invM, 25.5f) * cvo;
            const float sc = pow2_scale(bound, 15, &invM);
            sts64(sb + O_SCL, __float_as_uint(sc * iv), __float_as_uint(invM));
            bar_arrive(2, 352);
        }
    } else if (w == 10) {
        bar_sync(9, 288);
        if (lane == 0) red_release(g_flag + F_W + layer * 128);
        if (lane == 0) {
#pragma unroll 1
            for (int n = 0; n < NSEG; n++) {
                mbar_sleep(sb + B_STG + (n & 1) * 8, (n >> 1) & 1);
                fence_async_smem();
                const uint32_t stg = sb + O_STG - (n & 1) * 16384;
                char* it = it0 + (size_t)(n % RING) * 32 * 32768;
                bulk_s2g(it + c * 8192, stg + (c == 2 ? 8192 : 0), 8192);
                bulk_commit();
                if (n + 1 >= RING && n + 1 < NSEG) wait_flag(flag - (RING - 1) * 32, 7);
                bulk_wait0();
                mbar_arrive(sb + B_FREE + (n & 1) * 8);
                fence_async_glb();
                red_relaxed(flag);
                flag += 32;
            }
        }
    } else {
        bool allx = false;
#pragma unroll 1
        for (int st = 0; st < NSEG; st++) {
            const int par = st & 1;
            char* const it = it0 + (size_t)(st % RING) * 32 * 32768;
            if (lane == 0 && !allx && st + 3 < NSEG) {
                allx = ld_acquire(xflag + 64) >= nact;
                if (!allx) wait_flag(st + 4 < NSEG ? xflag + ((st + 3) >> 1) : xflag + 64, st + 4 < NSEG ? 4 : nact);
                fence_async_glb();
            }
            __syncwarp();
            if (st < NSEG - 1 && c < 2) mbar_sleep(sb + B_VX + par * 8, (st >> 1) & 1);
            if (st < NSEG - 2) mbar_sleep(sb + B_XF + par * 8, ((st >> 1) + 1) & 1);
            bar_sync(1, 320);
            if (lane == 0 && st + 3 < NSEG) {
                mbar_expect(sb + B_XF + (par ^ 1) * 8, 40960);
                bulk_g2s_last(sb + O_XS + (par ^ 1) * 40960, (const char*)g_xn + (size_t)(st + 3) * 40960, 40960, sb + B_XF + (par ^ 1) * 8);
            } else if (lane == 0 && st < NSEG - 1) {
                tail_load_b(sb, h, c, (par ^ 1) * 2); tail_load_b(sb, h, c, (par ^ 1) * 2 + 1);
            }
            __syncwarp();
            if (lane == 0 && c < 2) {
                fence_async_smem();
#pragma unroll 1
                for (int i = 0; i < 4; i++) bulk_s2g(it + 24576 + (c * 4 + i) * 512, sb + O_QKP + i * 1024 + 512, 512);
                bulk_commit();
                asm volatile("cp.async.bulk.wait_group.read 0;" ::: "memory");
            }
            __syncwarp();
            if (st < NSEG - 1) bar_arrive(2, 352);
            mbar_sleep(sb + B_S, par);
            __syncwarp();
            if (lane == 0) {
                if (st < NSEG - 1) mbar_expect(sb + B_S, s_tx(c));
                if (c == 2) { fence_async_smem(); bulk_s2g(it + 28672, sb + O_VM + par * 2048, 2048); bulk_commit(); }
                if (st == NSEG - 1) asm volatile("cp.async.bulk.wait_group.read 0;" ::: "memory");
            }
            __syncwarp();
            if (st == NSEG - 1) bar_arrive(8, 320);
            if (lane == 0) { bulk_wait0(); fence_async_glb(); red_relaxed(flag); }
            __syncwarp();
            mbar_sleep(sb + B_FREE + par * 8, (st >> 1) & 1);
            flag += 32;
        }
    }
    __syncwarp();
    const int nc = c == 2 ? 10 : 11;
    if (w == 10) {
        bar_sync(8, 320);
        if (lane == 0) {
            if (layer == 1 && blockIdx.x == 0) g_ready[0].v = 0;
            fence_async_smem();
            __nanosleep(TDELAY);
            wait_flag(xflag + 64, nact);
            wait_flag<50>(g_flag + F_O + layer * 32 + 28 + (h >> 3), 64);
            fence_async_glb();
#pragma unroll 1
            for (int k = 0; k < nc; k++) {
                if (k >= 4) mbar_sleep(sb + T_EA + (k & 3) * 8, ((k >> 2) - 1) & 1);
                mbar_expect(sb + T_FA + (k & 3) * 8, 16384);
                bulk_g2s_last(sb + O_MS + (k & 3) * 16384, (const char*)g_O + (size_t)((28 + (h >> 3)) * GNC + c * 11 + k) * 16384, 16384, sb + T_FA + (k & 3) * 8);
            }
        }
    } else if (w == 9 && lane == 0) {
        __nanosleep(TDELAY);
#pragma unroll 1
        for (int k = 4; k < nc; k++) {
            if (k >= 7) mbar_sleep(sb + T_EB + (k - 7) * 8, 0);
            tail_load_b(sb, h, c, k);
        }
    }
    __syncwarp();
    asm volatile("barrier.cluster.wait.aligned;" ::: "memory");
    asm volatile("barrier.cluster.arrive.relaxed.aligned; barrier.cluster.wait.aligned;" ::: "memory");
    asm volatile("barrier.cluster.arrive.relaxed.aligned; barrier.cluster.wait.aligned;" ::: "memory");
}

constexpr int RI_A = 0, RI_TAB = 81920, RI_STG = RI_TAB + 82 * 768;
constexpr int RI_RES = RI_STG + 25600, RI_ST = RI_RES + 2 * 64 * 336;
constexpr int HB_A = G_BAR + 64, HB_AFREE = HB_A + 32, HB_LN = HB_A + 40, HB_FULL = HB_A + 64, HB_DONE = HB_FULL + 48, HB_FREE = HB_DONE + 48;
constexpr int HP_SMEM = HB_FREE + 48;
static_assert(G_BAR >= RI_ST + 2048, "helper shared-memory map");
#define IDL 280
#define ITEM_NS 60
#define PFW_AT 28
#define PFW_NS 150
__device__ __forceinline__ void helper_aux(const uint32_t sb, const int j, const int nh, const int na, const int nbh, const int layer, const bf16* Wq,
                                           const bf16* Wk, const bf16* Wv, const bf16* Wo) {
    const int w = threadIdx.x >> 5, lane = threadIdx.x & 31, p = w - 8;
    if (lane == 0 && j < (nh & ~3)) {
        int n = 0;
        for (int a = j >> 2; a < 32; a += nh >> 2, n++) {
            if (n == 0) continue;
            mbar_wait(sb + HB_AFREE, (n - 1) & 1);
            mbar_expect(sb + HB_A + p * 8, 20480);
            bulk_g2s_last(sb + RI_A + p * 20480, (const char*)g_YT + (size_t)a * 81920 + p * 20480, 20480, sb + HB_A + p * 8);
            if (p == 0) { mbar_wait(sb + HB_LN, (n - 1) & 1); red_release(g_flag + F_X + layer * 128 + a - (nh >> 2)); }
        }
        if (p == 0) { mbar_wait(sb + HB_LN, (n - 1) & 1); red_release(g_flag + F_X + layer * 128 + (j >> 2) + (n - 1) * (nh >> 2)); }
    }
    __syncwarp();
    if (layer == 0 && w == 8 && lane == 0) wait_flag<400>(g_flag + F_W, 96);
    __syncwarp();
    bar_sync(3, 384);
    if (p == 3 && lane == 0 && j < (nh & ~3)) red_release(g_flag + F_X + layer * 128 + 64);
    fence_async_smem();
    Flag* oflag = g_flag + F_O + layer * 32;
    if (j < na) {
        int sl = p & 1, ph = 1;
        for (int idx = j + (p & 1) * na; idx < NSEG * 32 && p >= 2 && lane == 0; idx += 2 * na) {
            mbar_wait(sb + HB_DONE + sl * 8, ph ^ 1);
            mbar_arrive(sb + HB_FREE + sl * 8);
            red_release(oflag + (idx >> 6));
            atomicAdd(&g_flag[layer * NSEG * 32 + idx].v, 1u);
            sl += 2;
            if (sl >= 6) { sl -= 6; ph ^= 1; }
        }
        for (int idx = j + p * na; idx < NSEG * 32 && p < 2 && lane == 0; idx += 2 * na) {
            mbar_wait(sb + HB_FREE + sl * 8, ph);
            wait_flag<ITEM_NS>(g_flag + layer * NSEG * 32 + idx, 6);
            fence_async_glb();
            if (idx < (NSEG - 2) * 32) __nanosleep(IDL);
            mbar_expect(sb + HB_FULL + sl * 8, 30720);
            bulk_g2s(sb + sl * 30720, g_item + (size_t)(idx % (RING * 32)) * 32768, 30720, sb + HB_FULL + sl * 8);
            sl += 2;
            if (sl >= 6) { sl -= 6; ph ^= 1; }
        }
    } else if (lane == 0 && p == 3) {
        if (layer == 0) {
            wait_flag<1000>(oflag + PFW_AT, 64);
            const int np = nh - na;
#pragma unroll 1
            for (int i = j - na; i < 1280; i += np) {
                const bf16* W = i < 320 ? Wq : i < 640 ? Wk : i < 960 ? Wv : Wo;
                prefetch_l2((const char*)W + (size_t)(i % 320) * 16384, 16384);
                __nanosleep(PFW_NS);
            }
#pragma unroll 1
            for (int i = j - na; i < 205; i += np) {
                const char* p_ = i < 160 ? (const char*)g_Wf + i * 16384 : i < 165 ? (const char*)g_stat + (i - 144) * 16384
                               : i < 167 ? (const char*)g_ctab + (i - 165) * 8192 : (const char*)(g_flag + NFLAG) - (i - 166) * 16384;
                prefetch_l2(p_, 16384);
                __nanosleep(PFW_NS);
            }
#pragma unroll 1
            for (int i = j - na; i < 130; i += np) { prefetch_l2((const char*)g_xb + i * 16384, 16384); __nanosleep(PFW_NS); }
        }
    } else if (lane == 0) {
        if (p == 2) wait_flag<500>(g_flag + F_X + layer * 128 + 64, nh & ~3);
        int c0 = 0;
        for (int mb = (j - na) >> 3; mb < nbh; mb += (nh - na) >> 3, c0 += GNC) {
            if (p < 2) wait_flag<300>(oflag + 2 * mb + p, 64);
            fence_async_glb();
            oproj_load(sb, p, mb, (j - na) & 7, c0, nh - na < 24 ? 0 : mb == nbh - 1 ? GPACE2 : GPACE);
        }
    }
}
__device__ __forceinline__ void helper_mma(char* sm, const int jh, const int nh, const int na, const int nbh, const int layer, const bf16* res, bf16* x,
                                           bf16* out) {
    const uint32_t sb = smem_u32(sm);
    const int tid = threadIdx.x, w = tid >> 5, lane = tid & 31, g = lane >> 2, t = lane & 3;
    const bool act = jh < (nh & ~3);
    const int j4 = jh & 3;
    const int fr = tid & 63, rg = w >> 1;
    auto chunk0 = [&](int u) { return u == 0 ? 5 * j4 : u == 1 ? 75 - 5 * j4 : u == 2 ? 40 + 5 * j4 : 35 - 5 * j4; };
    const int gr = tid / 20, gq_ = tid - gr * 20, go = gr * 80 + chunk0(gq_ / 5) + gq_ % 5;
    const uint32_t gs = sb + RI_RES + gr * 336 + gq_ * 16;
    auto residual = [&](int a, int n) {
#pragma unroll 1
        for (int r = 0; r < 64 - gr && tid < 240 && a < 32; r += 12) cp_async16(gs + (n & 1) * 21504 + r * 336, (const uint4*)res + (a * 64 + r) * 80 + go);
        cp_commit();
    };
    if (act) {
        if (tid < 240) {
            const int k0 = tid / 48, n = tid - k0 * 48;
            const float d = (float)(40 * j4 + n), amp = 2.f * 0.03952847075210474f;
#pragma unroll 4
            for (int u = 0; u < 16; u++)
                *(uint4*)(sm + RI_TAB + (tid + u * 240) * 16) = cos_row8(fmaf((float)((k0 + (u & 3) * 5) * 16 + ((u >> 2) & 1)), d, (float)((u & 8) * 20)), 2.f * d, amp);
            if (tid < 96) *(uint4*)(sm + RI_TAB + (3840 + tid) * 16) = make_uint4(k0 == 0 ? pack_h((n & 1) ? -amp : amp, 0.f) : 0u, 0, 0, 0);
        }
        fence_async_smem();
        residual(jh >> 2, 0);
    }
    bar_sync(1, 384);
    if (layer == TLL) TL(36);
    if (act) {
        const float4 wm = ((const float4*)g_wmax)[lane];
        const int wg = w >> 2;
        int n = 0;
#pragma unroll 1
        for (int a = jh >> 2; a < 32; a += nh >> 2, n++) {
            float acc[2][24];
            uint64_t da = mkdesc(sb + RI_A + wg * 40960, 1024, 1024, 1), db = mkdesc(sb + RI_TAB + wg * 30720, 768, 128, 0);
#pragma unroll
            for (int gq = 0; gq < 2; gq++) {
                mbar_wait(sb + HB_A + (wg * 2 + gq) * 8, n & 1);
                if (layer == TLL && n == TLN && gq == 0) TL(45);
                wg_fence();
#pragma unroll 5
                for (int k = 0; k < 10; k++) { wg_n48_ss_ta(acc[gq], da, db, k); da += 128; db += 96; }
                wg_commit();
            }
            if (wg == 0) {
                mbar_wait(sb + HB_A + 16, n & 1);
                wg_fence();
                wg_n48_ss_ta(acc[0], da, db + 20 * 96, 1);
                wg_commit();
            }
            float inv;
            pow2_scale(__uint_as_float(__reduce_max_sync(~0u, __float_as_uint(fmaxf(fmaxf(wm.x, wm.y), fmaxf(wm.z, wm.w))))), 0, &inv);
            const uint32_t ysc = pack_bf(inv, inv);
            wg_wait<0>();
            if (layer == TLL && n == TLN) TL(46);
            if (lane == 0) mbar_arrive(sb + HB_AFREE);
            const uint32_t ad = sb + RI_STG + ((w & 3) * 16 + (lane & 15)) * 400 + (lane >> 4) * 96 + wg * 192;
#pragma unroll
            for (int q = 0; q < 6; q++) {
                const float *e = acc[0] + q * 4, *o = acc[1] + q * 4;
                stsm4(ad + q * 16, pack_h(e[0] + o[0], e[1] + o[1]), pack_h(e[2] + o[2], e[3] + o[3]), pack_h(e[0] - o[0], e[1] - o[1]), pack_h(e[2] - o[2], e[3] - o[3]));
            }
            cp_wait<0>();
            bar_sync(4, 256);
            const uint32_t xa = sb + RI_RES + (n & 1) * 21504 + fr * 336 + rg * 80, sg = (rg & 1) ? 0xbc00bc00u : 0x3c003c00u;
            float sum = 0.f, sq = 0.f;
            uint32_t ya = sb + RI_STG + fr * 400 + (rg >> 1) * 96 + ((rg & 1) ? 64 : 0), carry;
            asm("fma.rn.f16x2 %0,%1,%2,%3;" : "=r"(carry) : "r"(lds32(ya + 208)), "r"(sg), "r"(lds32(ya + 16)));
#pragma unroll 1
            for (int ch = 0; ch < 5; ch++, ya += (rg & 1) ? -16 : 16) {
                uint32_t y[4], z[4], xr[4];
                lds128(y, ya); lds128(z, ya + 192); lds128(xr, xa + ch * 16);
#pragma unroll
                for (int q = 0; q < 4; q++) asm("fma.rn.f16x2 %0,%1,%2,%0;" : "+r"(y[q]) : "r"(z[q]), "r"(sg));
                if (rg & 1) {
                    const uint32_t y0 = y[0], y1 = y[1];
                    y[0] = __byte_perm(carry, y[3], 0x7610); y[1] = __byte_perm(y[3], y[2], 0x7610);
                    y[3] = __byte_perm(y1, y0, 0x7610); y[2] = __byte_perm(y[2], y1, 0x7610);
                    carry = y0;
                }
#pragma unroll
                for (int q = 0; q < 4; q++) {
                    const float2 yf = __half22float2(*(const __half2*)&y[q]);
                    xr[q] = bfma(pack_bf(yf.x, yf.y), ysc, xr[q]);
                    const float e = bf_lo(xr[q]), f = bf_hi(xr[q]);
                    sum += e + f; sq = fmaf(e, e, fmaf(f, f, sq));
                }
                sts128(xa + ch * 16, xr[0], xr[1], xr[2], xr[3]);
            }
            uint2* stat = g_stat + (size_t)(layer * 32 + a) * 1024 + rg * 64 + fr;
            asm volatile("st.relaxed.gpu.global.v2.u32 [%0],{%1,%2};" ::"l"(stat + j4 * 256), "r"(__float_as_uint(sum)), "r"(__float_as_uint(sq) | 0x80000000u) : "memory");
            if (layer == TLL && n == TLN) TL(47);
            uint32_t s0[3], s1[3];
            int lim = 0;
            do {
#pragma unroll
                for (int q = 0; q < 3; q++)
                    asm volatile("ld.relaxed.gpu.global.v2.u32 {%0,%1},[%2];" : "=r"(s0[q]), "=r"(s1[q]) : "l"(stat + ((j4 + 1 + q) & 3) * 256) : "memory");
            } while (__any_sync(~0u, (int)(s1[0] & s1[1] & s1[2]) >= 0) && ++lim < SPIN_LIM);
#pragma unroll
            for (int q = 0; q < 3; q++) { sum += __uint_as_float(s0[q]); sq -= __uint_as_float(s1[q]); }
            sts64(sb + RI_ST + tid * 8, __float_as_uint(sum), __float_as_uint(sq));
            bar_sync(4, 256);
            if (layer == TLL && n == TLN) TL(48);
#pragma unroll
            for (int q = 1; q < 4; q++) {
                uint32_t st2[2];
                lds64(st2, sb + RI_ST + ((tid + q * 64) & 255) * 8);
                sum += __uint_as_float(st2[0]); sq += __uint_as_float(st2[1]);
            }
            const float mean = sum * (1.f / 640.f), r = rsqrtf(fmaxf(fmaf(-mean, mean, sq * (1.f / 640.f)), 0.f) + 1e-5f), off = -mean * r;
            uint4* dst = (uint4*)g_xn + ((size_t)(2 * a + (w & 1)) * 80 + chunk0(rg)) * 32 + lane;
#pragma unroll
            for (int i = 0; i < 5; i++) {
                uint32_t u[4];
                lds128(u, xa + i * 16);
                dst[i * 32] = make_uint4(pack_h(fmaf(bf_lo(u[0]), r, off), fmaf(bf_hi(u[0]), r, off)), pack_h(fmaf(bf_lo(u[1]), r, off), fmaf(bf_hi(u[1]), r, off)),
                                         pack_h(fmaf(bf_lo(u[2]), r, off), fmaf(bf_hi(u[2]), r, off)), pack_h(fmaf(bf_lo(u[3]), r, off), fmaf(bf_hi(u[3]), r, off)));
            }
            __syncwarp();
            if (lane == 0) mbar_arrive(sb + HB_LN);
            if (layer == TLL) TL(37);
            if (layer == TLL && n == TLN) TL(44);
            residual(a + (nh >> 2), n + 1);
#pragma unroll 2
            for (int rr = 0; rr < 64 - gr && tid < 240; rr += 12) {
                uint32_t v[4];
                lds128(v, gs + (n & 1) * 21504 + rr * 336);
                ((uint4*)x)[(a * 64 + rr) * 80 + go] = make_uint4(v[0], v[1], v[2], v[3]);
            }
        }
    }
    bar_sync(3, 384);
    if (layer == TLL) TL(38);
    if (jh >= na) {
        int c0 = 0;
#pragma unroll 1
        for (int mb = (jh - na) >> 3; mb < nbh; mb += (nh - na) >> 3, c0 += GNC) oproj_mma(sb, mb, (jh - na) & 7, c0, x, out);
        if (layer == TLL) TL(42);
        return;
    }
    const int p = w >> 1, mi = w & 1;
    int slot = p, ph = 0;
    for (int idx = jh + p * na; idx < NSEG * 32; idx += 4 * na) {
        const uint32_t it = sb + slot * 30720 + lane * 16;
        float iq, ik, iv;
        weight_scale(idx & 31, 0, &iq); weight_scale(idx & 31, 1, &ik); weight_scale(idx & 31, 2, &iv);
        bar_sync(6 + p, 64);
        mbar_wait(sb + HB_DONE + slot * 8, ph ^ 1);
        mbar_wait(sb + HB_FULL + slot * 8, ph);
        if (layer == TLL && idx >= 63 * 32) TL(55);
        float s[6][4];
#pragma unroll
        for (int i = 0; i < 6; i++) s[i][0] = s[i][1] = s[i][2] = s[i][3] = 0.f;
#pragma unroll
        for (int e = 0; e < 8; e++) {
            uint32_t q[4], k[4];
            ldsm4t(q, it + (e >> 2) * 8192 + (e & 3) * 1024 + mi * 512);
            ldsm4t(k, it + 24576 + e * 512);
            mma_bf(s[4], q[0], q[2], q[1], q[3], k[0], k[1]);
            mma_bf(s[5], q[0], q[2], q[1], q[3], k[2], k[3]);
            ldsm4t(k, it + (e >> 2) * 8192 + 4096 + (e & 3) * 1024);
            mma_bf(s[0], q[0], q[2], q[1], q[3], k[0], k[1]);
            mma_bf(s[1], q[0], q[2], q[1], q[3], k[2], k[3]);
            if (mi) {
                ldsm4t(k, it + (e >> 2) * 8192 + 4096 + (e & 3) * 1024 + 512);
                mma_bf(s[2], q[0], q[2], q[1], q[3], k[0], k[1]);
                mma_bf(s[3], q[0], q[2], q[1], q[3], k[2], k[3]);
            }
        }
#pragma unroll
        for (int q = 0; q < 4; q++) s[4][q] += s[5][q];
        const int seg = idx >> 5, h = idx & 31;
        const float sl = iq * ik * (0.08838834764831845f * 1.4426950408889634f);
        float mx[2] = {-3.0e38f, -3.0e38f};
#pragma unroll
        for (int i = 0; i < 5; i++)
#pragma unroll
            for (int q = 0; q < 4; q++) {
                const bool ok = i == 4 || (i * 8 + 2 * t + (q & 1)) <= (mi * 16 + g + (q >> 1) * 8);
                s[i][q] = ok ? s[i][q] * sl : -1.0e9f * 1.4426950408889634f;
                mx[q >> 1] = fmaxf(mx[q >> 1], s[i][q]);
            }
        float sum[2] = {0.f, 0.f};
#pragma unroll
        for (int r = 0; r < 2; r++) {
            mx[r] = fmaxf(mx[r], __shfl_xor_sync(~0u, mx[r], 1));
            mx[r] = fmaxf(mx[r], __shfl_xor_sync(~0u, mx[r], 2));
        }
#pragma unroll
        for (int i = 0; i < 5; i++)
#pragma unroll
            for (int q = 0; q < 4; q++) { s[i][q] = ex2(s[i][q] - mx[q >> 1]); sum[q >> 1] += s[i][q]; }
#pragma unroll
        for (int r = 0; r < 2; r++) {
            sum[r] += __shfl_xor_sync(~0u, sum[r], 1);
            sum[r] += __shfl_xor_sync(~0u, sum[r], 2);
            sum[r] = iv * rcp(sum[r]);
        }
        uint32_t pp[5][2];
#pragma unroll
        for (int i = 0; i < 5; i++) { pp[i][0] = pack_bf(s[i][0] * sum[0], s[i][1] * sum[0]); pp[i][1] = pack_bf(s[i][2] * sum[1], s[i][3] * sum[1]); }
        uint32_t* o = (uint32_t*)g_O + (((size_t)(seg >> 1) * 512 + h * 16) * 8 + (seg & 1) * 4 + mi * 2) * 32 + lane;
#pragma unroll
        for (int e = 0; e < 8; e++) {
            float o0[4] = {0.f, 0.f, 0.f, 0.f}, o1[4] = {0.f, 0.f, 0.f, 0.f};
            uint32_t v[4];
            lds64(v, it - lane * 8 + 28672 + e * 256);
            mma_bf8(o0, pp[4][0], pp[4][1], v[0]);
            mma_bf8(o1, pp[4][0], pp[4][1], v[1]);
            ldsm4(v, it + 16384 + e * 1024);
            mma_bf(o0, pp[0][0], pp[0][1], pp[1][0], pp[1][1], v[0], v[2]);
            mma_bf(o1, pp[0][0], pp[0][1], pp[1][0], pp[1][1], v[1], v[3]);
            ldsm4(v, it + 16384 + e * 1024 + 512);
            mma_bf(o0, pp[2][0], pp[2][1], pp[3][0], pp[3][1], v[0], v[2]);
            mma_bf(o1, pp[2][0], pp[2][1], pp[3][0], pp[3][1], v[1], v[3]);
            o[(2 * e) * 256] = pack_bf(o0[0], o0[1]); o[(2 * e) * 256 + 32] = pack_bf(o0[2], o0[3]);
            o[(2 * e + 1) * 256] = pack_bf(o1[0], o1[1]); o[(2 * e + 1) * 256 + 32] = pack_bf(o1[2], o1[3]);
        }
        __syncwarp();
        if (lane == 0) mbar_arrive(sb + HB_DONE + slot * 8);
        slot += 4;
        if (slot >= 6) { slot -= 6; ph ^= 1; }
    }
    if (layer == TLL) TL(39);
}

__global__ void __cluster_dims__(3, 1, 1) __launch_bounds__(384, 1)
k_chain(const int layer, const int nact, const uint32_t zero, const bf16* __restrict__ Wq, const bf16* __restrict__ Wk, const bf16* __restrict__ Wv,
        const bf16* __restrict__ Wo, const bf16* res, bf16* out) {
    extern __shared__ __align__(1024) char sm[];
    const uint32_t sb = smem_u32(sm);
    const int b = blockIdx.x, h = b / 3, c = b - h * 3;
    pdl_go();
    if (threadIdx.x >= 256) {
        asm volatile("setmaxnreg.dec.sync.aligned.u32 24;");
        TL(11 + layer * 14);
        chain_aux(sb, c, h, layer, nact);
    } else {
        asm volatile("setmaxnreg.inc.sync.aligned.u32 240;");
        chain_mma(sb, c, h, layer, zero, Wq, Wk, Wv, Wo, res, out);
    }
}
__global__ void __launch_bounds__(384, 1) k_help(const bf16* res, bf16* x, bf16* out, const int layer, const int na, const int nbh, const int zero, const bf16* Wq,
                                                  const bf16* Wk, const bf16* Wv, const bf16* Wo) {
    extern __shared__ __align__(1024) char sm[];
    if (layer == TLL) TL(51);
    if (threadIdx.x >= 256) {
        const uint32_t sb = smem_u32(sm);
        const int p = (threadIdx.x >> 5) - 8, i = (threadIdx.x & 31) * 4 + p;
        if (i < 34) mbar_init(sb + G_BAR + i * 8, i < 4 ? 3 : i < 8 || i == 12 || i == 13 ? 8 : i >= 22 && i < 28 ? 2 : 1);
        fence_async_smem();
        wait_flag<100>(g_flag + F_X + layer * 128 + 65, 1);
        fence_async_glb();
        if (i == 8 + p && blockIdx.x < (gridDim.x & ~3)) {
            mbar_expect(sb + HB_A + p * 8, 20480);
            bulk_g2s(sb + RI_A + p * 20480, (const char*)g_YT + (size_t)(blockIdx.x >> 2) * 81920 + p * 20480, 20480, sb + HB_A + p * 8);
        }
        __syncwarp();
        bar_sync(2, 128);
        bar_arrive(1, 384);
    }
    if (threadIdx.x + zero >= 256) helper_aux(smem_u32(sm), blockIdx.x, gridDim.x, na, nbh, layer, Wq, Wk, Wv, Wo);
    else helper_mma(sm, blockIdx.x, gridDim.x, na, nbh, layer, res, x, out);
    __syncwarp();
    pdl_go();
    if (blockIdx.x == 0) pdl_wait();
}

#define COL_PAD 15872
template <class... P, class... A>
void launch_pdl(void (*k)(P...), int grid, int block, int smem, cudaStream_t st, A... args) {
    cudaLaunchConfig_t cfg = {};
    cfg.gridDim = dim3(grid); cfg.blockDim = dim3(block); cfg.dynamicSmemBytes = smem; cfg.stream = st;
    cudaLaunchAttribute at[1];
    at[0].id = cudaLaunchAttributeProgrammaticStreamSerialization; at[0].val.programmaticStreamSerializationAllowed = 1;
    cfg.attrs = at;
    cfg.numAttrs = 1;
    cudaLaunchKernelEx(&cfg, k, args...);
}

}

extern "C" void kernel_launch(void* const* d_in, const int* in_sizes, int n_in, void* d_out, int out_size) {
    const bf16* x = (const bf16*)d_in[0];
    const bf16* wr = (const bf16*)d_in[1];
    const bf16* wi = (const bf16*)d_in[2];
    const bf16* mem0 = (const bf16*)d_in[4];
    const bf16* Wq = (const bf16*)d_in[5];
    const bf16* Wk = (const bf16*)d_in[6];
    const bf16* Wv = (const bf16*)d_in[7];
    const bf16* Wo = (const bf16*)d_in[8];
    bf16* out = (bf16*)d_out;
    static int nhelp = 0;
    static bf16 *xa, *xb;
    static cudaStream_t s1;
    static cudaEvent_t ev_fork, ev_join;
    if (!nhelp) {
        cudaStreamCreateWithFlags(&s1, cudaStreamNonBlocking);
        cudaEventCreateWithFlags(&ev_fork, cudaEventDisableTiming);
        cudaEventCreateWithFlags(&ev_join, cudaEventDisableTiming);
        cudaFuncSetAttribute(k_setup, cudaFuncAttributeMaxDynamicSharedMemorySize, SU_SMEM);
        cudaFuncSetAttribute(k_rowf, cudaFuncAttributeMaxDynamicSharedMemorySize, RF_SMEM);
        cudaFuncSetAttribute(k_col, cudaFuncAttributeMaxDynamicSharedMemorySize, COL_PAD);
        cudaFuncSetAttribute(k_chain, cudaFuncAttributeMaxDynamicSharedMemorySize, CH_SMEM);
        cudaFuncSetAttribute(k_setup, cudaFuncAttributePreferredSharedMemoryCarveout, 100);
        cudaFuncSetAttribute(k_rowf, cudaFuncAttributePreferredSharedMemoryCarveout, 100);
        cudaFuncSetAttribute(k_col, cudaFuncAttributePreferredSharedMemoryCarveout, 100);
        cudaFuncSetAttribute(k_chain, cudaFuncAttributePreferredSharedMemoryCarveout, 100);
        cudaFuncSetAttribute(k_help, cudaFuncAttributeMaxDynamicSharedMemorySize, HP_SMEM);
        cudaFuncSetAttribute(k_help, cudaFuncAttributePreferredSharedMemoryCarveout, 100);
        int dev = 0, sms = 0;
        cudaGetDevice(&dev);
        cudaDeviceGetAttribute(&sms, cudaDevAttrMultiProcessorCount, dev);
        nhelp = sms - 96 < 12 ? 12 : sms - 96;
        cudaGetSymbolAddress((void**)&xa, g_xa);
        cudaGetSymbolAddress((void**)&xb, g_xb);
    }
    const int na = nhelp - (nhelp >= 36 ? 24 : nhelp >= 28 ? 16 : 8), nbh = 14;
    cudaStream_t s0 = cudaStreamPerThread;
    cudaEventRecord(ev_fork, s0);
    cudaStreamWaitEvent(s1, ev_fork, 0);
    k_rowf<<<(96 + nhelp) & ~1, 256, RF_SMEM, s0>>>(x, 1);
    k_setup<<<NSETUP, 256, SU_SMEM, s1>>>(wr, wi, mem0);
    cudaEventRecord(ev_join, s1);
#define NLAYER 2
    for (int l = 0; l < NLAYER; l++) {
        const bf16* xin = l == 0 ? x : xb;
        if (l == 1) launch_pdl(k_rowf, 128, 256, RF_SMEM, s0, xin, 0);
        launch_pdl(k_col, 321, 128, l == 0 ? 0 : COL_PAD, s0, (int)(l == 0));
        launch_pdl(k_chain, 96, 384, CH_SMEM, s0, l, nhelp & ~3, 0u, Wq, Wk, Wv, Wo, (const bf16*)xa, l == 0 ? xb : out);
        launch_pdl(k_help, nhelp, 384, HP_SMEM, s0, xin, xa, l == 0 ? xb : out, l, na, nbh, 0, Wq, Wk, Wv, Wo);
    }
    cudaStreamWaitEvent(s0, ev_join, 0);
}
```

```cpp
#include <cuda_runtime.h>
#include <cuda_bf16.h>
#include <cuda_fp16.h>
#include <stdint.h>
#include <string.h>

namespace {

typedef __nv_bfloat16 bf16;
constexpr int S_ = 2048, D_ = 640, NSEG = 64;
constexpr int SPIN_LIM = 1 << 13;

__device__ float                  g_wmx[96];
__device__ __align__(1024) bf16   g_wot[4096 * 640];
__device__ __align__(16) float    g_co[1024];
__device__ __align__(256) uint2   g_stat[2 * 32 * 16 * 64];
__device__ float                  g_invM0;
__device__ __align__(16) float    g_wmax[128];
__device__ __align__(1024) char   g_redraw[65 * 32768];
constexpr int F_X = 2 * NSEG * 32, F_O = F_X + 2 * 128, NFLAG = F_O + 128, RING = 8;
constexpr int F_W = F_X + 66;
constexpr int F_R = F_O + 64;
constexpr int NSETUP = 131;
struct __align__(256) Flag { unsigned v; };
__device__ Flag                   g_flag[NFLAG];
__device__ Flag                   g_ready[1];
__device__ __align__(1024) char   g_item[RING * 32 * 32768];
__device__ __align__(1024) bf16   g_O[S_ * 4096];
__device__ __align__(1024) __half g_xn[S_ * D_];
__device__ __align__(1024) bf16   g_xa[S_ * D_];
__device__ __align__(1024) bf16   g_xb[S_ * D_];
__device__ __align__(1024) __half g_UT[D_ * S_];
__device__ __align__(1024) __half g_YT[D_ * S_];
__device__ __align__(1024) __half g_ctab[64 * 128 + 64 * 64];
__device__ __align__(1024) uint32_t g_Wf[321 * 2048];

#define TL(i)
#define TLN 0
#define TLL 1
#define CK(i)
__device__ __forceinline__ uint32_t smem_u32(const void* p) { return (uint32_t)__cvta_generic_to_shared(p); }
__device__ __forceinline__ uint32_t mapa(uint32_t a, uint32_t r) { uint32_t o; asm("mapa.shared::cluster.u32 %0,%1,%2;" : "=r"(o) : "r"(a), "r"(r)); return o; }
__device__ __forceinline__ void mbar_init(uint32_t a, int c) { asm volatile("mbarrier.init.shared::cta.b64 [%0],%1;" ::"r"(a), "r"(c) : "memory"); }
__device__ __forceinline__ void mbar_expect(uint32_t a, int bytes) { asm volatile("mbarrier.arrive.expect_tx.shared::cta.b64 _,[%0],%1;" ::"r"(a), "r"(bytes) : "memory"); }
__device__ __forceinline__ void mbar_arrive(uint32_t a) { asm volatile("mbarrier.arrive.shared::cta.b64 _,[%0];" ::"r"(a) : "memory"); }
__device__ __forceinline__ bool mbar_try(uint32_t a, uint32_t par) {
    uint32_t p;
    asm volatile("{.reg .pred q; mbarrier.try_wait.parity.shared::cta.b64 q,[%1],%2; selp.u32 %0,1,0,q;}" : "=r"(p) : "r"(a), "r"(par) : "memory");
    return p;
}
__device__ __forceinline__ void mbar_wait(uint32_t a, uint32_t par) {
    if (!mbar_try(a, par)) {
        int lim = 0;
        while (!mbar_try(a, par) && ++lim < SPIN_LIM) {}
    }
}
__device__ __forceinline__ void mbar_sleep(uint32_t a, uint32_t par) {
    asm volatile("{.reg .pred q; .reg .u32 n; mov.u32 n,0;\n"
                 "W_LOOP: mbarrier.try_wait.parity.shared::cta.b64 q,[%0],%1,%2; add.u32 n,n,1; setp.lt.and.u32 q,n,%3,!q; @q bra W_LOOP;}"
                 ::"r"(a), "r"(par), "n"(20000), "n"(SPIN_LIM) : "memory");
}
__device__ __forceinline__ void bar_arrive(int id, int n) { asm volatile("bar.arrive %0,%1;" ::"r"(id), "r"(n) : "memory"); }
__device__ __forceinline__ uint32_t clock32() { uint32_t c; asm volatile("mov.u32 %0,%%clock;" : "=r"(c)); return c; }
__device__ __forceinline__ uint32_t read_tid() { uint32_t v; asm volatile("mov.u32 %0,%%tid.x;" : "=r"(v)); return v; }
__device__ __forceinline__ void bar_sync(int id, int n) { asm volatile("bar.sync %0,%1;" ::"r"(id), "r"(n) : "memory"); }
__device__ __forceinline__ void fence_async_smem() { asm volatile("fence.proxy.async.shared::cta;" ::: "memory"); }
__device__ __forceinline__ void fence_async_glb() { asm volatile("fence.proxy.async.global;" ::: "memory"); }
__device__ __forceinline__ void cluster_sync_full() { asm volatile("barrier.cluster.arrive.aligned; barrier.cluster.wait.aligned;" ::: "memory"); }
__device__ __forceinline__ void bulk_g2s(uint32_t dst, const void* src, int bytes, uint32_t mb) {
    asm volatile("cp.async.bulk.shared::cluster.global.mbarrier::complete_tx::bytes [%0],[%1],%2,[%3];" ::"r"(dst), "l"(src), "r"(bytes), "r"(mb) : "memory");
}
__device__ __forceinline__ void bulk_g2s_last(uint32_t dst, const void* src, int bytes, uint32_t mb) {
    asm volatile("{.reg .b64 p; createpolicy.fractional.L2::evict_first.b64 p, 1.0;\n"
                 "cp.async.bulk.shared::cluster.global.mbarrier::complete_tx::bytes.L2::cache_hint [%0],[%1],%2,[%3],p;}"
                 ::"r"(dst), "l"(src), "r"(bytes), "r"(mb) : "memory");
}
__device__ __forceinline__ void bulk_s2s(uint32_t dst, uint32_t src, int bytes, uint32_t mb) {
    asm volatile("cp.async.bulk.shared::cluster.shared::cta.mbarrier::complete_tx::bytes [%0],[%1],%2,[%3];" ::"r"(dst), "r"(src), "r"(bytes), "r"(mb) : "memory");
}
__device__ __forceinline__ void bulk_s2g(void* dst, uint32_t src, int bytes) {
    asm volatile("cp.async.bulk.global.shared::cta.bulk_group [%0],[%1],%2;" ::"l"(dst), "r"(src), "r"(bytes) : "memory");
}
__device__ __forceinline__ void cp_async16(uint32_t dst, const void* src, uint32_t bytes = 16) {
    asm volatile("cp.async.cg.shared.global [%0],[%1],16,%2;" ::"r"(dst), "l"(src), "r"(bytes) : "memory");
}
__device__ __forceinline__ void cp_commit() { asm volatile("cp.async.commit_group;" ::: "memory"); }
template <int N> __device__ __forceinline__ void cp_wait() { asm volatile("cp.async.wait_group %0;" ::"n"(N) : "memory"); }
__device__ __forceinline__ void bulk_commit() { asm volatile("cp.async.bulk.commit_group;" ::: "memory"); }
__device__ __forceinline__ void bulk_wait0() { asm volatile("cp.async.bulk.wait_group 0;" ::: "memory"); }
__device__ __forceinline__ void ldsm4(uint32_t* r, uint32_t a) {
    asm volatile("ldmatrix.sync.aligned.m8n8.x4.shared.b16 {%0,%1,%2,%3},[%4];" : "=r"(r[0]), "=r"(r[1]), "=r"(r[2]), "=r"(r[3]) : "r"(a) : "memory");
}
__device__ __forceinline__ void ldsm4t(uint32_t* r, uint32_t a) {
    asm volatile("ldmatrix.sync.aligned.m8n8.x4.trans.shared.b16 {%0,%1,%2,%3},[%4];" : "=r"(r[0]), "=r"(r[1]), "=r"(r[2]), "=r"(r[3]) : "r"(a) : "memory");
}
__device__ __forceinline__ void stsm4(uint32_t a, uint32_t r0, uint32_t r1, uint32_t r2, uint32_t r3) {
    asm volatile("stmatrix.sync.aligned.m8n8.x4.shared.b16 [%0],{%1,%2,%3,%4};" ::"r"(a), "r"(r0), "r"(r1), "r"(r2), "r"(r3) : "memory");
}
__device__ __forceinline__ void stsm4t(uint32_t a, uint32_t r0, uint32_t r1, uint32_t r2, uint32_t r3) {
    asm volatile("stmatrix.sync.aligned.m8n8.x4.trans.shared.b16 [%0],{%1,%2,%3,%4};" ::"r"(a), "r"(r0), "r"(r1), "r"(r2), "r"(r3) : "memory");
}
__device__ __forceinline__ void lds128(uint32_t* r, uint32_t a) {
    asm volatile("ld.shared.v4.b32 {%0,%1,%2,%3},[%4];" : "=r"(r[0]), "=r"(r[1]), "=r"(r[2]), "=r"(r[3]) : "r"(a) : "memory");
}
__device__ __forceinline__ void lds64(uint32_t* r, uint32_t a) {
    asm volatile("ld.shared.v2.b32 {%0,%1},[%2];" : "=r"(r[0]), "=r"(r[1]) : "r"(a) : "memory");
}
__device__ __forceinline__ uint32_t lds32(uint32_t a) { uint32_t v; asm volatile("ld.shared.b32 %0,[%1];" : "=r"(v) : "r"(a) : "memory"); return v; }
__device__ __forceinline__ void sts128(uint32_t a, uint32_t r0, uint32_t r1, uint32_t r2, uint32_t r3) {
    asm volatile("st.shared.v4.b32 [%0],{%1,%2,%3,%4};" ::"r"(a), "r"(r0), "r"(r1), "r"(r2), "r"(r3) : "memory");
}
__device__ __forceinline__ void sts64(uint32_t a, uint32_t v0, uint32_t v1) { asm volatile("st.shared.v2.b32 [%0],{%1,%2};" ::"r"(a), "r"(v0), "r"(v1) : "memory"); }
[[maybe_unused]] __device__ __forceinline__ void sts32(uint32_t a, uint32_t v) { asm volatile("st.shared.b32 [%0],%1;" ::"r"(a), "r"(v) : "memory"); }
#define AU_(op) "{.reg .u32 t; add.u32 t,%4,%5; " op " {%0,%1,%2,%3},[t+%6];}"
template <int I> __device__ __forceinline__ void ldsm4_u(uint32_t* r, uint32_t a, uint32_t u) {
    asm volatile(AU_("ldmatrix.sync.aligned.m8n8.x4.shared.b16") : "=r"(r[0]), "=r"(r[1]), "=r"(r[2]), "=r"(r[3]) : "r"(a), "r"(u), "n"(I) : "memory");
}
template <int I> __device__ __forceinline__ void ldsm4t_u(uint32_t* r, uint32_t a, uint32_t u) {
    asm volatile(AU_("ldmatrix.sync.aligned.m8n8.x4.trans.shared.b16") : "=r"(r[0]), "=r"(r[1]), "=r"(r[2]), "=r"(r[3]) : "r"(a), "r"(u), "n"(I) : "memory");
}
template <int I> __device__ __forceinline__ void lds128_u(uint32_t* r, uint32_t a, uint32_t u) {
    asm volatile(AU_("ld.shared.v4.b32") : "=r"(r[0]), "=r"(r[1]), "=r"(r[2]), "=r"(r[3]) : "r"(a), "r"(u), "n"(I) : "memory");
}
template <int I> __device__ __forceinline__ void lds64_u(uint32_t* r, uint32_t a, uint32_t u) {
    asm volatile("{.reg .u32 t; add.u32 t,%2,%3; ld.shared.v2.b32 {%0,%1},[t+%4];}" : "=r"(r[0]), "=r"(r[1]) : "r"(a), "r"(u), "n"(I) : "memory");
}
template <int I> __device__ __forceinline__ uint32_t lds32_u(uint32_t a, uint32_t u) {
    uint32_t v;
    asm volatile("{.reg .u32 t; add.u32 t,%1,%2; ld.shared.b32 %0,[t+%3];}" : "=r"(v) : "r"(a), "r"(u), "n"(I) : "memory");
    return v;
}
template <int I> __device__ __forceinline__ void sts64_u(uint32_t a, uint32_t u, uint32_t v0, uint32_t v1) {
    asm volatile("{.reg .u32 t; add.u32 t,%0,%1; st.shared.v2.b32 [t+%2],{%3,%4};}" ::"r"(a), "r"(u), "n"(I), "r"(v0), "r"(v1) : "memory");
}
template <int I> __device__ __forceinline__ void sts32_u(uint32_t a, uint32_t u, uint32_t v) {
    asm volatile("{.reg .u32 t; add.u32 t,%0,%1; st.shared.b32 [t+%2],%3;}" ::"r"(a), "r"(u), "n"(I), "r"(v) : "memory");
}
template <int I> __device__ __forceinline__ void sts16_u(uint32_t a, uint32_t u, uint32_t v) {
    asm volatile("{.reg .u32 t; add.u32 t,%0,%1; st.shared.b16 [t+%2],%3;}" ::"r"(a), "r"(u), "n"(I), "h"((unsigned short)v) : "memory");
}
template <int I> __device__ __forceinline__ void sts128_u(uint32_t a, uint32_t u, uint32_t r0, uint32_t r1, uint32_t r2, uint32_t r3) {
    asm volatile("{.reg .u32 t; add.u32 t,%0,%1; st.shared.v4.b32 [t+%2],{%3,%4,%5,%6};}" ::"r"(a), "r"(u), "n"(I), "r"(r0), "r"(r1), "r"(r2), "r"(r3) : "memory");
}
template <int I> __device__ __forceinline__ void stsm4_u(uint32_t a, uint32_t u, uint32_t r0, uint32_t r1, uint32_t r2, uint32_t r3) {
    asm volatile("{.reg .u32 t; add.u32 t,%0,%1; stmatrix.sync.aligned.m8n8.x4.shared.b16 [t+%2],{%3,%4,%5,%6};}"
                 ::"r"(a), "r"(u), "n"(I), "r"(r0), "r"(r1), "r"(r2), "r"(r3) : "memory");
}
__device__ __forceinline__ void st_share2(uint32_t a, uint32_t u, uint32_t mb, uint32_t d0, uint32_t d1, uint32_t v0, uint32_t v1) {
    asm volatile("{.reg .pred p; .reg .u32 t,x,y; add.u32 t,%0,%1;\n"
                 "add.u32 x,t,%3; add.u32 y,%2,%3; st.async.shared::cluster.mbarrier::complete_tx::bytes.v2.b32 [x],{%5,%6},[y];\n"
                 "add.u32 x,t,%4; add.u32 y,%2,%4; st.async.shared::cluster.mbarrier::complete_tx::bytes.v2.b32 [x],{%5,%6},[y];\n"
                 "st.shared.v2.b32 [t],{%5,%6}; bar.warp.sync -1; setp.eq.u32 p,%0,0; @p mbarrier.arrive.shared::cta.b64 _,[%2];}"
                 ::"r"(a), "r"(u), "r"(mb), "r"(d0), "r"(d1), "r"(v0), "r"(v1) : "memory");
}
template <int V> struct IC { __host__ __device__ constexpr operator int() const { return V; } };
template <int N, class F> __device__ __forceinline__ void sfor(F f) {
    if constexpr (N > 0) { sfor<N - 1>(f); f(IC<N - 1>()); }
}
__device__ __forceinline__ void mma_f16(float* d, const uint32_t* a, uint32_t b0, uint32_t b1) {
    asm volatile("mma.sync.aligned.m16n8k16.row.col.f32.f16.f16.f32 {%0,%1,%2,%3},{%4,%5,%6,%7},{%8,%9},{%0,%1,%2,%3};"
                 : "+f"(d[0]), "+f"(d[1]), "+f"(d[2]), "+f"(d[3]) : "r"(a[0]), "r"(a[1]), "r"(a[2]), "r"(a[3]), "r"(b0), "r"(b1));
}
__device__ __forceinline__ void mma_bf(float* d, uint32_t a0, uint32_t a1, uint32_t a2, uint32_t a3, uint32_t b0, uint32_t b1) {
    asm volatile("mma.sync.aligned.m16n8k16.row.col.f32.bf16.bf16.f32 {%0,%1,%2,%3},{%4,%5,%6,%7},{%8,%9},{%0,%1,%2,%3};"
                 : "+f"(d[0]), "+f"(d[1]), "+f"(d[2]), "+f"(d[3]) : "r"(a0), "r"(a1), "r"(a2), "r"(a3), "r"(b0), "r"(b1));
}
__device__ __forceinline__ void mma_bf8(float* d, uint32_t a0, uint32_t a1, uint32_t b0) {
    asm volatile("mma.sync.aligned.m16n8k8.row.col.f32.bf16.bf16.f32 {%0,%1,%2,%3},{%4,%5},{%6},{%0,%1,%2,%3};"
                 : "+f"(d[0]), "+f"(d[1]), "+f"(d[2]), "+f"(d[3]) : "r"(a0), "r"(a1), "r"(b0));
}
__device__ __forceinline__ uint32_t pack_bf(float lo, float hi) { uint32_t r; asm("cvt.rn.bf16x2.f32 %0,%1,%2;" : "=r"(r) : "f"(hi), "f"(lo)); return r; }
__device__ __forceinline__ uint32_t pack_h(float lo, float hi) { uint32_t r; asm("cvt.rn.f16x2.f32 %0,%1,%2;" : "=r"(r) : "f"(hi), "f"(lo)); return r; }
__device__ __forceinline__ float bf_lo(uint32_t v) { return __uint_as_float(v << 16); }
__device__ __forceinline__ float bf_hi(uint32_t v) { return __uint_as_float(v & 0xffff0000u); }
__device__ __forceinline__ uint32_t bfma(uint32_t a, uint32_t b, uint32_t c) { uint32_t r; asm("fma.rn.bf16x2 %0,%1,%2,%3;" : "=r"(r) : "r"(a), "r"(b), "r"(c)); return r; }
__device__ __forceinline__ uint4 add_bf8(const uint4 x, const uint32_t* y, const uint32_t k = 0x3f803f80u) {
    return make_uint4(bfma(y[0], k, x.x), bfma(y[1], k, x.y), bfma(y[2], k, x.z), bfma(y[3], k, x.w));
}
__device__ __forceinline__ float ex2(float x) { float r; asm("ex2.approx.ftz.f32 %0,%1;" : "=f"(r) : "f"(x)); return r; }
__device__ __forceinline__ float rcp(float x) { float r; asm("rcp.approx.ftz.f32 %0,%1;" : "=f"(r) : "f"(x)); return r; }
__device__ __forceinline__ void wg_fence() { asm volatile("wgmma.fence.sync.aligned;" ::: "memory"); }
__device__ __forceinline__ void wg_commit() { asm volatile("wgmma.commit_group.sync.aligned;" ::: "memory"); }
template <int N> __device__ __forceinline__ void wg_wait() { asm volatile("wgmma.wait_group.sync.aligned %0;" ::"n"(N) : "memory"); }
__device__ __forceinline__ uint64_t mkdesc(uint32_t a, uint32_t lbo, uint32_t sbo, uint32_t sw) {
    return (uint64_t)((a & 0x3FFFF) >> 4) | ((uint64_t)(lbo >> 4) << 16) | ((uint64_t)(sbo >> 4) << 32) | ((uint64_t)sw << 62);
}
#define F4(d, i) "+f"(d[i]), "+f"(d[i + 1]), "+f"(d[i + 2]), "+f"(d[i + 3])
#define F8(d, i) F4(d, i), F4(d, i + 4)
#define F16(d, i) F8(d, i), F8(d, i + 8)
template <int OFF, int SC> __device__ __forceinline__ void wg_n32_x(float* d, const uint32_t* a, uint32_t lo) {
    asm volatile("{.reg .pred p; .reg .b32 l; .reg .b64 q; setp.ne.b32 p,%22,0; add.u32 l,%20,%21; mov.b64 q,{l,8};\n"
                 "wgmma.mma_async.sync.aligned.m64n32k16.f32.f16.f16 "
                 "{%0,%1,%2,%3,%4,%5,%6,%7,%8,%9,%10,%11,%12,%13,%14,%15},{%16,%17,%18,%19},q,p,1,1,0;}"
                 : F16(d, 0) : "r"(a[0]), "r"(a[1]), "r"(a[2]), "r"(a[3]), "r"(lo), "n"(OFF), "n"(SC));
}
__device__ __forceinline__ void wg_n128_rs(float* d, const uint32_t* a, uint64_t db, int sc) {
    asm volatile("{.reg .pred p; setp.ne.b32 p,%69,0; wgmma.mma_async.sync.aligned.m64n128k16.f32.f16.f16 "
                 "{%0,%1,%2,%3,%4,%5,%6,%7,%8,%9,%10,%11,%12,%13,%14,%15,%16,%17,%18,%19,%20,%21,%22,%23,%24,%25,%26,%27,%28,%29,%30,%31,"
                 "%32,%33,%34,%35,%36,%37,%38,%39,%40,%41,%42,%43,%44,%45,%46,%47,%48,%49,%50,%51,%52,%53,%54,%55,%56,%57,%58,%59,%60,%61,%62,%63},"
                 "{%64,%65,%66,%67},%68,p,1,1,0;}"
                 : F16(d, 0), F16(d, 16), F16(d, 32), F16(d, 48) : "r"(a[0]), "r"(a[1]), "r"(a[2]), "r"(a[3]), "l"(db), "r"(sc));
}
#define N80_REGS "{%0,%1,%2,%3,%4,%5,%6,%7,%8,%9,%10,%11,%12,%13,%14,%15,%16,%17,%18,%19,%20,%21,%22,%23,%24,%25,%26,%27,%28,%29,%30,%31,%32,%33,%34,%35,%36,%37,%38,%39}"
__device__ __forceinline__ void wg_n80_ss(float* d, uint64_t da, uint64_t db, int sc) {
    asm volatile("{.reg .pred p; setp.ne.b32 p,%42,0; wgmma.mma_async.sync.aligned.m64n80k16.f32.bf16.bf16 " N80_REGS ",%40,%41,p,1,1,0,0;}"
                 : F16(d, 0), F16(d, 16), F8(d, 32) : "l"(da), "l"(db), "r"(sc));
}
__device__ __forceinline__ void wg_n88_ss(float* d, uint64_t da, uint64_t db, int sc) {
    asm volatile("{.reg .pred p; setp.ne.b32 p,%46,0; wgmma.mma_async.sync.aligned.m64n88k16.f32.f16.f16 "
                 "{%0,%1,%2,%3,%4,%5,%6,%7,%8,%9,%10,%11,%12,%13,%14,%15,%16,%17,%18,%19,%20,%21,%22,%23,%24,%25,%26,%27,%28,%29,%30,%31,"
                 "%32,%33,%34,%35,%36,%37,%38,%39,%40,%41,%42,%43},%44,%45,p,1,1,0,0;}"
                 : F16(d, 0), F16(d, 16), F8(d, 32), F4(d, 40) : "l"(da), "l"(db), "r"(sc));
}
__device__ __forceinline__ void wg_n48_ss_ta(float* d, uint64_t da, uint64_t db, int sc) {
    asm volatile("{.reg .pred p; setp.ne.b32 p,%26,0; wgmma.mma_async.sync.aligned.m64n48k16.f32.f16.f16 "
                 "{%0,%1,%2,%3,%4,%5,%6,%7,%8,%9,%10,%11,%12,%13,%14,%15,%16,%17,%18,%19,%20,%21,%22,%23},%24,%25,p,1,1,1,0;}"
                 : F16(d, 0), F8(d, 16) : "l"(da), "l"(db), "r"(sc));
}
template <int TA> __device__ __forceinline__ void wg_n64_ss_tb(float* d, uint64_t da, uint64_t db, int sc) {
    asm volatile("{.reg .pred p; setp.ne.b32 p,%34,0; wgmma.mma_async.sync.aligned.m64n64k16.f32.f16.f16 "
                 "{%0,%1,%2,%3,%4,%5,%6,%7,%8,%9,%10,%11,%12,%13,%14,%15,%16,%17,%18,%19,%20,%21,%22,%23,%24,%25,%26,%27,%28,%29,%30,%31},"
                 "%32,%33,p,1,1,%35,1;}"
                 : F16(d, 0), F16(d, 16) : "l"(da), "l"(db), "r"(sc), "n"(TA));
}
__device__ __forceinline__ void pdl_wait() { asm volatile("griddepcontrol.wait;" ::: "memory"); }
__device__ __forceinline__ void pdl_go() { asm volatile("griddepcontrol.launch_dependents;" ::: "memory"); }
__device__ __forceinline__ float cos640(float p) {
    const float q = fmaf(p, 0.0015625f, 12582912.f) - 12582912.f;
    return __cosf(fmaf(q, -640.f, p) * 0.009817477042468103f);
}
__device__ __forceinline__ uint4 cos_row8(float p0, float step, float amp = 1.f) {
    float v[8];
    const float k = 2.f * cos640(step);
    v[0] = amp * cos640(p0); v[1] = amp * cos640(p0 + step);
#pragma unroll
    for (int i = 2; i < 8; i++) v[i] = fmaf(k, v[i - 1], -v[i - 2]);
    return make_uint4(pack_h(v[0], v[1]), pack_h(v[2], v[3]), pack_h(v[4], v[5]), pack_h(v[6], v[7]));
}
__device__ __forceinline__ float wfilter_max(int lane) {
    float m = fmaxf(fmaxf(g_wmax[lane], g_wmax[lane + 32]), fmaxf(g_wmax[lane + 64], g_wmax[lane + 96]));
    return __uint_as_float(__reduce_max_sync(~0u, __float_as_uint(m)));
}
__device__ __forceinline__ unsigned ld_acquire(const Flag* p) { unsigned v; asm volatile("ld.acquire.gpu.global.u32 %0,[%1];" : "=r"(v) : "l"(p) : "memory"); return v; }
#define POLL_NS 200
template <int NS = POLL_NS> __device__ __forceinline__ void wait_flag(const Flag* p, unsigned v) {
    if (ld_acquire(p) >= v) return;
    unsigned x;
    int lim = 0;
    do {
        __nanosleep(NS);
        asm volatile("ld.relaxed.gpu.global.u32 %0,[%1];" : "=r"(x) : "l"(p) : "memory");
    } while (x < v && ++lim < SPIN_LIM);
    ld_acquire(p);
}
__device__ __forceinline__ void prefetch_l2(const void* p, int bytes) { asm volatile("cp.async.bulk.prefetch.L2.global [%0],%1;" ::"l"(p), "r"(bytes) : "memory"); }
__device__ __forceinline__ void red_release(Flag* p) { asm volatile("red.release.gpu.global.add.u32 [%0],1;" ::"l"(p) : "memory"); }
__device__ __forceinline__ void red_relaxed(Flag* p) { asm volatile("red.relaxed.gpu.global.add.u32 [%0],1;" ::"l"(p) : "memory"); }
__device__ __forceinline__ void red_h8(void* p, uint32_t a, uint32_t b, uint32_t c, uint32_t d) {
    asm volatile("red.relaxed.gpu.global.add.noftz.v4.f16x2 [%0],{%1,%2,%3,%4};" ::"l"(p), "r"(a), "r"(b), "r"(c), "r"(d) : "memory");
}
__device__ __forceinline__ float pow2_scale(float bound, int top, float* inv) {
    int e = (int)((__float_as_uint(bound) >> 23) & 0xff) - 126;
    int k = top - e;
    k = max(-100, min(100, k));
    *inv = __uint_as_float((uint32_t)(127 - k) << 23);
    return __uint_as_float((uint32_t)(127 + k) << 23);
}
__device__ __forceinline__ char* red_base() { return (char*)(((uintptr_t)g_redraw + 32767) & ~(uintptr_t)32767); }

__device__ __forceinline__ void setup_a(char* sm, const int b, const bf16* __restrict__ wr, const bf16* __restrict__ wi) {
    const int tid = threadIdx.x, lane = tid & 31;
    const uint32_t sb = smem_u32(sm);
    auto row_byte = [&](int q) { return ((b >> 2) + 32 * ((q >> 1) * 8 + 2 * (b & 3) + (q & 1))) * 642; };
#pragma unroll 1
    for (int r = tid >> 5; r < 32; r += 8) {
        const char* src = (const char*)(r < 16 ? wr : wi) + (row_byte(r & 15) & ~15);
        cp_async16(sb + r * 672 + lane * 16, src + lane * 16);
        if (lane < 9) cp_async16(sb + r * 672 + 512 + lane * 16, src + 512 + lane * 16);
    }
    ((uint4*)g_stat)[b * 256 + tid] = make_uint4(0, 0, 0, 0);
    if (tid < 2 * (NFLAG / 128)) ((uint4*)(g_flag + b * (NFLAG / 128) + (tid >> 1)))[tid & 1] = make_uint4(0, 0, 0, 0);
    if (tid < 12) {
        const int i = b * 12 + tid;
        const int f = ((i >> 4) & 3) * 8 + (i & 7), im = (i >> 3) & 1, part = (i >> 8) & 1;
        ((uint4*)g_ctab)[i] = cos_row8((float)(i < 1024 ? (i >> 7) * 80 * (i & 63) + ((i & 64) ? 480 : 0) : ((i >> 6) & 3) * 160 * f + (im == part ? 0 : im ? 160 : 480)),
                                       (float)(i < 1024 ? 10 * (i & 63) : 20 * f));
    }
    asm volatile("cp.async.wait_all;" ::: "memory");
    __syncthreads();
    const int q0 = (tid & 3) * 4;
    const char* rp[4];
#pragma unroll
    for (int u = 0; u < 4; u++) rp[u] = sm + (q0 + u) * 672 + (row_byte(q0 + u) & 15);
    uint32_t mx = 0;
#pragma unroll 2
    for (int c = tid >> 2; c < 321; c += 64) {
        uint32_t v[4];
#pragma unroll
        for (int u = 0; u < 4; u++) {
            v[u] = ((const unsigned short*)rp[u])[c] | ((uint32_t)((const unsigned short*)(rp[u] + 16 * 672))[c] << 16);
            mx = __vmaxu2(mx, v[u] & 0x7fff7fffu);
        }
        ((uint4*)g_Wf)[(size_t)c * 512 + b * 4 + ((tid ^ (b >> 1)) & 3)] = make_uint4(v[0], v[1], v[2], v[3]);
    }
    mx = __reduce_max_sync(~0u, max(mx & 0xffffu, mx >> 16));
    __syncthreads();
    if (lane == 0) ((uint32_t*)sm)[tid >> 5] = mx;
    __syncthreads();
    if (tid < 32) {
        mx = __reduce_max_sync(~0u, ((uint32_t*)sm)[lane & 7]);
        if (tid == 0) g_wmax[b] = __uint_as_float(mx << 16);
    }
}
__device__ __forceinline__ void setup_b(const int b, const bf16* __restrict__ mem0) {
    const int tid = threadIdx.x;
    uint4* z = (uint4*)red_base();
    if (b < 3) {
        const int w = tid >> 5, lane = tid & 31, p = b * 2 + ((w >> 1) & 1), odd = w & 1;
        uint32_t mx = 0;
#pragma unroll 4
        for (int i = lane; i < 640; i += 32) {
            const uint4 u = ((const uint4*)mem0)[i];
            mx = __vmaxu2(__vmaxu2(mx, u.x & 0x7fff7fffu), __vmaxu2(__vmaxu2(u.y & 0x7fff7fffu, u.z & 0x7fff7fffu), u.w & 0x7fff7fffu));
        }
        float inv, v[7];
        const float sc = pow2_scale(__uint_as_float(__reduce_max_sync(~0u, max(mx & 0xffffu, mx >> 16)) << 16), 14, &inv);
        if (tid == 0) g_invM0 = inv;
#pragma unroll
        for (int j = 0; j < 7; j++) {
            const int r = p * 56 + (j < 6 ? odd * 32 + (j >> 1) * 8 : 24) + (lane >> 2), mr = 2 * (lane & 3) + (j < 6 ? (j & 1) : odd);
            v[j] = r < 320 ? __bfloat162float(mem0[mr * 640 + (w >> 2) * 320 + r]) * sc : 0.f;
        }
        const int off = w * 2048 + (lane >> 4) * 1024 + ((lane >> 3) & 1) * 256 + (lane & 7) * 16 + (b == 2 ? (w >> 1) * 4096 + 128 : b * 16384);
        const uint4 u = make_uint4(pack_h(v[0], v[1]), pack_h(v[2], v[3]), pack_h(v[4], v[5]), pack_h(v[6], 32.f));
        z[off >> 4] = u; z[65536 + (off >> 4)] = u;
    }
}

#define SU_PAD 40960
constexpr int SU_SMEM = SU_PAD;
__global__ void __launch_bounds__(256, 4) k_setup(const bf16* __restrict__ wr, const bf16* __restrict__ wi, const bf16* __restrict__ mem0) {
    extern __shared__ __align__(1024) char sm[];
    TL(0);
    if (blockIdx.x >= 128) setup_b(blockIdx.x - 128, mem0);
    else setup_a(sm, blockIdx.x, wr, wi);
    __syncthreads();
    if (threadIdx.x == 0) red_release(g_ready);
    TL(1);
}
__device__ __forceinline__ float weight_scale(int h, int ty, float* inv) { return pow2_scale(__ldcg(g_wmx + h * 3 + ty), 6, inv); }

#define STR_(x) #x
#define STR(x) STR_(x)
#define RF_U 1
constexpr int RF_A = 22 * 2816, RF_X = RF_A + 22 * 1024, RF_BAR = RF_X + 64 * 1344, RF_SMEM = RF_BAR + 80;
__device__ __align__(1024) char g_rtab[4 * RF_A];
template <int first> __global__ void __cluster_dims__(2, 1, 1) __launch_bounds__(256, 2) k_rowf(const bf16* x) {
    extern __shared__ __align__(1024) char sm[];
    TL(first ? 2 : 16);
    const int tid = threadIdx.x, w = tid >> 5, lane = tid & 31, g = lane >> 2, t = lane & 3;
    if (blockIdx.x >= 128) { __nanosleep(2500); return; }
    const int a = first ? blockIdx.x >> 2 : 31 - (blockIdx.x >> 2), gq = blockIdx.x & 3;
    if (!first) pdl_go();
    const uint32_t sb = smem_u32(sm), mb = sb + RF_BAR + w * 8;
    if (lane == 0) {
        mbar_init(mb, 1);
        asm volatile("fence.mbarrier_init.release.cluster;" ::: "memory");
        if (!first && w == 0) {
            mbar_init(sb + RF_BAR + 64, 1);
            fence_async_smem();
            mbar_expect(sb + RF_BAR + 64, RF_A);
            bulk_g2s(sb, g_rtab + gq * RF_A, RF_A, sb + RF_BAR + 64);
        }
    }
    if (lane == 0) mbar_expect(mb, 8 * 1280);
    __syncwarp();
    asm volatile("barrier.cluster.arrive.relaxed.aligned; barrier.cluster.wait.aligned;" ::: "memory");
    if (!first) {
        if (lane == 0) wait_flag<100>(g_flag + F_R + a, a < 28 ? 32 : 192);
        __syncwarp();
        fence_async_glb();
    }
    TL(first ? 3 : 17);
    if (lane < 4)
        asm volatile("cp.async.bulk.shared::cluster.global.mbarrier::complete_tx::bytes.multicast::cluster [%0],[%1],1280,[%2],%3;"
                     ::"r"(sb + RF_X + (w * 8 + (gq & 1) * 4 + lane) * 1344), "l"(x + (size_t)(a * 64 + w * 8 + (gq & 1) * 4 + lane) * 640), "r"(mb),
                     "h"((unsigned short)3) : "memory");
    __syncwarp();
    if (first) pdl_go();
    if (first) {
#pragma unroll 3
        for (int id = tid; id < 22 * 176; id += 256) {
            const int kg = id / 176, n = id - kg * 176;
            const float c = (float)(2 * n + (gq & 1));
            *(uint4*)(sm + id * 16) = cos_row8(fmaf((float)(kg * 8), c, (float)((gq & 2) * 80)), c, 0.03952847075210474f);
        }
    }
    mbar_wait(mb, 0);
    const uint32_t row = sb + RF_X + (w * 8 + g) * 1344;
    float st[4][4] = {};
#pragma unroll 1
    for (int i = 0; i < 20; i += 4) {
        uint32_t u[4][4];
#pragma unroll
        for (int q = 0; q < 4; q++) lds128(u[q], row + (4 * (i + q) + t) * 16);
#pragma unroll
        for (int q = 0; q < 4; q++) {
            mma_bf(st[(q & 1) * 2], u[q][0], 0x3f803f80u, u[q][1], 0x3f803f80u, u[q][0], u[q][1]);
            mma_bf(st[(q & 1) * 2 + 1], u[q][2], 0x3f803f80u, u[q][3], 0x3f803f80u, u[q][2], u[q][3]);
        }
    }
#pragma unroll
    for (int q = 0; q < 4; q++) { st[0][q] += st[2][q]; st[1][q] += st[3][q]; }
    const float sq = __shfl_sync(~0u, (g & 1) ? st[0][1] + st[1][1] : st[0][0] + st[1][0], g * 4 + (g >> 1));
    const float mean = __shfl_sync(~0u, (g & 1) ? st[0][3] + st[1][3] : st[0][2] + st[1][2], g * 4 + (g >> 1)) * (1.f / 640.f);
    const float r = rsqrtf(fmaxf(fmaf(-mean, mean, sq * (1.f / 640.f)), 0.f) + 1e-5f), off = gq == 0 ? -4.f * mean * r : 0.f;
    const float r1 = (gq == 1 || gq == 2) ? -r : r, r2 = (gq & 1) ? -r : r, r3 = gq >= 2 ? -r : r;
    const uint32_t aa = sb + RF_A + w * 128 + g * 16;
    auto el = [&](int d) { unsigned short v; asm volatile("ld.shared.u16 %0,[%1];" : "=h"(v) : "r"(row + d * 2)); return __uint_as_float((uint32_t)v << 16); };
_Pragma(STR(unroll RF_U))
    for (int i = 0; i < 5; i++) {
        const int ch = t + 4 * i;
        uint32_t u[4][4];
        lds128(u[0], row + ch * 16); lds128(u[1], row + (39 - ch) * 16); lds128(u[2], row + (40 + ch) * 16); lds128(u[3], row + (79 - ch) * 16);
        const float nb0 = el(320 - 8 * ch), nb1 = el(ch ? 640 - 8 * ch : 0);
        float o[8];
#pragma unroll
        for (int q = 0; q < 8; q++) {
            const int m = (8 - q) >> 1;
            const float e0 = (q & 1) ? bf_hi(u[0][q >> 1]) : bf_lo(u[0][q >> 1]), e2 = (q & 1) ? bf_hi(u[2][q >> 1]) : bf_lo(u[2][q >> 1]);
            const float e1 = q == 0 ? nb0 : (q & 1) ? bf_hi(u[1][m & 3]) : bf_lo(u[1][m & 3]), e3 = q == 0 ? nb1 : (q & 1) ? bf_hi(u[3][m & 3]) : bf_lo(u[3][m & 3]);
            o[q] = fmaf(e3, r3, fmaf(e2, r2, fmaf(e1, r1, fmaf(e0, r, off))));
        }
        if (ch == 0) o[0] *= 0.5f;
        sts128(aa + ch * 1024, pack_h(o[0], o[1]), pack_h(o[2], o[3]), pack_h(o[4], o[5]), pack_h(o[6], o[7]));
    }
    if (t < 2) sts128(aa + (20 + t) * 1024, t == 0 ? pack_h(fmaf(el(480), r2, fmaf(el(160), r, 0.5f * off)), 0.f) : 0u, 0u, 0u, 0u);
    fence_async_smem();
    __syncthreads();
    if (!first) mbar_wait(sb + RF_BAR + 64, 0);
    else if (a == 0 && tid == 0) { bulk_s2g(g_rtab + gq * RF_A, sb, RF_A); bulk_commit(); }
    const int wg = w >> 2;
    float acc[44];
    uint64_t da = mkdesc(sb + RF_A, 1024, 128, 0), db = mkdesc(sb + wg * 1408, 2816, 128, 0);
    wg_fence();
#pragma unroll 1
    for (int k = 0; k < 11; k++) { wg_n88_ss(acc, da, db, k); da += 128; db += 352; }
    wg_commit(); wg_wait<0>();
    const uint32_t stg = sb + RF_X + wg * 96 * 144;
#pragma unroll
    for (int j = 0; j < 12; j += 2) {
        const int m = lane >> 3, j1 = j < 10 ? j + 1 : j;
        stsm4t(stg + ((j + (m >> 1)) * 8 + (lane & 7)) * 144 + ((w & 3) * 16 + (m & 1) * 8) * 2, pack_h(acc[j * 4], acc[j * 4 + 1]),
               pack_h(acc[j * 4 + 2], acc[j * 4 + 3]), pack_h(acc[j1 * 4], acc[j1 * 4 + 1]), pack_h(acc[j1 * 4 + 2], acc[j1 * 4 + 3]));
    }
    bar_sync(1 + wg, 128);
#pragma unroll 3
    for (int rr = (tid & 127) >> 3; rr < 88; rr += 16) {
        const int ch = tid & 7, c = 2 * (wg * 88 + rr) + (gq & 1);
        if (c <= 320 - (gq >> 1) && (c | (gq ^ 2))) {
            uint32_t u[4];
            lds128(u, stg + rr * 144 + ch * 16);
            ((uint4*)g_UT)[((size_t)(c == 320 ? 1 : 2 * c + (gq >> 1)) * 32 + a) * 8 + (ch ^ (a & 7))] = make_uint4(u[0], u[1], u[2], u[3]);
        }
    }
    if (first && blockIdx.x < 4 && tid == 0) asm volatile("cp.async.bulk.wait_group.read 0;" ::: "memory");
    TL(first ? 4 : 18);
}

constexpr int GST = 4, GSTB = 32768 + 20480, GNC = 32;
constexpr int G_BAR = GST * GSTB + 3072;
#define GPACE 1100
#define GPACE2 650
__device__ __forceinline__ void oproj_load(const uint32_t sb, const int op, const int mb, const int nb, const int c0, const uint32_t pace) {
    const int by = op == 2 ? 20480 : 16384;
    const char* src = op == 2 ? (const char*)g_wot + (size_t)nb * GNC * 20480 : (const char*)g_O + (size_t)(2 * mb + op) * GNC * 16384;
    uint32_t t0 = clock32() - pace + op * (pace / 3);
#pragma unroll 1
    for (int c = c0; c < c0 + GNC; c++, src += by) {
        const int st = c % GST;
        if (c >= GST) mbar_wait(sb + G_BAR + (GST + st) * 8, ((c / GST) - 1) & 1);
        while (clock32() - t0 < pace) {}
        t0 = clock32();
        const int by_ = by;
        mbar_expect(sb + G_BAR + st * 8, by_);
        if (op == 2) bulk_g2s(sb + st * GSTB + 32768, src, by_, sb + G_BAR + st * 8);
        else bulk_g2s_last(sb + st * GSTB + op * 16384, src, by_, sb + G_BAR + st * 8);
    }
}
__device__ __forceinline__ void oproj_mma(const uint32_t sb, const int mb, const int nb, const int c0, const bf16* res, bf16* out, const int layer) {
    const int w = threadIdx.x >> 5, lane = threadIdx.x & 31, wg = w >> 2;
    float acc[40];
    uint4 rv[5];
#pragma unroll 1
    for (int c = c0; c < c0 + GNC; c++) {
        const int st = c % GST;
        mbar_wait(sb + G_BAR + st * 8, (c / GST) & 1);
        const uint32_t d = sb + st * GSTB;
        wg_fence();
#pragma unroll
        for (int k = 0; k < 8; k++)
            wg_n80_ss(acc, mkdesc(d + wg * 16384 + k * 2048, 1024, 128, 0), mkdesc(d + 32768 + k * 2560, 1280, 128, 0), (c - c0) | k);
        wg_commit();
        if (c > c0) {
            wg_wait<1>();
            if (lane == 0) mbar_arrive(sb + G_BAR + (GST + (c - 1) % GST) * 8);
        }
    }
#pragma unroll
    for (int i = 0; i < 5; i++) {
        const int id = i * 32 + lane, r = id / 10;
        rv[i] = __ldcg((const uint4*)res + (size_t)(mb * 128 + w * 16 + r) * 80 + nb * 10 + id - r * 10);
    }
    wg_wait<0>();
    bar_sync(5, 256);
    const uint32_t stg = sb + (GST - 1) * GSTB + w * 16 * 176;
#pragma unroll
    for (int j = 0; j < 5; j++)
        stsm4(stg + (lane & 15) * 176 + (2 * j + (lane >> 4)) * 16, pack_bf(acc[j * 8], acc[j * 8 + 1]), pack_bf(acc[j * 8 + 2], acc[j * 8 + 3]),
              pack_bf(acc[j * 8 + 4], acc[j * 8 + 5]), pack_bf(acc[j * 8 + 6], acc[j * 8 + 7]));
    __syncwarp();
#pragma unroll
    for (int i = 0; i < 5; i++) {
        const int id = i * 32 + lane, r = id / 10, ch = id - r * 10;
        uint32_t y[4];
        lds128(y, stg + r * 176 + ch * 16);
        ((uint4*)out)[(size_t)(mb * 128 + w * 16 + r) * 80 + nb * 10 + ch] = add_bf8(rv[i], y);
    }
    fence_async_smem();
    __syncwarp();
    if (lane == 0) {
        mbar_arrive(sb + G_BAR + (2 * GST - 1) * 8);
        if (layer == 0) red_release(g_flag + F_R + 2 * mb + wg);
    }
}

__global__ void __launch_bounds__(128, 4) k_col(const int first) {
    __shared__ __align__(1024) char sz[8192];
    __shared__ __align__(1024) char stab[24576];
    __shared__ __align__(1024) char swf[8192];
    __shared__ __align__(8) uint64_t bar[2];
    const int tid = threadIdx.x, wl = tid >> 5, lane = tid & 31, g = lane >> 2, t = lane & 3;
    const int c = blockIdx.x;
    TL(first ? 5 : 19);
    const bool realc = c == 0 || c == 320;
    const uint32_t z = smem_u32(sz), b2 = smem_u32(stab), a1 = b2 + 16384, wf = smem_u32(swf), mb = smem_u32(bar);
    if (tid == 0) { mbar_init(mb, 1); mbar_init(mb + 8, 1); fence_async_smem(); }
    if (realc) {
        for (int i = tid; i < 256; i += 128) sts128(z + 4096 + i * 16, 0, 0, 0, 0);
        fence_async_smem();
    }
    const int k1 = wl * 8 + g;
    float tc[16], ts[16];
#pragma unroll
    for (int j = 0; j < 16; j++) {
        const int p = ((j >> 1) * 8 + 2 * t + (j & 1)) * k1;
        __sincosf((float)(p - 1024) * 0.003067961575771282f, &ts[j], &tc[j]);
        ts[j] = -ts[j]; tc[j] = -tc[j];
    }
    if (first && tid == 32) { wait_flag<400>(g_ready, NSETUP); fence_async_glb(); }
    __syncthreads();
    if (tid == 32) {
        mbar_expect(mb + 8, 24576 + 8192);
        bulk_g2s(b2, g_ctab, 24576, mb + 8);
        bulk_g2s(wf, g_Wf + (size_t)c * 2048, 8192, mb + 8);
    }
    float inv;
    const float wsc = pow2_scale(wfilter_max(lane), 0, &inv) * (realc ? 0.0625f : 0.125f);
    pdl_wait();
    TL(first ? 6 : 20);
    if (tid == 0) {
        const int by = realc ? 4096 : 8192;
        mbar_expect(mb, by);
        bulk_g2s_last(z, (const char*)g_UT + (size_t)(c == 320 ? 1 : 2 * c) * 4096, by, mb);
    }
    pdl_go();
    mbar_wait(mb + 8, 0);
    mbar_wait(mb, 0);
    float d[64];
    uint32_t a[4][4];
    wg_fence();
#pragma unroll
    for (int ks = 0; ks < 4; ks++) wg_n64_ss_tb<0>(d, mkdesc(a1 + ks * 2048, 1024, 128, 0), mkdesc(z + ks * 2048, 1024, 1024, 1), ks);
    wg_commit(); wg_wait<0>();
    const float r32 = 0.17677669529663687f;
#pragma unroll
    for (int j = 0; j < 8; j++) {
        float yr[2], yi[2];
#pragma unroll
        for (int e = 0; e < 2; e++) {
            const float re = d[j * 4 + e] * r32, im = d[j * 4 + 2 + e] * r32, cc = tc[j * 2 + e], ss = ts[j * 2 + e];
            yr[e] = re * cc + im * ss; yi[e] = im * cc - re * ss;
        }
        a[j >> 1][(j & 1) * 2] = pack_h(yr[0], yr[1]); a[j >> 1][(j & 1) * 2 + 1] = pack_h(yi[0], yi[1]);
    }
    wg_fence();
#pragma unroll
    for (int ks = 0; ks < 4; ks++) wg_n128_rs(d, a[ks], mkdesc(b2 + ks * 4096, 2048, 128, 0), ks);
    wg_commit(); wg_wait<0>();
#pragma unroll
    for (int q = 0; q < 4; q++) {
        uint32_t wv[4];
        lds128(wv, wf + tid * 64 + ((q ^ (tid >> 1)) & 3) * 16);
#pragma unroll
        for (int jj = 0; jj < 2; jj++) {
            const int j = 2 * q + jj;
            float yr[2], yi[2];
#pragma unroll
            for (int e = 0; e < 2; e++) {
                const float xr = d[j * 4 + e] + d[32 + j * 4 + 2 + e], xi = d[j * 4 + 2 + e] - d[32 + j * 4 + e];
                const float fr = bf_lo(wv[jj * 2 + e]) * wsc, fi = bf_hi(wv[jj * 2 + e]) * wsc;
                yr[e] = xr * fr - xi * fi; yi[e] = xr * fi + xi * fr;
            }
            a[q][jj * 2] = pack_h(yr[0], yr[1]); a[q][jj * 2 + 1] = pack_h(yi[0], yi[1]);
        }
    }
    wg_fence();
#pragma unroll
    for (int ks = 0; ks < 4; ks++) wg_n128_rs(d, a[ks], mkdesc(b2 + ks * 4096, 2048, 128, 0), ks);
    wg_commit(); wg_wait<0>();
#pragma unroll
    for (int j = 0; j < 8; j++) {
        float yr[2], yi[2];
#pragma unroll
        for (int e = 0; e < 2; e++) {
            const float vr = (d[j * 4 + e] - d[32 + j * 4 + 2 + e]) * 0.125f, vi = (d[j * 4 + 2 + e] + d[32 + j * 4 + e]) * 0.125f;
            const float cc = tc[j * 2 + e], ss = ts[j * 2 + e];
            yr[e] = vr * cc - vi * ss; yi[e] = vi * cc + vr * ss;
        }
        a[j >> 1][(j & 1) * 2] = pack_h(yr[0], yr[1]); a[j >> 1][(j & 1) * 2 + 1] = pack_h(yi[0], yi[1]);
    }
    __syncthreads();
    const int mm = lane >> 3, rr = lane & 7;
    const uint32_t rowo = (wl * 16 + (mm & 1) * 8 + rr) * 128;
#pragma unroll
    for (int q = 0; q < 4; q++) stsm4(z + rowo + (((2 * q + (mm >> 1)) ^ rr) << 4), a[q][0], a[q][1], a[q][2], a[q][3]);
    fence_async_smem();
    __syncthreads();
    wg_fence();
#pragma unroll
    for (int ks = 0; ks < 4; ks++) wg_n64_ss_tb<1>(d, mkdesc(a1 + ks * 256, 128, 1024, 0), mkdesc(z + ks * 2048, 1024, 1024, 1), ks);
    wg_commit(); wg_wait<0>();
#pragma unroll
    for (int q = 0; q < 4; q++)
        stsm4(wf + rowo + (((2 * q + (mm >> 1)) ^ rr) << 4), pack_h(d[q * 8] * r32, d[q * 8 + 1] * r32), pack_h(d[q * 8 + 2] * r32, d[q * 8 + 3] * r32),
              pack_h(d[q * 8 + 4] * r32, d[q * 8 + 5] * r32), pack_h(d[q * 8 + 6] * r32, d[q * 8 + 7] * r32));
    __syncwarp();
    if (!(realc && wl >= 2)) {
        const int kk = c == 320 ? 320 : (c & 1) * 160 + (c >> 1) + (wl >> 1) * 320;
#pragma unroll
        for (int i = 0; i < 4; i++) {
            const int r = wl * 16 + i * 4 + (lane >> 3), ch = lane & 7;
            uint32_t v[4];
            lds128(v, wf + r * 128 + ((ch ^ (r & 7)) << 4));
            ((uint4*)g_YT)[((size_t)(r & 31) * 640 + kk) * 8 + (ch ^ (kk & 7))] = make_uint4(v[0], v[1], v[2], v[3]);
        }
    }
    TL(first ? 7 : 21);
}

constexpr int O_XS = 0;
constexpr int O_MS = 81920;
constexpr int O_QKP = O_MS + 10752;
constexpr int O_VM = O_QKP + 4096;
constexpr int O_SC = O_VM + 4096;
constexpr int O_OS = O_SC + 1536;
constexpr int O_XCH = O_OS + 2048;
constexpr int O_SUM = O_XCH + 8192;
constexpr int O_MX = O_SUM + 256;
constexpr int O_STG = O_MS + 65536 - 8192;
static_assert(O_STG - 16384 >= O_MX + 1024, "shared-memory map");
constexpr int O_WO = O_STG + 16384;
constexpr int O_SCL = O_WO + 65536;
constexpr int O_BAR = O_SCL + 64;
constexpr int B_XF = O_BAR, B_S = O_BAR + 16, B_VX = O_BAR + 32, B_STG = O_BAR + 48, B_FREE = O_BAR + 72;
constexpr int T_FA = O_BAR + 96, T_EA = T_FA + 32, T_FB = T_EA + 32, T_EB = T_FB + 56, T_RED = T_EB + 32;
constexpr int O_WMX = O_BAR + 512, B_W = O_BAR + 64;
constexpr int O_LAST = (O_WMX + 192 + 1023) / 1024 * 1024;
constexpr int CH_SMEM = O_LAST + 8192;
static_assert(O_WO == 19 * 8192, "weight staging");
__device__ __forceinline__ uint32_t tail_b(int c) { return c % 7 < 4 ? O_XS + (c % 7) * 20480 : O_WO + (c % 7 - 4) * 20480; }
__device__ __forceinline__ int s_tx(int c) { return c == 2 ? 2 * 768 : 768 + 2048; }

#define NPERM 1
#define NWO0 1
#define NWO0B 4
#define NWO1 6
#define TDELAY 800
#define WDEPTH 6
#define RDELAY 580

#define STAMP(i)

#define NTA 23
#define NTB 26
template <int LO, int HI>
__device__ __forceinline__ void tok_issue(const uint32_t (&A0)[20][4], const uint32_t (&A1)[20][4], float (&b0)[16], float (&b1)[16], uint32_t xd,
                                          const uint32_t zero) {
    if (LO == 0) wg_fence();
    sfor<HI - LO>([&](auto I) {
        constexpr int i = LO + I;
        if constexpr (i < 20) wg_n32_x<i * 64, i>(b0, A0[i], xd); else wg_n32_x<(i - 20) * 64, i - 20>(b1, A1[i - 20], xd + zero);
        if constexpr (i == 19 || i == NTB - 1 || i == 39) wg_commit();
    });
}
__device__ __forceinline__ void tok_give(const float (&b0)[16], const uint32_t L16, const uint32_t xch0) {
    wg_wait<1>();
    sfor<2>([&](auto I) {
        constexpr int i = I;
        sts128_u<i * 512>(L16, xch0, pack_h(b0[8 * i], b0[8 * i + 1]), pack_h(b0[8 * i + 2], b0[8 * i + 3]), pack_h(b0[8 * i + 4], b0[8 * i + 5]),
                          pack_h(b0[8 * i + 6], b0[8 * i + 7]));
    });
}
__device__ __forceinline__ void tok_finish(float (&b1)[16], const uint32_t (&e)[2][4], const uint32_t L16, const uint32_t dst, const uint32_t idn) {
#pragma unroll
    for (int j = 0; j < 4; j++)
        asm volatile("mma.sync.aligned.m16n8k8.row.col.f32.f16.f16.f32 {%0,%1,%2,%3},{%4,%5},{%6},{%0,%1,%2,%3};"
                     : F4(b1, 4 * j) : "r"(e[j >> 1][(j & 1) * 2]), "r"(e[j >> 1][(j & 1) * 2 + 1]), "r"(idn));
    stsm4_u<0>(L16, dst, pack_bf(b1[0], b1[1]), pack_bf(b1[2], b1[3]), pack_bf(b1[4], b1[5]), pack_bf(b1[6], b1[7]));
    stsm4_u<512>(L16, dst, pack_bf(b1[8], b1[9]), pack_bf(b1[10], b1[11]), pack_bf(b1[12], b1[13]), pack_bf(b1[14], b1[15]));
}
__device__ __forceinline__ uint32_t uni(uint32_t v) { return __shfl_sync(~0u, v, 0); }
__device__ __forceinline__ uint32_t badd(uint32_t a, uint32_t b) { uint32_t r; asm("add.rn.bf16x2 %0,%1,%2;" : "=r"(r) : "r"(a), "r"(b)); return r; }
__device__ __forceinline__ uint32_t bmax(uint32_t a, uint32_t b) { uint32_t r; asm("max.bf16x2 %0,%1,%2;" : "=r"(r) : "r"(a), "r"(b)); return r; }
__device__ __forceinline__ uint32_t babsmax(uint32_t a, uint32_t b) { uint32_t r; asm("max.xorsign.abs.bf16x2 %0,%1,%2;" : "=r"(r) : "r"(a), "r"(b)); return r; }
__device__ __forceinline__ uint32_t habsmax(uint32_t a, uint32_t b) { uint32_t r; asm("max.xorsign.abs.f16x2 %0,%1,%2;" : "=r"(r) : "r"(a), "r"(b)); return r; }

template <int NPF>
__device__ __forceinline__ float mem_out(const uint32_t sb, const uint32_t L16, const uint32_t L8, uint32_t (&wo)[16][4], const uint32_t woa,
                                         char* dst, const bool odd) {
    bar_sync(2, 352);
    float a[4][4];
#pragma unroll
    for (int i = 0; i < 4; i++) a[i][0] = a[i][1] = a[i][2] = a[i][3] = 0.f;
    uint32_t ob[4][4], sm_[2], sc[2];
    sfor<8>([&](auto I) {
        constexpr int i = I;
        if constexpr (!(i & 1)) ldsm4t_u<O_OS + (i >> 1) * 512>(ob[i >> 1], L16, sb);
        if constexpr (i >= NPF) { ldsm4t(wo[i], woa + i * 1024); ldsm4t(wo[8 + i], (woa ^ 32) + i * 1024); }
    });
    lds64_u<O_SUM>(sm_, L8 & 24, sb); lds64(sc, sb + O_SCL);
#pragma unroll
    for (int i = 0; i < 8; i++) {
        mma_bf(a[i & 1], wo[i][0], wo[i][1], wo[i][2], wo[i][3], ob[i >> 1][(i & 1) * 2], ob[i >> 1][(i & 1) * 2 + 1]);
        mma_bf(a[2 + (i & 1)], wo[8 + i][0], wo[8 + i][1], wo[8 + i][2], wo[8 + i][3], ob[i >> 1][(i & 1) * 2], ob[i >> 1][(i & 1) * 2 + 1]);
    }
    const float f0 = rcp(__uint_as_float(sm_[0])) * __uint_as_float(sc[0]), f1 = rcp(__uint_as_float(sm_[1])) * __uint_as_float(sc[0]);
    red_h8(dst, pack_h((a[0][0] + a[1][0]) * f0, (a[0][1] + a[1][1]) * f1), pack_h((a[0][2] + a[1][2]) * f0, (a[0][3] + a[1][3]) * f1),
           pack_h((a[2][0] + a[3][0]) * f0, (a[2][1] + a[3][1]) * f1), pack_h(odd ? (a[2][3] + a[3][3]) * f1 : (a[2][2] + a[3][2]) * f0, 1.f));
    return __uint_as_float(sc[1]);
}

__device__ __forceinline__ void chain_mma(const uint32_t sb, const int c, const int h, const int layer, const uint32_t zero, const bf16* __restrict__ Wq,
                                          const bf16* __restrict__ Wk, const bf16* __restrict__ Wv, const bf16* __restrict__ Wo,
                                          const bf16* res, bf16* out) {
    int tid = read_tid(), lane = tid & 31;
    const int w = __shfl_sync(~0u, tid >> 5, 0), wg = w >> 2;
    [[maybe_unused]] const int cta = h * 3 + c;
    uint32_t A0[20][4], A1[20][4];
    const int t0 = (w & 3) + wg * 4, t1 = t0 ^ 4;
    float sl;
    {
        const int tl = tid & 127, r = tl >> 3, ch = tl & 7;
        const size_t so = (size_t)(wg * 320 + r) * 4096 + h * 128 + ch * 8;
        const bf16 *wa = (c == 2 ? Wv : Wq + c * 64) + so, *wb = (c == 2 ? Wv + 64 : Wk + c * 64) + so;
        const uint32_t ring = sb + wg * 4096;
        const uint32_t dst = ring + r * 128 + ((ch ^ r) & 7) * 16;
        const uint32_t src = ring + ((lane & 7) + (lane >> 4) * 8) * 128 + ((((w & 3) * 2 + ((lane >> 3) & 1)) ^ lane) & 7) * 16;
        const int q4 = lane & 3, gr = (c * 2 + ((w >> 1) & 1)) * 56 + (q4 == 3 ? 24 : (w & 1) * 32 + q4 * 8);
        const bf16* wo_ = Wo + (size_t)(h * 128 + (lane >> 2)) * 640 + wg * 320 + min(gr, 312);
        const uint32_t wdst = sb + O_WO + w * 8192 + (lane >> 2) * 64 + ((q4 ^ (lane >> 3)) & 3) * 16;
        auto issue = [&](int i) {
            if (i < 20) {
                const uint32_t d = dst + (i < 19 ? i * 8192 : O_LAST);
                cp_async16(d, wa + (size_t)i * 65536); cp_async16(d + 2048, wb + (size_t)i * 65536);
                if (i < 16) cp_async16(wdst + i * 512, wo_ + i * 5120, gr < 320 ? 16 : 0);
            }
            cp_commit();
        };
#pragma unroll 1
        for (int i = 0; i < WDEPTH; i++) issue(i);
        asm volatile("barrier.cluster.arrive.relaxed.aligned;" ::: "memory");
        float fa, fb;
        if (layer == 0) {
            uint32_t ma = 0, mb = 0;
#pragma unroll 1
            for (int i = 0; i < 20; i++) {
                issue(i + WDEPTH);
                cp_wait<WDEPTH>();
                const uint32_t d = dst + (i < 19 ? i * 8192 : O_LAST);
                uint32_t u[8];
                lds128(u, d); lds128(u + 4, d + 2048);
                ma = babsmax(babsmax(ma, babsmax(u[0], u[1])), babsmax(u[2], u[3])); mb = babsmax(babsmax(mb, babsmax(u[4], u[5])), babsmax(u[6], u[7]));
            }
            ma = __reduce_max_sync(~0u, max(ma & 0x7fffu, (ma >> 16) & 0x7fffu)); mb = __reduce_max_sync(~0u, max(mb & 0x7fffu, (mb >> 16) & 0x7fffu));
            asm volatile("barrier.cluster.wait.aligned;" ::: "memory");
            if (lane < 3)
                asm volatile("st.async.shared::cluster.mbarrier::complete_tx::bytes.v2.b32 [%0],{%1,%2},[%3];"
                             ::"r"(mapa(sb + O_WMX + (c * 8 + w) * 8, lane)), "r"(ma), "r"(mb), "r"(mapa(sb + B_W, lane)) : "memory");
            __syncwarp();
            {
                uint32_t off[4];
                float cs[4] = {0.f, 0.f, 0.f, 0.f};
#pragma unroll
                for (int q = 0; q < 4; q++) {
                    const int g_ = (c * 2 + ((w >> 1) & 1)) * 56 + (q == 3 ? 24 : (w & 1) * 32 + q * 8), col = wg * 320 + g_, nb = col / 80;
                    off[q] = g_ < 320 && !(q == 3 && (w & 1)) ? ((nb * 512 + h * 16) * 10 + (col - nb * 80) / 8) * 32 + lane : ~0u;
                }
                const uint32_t ta = sb + O_WO + w * 8192 + (lane & 7) * 64 + (((lane >> 3) ^ (lane >> 1)) & 3) * 16;
#pragma unroll 2
                for (int i = 0; i < 16; i++) {
                    uint32_t r[4];
                    ldsm4t(r, ta + i * 512);
#pragma unroll
                    for (int q = 0; q < 4; q++) {
                        if (off[q] != ~0u) ((uint32_t*)g_wot)[off[q] + i * 320] = r[q];
                        cs[q] += fabsf(bf_lo(r[q])) + fabsf(bf_hi(r[q]));
                    }
                }
                float cm = 0.f;
#pragma unroll
                for (int q = 0; q < 4; q++) {
                    cs[q] += __shfl_xor_sync(~0u, cs[q], 1); cs[q] += __shfl_xor_sync(~0u, cs[q], 2);
                    cm = fmaxf(cm, cs[q]);
                }
                const uint32_t n1 = __reduce_max_sync(~0u, __float_as_uint(cm));
                if (lane == 0) g_co[h * 32 + c * 8 + w] = __uint_as_float(n1);
            }
            mbar_wait(sb + B_W, 0);
            uint32_t v[2];
            lds64(v, sb + O_WMX + (lane < 24 ? lane : 0) * 8);
            const bool mine = (lane >> 3) < 3 && ((lane >> 4) == 1) == (c == 2);
            ma = __reduce_max_sync(~0u, mine ? v[0] : 0u); mb = __reduce_max_sync(~0u, mine ? v[1] : 0u);
            if (c == 2) ma = mb = max(ma, mb);
            fa = __uint_as_float(ma << 16); fb = __uint_as_float(mb << 16);
            if (tid == 0) {
                if (c != 1) g_wmx[h * 3 + c] = fa;
                if (c == 0) g_wmx[h * 3 + 1] = fb;
            }
        } else {
            fa = __ldcg(g_wmx + h * 3 + (c == 2 ? 2 : 0)); fb = __ldcg(g_wmx + h * 3 + (c == 2 ? 2 : 1));
            asm volatile("barrier.cluster.wait.aligned;" ::: "memory");
        }
        if (layer == TLL) TL(49);
        float ia, ib;
        const float sa = pow2_scale(fa, 6, &ia), sc_b = pow2_scale(fb, 6, &ib);
        sl = __uint_as_float(uni(__float_as_uint(ia * ib * (0.08838834764831845f * 1.4426950408889634f))));
        const uint32_t pa = pack_bf(sa, sa), pb = pack_bf(sc_b, sc_b);
        const int ahead = layer == 0 ? 20 : WDEPTH;
        auto convert = [&](int lo) {
#pragma unroll 1
            for (int i = lo; i < lo + 10; i++) {
                issue(i + ahead);
                cp_wait<WDEPTH>();
                const uint32_t d = dst + (i < 19 ? i * 8192 : O_LAST);
                uint32_t u[8];
                lds128(u, d); lds128(u + 4, d + 2048);
#pragma unroll
                for (int q = 0; q < 8; q++)
                    asm("{.reg .b32 m,l,u; mul.rn.bf16x2 m,%0,%1; shl.b32 l,m,16; and.b32 u,m,0xffff0000; cvt.rn.f16x2.f32 %0,u,l;}" : "+r"(u[q]) : "r"(q < 4 ? pa : pb));
                sts128(d, u[0], u[1], u[2], u[3]); sts128(d + 2048, u[4], u[5], u[6], u[7]);
            }
            bar_sync(6 + wg, 128);
        };
        const uint32_t s0 = src + wg * 2048, s1 = src + 2048 - wg * 2048;
        convert(0);
#pragma unroll
        for (int i = 0; i < 10; i++) { ldsm4t(A0[i], s0 + i * 8192); ldsm4t(A1[i], s1 + i * 8192); }
        if (layer == TLL) TL(50);
        convert(10);
#pragma unroll
        for (int i = 10; i < 20; i++) { ldsm4t(A0[i], s0 + (i < 19 ? i * 8192 : O_LAST)); ldsm4t(A1[i], s1 + (i < 19 ? i * 8192 : O_LAST)); }
        if (layer == TLL) TL(53);
        bar_arrive(9, 288);
        bar_sync(4, 288);
        asm volatile("barrier.cluster.arrive.relaxed.aligned;" ::: "memory");
    }
    const uint32_t idn = (lane >> 3) == (lane & 3) ? ((lane & 4) ? 0x3c000000u : 0x3c00u) : 0u;
    float invM = g_invM0;
    char* redp = red_base() + (size_t)layer * 32 * 32768 + w * 2048 + (lane >> 4) * 1024 + ((lane >> 3) & 1) * 256 + (lane & 7) * 16;
    const uint32_t ro2 = uni((w >> 1) * 4096 + 128), rown = uni(c == 2 ? ro2 : c * 16384);
    const uint32_t L16 = lane * 16, L8 = lane * 8, L4 = lane * 4;
    const uint32_t xch0 = uni(sb + O_XCH + t0 * 1024), xch1 = uni(sb + O_XCH + t1 * 1024);
    const uint32_t qo0 = uni(sb + O_QKP + (w & 3) * 1024 + (wg ? 768 : 0)), qp0 = uni(qo0 + (wg ? 128 : 256));
    const uint32_t qo1 = uni(sb + O_QKP + (w & 3) * 1024 + (wg ? 128 : 512)), qp1 = uni(qo1 + (wg ? 256 : 128));
    const uint32_t vo1 = uni(qo1 + (wg ? -128 : 256)), vp1 = uni(qp1 + (wg ? -128 : 256));
    const uint32_t msr = uni(sb + O_MS + wg * 5376);
    const uint32_t msw = uni(msr + ((w >> 1) & 1) * 896 + (w & 1) * 512), msh = uni(msr + ((w >> 1) & 1) * 896 + 384 + (w & 1) * 2);
    const uint32_t sco = uni(sb + O_SC + c * 768 + (w & 3) * 256);
    const uint32_t woa = sb + O_WO + w * 8192 + (lane >> 4) * 512 + (lane & 7) * 64 + (((lane >> 3) ^ (lane >> 1)) & 1) * 16 + ((lane >> 2) & 1) * 32;
    const uint32_t w512 = uni(sb + w * 512), w128 = uni(sb + w * 128);
    const uint32_t pd0 = uni(mapa(sb, c == 2 ? 0 : 2) - sb), pd1 = uni(mapa(sb, c == 1 ? 0 : 1) - sb);
    const bool scw = c < 2 && w >= 4 && w <= 6;
    uint32_t sn = uni(sb + O_STG + (c == 2 ? 8192 : 0) + t1 * 1024);
    uint32_t ka = uni(sb + (w == 6 ? O_QKP + 512 : O_STG + 4096 + (w & 1) * 512));
    uint32_t vs = uni(sb + O_VM + t1 * 256);
    uint32_t va = uni(sb + O_STG + 8192 + w * 2048), vr = uni(sb + O_VM + w * 512);
    const uint32_t sn2 = uni(2 * sn - 16384), ka2 = uni(2 * ka - (w == 6 ? 0 : 16384)), vs2 = uni(2 * vs + 2048), va2 = uni(2 * va - 16384),
                   vr2 = uni(2 * vr + 2048);
    uint32_t xd = uni((uint32_t)mkdesc(sb + O_XS + wg * 20480, 512, 128, 0));
    const uint32_t xd2 = uni(2 * xd + 2560);

    uint32_t wp[2 * NPERM + 1][4];
    sfor<NPERM>([&](auto I) { constexpr int i = I; ldsm4t(wp[2 * i], woa + i * 1024); ldsm4t(wp[2 * i + 1], (woa ^ 32) + i * 1024); });
    auto wo_fetch = [&](uint32_t (&wo)[16][4], auto I) {
        constexpr int i = I;
        if constexpr (i < NPERM) {
#pragma unroll
            for (int q = 0; q < 4; q++) { wo[i][q] = wp[2 * i][q]; wo[8 + i][q] = wp[2 * i + 1][q]; }
        } else { ldsm4t(wo[i], woa + i * 1024); ldsm4t(wo[8 + i], (woa ^ 32) + i * 1024); }
    };
    if (layer == TLL) TL(32);
    float b0[16], b1[16];
    mbar_wait(sb + B_XF, 0);
    if (layer == TLL) TL(33);
    tok_issue<0, NTB>(A0, A1, b0, b1, xd, zero);
    tok_give(b0, L16, xch0);
    tok_issue<NTB, 40>(A0, A1, b0, b1, xd, zero);
    bar_sync(4, 256);
    wg_wait<0>();
    {
        uint32_t e[2][4];
        lds128_u<0>(e[0], L16, xch1); lds128_u<512>(e[1], L16, xch1);
        tok_finish(b1, e, L16, sn, idn);
    }
    sn = sn2 - sn; xd = xd2 - xd;
    bar_sync(5, 288);
    asm volatile("barrier.cluster.wait.aligned;" ::: "memory");
    if (layer == TLL) TL(34);
    mbar_wait(sb + B_XF + 8, 0);
    if (layer == TLL) TL(35);
    tok_issue<0, NTA>(A0, A1, b0, b1, xd, zero);
    uint32_t tr = clock32() - RDELAY;

#pragma unroll 1
    for (int st = 0;; st++) {
        uint4 mv[3];
        asm volatile("{.reg .pred p; .reg .b32 t;\n"
                     "mov.b32 %0,0; mov.b32 %1,0; mov.b32 %2,0; mov.b32 %3,0; mov.b32 %4,0; mov.b32 %5,0; mov.b32 %6,0; mov.b32 %7,0;\n"
                     "mov.b32 %8,0; mov.b32 %9,0; mov.b32 %10,0; mov.b32 %11,0;\n"
                     "T_LOOP: mov.u32 t,%%clock; sub.u32 t,t,%14; setp.ge.u32 p,t,%15;\n"
                     "@p ld.relaxed.gpu.global.v4.u32 {%0,%1,%2,%3},[%12]; @p ld.relaxed.gpu.global.v4.u32 {%4,%5,%6,%7},[%12+16384];\n"
                     "@p ld.relaxed.gpu.global.v4.u32 {%8,%9,%10,%11},[%13];\n"
                     "@!p bra T_LOOP;}"
                     : "=r"(mv[0].x), "=r"(mv[0].y), "=r"(mv[0].z), "=r"(mv[0].w), "=r"(mv[1].x), "=r"(mv[1].y), "=r"(mv[1].z), "=r"(mv[1].w),
                       "=r"(mv[2].x), "=r"(mv[2].y), "=r"(mv[2].z), "=r"(mv[2].w)
                     : "l"(redp), "l"(redp + ro2), "r"(tr), "n"(RDELAY) : "memory");
        STAMP(10);
        tok_issue<NTA, NTB>(A0, A1, b0, b1, xd, zero);
        tok_give(b0, L16, xch0);
        tok_issue<NTB, 40>(A0, A1, b0, b1, xd, zero);
        xd = xd2 - xd;
        STAMP(9);
        if (zero >> 30) break;
        asm volatile("{.reg .pred p; .reg .b32 a,h,t,n; .reg .b16 l,u; .reg .b64 q;\n"
                     "add.u32 a,%12,%13; add.u32 h,%12,%14; mov.u32 n,0;\n"
                     "M_LOOP:\n .pragma \"nounroll\";\n"
                     "st.shared.b32 [a],%0; st.shared.b32 [a+128],%1; st.shared.b32 [a+256],%2; mov.b32 {l,u},%3; st.shared.b16 [h],l;\n"
                     "st.shared.b32 [a+1792],%4; st.shared.b32 [a+1920],%5; st.shared.b32 [a+2048],%6; mov.b32 {l,u},%7; st.shared.b16 [h+1792],l;\n"
                     "st.shared.b32 [a+3584],%8; st.shared.b32 [a+3712],%9; st.shared.b32 [a+3840],%10; mov.b32 {l,u},%11; st.shared.b16 [h+3584],l;\n"
                     "lop3.b32 t,%3,%7,0x50000000,0x7e; lop3.b32 t,t,%11,0x50000000,0xf6; setp.gt.u32 p,t,0xffff;\n"
                     "vote.sync.any.pred p,p,-1; add.u32 n,n,1; setp.lt.and.u32 p,n,%17,p; @!p bra M_DONE;\n"
                     "ld.relaxed.gpu.global.v4.u32 {%0,%1,%2,%3},[%15]; ld.relaxed.gpu.global.v4.u32 {%4,%5,%6,%7},[%15+16384];\n"
                     "cvt.u64.u32 q,%16; add.u64 q,q,%15; ld.relaxed.gpu.global.v4.u32 {%8,%9,%10,%11},[q];\n"
                     "bra M_LOOP;\n"
                     "M_DONE:}"
                     : "+r"(mv[0].x), "+r"(mv[0].y), "+r"(mv[0].z), "+r"(mv[0].w), "+r"(mv[1].x), "+r"(mv[1].y), "+r"(mv[1].z), "+r"(mv[1].w),
                       "+r"(mv[2].x), "+r"(mv[2].y), "+r"(mv[2].z), "+r"(mv[2].w)
                     : "r"(L4), "r"(msw), "r"(msh), "l"(redp), "r"(ro2), "n"(SPIN_LIM) : "memory");
        bar_sync(3, 256);
        STAMP(0);
        uint32_t e[2][4];
        float f1[4];
        {
            uint32_t b[10][4];
            float acc[4][4];
#pragma unroll
            for (int i = 0; i < 4; i++) acc[i][0] = acc[i][1] = acc[i][2] = acc[i][3] = 0.f;
            auto ld = [&](auto I) { constexpr int i = I; ldsm4t_u<i * 512>(b[i], L16, msr); };
            auto mm = [&](auto I) {
                constexpr int i = I;
                mma_f16(acc[0], A0[2 * i], b[i][0], b[i][1]); mma_f16(acc[2], A1[2 * i], b[i][0], b[i][1]);
                mma_f16(acc[1], A0[2 * i + 1], b[i][2], b[i][3]); mma_f16(acc[3], A1[2 * i + 1], b[i][2], b[i][3]);
            };
            ld(IC<0>()); ld(IC<1>()); ld(IC<2>()); ld(IC<3>());
            sts32_u<O_MX>(L4, w128,
                          habsmax(habsmax(habsmax(habsmax(mv[0].x, mv[0].y), habsmax(mv[0].z, mv[1].x)), habsmax(habsmax(mv[1].y, mv[1].z), mv[2].x)),
                                  habsmax(habsmax(mv[2].y, mv[2].z), habsmax(habsmax(mv[0].w, mv[1].w), mv[2].w) & 0xffffu)));
            wg_wait<0>();
            ld(IC<4>()); mm(IC<0>()); ld(IC<5>()); mm(IC<1>()); ld(IC<6>()); mm(IC<2>());
            ld(IC<7>()); mm(IC<3>()); ld(IC<8>()); mm(IC<4>()); ld(IC<9>()); mm(IC<5>());
            lds128_u<0>(e[0], L16, xch1); lds128_u<512>(e[1], L16, xch1);
            mm(IC<6>()); mm(IC<7>()); mm(IC<8>()); mm(IC<9>());
            const uint32_t u0 = pack_bf((acc[0][0] + acc[1][0]) * invM, (acc[0][1] + acc[1][1]) * invM);
            const uint32_t u1 = pack_bf((acc[0][2] + acc[1][2]) * invM, (acc[0][3] + acc[1][3]) * invM);
#pragma unroll
            for (int i = 0; i < 4; i++) f1[i] = (acc[2][i] + acc[3][i]) * invM;
            sts32_u<0>(L4, qo0, u0); sts32_u<0>(L4, qp0, u1); sts32_u<0>(L4, qo1, pack_bf(f1[0], f1[1])); sts32_u<0>(L4, qp1, pack_bf(f1[2], f1[3]));
        }
        STAMP(1);
        bar_sync(1, 320);
        if (__builtin_expect(scw, 1)) {
            float a[4][4];
#pragma unroll
            for (int i = 0; i < 4; i++) a[i][0] = a[i][1] = a[i][2] = a[i][3] = 0.f;
            uint32_t q[4][4], k[4][4];
            sfor<4>([&](auto I) {
                constexpr int i = I;
                ldsm4t_u<O_QKP + i * 1024>(q[i], L16, sb); ldsm4t_u<i * 1024>(k[i], L16, ka);
            });
#pragma unroll
            for (int i = 0; i < 4; i++) {
                mma_bf(a[i & 1], q[i][0], q[i][1], q[i][2], q[i][3], k[i][0], k[i][1]);
                mma_bf(a[2 + (i & 1)], q[i][0], q[i][1], q[i][2], q[i][3], k[i][2], k[i][3]);
            }
            const float mk = w == 6 ? 1.f : 0.f;
            const float x0 = (a[0][0] + a[0][2]) + (a[1][0] + a[1][2]), x1 = (a[0][1] + a[0][3]) + (a[1][1] + a[1][3]);
            const float y0 = (a[2][0] + a[2][2]) + (a[3][0] + a[3][2]), y1 = (a[2][1] + a[2][3]) + (a[3][1] + a[3][3]);
            st_share2(L8, sco, sb + B_S, pd0, pd1, pack_bf(fmaf(y0, mk, x0) * sl, fmaf(y1, mk, x1) * sl), pack_bf(y0 * sl, y1 * sl));
        }
        if (c == 2) {
            const uint32_t x = lds32_u<0>(L4, vo1), y = lds32_u<0>(L4, vp1);
            st_share2(L8, vs, sb + B_S, pd0, pd1, pack_bf(f1[0] + bf_lo(x), f1[1] + bf_hi(x)), pack_bf(f1[2] + bf_lo(y), f1[3] + bf_hi(y)));
        }
        STAMP(3);
        if (st == NSEG - 1) break;
        tok_finish(b1, e, L16, sn, idn);
        redp += (st & 1) ? 32768 - 512 : 512;
        if (wg == 0) {
            uint32_t wo[16][4], vx[2][2][4], vm[2][2];
            ldsm4_u<0>(vx[0][0], L16, va); ldsm4_u<512>(vx[0][1], L16, va); ldsm4_u<1024>(vx[1][0], L16, va); ldsm4_u<1536>(vx[1][1], L16, va);
            sfor<NWO0>([&](auto I) { wo_fetch(wo, I); });
            mbar_wait(sb + B_S, st & 1);
            STAMP(4);
            uint32_t s[5];
            {
                uint32_t p[2][5];
                sfor<2>([&](auto R) {
                    constexpr int r = R;
                    lds64_u<O_SC + r * 768>(p[r], L8, sb); lds64_u<O_SC + r * 768 + 256>(p[r] + 2, L8, sb); p[r][4] = lds32_u<O_SC + r * 768 + 512>(L8, sb);
                });
#pragma unroll
                for (int j = 0; j < 5; j++) s[j] = badd(p[0][j], p[1][j]);
            }
            lds64_u<0>(vm[0], L8, vr); lds64_u<256>(vm[1], L8, vr);
            uint32_t mm = bmax(bmax(bmax(s[0], s[1]), bmax(s[2], s[3])), s[4]);
            mm = bmax(bmax(mm, __shfl_xor_sync(~0u, mm, 1)), bmax(__shfl_xor_sync(~0u, mm, 2), __shfl_xor_sync(~0u, mm, 3)));
            const float m = fmaxf(bf_lo(mm), bf_hi(mm));
            float o0[4] = {0.f, 0.f, 0.f, 0.f}, o1[4] = {0.f, 0.f, 0.f, 0.f}, d[10];
#pragma unroll
            for (int j = 0; j < 5; j++) { d[2 * j] = bf_lo(s[j]) - m; d[2 * j + 1] = bf_hi(s[j]) - m; }
#pragma unroll
            for (int j = 0; j < 10; j++) d[(j + 8) % 10] = ex2(d[(j + 8) % 10]);
            float sum = ((d[8] + d[9]) + (d[0] + d[1])) + ((d[2] + d[3]) + (d[4] + d[5])) + (d[6] + d[7]);
            const uint32_t p4 = pack_bf(d[8], d[9]), p0 = pack_bf(d[0], d[1]), p1 = pack_bf(d[2], d[3]), p2 = pack_bf(d[4], d[5]), p3 = pack_bf(d[6], d[7]);
            mma_bf8(o0, vm[0][0], vm[0][1], p4);
            mma_bf8(o1, vm[1][0], vm[1][1], p4);
            mma_bf(o0, vx[0][0][0], vx[0][0][1], vx[0][0][2], vx[0][0][3], p0, p1);
            mma_bf(o1, vx[1][0][0], vx[1][0][1], vx[1][0][2], vx[1][0][3], p0, p1);
            mma_bf(o0, vx[0][1][0], vx[0][1][1], vx[0][1][2], vx[0][1][3], p2, p3);
            mma_bf(o1, vx[1][1][0], vx[1][1][1], vx[1][1][2], vx[1][1][3], p2, p3);
            sfor<NWO0B - NWO0>([&](auto I) { constexpr int i = I; wo_fetch(wo, IC<NWO0 + i>()); });
            sum += __shfl_xor_sync(~0u, sum, 1);
            sum += __shfl_xor_sync(~0u, sum, 2);
            sts32_u<O_OS>(L4, w512, pack_bf(o0[0], o0[1])); sts32_u<O_OS + 128>(L4, w512, pack_bf(o0[2], o0[3]));
            sts32_u<O_OS + 256>(L4, w512, pack_bf(o1[0], o1[1])); sts32_u<O_OS + 384>(L4, w512, pack_bf(o1[2], o1[3]));
            sts32_u<O_SUM>(lane & 28, sb, __float_as_uint(sum));
            STAMP(5);
            invM = mem_out<NWO0B>(sb, L16, L8, wo, woa, redp + rown, w & 1);
            tr = clock32();

        } else {
            uint32_t wo[16][4];
            sfor<NWO1>([&](auto I) { wo_fetch(wo, I); });
            invM = mem_out<NWO1>(sb, L16, L8, wo, woa, redp + rown, w & 1);
            tr = clock32();

        }
        STAMP(7);
        tok_issue<0, NTA>(A0, A1, b0, b1, xd, zero);
        sn = sn2 - sn; ka = ka2 - ka; vs = vs2 - vs; va = va2 - va; vr = vr2 - vr;
        STAMP(8);
    }
    if (layer == TLL) TL(40);
    bar_arrive(8, 320);
    tid = read_tid(); lane = tid & 31;
    float acc[40];
    const int nc = c == 2 ? 10 : 11;
    const int mb = 28 + (h >> 3), nj = c == 2 ? 1 : 2;
    uint32_t rv[2][2];
    const size_t go = ((size_t)(mb * 64 + (w & 3) * 16 + (lane >> 2)) * 640 + (h & 7) * 80 + (wg * 5 + c * 2) * 8 + (lane & 3) * 2) >> 1;
#pragma unroll
    for (int u = 0; u < 4; u++) rv[u >> 1][u & 1] = (u >> 1) < nj ? __ldcg((const uint32_t*)res + go + (u >> 1) * 4 + (u & 1) * 2560) : 0u;
#pragma unroll 1
    for (int k = 0; k < nc; k++) {
        mbar_wait(sb + T_FB + (k % 7) * 8, k >= 7);
        mbar_wait(sb + T_FA + (k & 3) * 8, (k >> 2) & 1);
        if (layer == TLL && k == 0) TL(41);
        const uint64_t da = mkdesc(sb + O_MS + (k & 3) * 16384 + wg * 8192, 1024, 128, 0), db = mkdesc(sb + tail_b(k) + wg * 10240, 1280, 128, 0);
        wg_fence();
#pragma unroll
        for (int q = 0; q < 4; q++) wg_n80_ss(acc, da + q * 128, db + q * 160, k | q);
        wg_commit();
        if (k > 0) {
            wg_wait<1>();
            if (lane == 0) { mbar_arrive(sb + T_EA + ((k - 1) & 3) * 8); if (k <= 4) mbar_arrive(sb + T_EB + (k - 1) * 8); }
        }
    }
    if (layer == TLL) TL(52);
    wg_wait<0>();
    asm volatile("barrier.cluster.arrive.relaxed.aligned; barrier.cluster.wait.aligned;" ::: "memory");
    const uint32_t ra = sb + O_XS + tid * 16, rb = sb + O_MS + tid * 16;
#pragma unroll
    for (int j = 0; j < 5; j++) {
        const float* q = acc + 4 * j;
        sts128(rb + j * 4096, __float_as_uint(wg ? q[0] : q[20]), __float_as_uint(wg ? q[1] : q[21]), __float_as_uint(wg ? q[2] : q[22]), __float_as_uint(wg ? q[3] : q[23]));
    }
    bar_sync(4, 256);
#pragma unroll
    for (int j = 0; j < 5; j++) {
        const float* q = acc + 4 * j;
        uint32_t p[4];
        lds128(p, sb + O_MS + (tid ^ 128) * 16 + j * 4096);
        asm volatile("st.async.shared::cluster.mbarrier::complete_tx::bytes.v4.f32 [%0],{%1,%2,%3,%4},[%5];" ::"r"(mapa(ra + c * 8192 + (j & 1) * 4096, j >> 1)),
                     "f"((wg ? q[20] : q[0]) + __uint_as_float(p[0])), "f"((wg ? q[21] : q[1]) + __uint_as_float(p[1])),
                     "f"((wg ? q[22] : q[2]) + __uint_as_float(p[2])), "f"((wg ? q[23] : q[3]) + __uint_as_float(p[3])), "r"(mapa(sb + T_RED, j >> 1)) : "memory");
    }
    mbar_wait(sb + T_RED, 0);
#pragma unroll 1
    for (int u = 0; u < nj; u++) {
        uint32_t p[3][4];
#pragma unroll
        for (int q = 0; q < 3; q++) lds128(p[q], ra + q * 8192 + u * 4096);
        float y[4];
#pragma unroll
        for (int i = 0; i < 4; i++) y[i] = __uint_as_float(p[0][i]) + __uint_as_float(p[1][i]) + __uint_as_float(p[2][i]);
        ((uint32_t*)out)[go + u * 4] = bfma(pack_bf(y[0], y[1]), 0x3f803f80u, u ? rv[1][0] : rv[0][0]);
        ((uint32_t*)out)[go + u * 4 + 2560] = bfma(pack_bf(y[2], y[3]), 0x3f803f80u, u ? rv[1][1] : rv[0][1]);
    }
    __syncwarp();
    if (layer == 0 && lane == 0) red_release(g_flag + F_R + mb);
    TL(layer == 0 ? 15 : 29);
    asm volatile("barrier.cluster.arrive.relaxed.aligned; barrier.cluster.wait.aligned;" ::: "memory");
}

__device__ __forceinline__ void tail_load_b(const uint32_t sb, const int h, const int c, const int k) {
    mbar_expect(sb + T_FB + (k % 7) * 8, 20480);
    bulk_g2s(sb + tail_b(k), (const char*)g_wot + (size_t)((h & 7) * GNC + c * 11 + k) * 20480, 20480, sb + T_FB + (k % 7) * 8);
}
__device__ __forceinline__ void chain_aux(const uint32_t sb, const int c, const int h, const int layer, const int nact) {
    const int tid = read_tid(), w = __shfl_sync(~0u, tid >> 5, 0), lane = tid & 31;
    if (w == 8) {
        mbar_init(sb + O_BAR + lane * 8, lane == 2 ? (c == 2 ? 9 : 4) : (lane >= 16 && lane < 20) || (lane >= 27 && lane < 31) ? 8 : 1);
        asm volatile("fence.mbarrier_init.release.cluster;" ::: "memory");
        fence_async_smem();
        __syncwarp();
    }
    {
        uint4* z = (uint4*)red_base() + layer * 65536;
#pragma unroll 1
        for (int i = blockIdx.x * 128 + tid - 256; i < 65536; i += 96 * 128)
            if (i >= 2048 || (i & 32)) z[i] = make_uint4(0, 0, 0, 0);
    }
    if (w == 8 && lane == 0) {
        mbar_expect(sb + B_S, s_tx(c));
        mbar_expect(sb + B_W, 192);
        mbar_expect(sb + T_RED, (c == 2 ? 1 : 2) * 3 * 4096);
        if (layer == 1) prefetch_l2(red_base() + 32 * 32768 + blockIdx.x * 1024, 1024);
        if (layer == 0) wait_flag<400>(g_ready, NSETUP);
    }
    __syncwarp();
    cluster_sync_full();
    asm volatile("barrier.cluster.arrive.relaxed.aligned;" ::: "memory");
    pdl_wait();
    if (w == 11 && lane == 0) red_relaxed(g_flag + F_X + layer * 128 + 65);
    Flag* flag = g_flag + layer * NSEG * 32 + h;
    const Flag* xflag = g_flag + F_X + layer * 128;
    char* const it0 = g_item + (size_t)h * 32768;
    if (w == 8) {
#pragma unroll 1
        for (int n = 0; n < 3; n++) {
            wait_flag<100>(xflag + (n >> 1), 4);
            fence_async_glb();
            if (n == 0) { bar_sync(4, 288); fence_async_smem(); }
            if (lane == 0 && n < 2) {
                mbar_expect(sb + B_XF + n * 8, 40960);
                bulk_g2s(sb + O_XS + n * 40960, (const char*)g_xn + n * 40960, 40960, sb + B_XF + n * 8);
            }
            __syncwarp();
        }
#pragma unroll 1
        for (int n = 0; n < NSEG; n++) {
            const int np = n & 1;
            if (n == 0) { wait_flag<100>(g_flag + F_W + layer * 128, 96); bar_sync(5, 288); } else bar_sync(2, 352);
            if (n == 1) TL(12 + layer * 14);
            if (n == 63) TL(13 + layer * 14);
            if (lane == 0 && n == NSEG - 1) mbar_arrive(sb + B_STG + 8);
            if (lane == 0 && n < NSEG - 1) {
                const uint32_t vs = sb + O_STG + 8192 - np * 16384, vb = sb + B_VX + np * 8;
                if (c == 2) {
                    fence_async_smem();
                    bulk_s2s(mapa(vs, 0), vs, 8192, mapa(vb, 0));
                    bulk_s2s(mapa(vs, 1), vs, 8192, mapa(vb, 1));
                } else mbar_expect(vb, 8192);
                if (n == 0) { mbar_expect(sb + B_XF, 40960); bulk_g2s(sb + O_XS, (const char*)g_xn + 2 * 40960, 40960, sb + B_XF); }
                if (n == h * 3 + c && !np && n + 6 < NSEG) prefetch_l2(red_base() + (size_t)(layer * 32 + (n >> 1) + 3) * 32768, 32768);
            }
            __syncwarp();
        }
    } else if (w == 11) {
        float cvo;
        {
            auto max8 = [&](const float* p) {
                const float4 u = ((const float4*)p)[0], v = ((const float4*)p)[1];
                return fmaxf(fmaxf(fmaxf(u.x, u.y), fmaxf(u.z, u.w)), fmaxf(fmaxf(v.x, v.y), fmaxf(v.z, v.w)));
            };
            wait_flag<300>(g_flag + F_W + layer * 128, 96);
            const float* pc = g_co + lane * 32;
            float a = 640.f * __ldcg(g_wmx + lane * 3 + 2), o = fmaxf(fmaxf(max8(pc), max8(pc + 8)), max8(pc + 16));
#pragma unroll 1
            for (int s = 16; s; s >>= 1) { a = fmaxf(a, __shfl_xor_sync(~0u, a, s)); o += __shfl_xor_sync(~0u, o, s); }
            cvo = a * o * 2.f;
        }
        float invM = g_invM0;
        float iv;
        weight_scale(h, 2, &iv);
        const uint32_t L16 = sb + lane * 16 + O_MX;
#pragma unroll 1
        for (int st = 0; st < NSEG; st++) {
            bar_sync(1, 320);
            if (st == NSEG - 1) break;
            if (lane == 0) mbar_arrive(sb + B_STG + (st & 1) * 8);
            uint32_t u[2][4];
            lds128(u[0], L16); lds128(u[1], L16 + 512);
            uint32_t mx = habsmax(habsmax(habsmax(u[0][0], u[0][1]), habsmax(u[0][2], u[0][3])), habsmax(habsmax(u[1][0], u[1][1]), habsmax(u[1][2], u[1][3])));
            mx = __reduce_max_sync(~0u, max(mx & 0x7fffu, (mx >> 16) & 0x7fffu));
            const float bound = fmaxf(__half2float(__ushort_as_half((unsigned short)mx)) * invM, 25.5f) * cvo;
            const float sc = pow2_scale(bound, 15, &invM);
            sts64(sb + O_SCL, __float_as_uint(sc * iv), __float_as_uint(invM));
            bar_arrive(2, 352);
        }
    } else if (w == 10) {
        bar_sync(9, 288);
        if (lane == 0) red_release(g_flag + F_W + layer * 128);
        if (lane == 0) {
#pragma unroll 1
            for (int n = 0; n < NSEG; n++) {
                mbar_sleep(sb + B_STG + (n & 1) * 8, (n >> 1) & 1);
                fence_async_smem();
                const uint32_t stg = sb + O_STG - (n & 1) * 16384;
                char* it = it0 + (size_t)(n % RING) * 32 * 32768;
                bulk_s2g(it + c * 8192, stg + (c == 2 ? 8192 : 0), 8192);
                bulk_commit();
                if (n + 1 >= RING && n + 1 < NSEG) wait_flag(flag - (RING - 1) * 32, 7);
                bulk_wait0();
                mbar_arrive(sb + B_FREE + (n & 1) * 8);
                fence_async_glb();
                red_relaxed(flag);
                flag += 32;
            }
        }
    } else {
        bool allx = false;
#pragma unroll 1
        for (int st = 0; st < NSEG; st++) {
            const int par = st & 1;
            char* const it = it0 + (size_t)(st % RING) * 32 * 32768;
            if (lane == 0 && !allx && st + 3 < NSEG) {
                allx = ld_acquire(xflag + 64) >= nact;
                if (!allx) wait_flag(st + 4 < NSEG ? xflag + ((st + 3) >> 1) : xflag + 64, st + 4 < NSEG ? 4 : nact);
                fence_async_glb();
            }
            __syncwarp();
            if (st < NSEG - 1 && c < 2) mbar_sleep(sb + B_VX + par * 8, (st >> 1) & 1);
            if (st < NSEG - 2) mbar_sleep(sb + B_XF + par * 8, ((st >> 1) + 1) & 1);
            bar_sync(1, 320);
            if (lane == 0 && st + 3 < NSEG) {
                mbar_expect(sb + B_XF + (par ^ 1) * 8, 40960);
                bulk_g2s_last(sb + O_XS + (par ^ 1) * 40960, (const char*)g_xn + (size_t)(st + 3) * 40960, 40960, sb + B_XF + (par ^ 1) * 8);
            } else if (lane == 0 && st < NSEG - 1) {
                tail_load_b(sb, h, c, (par ^ 1) * 2); tail_load_b(sb, h, c, (par ^ 1) * 2 + 1);
            }
            __syncwarp();
            if (lane == 0 && c < 2) {
                fence_async_smem();
#pragma unroll 1
                for (int i = 0; i < 4; i++) bulk_s2g(it + 24576 + (c * 4 + i) * 512, sb + O_QKP + i * 1024 + 512, 512);
                bulk_commit();
                asm volatile("cp.async.bulk.wait_group.read 0;" ::: "memory");
            }
            __syncwarp();
            if (st < NSEG - 1) bar_arrive(2, 352);
            mbar_sleep(sb + B_S, par);
            __syncwarp();
            if (lane == 0) {
                if (st < NSEG - 1) mbar_expect(sb + B_S, s_tx(c));
                if (c == 2) { fence_async_smem(); bulk_s2g(it + 28672, sb + O_VM + par * 2048, 2048); bulk_commit(); }
                if (st == NSEG - 1) asm volatile("cp.async.bulk.wait_group.read 0;" ::: "memory");
            }
            __syncwarp();
            if (st == NSEG - 1) bar_arrive(8, 320);
            if (lane == 0) { bulk_wait0(); fence_async_glb(); red_relaxed(flag); }
            __syncwarp();
            mbar_sleep(sb + B_FREE + par * 8, (st >> 1) & 1);
            flag += 32;
        }
    }
    __syncwarp();
    const int nc = c == 2 ? 10 : 11;
    if (w == 10) {
        bar_sync(8, 320);
        if (lane == 0) {
            if (layer == 1 && blockIdx.x == 0) g_ready[0].v = 0;
            fence_async_smem();
            __nanosleep(TDELAY);
            wait_flag(xflag + 64, nact);
            wait_flag<50>(g_flag + F_O + layer * 32 + 28 + (h >> 3), 64);
            fence_async_glb();
#pragma unroll 1
            for (int k = 0; k < nc; k++) {
                if (k >= 4) mbar_sleep(sb + T_EA + (k & 3) * 8, ((k >> 2) - 1) & 1);
                mbar_expect(sb + T_FA + (k & 3) * 8, 16384);
                bulk_g2s_last(sb + O_MS + (k & 3) * 16384, (const char*)g_O + (size_t)((28 + (h >> 3)) * GNC + c * 11 + k) * 16384, 16384, sb + T_FA + (k & 3) * 8);
            }
        }
    } else if (w == 9 && lane == 0) {
        __nanosleep(TDELAY);
#pragma unroll 1
        for (int k = 4; k < nc; k++) {
            if (k >= 7) mbar_sleep(sb + T_EB + (k - 7) * 8, 0);
            tail_load_b(sb, h, c, k);
        }
    }
    __syncwarp();
    asm volatile("barrier.cluster.wait.aligned;" ::: "memory");
    asm volatile("barrier.cluster.arrive.relaxed.aligned; barrier.cluster.wait.aligned;" ::: "memory");
    asm volatile("barrier.cluster.arrive.relaxed.aligned; barrier.cluster.wait.aligned;" ::: "memory");
}

constexpr int RI_A = 0, RI_TAB = 81920, RI_STG = RI_TAB + 82 * 768;
constexpr int RI_RES = RI_STG + 25600, RI_ST = RI_RES + 2 * 64 * 336;
constexpr int HB_A = G_BAR + 64, HB_AFREE = HB_A + 32, HB_LN = HB_A + 40, HB_FULL = HB_A + 64, HB_DONE = HB_FULL + 48, HB_FREE = HB_DONE + 48;
constexpr int HP_SMEM = HB_FREE + 48;
static_assert(G_BAR >= RI_ST + 2048, "helper shared-memory map");
#define IDL 280
#define ITEM_NS 60
#define PFW_AT 28
#define PFW_NS 150
__device__ __forceinline__ void helper_aux(const uint32_t sb, const int j, const int nh, const int na, const int nbh, const int layer, const bf16* Wq,
                                           const bf16* Wk, const bf16* Wv, const bf16* Wo) {
    const int w = threadIdx.x >> 5, lane = threadIdx.x & 31, p = w - 8;
    if (lane == 0 && j < (nh & ~3)) {
        int n = 0;
        for (int a = j >> 2; a < 32; a += nh >> 2, n++) {
            if (n == 0) continue;
            mbar_wait(sb + HB_AFREE, (n - 1) & 1);
            mbar_expect(sb + HB_A + p * 8, 20480);
            bulk_g2s_last(sb + RI_A + p * 20480, (const char*)g_YT + (size_t)a * 81920 + p * 20480, 20480, sb + HB_A + p * 8);
            if (p == 0) { mbar_wait(sb + HB_LN, (n - 1) & 1); red_release(g_flag + F_X + layer * 128 + a - (nh >> 2)); }
        }
        if (p == 0) { mbar_wait(sb + HB_LN, (n - 1) & 1); red_release(g_flag + F_X + layer * 128 + (j >> 2) + (n - 1) * (nh >> 2)); }
    }
    __syncwarp();
    if (layer == 0 && w == 8 && lane == 0) wait_flag<400>(g_flag + F_W, 96);
    __syncwarp();
    bar_sync(3, 384);
    if (p == 3 && lane == 0 && j < (nh & ~3)) red_release(g_flag + F_X + layer * 128 + 64);
    fence_async_smem();
    Flag* oflag = g_flag + F_O + layer * 32;
    if (j < na) {
        int sl = p & 1, ph = 1;
        for (int idx = j + (p & 1) * na; idx < NSEG * 32 && p >= 2 && lane == 0; idx += 2 * na) {
            mbar_wait(sb + HB_DONE + sl * 8, ph ^ 1);
            mbar_arrive(sb + HB_FREE + sl * 8);
            red_release(oflag + (idx >> 6));
            atomicAdd(&g_flag[layer * NSEG * 32 + idx].v, 1u);
            sl += 2;
            if (sl >= 6) { sl -= 6; ph ^= 1; }
        }
        for (int idx = j + p * na; idx < NSEG * 32 && p < 2 && lane == 0; idx += 2 * na) {
            mbar_wait(sb + HB_FREE + sl * 8, ph);
            wait_flag<ITEM_NS>(g_flag + layer * NSEG * 32 + idx, 6);
            fence_async_glb();
            if (idx < (NSEG - 2) * 32) __nanosleep(IDL);
            mbar_expect(sb + HB_FULL + sl * 8, 30720);
            bulk_g2s(sb + sl * 30720, g_item + (size_t)(idx % (RING * 32)) * 32768, 30720, sb + HB_FULL + sl * 8);
            sl += 2;
            if (sl >= 6) { sl -= 6; ph ^= 1; }
        }
    } else if (lane == 0 && p == 3) {
        if (layer == 0) {
            wait_flag<1000>(oflag + PFW_AT, 64);
            const int np = nh - na;
#pragma unroll 1
            for (int i = j - na; i < 1280; i += np) {
                const bf16* W = i < 320 ? Wq : i < 640 ? Wk : i < 960 ? Wv : Wo;
                prefetch_l2((const char*)W + (size_t)(i % 320) * 16384, 16384);
                __nanosleep(PFW_NS);
            }
#pragma unroll 1
            for (int i = j - na; i < 205; i += np) {
                const char* p_ = i < 160 ? (const char*)g_Wf + i * 16384 : i < 165 ? (const char*)g_stat + (i - 144) * 16384
                               : i < 167 ? (const char*)g_ctab + (i - 165) * 8192 : (const char*)(g_flag + NFLAG) - (i - 166) * 16384;
                prefetch_l2(p_, 16384);
                __nanosleep(PFW_NS);
            }
            if (j - na < 16) prefetch_l2(g_rtab + (j - na) * (RF_A / 4), RF_A / 4);
#pragma unroll 1
            for (int i = j - na; i < 130; i += np) { prefetch_l2((const char*)g_xb + i * 16384, 16384); __nanosleep(PFW_NS); }
        }
    } else if (lane == 0) {
        if (p == 2) wait_flag<500>(g_flag + F_X + layer * 128 + 64, nh & ~3);
        int c0 = 0;
        for (int mb = (j - na) >> 3; mb < nbh; mb += (nh - na) >> 3, c0 += GNC) {
            if (p < 2) wait_flag<300>(oflag + 2 * mb + p, 64);
            fence_async_glb();
            oproj_load(sb, p, mb, (j - na) & 7, c0, nh - na < 24 ? 0 : mb == nbh - 1 ? GPACE2 : GPACE);
        }
    }
}
__device__ __forceinline__ void helper_mma(char* sm, const int jh, const int nh, const int na, const int nbh, const int layer, const bf16* res, bf16* x,
                                           bf16* out) {
    const uint32_t sb = smem_u32(sm);
    const int tid = threadIdx.x, w = tid >> 5, lane = tid & 31, g = lane >> 2, t = lane & 3;
    const bool act = jh < (nh & ~3);
    const int j4 = jh & 3;
    const int fr = tid & 63, rg = w >> 1;
    auto chunk0 = [&](int u) { return u == 0 ? 5 * j4 : u == 1 ? 75 - 5 * j4 : u == 2 ? 40 + 5 * j4 : 35 - 5 * j4; };
    const int gr = tid / 20, gq_ = tid - gr * 20, go = gr * 80 + chunk0(gq_ / 5) + gq_ % 5;
    const uint32_t gs = sb + RI_RES + gr * 336 + gq_ * 16;
    auto residual = [&](int a, int n) {
#pragma unroll 1
        for (int r = 0; r < 64 - gr && tid < 240 && a < 32; r += 12) cp_async16(gs + (n & 1) * 21504 + r * 336, (const uint4*)res + (a * 64 + r) * 80 + go);
        cp_commit();
    };
    if (act) {
        if (tid < 240) {
            const int k0 = tid / 48, n = tid - k0 * 48;
            const float d = (float)(40 * j4 + n), amp = 2.f * 0.03952847075210474f;
#pragma unroll 4
            for (int u = 0; u < 16; u++)
                *(uint4*)(sm + RI_TAB + (tid + u * 240) * 16) = cos_row8(fmaf((float)((k0 + (u & 3) * 5) * 16 + ((u >> 2) & 1)), d, (float)((u & 8) * 20)), 2.f * d, amp);
            if (tid < 96) *(uint4*)(sm + RI_TAB + (3840 + tid) * 16) = make_uint4(k0 == 0 ? pack_h((n & 1) ? -amp : amp, 0.f) : 0u, 0, 0, 0);
        }
        fence_async_smem();
        residual(jh >> 2, 0);
    }
    bar_sync(1, 384);
    if (layer == TLL) TL(36);
    if (act) {
        const float4 wm = ((const float4*)g_wmax)[lane];
        const int wg = w >> 2;
        int n = 0;
#pragma unroll 1
        for (int a = jh >> 2; a < 32; a += nh >> 2, n++) {
            float acc[2][24];
            uint64_t da = mkdesc(sb + RI_A + wg * 40960, 1024, 1024, 1), db = mkdesc(sb + RI_TAB + wg * 30720, 768, 128, 0);
#pragma unroll
            for (int gq = 0; gq < 2; gq++) {
                mbar_wait(sb + HB_A + (wg * 2 + gq) * 8, n & 1);
                if (layer == TLL && n == TLN && gq == 0) TL(45);
                wg_fence();
#pragma unroll 5
                for (int k = 0; k < 10; k++) { wg_n48_ss_ta(acc[gq], da, db, k); da += 128; db += 96; }
                wg_commit();
            }
            if (wg == 0) {
                mbar_wait(sb + HB_A + 16, n & 1);
                wg_fence();
                wg_n48_ss_ta(acc[0], da, db + 20 * 96, 1);
                wg_commit();
            }
            float inv;
            pow2_scale(__uint_as_float(__reduce_max_sync(~0u, __float_as_uint(fmaxf(fmaxf(wm.x, wm.y), fmaxf(wm.z, wm.w))))), 0, &inv);
            const uint32_t ysc = pack_bf(inv, inv);
            wg_wait<0>();
            if (layer == TLL && n == TLN) TL(46);
            if (lane == 0) mbar_arrive(sb + HB_AFREE);
            const uint32_t ad = sb + RI_STG + ((w & 3) * 16 + (lane & 15)) * 400 + (lane >> 4) * 96 + wg * 192;
#pragma unroll
            for (int q = 0; q < 6; q++) {
                const float *e = acc[0] + q * 4, *o = acc[1] + q * 4;
                stsm4(ad + q * 16, pack_h(e[0] + o[0], e[1] + o[1]), pack_h(e[2] + o[2], e[3] + o[3]), pack_h(e[0] - o[0], e[1] - o[1]), pack_h(e[2] - o[2], e[3] - o[3]));
            }
            cp_wait<0>();
            bar_sync(4, 256);
            const uint32_t xa = sb + RI_RES + (n & 1) * 21504 + fr * 336 + rg * 80, sg = (rg & 1) ? 0xbc00bc00u : 0x3c003c00u;
            float sum = 0.f, sq = 0.f;
            uint32_t ya = sb + RI_STG + fr * 400 + (rg >> 1) * 96 + ((rg & 1) ? 64 : 0), carry;
            asm("fma.rn.f16x2 %0,%1,%2,%3;" : "=r"(carry) : "r"(lds32(ya + 208)), "r"(sg), "r"(lds32(ya + 16)));
#pragma unroll 1
            for (int ch = 0; ch < 5; ch++, ya += (rg & 1) ? -16 : 16) {
                uint32_t y[4], z[4], xr[4];
                lds128(y, ya); lds128(z, ya + 192); lds128(xr, xa + ch * 16);
#pragma unroll
                for (int q = 0; q < 4; q++) asm("fma.rn.f16x2 %0,%1,%2,%0;" : "+r"(y[q]) : "r"(z[q]), "r"(sg));
                if (rg & 1) {
                    const uint32_t y0 = y[0], y1 = y[1];
                    y[0] = __byte_perm(carry, y[3], 0x7610); y[1] = __byte_perm(y[3], y[2], 0x7610);
                    y[3] = __byte_perm(y1, y0, 0x7610); y[2] = __byte_perm(y[2], y1, 0x7610);
                    carry = y0;
                }
#pragma unroll
                for (int q = 0; q < 4; q++) {
                    const float2 yf = __half22float2(*(const __half2*)&y[q]);
                    xr[q] = bfma(pack_bf(yf.x, yf.y), ysc, xr[q]);
                    const float e = bf_lo(xr[q]), f = bf_hi(xr[q]);
                    sum += e + f; sq = fmaf(e, e, fmaf(f, f, sq));
                }
                sts128(xa + ch * 16, xr[0], xr[1], xr[2], xr[3]);
            }
            uint2* stat = g_stat + (size_t)(layer * 32 + a) * 1024 + rg * 64 + fr;
            asm volatile("st.relaxed.gpu.global.v2.u32 [%0],{%1,%2};" ::"l"(stat + j4 * 256), "r"(__float_as_uint(sum)), "r"(__float_as_uint(sq) | 0x80000000u) : "memory");
            if (layer == TLL && n == TLN) TL(47);
            uint32_t s0[3], s1[3];
            int lim = 0;
            do {
#pragma unroll
                for (int q = 0; q < 3; q++)
                    asm volatile("ld.relaxed.gpu.global.v2.u32 {%0,%1},[%2];" : "=r"(s0[q]), "=r"(s1[q]) : "l"(stat + ((j4 + 1 + q) & 3) * 256) : "memory");
            } while (__any_sync(~0u, (int)(s1[0] & s1[1] & s1[2]) >= 0) && ++lim < SPIN_LIM);
#pragma unroll
            for (int q = 0; q < 3; q++) { sum += __uint_as_float(s0[q]); sq -= __uint_as_float(s1[q]); }
            sts64(sb + RI_ST + tid * 8, __float_as_uint(sum), __float_as_uint(sq));
            bar_sync(4, 256);
            if (layer == TLL && n == TLN) TL(48);
#pragma unroll
            for (int q = 1; q < 4; q++) {
                uint32_t st2[2];
                lds64(st2, sb + RI_ST + ((tid + q * 64) & 255) * 8);
                sum += __uint_as_float(st2[0]); sq += __uint_as_float(st2[1]);
            }
            const float mean = sum * (1.f / 640.f), r = rsqrtf(fmaxf(fmaf(-mean, mean, sq * (1.f / 640.f)), 0.f) + 1e-5f), off = -mean * r;
            uint4* dst = (uint4*)g_xn + ((size_t)(2 * a + (w & 1)) * 80 + chunk0(rg)) * 32 + lane;
#pragma unroll
            for (int i = 0; i < 5; i++) {
                uint32_t u[4];
                lds128(u, xa + i * 16);
                dst[i * 32] = make_uint4(pack_h(fmaf(bf_lo(u[0]), r, off), fmaf(bf_hi(u[0]), r, off)), pack_h(fmaf(bf_lo(u[1]), r, off), fmaf(bf_hi(u[1]), r, off)),
                                         pack_h(fmaf(bf_lo(u[2]), r, off), fmaf(bf_hi(u[2]), r, off)), pack_h(fmaf(bf_lo(u[3]), r, off), fmaf(bf_hi(u[3]), r, off)));
            }
            __syncwarp();
            if (lane == 0) mbar_arrive(sb + HB_LN);
            if (layer == TLL) TL(37);
            if (layer == TLL && n == TLN) TL(44);
            residual(a + (nh >> 2), n + 1);
#pragma unroll 2
            for (int rr = 0; rr < 64 - gr && tid < 240; rr += 12) {
                uint32_t v[4];
                lds128(v, gs + (n & 1) * 21504 + rr * 336);
                ((uint4*)x)[(a * 64 + rr) * 80 + go] = make_uint4(v[0], v[1], v[2], v[3]);
            }
        }
    }
    bar_sync(3, 384);
    if (layer == TLL) TL(38);
    if (jh >= na) {
        int c0 = 0;
#pragma unroll 1
        for (int mb = (jh - na) >> 3; mb < nbh; mb += (nh - na) >> 3, c0 += GNC) oproj_mma(sb, mb, (jh - na) & 7, c0, x, out, layer);
        if (layer == TLL) TL(42);
        return;
    }
    const int p = w >> 1, mi = w & 1;
    int slot = p, ph = 0;
    for (int idx = jh + p * na; idx < NSEG * 32; idx += 4 * na) {
        const uint32_t it = sb + slot * 30720 + lane * 16;
        float iq, ik, iv;
        weight_scale(idx & 31, 0, &iq); weight_scale(idx & 31, 1, &ik); weight_scale(idx & 31, 2, &iv);
        bar_sync(6 + p, 64);
        mbar_wait(sb + HB_DONE + slot * 8, ph ^ 1);
        mbar_wait(sb + HB_FULL + slot * 8, ph);
        if (layer == TLL && idx >= 63 * 32) TL(55);
        float s[6][4];
#pragma unroll
        for (int i = 0; i < 6; i++) s[i][0] = s[i][1] = s[i][2] = s[i][3] = 0.f;
#pragma unroll
        for (int e = 0; e < 8; e++) {
            uint32_t q[4], k[4];
            ldsm4t(q, it + (e >> 2) * 8192 + (e & 3) * 1024 + mi * 512);
            ldsm4t(k, it + 24576 + e * 512);
            mma_bf(s[4], q[0], q[2], q[1], q[3], k[0], k[1]);
            mma_bf(s[5], q[0], q[2], q[1], q[3], k[2], k[3]);
            ldsm4t(k, it + (e >> 2) * 8192 + 4096 + (e & 3) * 1024);
            mma_bf(s[0], q[0], q[2], q[1], q[3], k[0], k[1]);
            mma_bf(s[1], q[0], q[2], q[1], q[3], k[2], k[3]);
            if (mi) {
                ldsm4t(k, it + (e >> 2) * 8192 + 4096 + (e & 3) * 1024 + 512);
                mma_bf(s[2], q[0], q[2], q[1], q[3], k[0], k[1]);
                mma_bf(s[3], q[0], q[2], q[1], q[3], k[2], k[3]);
            }
        }
#pragma unroll
        for (int q = 0; q < 4; q++) s[4][q] += s[5][q];
        const int seg = idx >> 5, h = idx & 31;
        const float sl = iq * ik * (0.08838834764831845f * 1.4426950408889634f);
        float mx[2] = {-3.0e38f, -3.0e38f};
#pragma unroll
        for (int i = 0; i < 5; i++)
#pragma unroll
            for (int q = 0; q < 4; q++) {
                const bool ok = i == 4 || (i * 8 + 2 * t + (q & 1)) <= (mi * 16 + g + (q >> 1) * 8);
                s[i][q] = ok ? s[i][q] * sl : -1.0e9f * 1.4426950408889634f;
                mx[q >> 1] = fmaxf(mx[q >> 1], s[i][q]);
            }
        float sum[2] = {0.f, 0.f};
#pragma unroll
        for (int r = 0; r < 2; r++) {
            mx[r] = fmaxf(mx[r], __shfl_xor_sync(~0u, mx[r], 1));
            mx[r] = fmaxf(mx[r], __shfl_xor_sync(~0u, mx[r], 2));
        }
#pragma unroll
        for (int i = 0; i < 5; i++)
#pragma unroll
            for (int q = 0; q < 4; q++) { s[i][q] = ex2(s[i][q] - mx[q >> 1]); sum[q >> 1] += s[i][q]; }
#pragma unroll
        for (int r = 0; r < 2; r++) {
            sum[r] += __shfl_xor_sync(~0u, sum[r], 1);
            sum[r] += __shfl_xor_sync(~0u, sum[r], 2);
            sum[r] = iv * rcp(sum[r]);
        }
        uint32_t pp[5][2];
#pragma unroll
        for (int i = 0; i < 5; i++) { pp[i][0] = pack_bf(s[i][0] * sum[0], s[i][1] * sum[0]); pp[i][1] = pack_bf(s[i][2] * sum[1], s[i][3] * sum[1]); }
        uint32_t* o = (uint32_t*)g_O + (((size_t)(seg >> 1) * 512 + h * 16) * 8 + (seg & 1) * 4 + mi * 2) * 32 + lane;
#pragma unroll
        for (int e = 0; e < 8; e++) {
            float o0[4] = {0.f, 0.f, 0.f, 0.f}, o1[4] = {0.f, 0.f, 0.f, 0.f};
            uint32_t v[4];
            lds64(v, it - lane * 8 + 28672 + e * 256);
            mma_bf8(o0, pp[4][0], pp[4][1], v[0]);
            mma_bf8(o1, pp[4][0], pp[4][1], v[1]);
            ldsm4(v, it + 16384 + e * 1024);
            mma_bf(o0, pp[0][0], pp[0][1], pp[1][0], pp[1][1], v[0], v[2]);
            mma_bf(o1, pp[0][0], pp[0][1], pp[1][0], pp[1][1], v[1], v[3]);
            ldsm4(v, it + 16384 + e * 1024 + 512);
            mma_bf(o0, pp[2][0], pp[2][1], pp[3][0], pp[3][1], v[0], v[2]);
            mma_bf(o1, pp[2][0], pp[2][1], pp[3][0], pp[3][1], v[1], v[3]);
            o[(2 * e) * 256] = pack_bf(o0[0], o0[1]); o[(2 * e) * 256 + 32] = pack_bf(o0[2], o0[3]);
            o[(2 * e + 1) * 256] = pack_bf(o1[0], o1[1]); o[(2 * e + 1) * 256 + 32] = pack_bf(o1[2], o1[3]);
        }
        __syncwarp();
        if (lane == 0) mbar_arrive(sb + HB_DONE + slot * 8);
        slot += 4;
        if (slot >= 6) { slot -= 6; ph ^= 1; }
    }
    if (layer == TLL) TL(39);
}

__global__ void __cluster_dims__(3, 1, 1) __launch_bounds__(384, 1)
k_chain(const int layer, const int nact, const uint32_t zero, const bf16* __restrict__ Wq, const bf16* __restrict__ Wk, const bf16* __restrict__ Wv,
        const bf16* __restrict__ Wo, const bf16* res, bf16* out) {
    extern __shared__ __align__(1024) char sm[];
    const uint32_t sb = smem_u32(sm);
    const int b = blockIdx.x, h = b / 3, c = b - h * 3;
    pdl_go();
    if (threadIdx.x >= 256) {
        asm volatile("setmaxnreg.dec.sync.aligned.u32 24;");
        TL(11 + layer * 14);
        chain_aux(sb, c, h, layer, nact);
    } else {
        asm volatile("setmaxnreg.inc.sync.aligned.u32 240;");
        chain_mma(sb, c, h, layer, zero, Wq, Wk, Wv, Wo, res, out);
    }
}
__global__ void __launch_bounds__(384, 1) k_help(const bf16* res, bf16* x, bf16* out, const int layer, const int na, const int nbh, const int zero, const bf16* Wq,
                                                  const bf16* Wk, const bf16* Wv, const bf16* Wo) {
    extern __shared__ __align__(1024) char sm[];
    if (layer == TLL) TL(51);
    pdl_go();
    if (threadIdx.x >= 256) {
        const uint32_t sb = smem_u32(sm);
        const int p = (threadIdx.x >> 5) - 8, i = (threadIdx.x & 31) * 4 + p;
        if (i < 34) mbar_init(sb + G_BAR + i * 8, i < 4 ? 3 : i < 8 || i == 12 || i == 13 ? 8 : i >= 22 && i < 28 ? 2 : 1);
        fence_async_smem();
        wait_flag<100>(g_flag + F_X + layer * 128 + 65, 1);
        fence_async_glb();
        if (i == 8 + p && blockIdx.x < (gridDim.x & ~3)) {
            mbar_expect(sb + HB_A + p * 8, 20480);
            bulk_g2s(sb + RI_A + p * 20480, (const char*)g_YT + (size_t)(blockIdx.x >> 2) * 81920 + p * 20480, 20480, sb + HB_A + p * 8);
        }
        __syncwarp();
        bar_sync(2, 128);
        bar_arrive(1, 384);
    }
    if (threadIdx.x + zero >= 256) helper_aux(smem_u32(sm), blockIdx.x, gridDim.x, na, nbh, layer, Wq, Wk, Wv, Wo);
    else helper_mma(sm, blockIdx.x, gridDim.x, na, nbh, layer, res, x, out);
    __syncwarp();
    if (blockIdx.x == 0) pdl_wait();
}

#define COL_PAD 15872
template <class... P, class... A>
void launch_pdl(void (*k)(P...), int grid, int block, int smem, cudaStream_t st, A... args) {
    cudaLaunchConfig_t cfg = {};
    cfg.gridDim = dim3(grid); cfg.blockDim = dim3(block); cfg.dynamicSmemBytes = smem; cfg.stream = st;
    cudaLaunchAttribute at[1];
    at[0].id = cudaLaunchAttributeProgrammaticStreamSerialization; at[0].val.programmaticStreamSerializationAllowed = 1;
    cfg.attrs = at;
    cfg.numAttrs = 1;
    cudaLaunchKernelEx(&cfg, k, args...);
}

}

extern "C" void kernel_launch(void* const* d_in, const int* in_sizes, int n_in, void* d_out, int out_size) {
    const bf16* x = (const bf16*)d_in[0];
    const bf16* wr = (const bf16*)d_in[1];
    const bf16* wi = (const bf16*)d_in[2];
    const bf16* mem0 = (const bf16*)d_in[4];
    const bf16* Wq = (const bf16*)d_in[5];
    const bf16* Wk = (const bf16*)d_in[6];
    const bf16* Wv = (const bf16*)d_in[7];
    const bf16* Wo = (const bf16*)d_in[8];
    bf16* out = (bf16*)d_out;
    static int nhelp = 0;
    static bf16 *xa, *xb;
    static cudaStream_t s1;
    static cudaEvent_t ev_fork, ev_join;
    if (!nhelp) {
        cudaStreamCreateWithFlags(&s1, cudaStreamNonBlocking);
        cudaEventCreateWithFlags(&ev_fork, cudaEventDisableTiming);
        cudaEventCreateWithFlags(&ev_join, cudaEventDisableTiming);
        cudaFuncSetAttribute(k_setup, cudaFuncAttributeMaxDynamicSharedMemorySize, SU_SMEM);
        cudaFuncSetAttribute(k_rowf<0>, cudaFuncAttributeMaxDynamicSharedMemorySize, RF_SMEM);
        cudaFuncSetAttribute(k_rowf<1>, cudaFuncAttributeMaxDynamicSharedMemorySize, RF_SMEM);
        cudaFuncSetAttribute(k_col, cudaFuncAttributeMaxDynamicSharedMemorySize, COL_PAD);
        cudaFuncSetAttribute(k_chain, cudaFuncAttributeMaxDynamicSharedMemorySize, CH_SMEM);
        cudaFuncSetAttribute(k_setup, cudaFuncAttributePreferredSharedMemoryCarveout, 100);
        cudaFuncSetAttribute(k_rowf<0>, cudaFuncAttributePreferredSharedMemoryCarveout, 100);
        cudaFuncSetAttribute(k_rowf<1>, cudaFuncAttributePreferredSharedMemoryCarveout, 100);
        cudaFuncSetAttribute(k_col, cudaFuncAttributePreferredSharedMemoryCarveout, 100);
        cudaFuncSetAttribute(k_chain, cudaFuncAttributePreferredSharedMemoryCarveout, 100);
        cudaFuncSetAttribute(k_help, cudaFuncAttributeMaxDynamicSharedMemorySize, HP_SMEM);
        cudaFuncSetAttribute(k_help, cudaFuncAttributePreferredSharedMemoryCarveout, 100);
        int dev = 0, sms = 0;
        cudaGetDevice(&dev);
        cudaDeviceGetAttribute(&sms, cudaDevAttrMultiProcessorCount, dev);
        nhelp = sms - 96 < 12 ? 12 : sms - 96;
        cudaGetSymbolAddress((void**)&xa, g_xa);
        cudaGetSymbolAddress((void**)&xb, g_xb);
    }
    const int na = nhelp - (nhelp >= 36 ? 24 : nhelp >= 28 ? 16 : 8), nbh = 14;
    cudaStream_t s0 = cudaStreamPerThread;
    cudaEventRecord(ev_fork, s0);
    cudaStreamWaitEvent(s1, ev_fork, 0);
    k_rowf<1><<<(96 + nhelp) & ~1, 256, RF_SMEM, s0>>>(x);
    k_setup<<<NSETUP, 256, SU_SMEM, s1>>>(wr, wi, mem0);
    cudaEventRecord(ev_join, s1);
#define NLAYER 2
    for (int l = 0; l < NLAYER; l++) {
        const bf16* xin = l == 0 ? x : xb;
        if (l == 1) launch_pdl(k_rowf<0>, 128, 256, RF_SMEM, s0, xin);
        launch_pdl(k_col, 321, 128, l == 0 ? 0 : COL_PAD, s0, (int)(l == 0));
        launch_pdl(k_chain, 96, 384, CH_SMEM, s0, l, nhelp & ~3, 0u, Wq, Wk, Wv, Wo, (const bf16*)xa, l == 0 ? xb : out);
        launch_pdl(k_help, nhelp, 384, HP_SMEM, s0, xin, xa, l == 0 ? xb : out, l, na, nbh, 0, Wq, Wk, Wv, Wo);
    }
    cudaStreamWaitEvent(s0, ev_join, 0);
}
```

```cpp
#include <cuda_runtime.h>
#include <cuda_bf16.h>
#include <cuda_fp16.h>
#include <stdint.h>
#include <string.h>

namespace {

typedef __nv_bfloat16 bf16;
constexpr int S_ = 2048, D_ = 640, NSEG = 64;
constexpr int SPIN_LIM = 1 << 13;

__device__ float                  g_wmx[96];
__device__ __align__(1024) bf16   g_wot[4096 * 640];
__device__ __align__(16) float    g_co[1024];
__device__ __align__(256) uint2   g_stat[2 * 32 * 16 * 64];
__device__ float                  g_invM0;
__device__ __align__(16) float    g_wmax[128];
__device__ __align__(1024) char   g_redraw[65 * 32768];
constexpr int F_X = 2 * NSEG * 32, F_O = F_X + 2 * 128, NFLAG = F_O + 128, RING = 8;
constexpr int F_W = F_X + 66;
constexpr int F_R = F_O + 64;
constexpr int NSETUP = 131;
struct __align__(256) Flag { unsigned v; };
__device__ Flag                   g_flag[NFLAG];
__device__ Flag                   g_ready[1];
__device__ __align__(1024) char   g_item[RING * 32 * 32768];
__device__ __align__(1024) bf16   g_O[S_ * 4096];
__device__ __align__(1024) __half g_xn[S_ * D_];
__device__ __align__(1024) bf16   g_xa[S_ * D_];
__device__ __align__(1024) bf16   g_xb[S_ * D_];
__device__ __align__(1024) __half g_UT[D_ * S_];
__device__ __align__(1024) __half g_YT[D_ * S_];
__device__ __align__(1024) __half g_ctab[64 * 128 + 64 * 64];
__device__ __align__(1024) uint32_t g_Wf[321 * 2048];

#define TL(i)
#define TLN 0
#define TLL 1
#define CK(i)
__device__ __forceinline__ uint32_t smem_u32(const void* p) { return (uint32_t)__cvta_generic_to_shared(p); }
__device__ __forceinline__ uint32_t mapa(uint32_t a, uint32_t r) { uint32_t o; asm("mapa.shared::cluster.u32 %0,%1,%2;" : "=r"(o) : "r"(a), "r"(r)); return o; }
__device__ __forceinline__ void mbar_init(uint32_t a, int c) { asm volatile("mbarrier.init.shared::cta.b64 [%0],%1;" ::"r"(a), "r"(c) : "memory"); }
__device__ __forceinline__ void mbar_expect(uint32_t a, int bytes) { asm volatile("mbarrier.arrive.expect_tx.shared::cta.b64 _,[%0],%1;" ::"r"(a), "r"(bytes) : "memory"); }
__device__ __forceinline__ void mbar_arrive(uint32_t a) { asm volatile("mbarrier.arrive.shared::cta.b64 _,[%0];" ::"r"(a) : "memory"); }
__device__ __forceinline__ bool mbar_try(uint32_t a, uint32_t par) {
    uint32_t p;
    asm volatile("{.reg .pred q; mbarrier.try_wait.parity.shared::cta.b64 q,[%1],%2; selp.u32 %0,1,0,q;}" : "=r"(p) : "r"(a), "r"(par) : "memory");
    return p;
}
__device__ __forceinline__ void mbar_wait(uint32_t a, uint32_t par) {
    if (!mbar_try(a, par)) {
        int lim = 0;
        while (!mbar_try(a, par) && ++lim < SPIN_LIM) {}
    }
}
__device__ __forceinline__ void mbar_sleep(uint32_t a, uint32_t par) {
    asm volatile("{.reg .pred q; .reg .u32 n; mov.u32 n,0;\n"
                 "W_LOOP: mbarrier.try_wait.parity.shared::cta.b64 q,[%0],%1,%2; add.u32 n,n,1; setp.lt.and.u32 q,n,%3,!q; @q bra W_LOOP;}"
                 ::"r"(a), "r"(par), "n"(20000), "n"(SPIN_LIM) : "memory");
}
__device__ __forceinline__ void bar_arrive(int id, int n) { asm volatile("bar.arrive %0,%1;" ::"r"(id), "r"(n) : "memory"); }
__device__ __forceinline__ uint32_t clock32() { uint32_t c; asm volatile("mov.u32 %0,%%clock;" : "=r"(c)); return c; }
__device__ __forceinline__ uint32_t read_tid() { uint32_t v; asm volatile("mov.u32 %0,%%tid.x;" : "=r"(v)); return v; }
__device__ __forceinline__ void bar_sync(int id, int n) { asm volatile("bar.sync %0,%1;" ::"r"(id), "r"(n) : "memory"); }
__device__ __forceinline__ void fence_async_smem() { asm volatile("fence.proxy.async.shared::cta;" ::: "memory"); }
__device__ __forceinline__ void fence_async_glb() { asm volatile("fence.proxy.async.global;" ::: "memory"); }
__device__ __forceinline__ void cluster_sync_full() { asm volatile("barrier.cluster.arrive.aligned; barrier.cluster.wait.aligned;" ::: "memory"); }
__device__ __forceinline__ void bulk_g2s(uint32_t dst, const void* src, int bytes, uint32_t mb) {
    asm volatile("cp.async.bulk.shared::cluster.global.mbarrier::complete_tx::bytes [%0],[%1],%2,[%3];" ::"r"(dst), "l"(src), "r"(bytes), "r"(mb) : "memory");
}
__device__ __forceinline__ void bulk_g2s_last(uint32_t dst, const void* src, int bytes, uint32_t mb) {
    asm volatile("{.reg .b64 p; createpolicy.fractional.L2::evict_first.b64 p, 1.0;\n"
                 "cp.async.bulk.shared::cluster.global.mbarrier::complete_tx::bytes.L2::cache_hint [%0],[%1],%2,[%3],p;}"
                 ::"r"(dst), "l"(src), "r"(bytes), "r"(mb) : "memory");
}
__device__ __forceinline__ void bulk_s2s(uint32_t dst, uint32_t src, int bytes, uint32_t mb) {
    asm volatile("cp.async.bulk.shared::cluster.shared::cta.mbarrier::complete_tx::bytes [%0],[%1],%2,[%3];" ::"r"(dst), "r"(src), "r"(bytes), "r"(mb) : "memory");
}
__device__ __forceinline__ void bulk_s2g(void* dst, uint32_t src, int bytes) {
    asm volatile("cp.async.bulk.global.shared::cta.bulk_group [%0],[%1],%2;" ::"l"(dst), "r"(src), "r"(bytes) : "memory");
}
__device__ __forceinline__ void cp_async16(uint32_t dst, const void* src, uint32_t bytes = 16) {
    asm volatile("cp.async.cg.shared.global [%0],[%1],16,%2;" ::"r"(dst), "l"(src), "r"(bytes) : "memory");
}
__device__ __forceinline__ void cp_commit() { asm volatile("cp.async.commit_group;" ::: "memory"); }
template <int N> __device__ __forceinline__ void cp_wait() { asm volatile("cp.async.wait_group %0;" ::"n"(N) : "memory"); }
__device__ __forceinline__ void bulk_commit() { asm volatile("cp.async.bulk.commit_group;" ::: "memory"); }
__device__ __forceinline__ void bulk_wait0() { asm volatile("cp.async.bulk.wait_group 0;" ::: "memory"); }
__device__ __forceinline__ void ldsm4(uint32_t* r, uint32_t a) {
    asm volatile("ldmatrix.sync.aligned.m8n8.x4.shared.b16 {%0,%1,%2,%3},[%4];" : "=r"(r[0]), "=r"(r[1]), "=r"(r[2]), "=r"(r[3]) : "r"(a) : "memory");
}
__device__ __forceinline__ void ldsm4t(uint32_t* r, uint32_t a) {
    asm volatile("ldmatrix.sync.aligned.m8n8.x4.trans.shared.b16 {%0,%1,%2,%3},[%4];" : "=r"(r[0]), "=r"(r[1]), "=r"(r[2]), "=r"(r[3]) : "r"(a) : "memory");
}
__device__ __forceinline__ void stsm4(uint32_t a, uint32_t r0, uint32_t r1, uint32_t r2, uint32_t r3) {
    asm volatile("stmatrix.sync.aligned.m8n8.x4.shared.b16 [%0],{%1,%2,%3,%4};" ::"r"(a), "r"(r0), "r"(r1), "r"(r2), "r"(r3) : "memory");
}
__device__ __forceinline__ void stsm4t(uint32_t a, uint32_t r0, uint32_t r1, uint32_t r2, uint32_t r3) {
    asm volatile("stmatrix.sync.aligned.m8n8.x4.trans.shared.b16 [%0],{%1,%2,%3,%4};" ::"r"(a), "r"(r0), "r"(r1), "r"(r2), "r"(r3) : "memory");
}
__device__ __forceinline__ void lds128(uint32_t* r, uint32_t a) {
    asm volatile("ld.shared.v4.b32 {%0,%1,%2,%3},[%4];" : "=r"(r[0]), "=r"(r[1]), "=r"(r[2]), "=r"(r[3]) : "r"(a) : "memory");
}
__device__ __forceinline__ void lds64(uint32_t* r, uint32_t a) {
    asm volatile("ld.shared.v2.b32 {%0,%1},[%2];" : "=r"(r[0]), "=r"(r[1]) : "r"(a) : "memory");
}
__device__ __forceinline__ uint32_t lds32(uint32_t a) { uint32_t v; asm volatile("ld.shared.b32 %0,[%1];" : "=r"(v) : "r"(a) : "memory"); return v; }
__device__ __forceinline__ void sts128(uint32_t a, uint32_t r0, uint32_t r1, uint32_t r2, uint32_t r3) {
    asm volatile("st.shared.v4.b32 [%0],{%1,%2,%3,%4};" ::"r"(a), "r"(r0), "r"(r1), "r"(r2), "r"(r3) : "memory");
}
__device__ __forceinline__ void sts64(uint32_t a, uint32_t v0, uint32_t v1) { asm volatile("st.shared.v2.b32 [%0],{%1,%2};" ::"r"(a), "r"(v0), "r"(v1) : "memory"); }
[[maybe_unused]] __device__ __forceinline__ void sts32(uint32_t a, uint32_t v) { asm volatile("st.shared.b32 [%0],%1;" ::"r"(a), "r"(v) : "memory"); }
#define AU_(op) "{.reg .u32 t; add.u32 t,%4,%5; " op " {%0,%1,%2,%3},[t+%6];}"
template <int I> __device__ __forceinline__ void ldsm4_u(uint32_t* r, uint32_t a, uint32_t u) {
    asm volatile(AU_("ldmatrix.sync.aligned.m8n8.x4.shared.b16") : "=r"(r[0]), "=r"(r[1]), "=r"(r[2]), "=r"(r[3]) : "r"(a), "r"(u), "n"(I) : "memory");
}
template <int I> __device__ __forceinline__ void ldsm4t_u(uint32_t* r, uint32_t a, uint32_t u) {
    asm volatile(AU_("ldmatrix.sync.aligned.m8n8.x4.trans.shared.b16") : "=r"(r[0]), "=r"(r[1]), "=r"(r[2]), "=r"(r[3]) : "r"(a), "r"(u), "n"(I) : "memory");
}
template <int I> __device__ __forceinline__ void lds128_u(uint32_t* r, uint32_t a, uint32_t u) {
    asm volatile(AU_("ld.shared.v4.b32") : "=r"(r[0]), "=r"(r[1]), "=r"(r[2]), "=r"(r[3]) : "r"(a), "r"(u), "n"(I) : "memory");
}
template <int I> __device__ __forceinline__ void lds64_u(uint32_t* r, uint32_t a, uint32_t u) {
    asm volatile("{.reg .u32 t; add.u32 t,%2,%3; ld.shared.v2.b32 {%0,%1},[t+%4];}" : "=r"(r[0]), "=r"(r[1]) : "r"(a), "r"(u), "n"(I) : "memory");
}
template <int I> __device__ __forceinline__ uint32_t lds32_u(uint32_t a, uint32_t u) {
    uint32_t v;
    asm volatile("{.reg .u32 t; add.u32 t,%1,%2; ld.shared.b32 %0,[t+%3];}" : "=r"(v) : "r"(a), "r"(u), "n"(I) : "memory");
    return v;
}
template <int I> __device__ __forceinline__ void sts64_u(uint32_t a, uint32_t u, uint32_t v0, uint32_t v1) {
    asm volatile("{.reg .u32 t; add.u32 t,%0,%1; st.shared.v2.b32 [t+%2],{%3,%4};}" ::"r"(a), "r"(u), "n"(I), "r"(v0), "r"(v1) : "memory");
}
template <int I> __device__ __forceinline__ void sts32_u(uint32_t a, uint32_t u, uint32_t v) {
    asm volatile("{.reg .u32 t; add.u32 t,%0,%1; st.shared.b32 [t+%2],%3;}" ::"r"(a), "r"(u), "n"(I), "r"(v) : "memory");
}
template <int I> __device__ __forceinline__ void sts16_u(uint32_t a, uint32_t u, uint32_t v) {
    asm volatile("{.reg .u32 t; add.u32 t,%0,%1; st.shared.b16 [t+%2],%3;}" ::"r"(a), "r"(u), "n"(I), "h"((unsigned short)v) : "memory");
}
template <int I> __device__ __forceinline__ void sts128_u(uint32_t a, uint32_t u, uint32_t r0, uint32_t r1, uint32_t r2, uint32_t r3) {
    asm volatile("{.reg .u32 t; add.u32 t,%0,%1; st.shared.v4.b32 [t+%2],{%3,%4,%5,%6};}" ::"r"(a), "r"(u), "n"(I), "r"(r0), "r"(r1), "r"(r2), "r"(r3) : "memory");
}
template <int I> __device__ __forceinline__ void stsm4_u(uint32_t a, uint32_t u, uint32_t r0, uint32_t r1, uint32_t r2, uint32_t r3) {
    asm volatile("{.reg .u32 t; add.u32 t,%0,%1; stmatrix.sync.aligned.m8n8.x4.shared.b16 [t+%2],{%3,%4,%5,%6};}"
                 ::"r"(a), "r"(u), "n"(I), "r"(r0), "r"(r1), "r"(r2), "r"(r3) : "memory");
}
__device__ __forceinline__ void st_share2(uint32_t a, uint32_t u, uint32_t mb, uint32_t d0, uint32_t d1, uint32_t v0, uint32_t v1) {
    asm volatile("{.reg .pred p; .reg .u32 t,x,y; add.u32 t,%0,%1;\n"
                 "add.u32 x,t,%3; add.u32 y,%2,%3; st.async.shared::cluster.mbarrier::complete_tx::bytes.v2.b32 [x],{%5,%6},[y];\n"
                 "add.u32 x,t,%4; add.u32 y,%2,%4; st.async.shared::cluster.mbarrier::complete_tx::bytes.v2.b32 [x],{%5,%6},[y];\n"
                 "st.shared.v2.b32 [t],{%5,%6}; bar.warp.sync -1; setp.eq.u32 p,%0,0; @p mbarrier.arrive.shared::cta.b64 _,[%2];}"
                 ::"r"(a), "r"(u), "r"(mb), "r"(d0), "r"(d1), "r"(v0), "r"(v1) : "memory");
}
template <int V> struct IC { __host__ __device__ constexpr operator int() const { return V; } };
template <int N, class F> __device__ __forceinline__ void sfor(F f) {
    if constexpr (N > 0) { sfor<N - 1>(f); f(IC<N - 1>()); }
}
__device__ __forceinline__ void mma_f16(float* d, const uint32_t* a, uint32_t b0, uint32_t b1) {
    asm volatile("mma.sync.aligned.m16n8k16.row.col.f32.f16.f16.f32 {%0,%1,%2,%3},{%4,%5,%6,%7},{%8,%9},{%0,%1,%2,%3};"
                 : "+f"(d[0]), "+f"(d[1]), "+f"(d[2]), "+f"(d[3]) : "r"(a[0]), "r"(a[1]), "r"(a[2]), "r"(a[3]), "r"(b0), "r"(b1));
}
__device__ __forceinline__ void mma_bf(float* d, uint32_t a0, uint32_t a1, uint32_t a2, uint32_t a3, uint32_t b0, uint32_t b1) {
    asm volatile("mma.sync.aligned.m16n8k16.row.col.f32.bf16.bf16.f32 {%0,%1,%2,%3},{%4,%5,%6,%7},{%8,%9},{%0,%1,%2,%3};"
                 : "+f"(d[0]), "+f"(d[1]), "+f"(d[2]), "+f"(d[3]) : "r"(a0), "r"(a1), "r"(a2), "r"(a3), "r"(b0), "r"(b1));
}
__device__ __forceinline__ void mma_bf8(float* d, uint32_t a0, uint32_t a1, uint32_t b0) {
    asm volatile("mma.sync.aligned.m16n8k8.row.col.f32.bf16.bf16.f32 {%0,%1,%2,%3},{%4,%5},{%6},{%0,%1,%2,%3};"
                 : "+f"(d[0]), "+f"(d[1]), "+f"(d[2]), "+f"(d[3]) : "r"(a0), "r"(a1), "r"(b0));
}
__device__ __forceinline__ uint32_t pack_bf(float lo, float hi) { uint32_t r; asm("cvt.rn.bf16x2.f32 %0,%1,%2;" : "=r"(r) : "f"(hi), "f"(lo)); return r; }
__device__ __forceinline__ uint32_t pack_h(float lo, float hi) { uint32_t r; asm("cvt.rn.f16x2.f32 %0,%1,%2;" : "=r"(r) : "f"(hi), "f"(lo)); return r; }
__device__ __forceinline__ float bf_lo(uint32_t v) { return __uint_as_float(v << 16); }
__device__ __forceinline__ float bf_hi(uint32_t v) { return __uint_as_float(v & 0xffff0000u); }
__device__ __forceinline__ uint32_t bfma(uint32_t a, uint32_t b, uint32_t c) { uint32_t r; asm("fma.rn.bf16x2 %0,%1,%2,%3;" : "=r"(r) : "r"(a), "r"(b), "r"(c)); return r; }
__device__ __forceinline__ uint4 add_bf8(const uint4 x, const uint32_t* y, const uint32_t k = 0x3f803f80u) {
    return make_uint4(bfma(y[0], k, x.x), bfma(y[1], k, x.y), bfma(y[2], k, x.z), bfma(y[3], k, x.w));
}
__device__ __forceinline__ float ex2(float x) { float r; asm("ex2.approx.ftz.f32 %0,%1;" : "=f"(r) : "f"(x)); return r; }
__device__ __forceinline__ float rcp(float x) { float r; asm("rcp.approx.ftz.f32 %0,%1;" : "=f"(r) : "f"(x)); return r; }
__device__ __forceinline__ void wg_fence() { asm volatile("wgmma.fence.sync.aligned;" ::: "memory"); }
__device__ __forceinline__ void wg_commit() { asm volatile("wgmma.commit_group.sync.aligned;" ::: "memory"); }
template <int N> __device__ __forceinline__ void wg_wait() { asm volatile("wgmma.wait_group.sync.aligned %0;" ::"n"(N) : "memory"); }
__device__ __forceinline__ uint64_t mkdesc(uint32_t a, uint32_t lbo, uint32_t sbo, uint32_t sw) {
    return (uint64_t)((a & 0x3FFFF) >> 4) | ((uint64_t)(lbo >> 4) << 16) | ((uint64_t)(sbo >> 4) << 32) | ((uint64_t)sw << 62);
}
#define F4(d, i) "+f"(d[i]), "+f"(d[i + 1]), "+f"(d[i + 2]), "+f"(d[i + 3])
#define F8(d, i) F4(d, i), F4(d, i + 4)
#define F16(d, i) F8(d, i), F8(d, i + 8)
template <int OFF, int SC> __device__ __forceinline__ void wg_n32_x(float* d, const uint32_t* a, uint32_t lo) {
    asm volatile("{.reg .pred p; .reg .b32 l; .reg .b64 q; setp.ne.b32 p,%22,0; add.u32 l,%20,%21; mov.b64 q,{l,8};\n"
                 "wgmma.mma_async.sync.aligned.m64n32k16.f32.f16.f16 "
                 "{%0,%1,%2,%3,%4,%5,%6,%7,%8,%9,%10,%11,%12,%13,%14,%15},{%16,%17,%18,%19},q,p,1,1,0;}"
                 : F16(d, 0) : "r"(a[0]), "r"(a[1]), "r"(a[2]), "r"(a[3]), "r"(lo), "n"(OFF), "n"(SC));
}
__device__ __forceinline__ void wg_n128_rs(float* d, const uint32_t* a, uint64_t db, int sc) {
    asm volatile("{.reg .pred p; setp.ne.b32 p,%69,0; wgmma.mma_async.sync.aligned.m64n128k16.f32.f16.f16 "
                 "{%0,%1,%2,%3,%4,%5,%6,%7,%8,%9,%10,%11,%12,%13,%14,%15,%16,%17,%18,%19,%20,%21,%22,%23,%24,%25,%26,%27,%28,%29,%30,%31,"
                 "%32,%33,%34,%35,%36,%37,%38,%39,%40,%41,%42,%43,%44,%45,%46,%47,%48,%49,%50,%51,%52,%53,%54,%55,%56,%57,%58,%59,%60,%61,%62,%63},"
                 "{%64,%65,%66,%67},%68,p,1,1,0;}"
                 : F16(d, 0), F16(d, 16), F16(d, 32), F16(d, 48) : "r"(a[0]), "r"(a[1]), "r"(a[2]), "r"(a[3]), "l"(db), "r"(sc));
}
#define N80_REGS "{%0,%1,%2,%3,%4,%5,%6,%7,%8,%9,%10,%11,%12,%13,%14,%15,%16,%17,%18,%19,%20,%21,%22,%23,%24,%25,%26,%27,%28,%29,%30,%31,%32,%33,%34,%35,%36,%37,%38,%39}"
__device__ __forceinline__ void wg_n80_ss(float* d, uint64_t da, uint64_t db, int sc) {
    asm volatile("{.reg .pred p; setp.ne.b32 p,%42,0; wgmma.mma_async.sync.aligned.m64n80k16.f32.bf16.bf16 " N80_REGS ",%40,%41,p,1,1,0,0;}"
                 : F16(d, 0), F16(d, 16), F8(d, 32) : "l"(da), "l"(db), "r"(sc));
}
__device__ __forceinline__ void wg_n88_ss(float* d, uint64_t da, uint64_t db, int sc) {
    asm volatile("{.reg .pred p; setp.ne.b32 p,%46,0; wgmma.mma_async.sync.aligned.m64n88k16.f32.f16.f16 "
                 "{%0,%1,%2,%3,%4,%5,%6,%7,%8,%9,%10,%11,%12,%13,%14,%15,%16,%17,%18,%19,%20,%21,%22,%23,%24,%25,%26,%27,%28,%29,%30,%31,"
                 "%32,%33,%34,%35,%36,%37,%38,%39,%40,%41,%42,%43},%44,%45,p,1,1,0,0;}"
                 : F16(d, 0), F16(d, 16), F8(d, 32), F4(d, 40) : "l"(da), "l"(db), "r"(sc));
}
__device__ __forceinline__ void wg_n48_ss_ta(float* d, uint64_t da, uint64_t db, int sc) {
    asm volatile("{.reg .pred p; setp.ne.b32 p,%26,0; wgmma.mma_async.sync.aligned.m64n48k16.f32.f16.f16 "
                 "{%0,%1,%2,%3,%4,%5,%6,%7,%8,%9,%10,%11,%12,%13,%14,%15,%16,%17,%18,%19,%20,%21,%22,%23},%24,%25,p,1,1,1,0;}"
                 : F16(d, 0), F8(d, 16) : "l"(da), "l"(db), "r"(sc));
}
template <int TA> __device__ __forceinline__ void wg_n64_ss_tb(float* d, uint64_t da, uint64_t db, int sc) {
    asm volatile("{.reg .pred p; setp.ne.b32 p,%34,0; wgmma.mma_async.sync.aligned.m64n64k16.f32.f16.f16 "
                 "{%0,%1,%2,%3,%4,%5,%6,%7,%8,%9,%10,%11,%12,%13,%14,%15,%16,%17,%18,%19,%20,%21,%22,%23,%24,%25,%26,%27,%28,%29,%30,%31},"
                 "%32,%33,p,1,1,%35,1;}"
                 : F16(d, 0), F16(d, 16) : "l"(da), "l"(db), "r"(sc), "n"(TA));
}
__device__ __forceinline__ void pdl_wait() { asm volatile("griddepcontrol.wait;" ::: "memory"); }
__device__ __forceinline__ void pdl_go() { asm volatile("griddepcontrol.launch_dependents;" ::: "memory"); }
__device__ __forceinline__ float cos640(float p) {
    const float q = fmaf(p, 0.0015625f, 12582912.f) - 12582912.f;
    return __cosf(fmaf(q, -640.f, p) * 0.009817477042468103f);
}
__device__ __forceinline__ uint4 cos_row8(float p0, float step, float amp = 1.f) {
    float v[8];
    const float k = 2.f * cos640(step);
    v[0] = amp * cos640(p0); v[1] = amp * cos640(p0 + step);
#pragma unroll
    for (int i = 2; i < 8; i++) v[i] = fmaf(k, v[i - 1], -v[i - 2]);
    return make_uint4(pack_h(v[0], v[1]), pack_h(v[2], v[3]), pack_h(v[4], v[5]), pack_h(v[6], v[7]));
}
__device__ __forceinline__ float wfilter_max(int lane) {
    float m = fmaxf(fmaxf(g_wmax[lane], g_wmax[lane + 32]), fmaxf(g_wmax[lane + 64], g_wmax[lane + 96]));
    return __uint_as_float(__reduce_max_sync(~0u, __float_as_uint(m)));
}
__device__ __forceinline__ unsigned ld_acquire(const Flag* p) { unsigned v; asm volatile("ld.acquire.gpu.global.u32 %0,[%1];" : "=r"(v) : "l"(p) : "memory"); return v; }
#define POLL_NS 200
template <int NS = POLL_NS> __device__ __forceinline__ void wait_flag(const Flag* p, unsigned v) {
    if (ld_acquire(p) >= v) return;
    unsigned x;
    int lim = 0;
    do {
        __nanosleep(NS);
        asm volatile("ld.relaxed.gpu.global.u32 %0,[%1];" : "=r"(x) : "l"(p) : "memory");
    } while (x < v && ++lim < SPIN_LIM);
    ld_acquire(p);
}
__device__ __forceinline__ void prefetch_l2(const void* p, int bytes) { asm volatile("cp.async.bulk.prefetch.L2.global [%0],%1;" ::"l"(p), "r"(bytes) : "memory"); }
__device__ __forceinline__ void red_release(Flag* p) { asm volatile("red.release.gpu.global.add.u32 [%0],1;" ::"l"(p) : "memory"); }
__device__ __forceinline__ void red_relaxed(Flag* p) { asm volatile("red.relaxed.gpu.global.add.u32 [%0],1;" ::"l"(p) : "memory"); }
__device__ __forceinline__ void red_h8(void* p, uint32_t a, uint32_t b, uint32_t c, uint32_t d) {
    asm volatile("red.relaxed.gpu.global.add.noftz.v4.f16x2 [%0],{%1,%2,%3,%4};" ::"l"(p), "r"(a), "r"(b), "r"(c), "r"(d) : "memory");
}
__device__ __forceinline__ float pow2_scale(float bound, int top, float* inv) {
    int e = (int)((__float_as_uint(bound) >> 23) & 0xff) - 126;
    int k = top - e;
    k = max(-100, min(100, k));
    *inv = __uint_as_float((uint32_t)(127 - k) << 23);
    return __uint_as_float((uint32_t)(127 + k) << 23);
}
__device__ __forceinline__ char* red_base() { return (char*)(((uintptr_t)g_redraw + 32767) & ~(uintptr_t)32767); }

__device__ __forceinline__ void setup_a(char* sm, const int b, const bf16* __restrict__ wr, const bf16* __restrict__ wi) {
    const int tid = threadIdx.x, lane = tid & 31;
    const uint32_t sb = smem_u32(sm);
    auto row_byte = [&](int q) { return ((b >> 2) + 32 * ((q >> 1) * 8 + 2 * (b & 3) + (q & 1))) * 642; };
#pragma unroll 1
    for (int r = tid >> 5; r < 32; r += 8) {
        const char* src = (const char*)(r < 16 ? wr : wi) + (row_byte(r & 15) & ~15);
        cp_async16(sb + r * 672 + lane * 16, src + lane * 16);
        if (lane < 9) cp_async16(sb + r * 672 + 512 + lane * 16, src + 512 + lane * 16);
    }
    ((uint4*)g_stat)[b * 256 + tid] = make_uint4(0, 0, 0, 0);
    if (tid < 2 * (NFLAG / 128)) ((uint4*)(g_flag + b * (NFLAG / 128) + (tid >> 1)))[tid & 1] = make_uint4(0, 0, 0, 0);
    if (tid < 12) {
        const int i = b * 12 + tid;
        const int f = ((i >> 4) & 3) * 8 + (i & 7), im = (i >> 3) & 1, part = (i >> 8) & 1;
        ((uint4*)g_ctab)[i] = cos_row8((float)(i < 1024 ? (i >> 7) * 80 * (i & 63) + ((i & 64) ? 480 : 0) : ((i >> 6) & 3) * 160 * f + (im == part ? 0 : im ? 160 : 480)),
                                       (float)(i < 1024 ? 10 * (i & 63) : 20 * f));
    }
    asm volatile("cp.async.wait_all;" ::: "memory");
    __syncthreads();
    const int q0 = (tid & 3) * 4;
    const char* rp[4];
#pragma unroll
    for (int u = 0; u < 4; u++) rp[u] = sm + (q0 + u) * 672 + (row_byte(q0 + u) & 15);
    uint32_t mx = 0;
#pragma unroll 2
    for (int c = tid >> 2; c < 321; c += 64) {
        uint32_t v[4];
#pragma unroll
        for (int u = 0; u < 4; u++) {
            v[u] = ((const unsigned short*)rp[u])[c] | ((uint32_t)((const unsigned short*)(rp[u] + 16 * 672))[c] << 16);
            mx = __vmaxu2(mx, v[u] & 0x7fff7fffu);
        }
        ((uint4*)g_Wf)[(size_t)c * 512 + b * 4 + ((tid ^ (b >> 1)) & 3)] = make_uint4(v[0], v[1], v[2], v[3]);
    }
    mx = __reduce_max_sync(~0u, max(mx & 0xffffu, mx >> 16));
    __syncthreads();
    if (lane == 0) ((uint32_t*)sm)[tid >> 5] = mx;
    __syncthreads();
    if (tid < 32) {
        mx = __reduce_max_sync(~0u, ((uint32_t*)sm)[lane & 7]);
        if (tid == 0) g_wmax[b] = __uint_as_float(mx << 16);
    }
}
__device__ __forceinline__ void setup_b(const int b, const bf16* __restrict__ mem0) {
    const int tid = threadIdx.x;
    uint4* z = (uint4*)red_base();
    if (b < 3) {
        const int w = tid >> 5, lane = tid & 31, p = b * 2 + ((w >> 1) & 1), odd = w & 1;
        uint32_t mx = 0;
#pragma unroll 4
        for (int i = lane; i < 640; i += 32) {
            const uint4 u = ((const uint4*)mem0)[i];
            mx = __vmaxu2(__vmaxu2(mx, u.x & 0x7fff7fffu), __vmaxu2(__vmaxu2(u.y & 0x7fff7fffu, u.z & 0x7fff7fffu), u.w & 0x7fff7fffu));
        }
        float inv, v[7];
        const float sc = pow2_scale(__uint_as_float(__reduce_max_sync(~0u, max(mx & 0xffffu, mx >> 16)) << 16), 14, &inv);
        if (tid == 0) g_invM0 = inv;
#pragma unroll
        for (int j = 0; j < 7; j++) {
            const int r = p * 56 + (j < 6 ? odd * 32 + (j >> 1) * 8 : 24) + (lane >> 2), mr = 2 * (lane & 3) + (j < 6 ? (j & 1) : odd);
            v[j] = r < 320 ? __bfloat162float(mem0[mr * 640 + (w >> 2) * 320 + r]) * sc : 0.f;
        }
        const int off = w * 2048 + (lane >> 4) * 1024 + ((lane >> 3) & 1) * 256 + (lane & 7) * 16 + (b == 2 ? (w >> 1) * 4096 + 128 : b * 16384);
        const uint4 u = make_uint4(pack_h(v[0], v[1]), pack_h(v[2], v[3]), pack_h(v[4], v[5]), pack_h(v[6], 32.f));
        z[off >> 4] = u; z[65536 + (off >> 4)] = u;
    }
}

#define SU_PAD 40960
constexpr int SU_SMEM = SU_PAD;
__global__ void __launch_bounds__(256, 4) k_setup(const bf16* __restrict__ wr, const bf16* __restrict__ wi, const bf16* __restrict__ mem0) {
    extern __shared__ __align__(1024) char sm[];
    TL(0);
    if (blockIdx.x >= 128) setup_b(blockIdx.x - 128, mem0);
    else setup_a(sm, blockIdx.x, wr, wi);
    __syncthreads();
    if (threadIdx.x == 0) red_release(g_ready);
    TL(1);
}
__device__ __forceinline__ float weight_scale(int h, int ty, float* inv) { return pow2_scale(__ldcg(g_wmx + h * 3 + ty), 6, inv); }

#define STR_(x) #x
#define STR(x) STR_(x)
#define RF_U 1
constexpr int RF_A = 22 * 2816, RF_X = RF_A + 22 * 1024, RF_BAR = RF_X + 64 * 1344, RF_SMEM = RF_BAR + 80;
__device__ __align__(1024) char g_rtab[4 * RF_A];
template <int first> __global__ void __cluster_dims__(2, 1, 1) __launch_bounds__(256, 2) k_rowf(const bf16* x) {
    extern __shared__ __align__(1024) char sm[];
    TL(first ? 2 : 16);
    const int tid = threadIdx.x, w = tid >> 5, lane = tid & 31, g = lane >> 2, t = lane & 3;
    if (blockIdx.x >= 128) { __nanosleep(2500); return; }
    const int a = first ? blockIdx.x >> 2 : 31 - (blockIdx.x >> 2), gq = blockIdx.x & 3;
    if (!first) pdl_go();
    const uint32_t sb = smem_u32(sm), mb = sb + RF_BAR + w * 8;
    if (lane == 0) {
        mbar_init(mb, 1);
        asm volatile("fence.mbarrier_init.release.cluster;" ::: "memory");
        if (!first && w == 0) {
            mbar_init(sb + RF_BAR + 64, 1);
            fence_async_smem();
            mbar_expect(sb + RF_BAR + 64, RF_A);
            bulk_g2s(sb, g_rtab + gq * RF_A, RF_A, sb + RF_BAR + 64);
        }
    }
    if (lane == 0) mbar_expect(mb, 8 * 1280);
    __syncwarp();
    asm volatile("barrier.cluster.arrive.relaxed.aligned; barrier.cluster.wait.aligned;" ::: "memory");
    if (!first) {
        if (lane == 0) wait_flag<100>(g_flag + F_R + a, a < 28 ? 32 : 192);
        __syncwarp();
        fence_async_glb();
    }
    TL(first ? 3 : 17);
    if (lane < 4)
        asm volatile("cp.async.bulk.shared::cluster.global.mbarrier::complete_tx::bytes.multicast::cluster [%0],[%1],1280,[%2],%3;"
                     ::"r"(sb + RF_X + (w * 8 + (gq & 1) * 4 + lane) * 1344), "l"(x + (size_t)(a * 64 + w * 8 + (gq & 1) * 4 + lane) * 640), "r"(mb),
                     "h"((unsigned short)3) : "memory");
    __syncwarp();
    if (first) pdl_go();
    if (first) {
#pragma unroll 3
        for (int id = tid; id < 22 * 176; id += 256) {
            const int kg = id / 176, n = id - kg * 176;
            const float c = (float)(2 * n + (gq & 1));
            *(uint4*)(sm + id * 16) = cos_row8(fmaf((float)(kg * 8), c, (float)((gq & 2) * 80)), c, 0.03952847075210474f);
        }
    }
    mbar_wait(mb, 0);
    const uint32_t row = sb + RF_X + (w * 8 + g) * 1344;
    float st[4][4] = {};
#pragma unroll 1
    for (int i = 0; i < 20; i += 4) {
        uint32_t u[4][4];
#pragma unroll
        for (int q = 0; q < 4; q++) lds128(u[q], row + (4 * (i + q) + t) * 16);
#pragma unroll
        for (int q = 0; q < 4; q++) {
            mma_bf(st[(q & 1) * 2], u[q][0], 0x3f803f80u, u[q][1], 0x3f803f80u, u[q][0], u[q][1]);
            mma_bf(st[(q & 1) * 2 + 1], u[q][2], 0x3f803f80u, u[q][3], 0x3f803f80u, u[q][2], u[q][3]);
        }
    }
#pragma unroll
    for (int q = 0; q < 4; q++) { st[0][q] += st[2][q]; st[1][q] += st[3][q]; }
    const float sq = __shfl_sync(~0u, (g & 1) ? st[0][1] + st[1][1] : st[0][0] + st[1][0], g * 4 + (g >> 1));
    const float mean = __shfl_sync(~0u, (g & 1) ? st[0][3] + st[1][3] : st[0][2] + st[1][2], g * 4 + (g >> 1)) * (1.f / 640.f);
    const float r = rsqrtf(fmaxf(fmaf(-mean, mean, sq * (1.f / 640.f)), 0.f) + 1e-5f), off = gq == 0 ? -4.f * mean * r : 0.f;
    const float r1 = (gq == 1 || gq == 2) ? -r : r, r2 = (gq & 1) ? -r : r, r3 = gq >= 2 ? -r : r;
    const uint32_t aa = sb + RF_A + w * 128 + g * 16;
    auto el = [&](int d) { unsigned short v; asm volatile("ld.shared.u16 %0,[%1];" : "=h"(v) : "r"(row + d * 2)); return __uint_as_float((uint32_t)v << 16); };
_Pragma(STR(unroll RF_U))
    for (int i = 0; i < 5; i++) {
        const int ch = t + 4 * i;
        uint32_t u[4][4];
        lds128(u[0], row + ch * 16); lds128(u[1], row + (39 - ch) * 16); lds128(u[2], row + (40 + ch) * 16); lds128(u[3], row + (79 - ch) * 16);
        const float nb0 = el(320 - 8 * ch), nb1 = el(ch ? 640 - 8 * ch : 0);
        float o[8];
#pragma unroll
        for (int q = 0; q < 8; q++) {
            const int m = (8 - q) >> 1;
            const float e0 = (q & 1) ? bf_hi(u[0][q >> 1]) : bf_lo(u[0][q >> 1]), e2 = (q & 1) ? bf_hi(u[2][q >> 1]) : bf_lo(u[2][q >> 1]);
            const float e1 = q == 0 ? nb0 : (q & 1) ? bf_hi(u[1][m & 3]) : bf_lo(u[1][m & 3]), e3 = q == 0 ? nb1 : (q & 1) ? bf_hi(u[3][m & 3]) : bf_lo(u[3][m & 3]);
            o[q] = fmaf(e3, r3, fmaf(e2, r2, fmaf(e1, r1, fmaf(e0, r, off))));
        }
        if (ch == 0) o[0] *= 0.5f;
        sts128(aa + ch * 1024, pack_h(o[0], o[1]), pack_h(o[2], o[3]), pack_h(o[4], o[5]), pack_h(o[6], o[7]));
    }
    if (t < 2) sts128(aa + (20 + t) * 1024, t == 0 ? pack_h(fmaf(el(480), r2, fmaf(el(160), r, 0.5f * off)), 0.f) : 0u, 0u, 0u, 0u);
    fence_async_smem();
    __syncthreads();
    if (!first) mbar_wait(sb + RF_BAR + 64, 0);
    else if (a == 0 && tid == 0) { bulk_s2g(g_rtab + gq * RF_A, sb, RF_A); bulk_commit(); }
    const int wg = w >> 2;
    float acc[44];
    uint64_t da = mkdesc(sb + RF_A, 1024, 128, 0), db = mkdesc(sb + wg * 1408, 2816, 128, 0);
    wg_fence();
#pragma unroll 1
    for (int k = 0; k < 11; k++) { wg_n88_ss(acc, da, db, k); da += 128; db += 352; }
    wg_commit(); wg_wait<0>();
    const uint32_t stg = sb + RF_X + wg * 96 * 144;
#pragma unroll
    for (int j = 0; j < 12; j += 2) {
        const int m = lane >> 3, j1 = j < 10 ? j + 1 : j;
        stsm4t(stg + ((j + (m >> 1)) * 8 + (lane & 7)) * 144 + ((w & 3) * 16 + (m & 1) * 8) * 2, pack_h(acc[j * 4], acc[j * 4 + 1]),
               pack_h(acc[j * 4 + 2], acc[j * 4 + 3]), pack_h(acc[j1 * 4], acc[j1 * 4 + 1]), pack_h(acc[j1 * 4 + 2], acc[j1 * 4 + 3]));
    }
    bar_sync(1 + wg, 128);
#pragma unroll 3
    for (int rr = (tid & 127) >> 3; rr < 88; rr += 16) {
        const int ch = tid & 7, c = 2 * (wg * 88 + rr) + (gq & 1);
        if (c <= 320 - (gq >> 1) && (c | (gq ^ 2))) {
            uint32_t u[4];
            lds128(u, stg + rr * 144 + ch * 16);
            ((uint4*)g_UT)[((size_t)(c == 320 ? 1 : 2 * c + (gq >> 1)) * 32 + a) * 8 + (ch ^ (a & 7))] = make_uint4(u[0], u[1], u[2], u[3]);
        }
    }
    if (first && blockIdx.x < 4 && tid == 0) asm volatile("cp.async.bulk.wait_group.read 0;" ::: "memory");
    TL(first ? 4 : 18);
}

constexpr int GST = 4, GSTB = 32768 + 20480, GNC = 32;
constexpr int G_BAR = GST * GSTB + 3072;
#define GPACE 1100
#define GPACE2 650
__device__ __forceinline__ void oproj_load(const uint32_t sb, const int op, const int mb, const int nb, const int c0, const uint32_t pace) {
    const int by = op == 2 ? 20480 : 16384;
    const char* src = op == 2 ? (const char*)g_wot + (size_t)nb * GNC * 20480 : (const char*)g_O + (size_t)(2 * mb + op) * GNC * 16384;
    uint32_t t0 = clock32() - pace + op * (pace / 3);
#pragma unroll 1
    for (int c = c0; c < c0 + GNC; c++, src += by) {
        const int st = c % GST;
        if (c >= GST) mbar_wait(sb + G_BAR + (GST + st) * 8, ((c / GST) - 1) & 1);
        while (clock32() - t0 < pace) {}
        t0 = clock32();
        const int by_ = by;
        mbar_expect(sb + G_BAR + st * 8, by_);
        if (op == 2) bulk_g2s(sb + st * GSTB + 32768, src, by_, sb + G_BAR + st * 8);
        else bulk_g2s_last(sb + st * GSTB + op * 16384, src, by_, sb + G_BAR + st * 8);
    }
}
__device__ __forceinline__ void oproj_mma(const uint32_t sb, const int mb, const int nb, const int c0, const bf16* res, bf16* out, const int layer) {
    const int w = threadIdx.x >> 5, lane = threadIdx.x & 31, wg = w >> 2;
    float acc[40];
    uint4 rv[5];
#pragma unroll 1
    for (int c = c0; c < c0 + GNC; c++) {
        const int st = c % GST;
        mbar_wait(sb + G_BAR + st * 8, (c / GST) & 1);
        const uint32_t d = sb + st * GSTB;
        wg_fence();
#pragma unroll
        for (int k = 0; k < 8; k++)
            wg_n80_ss(acc, mkdesc(d + wg * 16384 + k * 2048, 1024, 128, 0), mkdesc(d + 32768 + k * 2560, 1280, 128, 0), (c - c0) | k);
        wg_commit();
        if (c > c0) {
            wg_wait<1>();
            if (lane == 0) mbar_arrive(sb + G_BAR + (GST + (c - 1) % GST) * 8);
        }
    }
#pragma unroll
    for (int i = 0; i < 5; i++) {
        const int id = i * 32 + lane, r = id / 10;
        rv[i] = __ldcg((const uint4*)res + (size_t)(mb * 128 + w * 16 + r) * 80 + nb * 10 + id - r * 10);
    }
    wg_wait<0>();
    bar_sync(5, 256);
    const uint32_t stg = sb + (GST - 1) * GSTB + w * 16 * 176;
#pragma unroll
    for (int j = 0; j < 5; j++)
        stsm4(stg + (lane & 15) * 176 + (2 * j + (lane >> 4)) * 16, pack_bf(acc[j * 8], acc[j * 8 + 1]), pack_bf(acc[j * 8 + 2], acc[j * 8 + 3]),
              pack_bf(acc[j * 8 + 4], acc[j * 8 + 5]), pack_bf(acc[j * 8 + 6], acc[j * 8 + 7]));
    __syncwarp();
#pragma unroll
    for (int i = 0; i < 5; i++) {
        const int id = i * 32 + lane, r = id / 10, ch = id - r * 10;
        uint32_t y[4];
        lds128(y, stg + r * 176 + ch * 16);
        ((uint4*)out)[(size_t)(mb * 128 + w * 16 + r) * 80 + nb * 10 + ch] = add_bf8(rv[i], y);
    }
    fence_async_smem();
    __syncwarp();
    if (lane == 0) {
        mbar_arrive(sb + G_BAR + (2 * GST - 1) * 8);
        if (layer == 0) red_release(g_flag + F_R + 2 * mb + wg);
    }
}

__global__ void __launch_bounds__(128, 4) k_col(const int first) {
    __shared__ __align__(1024) char sz[8192];
    __shared__ __align__(1024) char stab[24576];
    __shared__ __align__(1024) char swf[8192];
    __shared__ __align__(8) uint64_t bar[2];
    const int tid = threadIdx.x, wl = tid >> 5, lane = tid & 31, g = lane >> 2, t = lane & 3;
    const int c = blockIdx.x;
    TL(first ? 5 : 19);
    const bool realc = c == 0 || c == 320;
    const uint32_t z = smem_u32(sz), b2 = smem_u32(stab), a1 = b2 + 16384, wf = smem_u32(swf), mb = smem_u32(bar);
    if (tid == 0) { mbar_init(mb, 1); mbar_init(mb + 8, 1); fence_async_smem(); }
    if (realc) {
        for (int i = tid; i < 256; i += 128) sts128(z + 4096 + i * 16, 0, 0, 0, 0);
        fence_async_smem();
    }
    const int k1 = wl * 8 + g;
    float tc[16], ts[16];
#pragma unroll
    for (int j = 0; j < 16; j++) {
        const int p = ((j >> 1) * 8 + 2 * t + (j & 1)) * k1;
        __sincosf((float)(p - 1024) * 0.003067961575771282f, &ts[j], &tc[j]);
        ts[j] = -ts[j]; tc[j] = -tc[j];
    }
    if (first && tid == 32) { wait_flag<400>(g_ready, NSETUP); fence_async_glb(); }
    __syncthreads();
    if (tid == 32) {
        mbar_expect(mb + 8, 24576 + 8192);
        bulk_g2s(b2, g_ctab, 24576, mb + 8);
        bulk_g2s(wf, g_Wf + (size_t)c * 2048, 8192, mb + 8);
    }
    float inv;
    const float wsc = pow2_scale(wfilter_max(lane), 0, &inv) * (realc ? 0.0625f : 0.125f);
    pdl_wait();
    TL(first ? 6 : 20);
    if (tid == 0) {
        const int by = realc ? 4096 : 8192;
        mbar_expect(mb, by);
        bulk_g2s_last(z, (const char*)g_UT + (size_t)(c == 320 ? 1 : 2 * c) * 4096, by, mb);
    }
    pdl_go();
    mbar_wait(mb + 8, 0);
    mbar_wait(mb, 0);
    float d[64];
    uint32_t a[4][4];
    wg_fence();
#pragma unroll
    for (int ks = 0; ks < 4; ks++) wg_n64_ss_tb<0>(d, mkdesc(a1 + ks * 2048, 1024, 128, 0), mkdesc(z + ks * 2048, 1024, 1024, 1), ks);
    wg_commit(); wg_wait<0>();
    const float r32 = 0.17677669529663687f;
#pragma unroll
    for (int j = 0; j < 8; j++) {
        float yr[2], yi[2];
#pragma unroll
        for (int e = 0; e < 2; e++) {
            const float re = d[j * 4 + e] * r32, im = d[j * 4 + 2 + e] * r32, cc = tc[j * 2 + e], ss = ts[j * 2 + e];
            yr[e] = re * cc + im * ss; yi[e] = im * cc - re * ss;
        }
        a[j >> 1][(j & 1) * 2] = pack_h(yr[0], yr[1]); a[j >> 1][(j & 1) * 2 + 1] = pack_h(yi[0], yi[1]);
    }
    wg_fence();
#pragma unroll
    for (int ks = 0; ks < 4; ks++) wg_n128_rs(d, a[ks], mkdesc(b2 + ks * 4096, 2048, 128, 0), ks);
    wg_commit(); wg_wait<0>();
#pragma unroll
    for (int q = 0; q < 4; q++) {
        uint32_t wv[4];
        lds128(wv, wf + tid * 64 + ((q ^ (tid >> 1)) & 3) * 16);
#pragma unroll
        for (int jj = 0; jj < 2; jj++) {
            const int j = 2 * q + jj;
            float yr[2], yi[2];
#pragma unroll
            for (int e = 0; e < 2; e++) {
                const float xr = d[j * 4 + e] + d[32 + j * 4 + 2 + e], xi = d[j * 4 + 2 + e] - d[32 + j * 4 + e];
                const float fr = bf_lo(wv[jj * 2 + e]) * wsc, fi = bf_hi(wv[jj * 2 + e]) * wsc;
                yr[e] = xr * fr - xi * fi; yi[e] = xr * fi + xi * fr;
            }
            a[q][jj * 2] = pack_h(yr[0], yr[1]); a[q][jj * 2 + 1] = pack_h(yi[0], yi[1]);
        }
    }
    wg_fence();
#pragma unroll
    for (int ks = 0; ks < 4; ks++) wg_n128_rs(d, a[ks], mkdesc(b2 + ks * 4096, 2048, 128, 0), ks);
    wg_commit(); wg_wait<0>();
#pragma unroll
    for (int j = 0; j < 8; j++) {
        float yr[2], yi[2];
#pragma unroll
        for (int e = 0; e < 2; e++) {
            const float vr = (d[j * 4 + e] - d[32 + j * 4 + 2 + e]) * 0.125f, vi = (d[j * 4 + 2 + e] + d[32 + j * 4 + e]) * 0.125f;
            const float cc = tc[j * 2 + e], ss = ts[j * 2 + e];
            yr[e] = vr * cc - vi * ss; yi[e] = vi * cc + vr * ss;
        }
        a[j >> 1][(j & 1) * 2] = pack_h(yr[0], yr[1]); a[j >> 1][(j & 1) * 2 + 1] = pack_h(yi[0], yi[1]);
    }
    __syncthreads();
    const int mm = lane >> 3, rr = lane & 7;
    const uint32_t rowo = (wl * 16 + (mm & 1) * 8 + rr) * 128;
#pragma unroll
    for (int q = 0; q < 4; q++) stsm4(z + rowo + (((2 * q + (mm >> 1)) ^ rr) << 4), a[q][0], a[q][1], a[q][2], a[q][3]);
    fence_async_smem();
    __syncthreads();
    wg_fence();
#pragma unroll
    for (int ks = 0; ks < 4; ks++) wg_n64_ss_tb<1>(d, mkdesc(a1 + ks * 256, 128, 1024, 0), mkdesc(z + ks * 2048, 1024, 1024, 1), ks);
    wg_commit(); wg_wait<0>();
#pragma unroll
    for (int q = 0; q < 4; q++)
        stsm4(wf + rowo + (((2 * q + (mm >> 1)) ^ rr) << 4), pack_h(d[q * 8] * r32, d[q * 8 + 1] * r32), pack_h(d[q * 8 + 2] * r32, d[q * 8 + 3] * r32),
              pack_h(d[q * 8 + 4] * r32, d[q * 8 + 5] * r32), pack_h(d[q * 8 + 6] * r32, d[q * 8 + 7] * r32));
    __syncwarp();
    if (!(realc && wl >= 2)) {
        const int kk = c == 320 ? 320 : (c & 1) * 160 + (c >> 1) + (wl >> 1) * 320;
#pragma unroll
        for (int i = 0; i < 4; i++) {
            const int r = wl * 16 + i * 4 + (lane >> 3), ch = lane & 7;
            uint32_t v[4];
            lds128(v, wf + r * 128 + ((ch ^ (r & 7)) << 4));
            ((uint4*)g_YT)[((size_t)(r & 31) * 640 + kk) * 8 + (ch ^ (kk & 7))] = make_uint4(v[0], v[1], v[2], v[3]);
        }
    }
    TL(first ? 7 : 21);
}

constexpr int O_XS = 0;
constexpr int O_MS = 81920;
constexpr int O_QKP = O_MS + 10752;
constexpr int O_VM = O_QKP + 4096;
constexpr int O_SC = O_VM + 4096;
constexpr int O_OS = O_SC + 1536;
constexpr int O_XCH = O_OS + 2048;
constexpr int O_SUM = O_XCH + 8192;
constexpr int O_MX = O_SUM + 256;
constexpr int O_STG = O_MS + 65536 - 8192;
static_assert(O_STG - 16384 >= O_MX + 1024, "shared-memory map");
constexpr int O_WO = O_STG + 16384;
constexpr int O_SCL = O_WO + 65536;
constexpr int O_BAR = O_SCL + 64;
constexpr int B_XF = O_BAR, B_S = O_BAR + 16, B_VX = O_BAR + 32, B_STG = O_BAR + 48, B_FREE = O_BAR + 72;
constexpr int T_FA = O_BAR + 96, T_EA = T_FA + 32, T_FB = T_EA + 32, T_EB = T_FB + 56, T_RED = T_EB + 32;
constexpr int O_WMX = O_BAR + 512, B_W = O_BAR + 64;
constexpr int O_LAST = (O_WMX + 192 + 1023) / 1024 * 1024;
constexpr int CH_SMEM = O_LAST + 8192;
static_assert(O_WO == 19 * 8192, "weight staging");
__device__ __forceinline__ uint32_t tail_b(int c) { return c % 7 < 4 ? O_XS + (c % 7) * 20480 : O_WO + (c % 7 - 4) * 20480; }
__device__ __forceinline__ int s_tx(int c) { return c == 2 ? 2 * 768 : 768 + 2048; }

#define NPERM 1
#define NWO0 1
#define NWO0B 4
#define NWO1 6
#define TDELAY 800
#define WDEPTH 6
#define RDELAY 580

#define STAMP(i)

#define NTA 23
#define NTB 26
template <int LO, int HI>
__device__ __forceinline__ void tok_issue(const uint32_t (&A0)[20][4], const uint32_t (&A1)[20][4], float (&b0)[16], float (&b1)[16], uint32_t xd,
                                          const uint32_t zero) {
    if (LO == 0) wg_fence();
    sfor<HI - LO>([&](auto I) {
        constexpr int i = LO + I;
        if constexpr (i < 20) wg_n32_x<i * 64, i>(b0, A0[i], xd); else wg_n32_x<(i - 20) * 64, i - 20>(b1, A1[i - 20], xd + zero);
        if constexpr (i == 19 || i == NTB - 1 || i == 39) wg_commit();
    });
}
__device__ __forceinline__ void tok_give(const float (&b0)[16], const uint32_t L16, const uint32_t xch0) {
    wg_wait<1>();
    sfor<2>([&](auto I) {
        constexpr int i = I;
        sts128_u<i * 512>(L16, xch0, pack_h(b0[8 * i], b0[8 * i + 1]), pack_h(b0[8 * i + 2], b0[8 * i + 3]), pack_h(b0[8 * i + 4], b0[8 * i + 5]),
                          pack_h(b0[8 * i + 6], b0[8 * i + 7]));
    });
}
__device__ __forceinline__ void tok_finish(float (&b1)[16], const uint32_t (&e)[2][4], const uint32_t L16, const uint32_t dst, const uint32_t idn) {
#pragma unroll
    for (int j = 0; j < 4; j++)
        asm volatile("mma.sync.aligned.m16n8k8.row.col.f32.f16.f16.f32 {%0,%1,%2,%3},{%4,%5},{%6},{%0,%1,%2,%3};"
                     : F4(b1, 4 * j) : "r"(e[j >> 1][(j & 1) * 2]), "r"(e[j >> 1][(j & 1) * 2 + 1]), "r"(idn));
    stsm4_u<0>(L16, dst, pack_bf(b1[0], b1[1]), pack_bf(b1[2], b1[3]), pack_bf(b1[4], b1[5]), pack_bf(b1[6], b1[7]));
    stsm4_u<512>(L16, dst, pack_bf(b1[8], b1[9]), pack_bf(b1[10], b1[11]), pack_bf(b1[12], b1[13]), pack_bf(b1[14], b1[15]));
}
__device__ __forceinline__ uint32_t uni(uint32_t v) { return __shfl_sync(~0u, v, 0); }
__device__ __forceinline__ uint32_t badd(uint32_t a, uint32_t b) { uint32_t r; asm("add.rn.bf16x2 %0,%1,%2;" : "=r"(r) : "r"(a), "r"(b)); return r; }
__device__ __forceinline__ uint32_t bmax(uint32_t a, uint32_t b) { uint32_t r; asm("max.bf16x2 %0,%1,%2;" : "=r"(r) : "r"(a), "r"(b)); return r; }
__device__ __forceinline__ uint32_t babsmax(uint32_t a, uint32_t b) { uint32_t r; asm("max.xorsign.abs.bf16x2 %0,%1,%2;" : "=r"(r) : "r"(a), "r"(b)); return r; }
__device__ __forceinline__ uint32_t habsmax(uint32_t a, uint32_t b) { uint32_t r; asm("max.xorsign.abs.f16x2 %0,%1,%2;" : "=r"(r) : "r"(a), "r"(b)); return r; }

template <int NPF>
__device__ __forceinline__ float mem_out(const uint32_t sb, const uint32_t L16, const uint32_t L8, uint32_t (&wo)[16][4], const uint32_t woa,
                                         char* dst, const bool odd) {
    bar_sync(2, 352);
    float a[4][4];
#pragma unroll
    for (int i = 0; i < 4; i++) a[i][0] = a[i][1] = a[i][2] = a[i][3] = 0.f;
    uint32_t ob[4][4], sm_[2], sc[2];
    sfor<8>([&](auto I) {
        constexpr int i = I;
        if constexpr (!(i & 1)) ldsm4t_u<O_OS + (i >> 1) * 512>(ob[i >> 1], L16, sb);
        if constexpr (i >= NPF) { ldsm4t(wo[i], woa + i * 1024); ldsm4t(wo[8 + i], (woa ^ 32) + i * 1024); }
    });
    lds64_u<O_SUM>(sm_, L8 & 24, sb); lds64(sc, sb + O_SCL);
#pragma unroll
    for (int i = 0; i < 8; i++) {
        mma_bf(a[i & 1], wo[i][0], wo[i][1], wo[i][2], wo[i][3], ob[i >> 1][(i & 1) * 2], ob[i >> 1][(i & 1) * 2 + 1]);
        mma_bf(a[2 + (i & 1)], wo[8 + i][0], wo[8 + i][1], wo[8 + i][2], wo[8 + i][3], ob[i >> 1][(i & 1) * 2], ob[i >> 1][(i & 1) * 2 + 1]);
    }
    const float f0 = rcp(__uint_as_float(sm_[0])) * __uint_as_float(sc[0]), f1 = rcp(__uint_as_float(sm_[1])) * __uint_as_float(sc[0]);
    red_h8(dst, pack_h((a[0][0] + a[1][0]) * f0, (a[0][1] + a[1][1]) * f1), pack_h((a[0][2] + a[1][2]) * f0, (a[0][3] + a[1][3]) * f1),
           pack_h((a[2][0] + a[3][0]) * f0, (a[2][1] + a[3][1]) * f1), pack_h(odd ? (a[2][3] + a[3][3]) * f1 : (a[2][2] + a[3][2]) * f0, 1.f));
    return __uint_as_float(sc[1]);
}

template <int layer> __device__ __forceinline__ void chain_mma(const uint32_t sb, const int c, const int h, const uint32_t zero, const bf16* __restrict__ Wq,
                                          const bf16* __restrict__ Wk, const bf16* __restrict__ Wv, const bf16* __restrict__ Wo,
                                          const bf16* res, bf16* out) {
    int tid = read_tid(), lane = tid & 31;
    const int w = __shfl_sync(~0u, tid >> 5, 0), wg = w >> 2;
    [[maybe_unused]] const int cta = h * 3 + c;
    uint32_t A0[20][4], A1[20][4];
    const int t0 = (w & 3) + wg * 4, t1 = t0 ^ 4;
    float sl;
    {
        const int tl = tid & 127, r = tl >> 3, ch = tl & 7;
        const size_t so = (size_t)(wg * 320 + r) * 4096 + h * 128 + ch * 8;
        const bf16 *wa = (c == 2 ? Wv : Wq + c * 64) + so, *wb = (c == 2 ? Wv + 64 : Wk + c * 64) + so;
        const uint32_t ring = sb + wg * 4096;
        const uint32_t dst = ring + r * 128 + ((ch ^ r) & 7) * 16;
        const uint32_t src = ring + ((lane & 7) + (lane >> 4) * 8) * 128 + ((((w & 3) * 2 + ((lane >> 3) & 1)) ^ lane) & 7) * 16;
        const int q4 = lane & 3, gr = (c * 2 + ((w >> 1) & 1)) * 56 + (q4 == 3 ? 24 : (w & 1) * 32 + q4 * 8);
        const bf16* wo_ = Wo + (size_t)(h * 128 + (lane >> 2)) * 640 + wg * 320 + min(gr, 312);
        const uint32_t wdst = sb + O_WO + w * 8192 + (lane >> 2) * 64 + ((q4 ^ (lane >> 3)) & 3) * 16;
        auto issue = [&](int i) {
            if (i < 20) {
                const uint32_t d = dst + (i < 19 ? i * 8192 : O_LAST);
                cp_async16(d, wa + (size_t)i * 65536); cp_async16(d + 2048, wb + (size_t)i * 65536);
                if (i < 16) cp_async16(wdst + i * 512, wo_ + i * 5120, gr < 320 ? 16 : 0);
            }
            cp_commit();
        };
#pragma unroll 1
        for (int i = 0; i < WDEPTH; i++) issue(i);
        asm volatile("barrier.cluster.arrive.relaxed.aligned;" ::: "memory");
        float fa, fb;
        if (layer == 0) {
            uint32_t ma = 0, mb = 0;
#pragma unroll 1
            for (int i = 0; i < 20; i++) {
                issue(i + WDEPTH);
                cp_wait<WDEPTH>();
                const uint32_t d = dst + (i < 19 ? i * 8192 : O_LAST);
                uint32_t u[8];
                lds128(u, d); lds128(u + 4, d + 2048);
                ma = babsmax(babsmax(ma, babsmax(u[0], u[1])), babsmax(u[2], u[3])); mb = babsmax(babsmax(mb, babsmax(u[4], u[5])), babsmax(u[6], u[7]));
            }
            ma = __reduce_max_sync(~0u, max(ma & 0x7fffu, (ma >> 16) & 0x7fffu)); mb = __reduce_max_sync(~0u, max(mb & 0x7fffu, (mb >> 16) & 0x7fffu));
            asm volatile("barrier.cluster.wait.aligned;" ::: "memory");
            if (lane < 3)
                asm volatile("st.async.shared::cluster.mbarrier::complete_tx::bytes.v2.b32 [%0],{%1,%2},[%3];"
                             ::"r"(mapa(sb + O_WMX + (c * 8 + w) * 8, lane)), "r"(ma), "r"(mb), "r"(mapa(sb + B_W, lane)) : "memory");
            __syncwarp();
            {
                uint32_t off[4];
                float cs[4] = {0.f, 0.f, 0.f, 0.f};
#pragma unroll
                for (int q = 0; q < 4; q++) {
                    const int g_ = (c * 2 + ((w >> 1) & 1)) * 56 + (q == 3 ? 24 : (w & 1) * 32 + q * 8), col = wg * 320 + g_, nb = col / 80;
                    off[q] = g_ < 320 && !(q == 3 && (w & 1)) ? ((nb * 512 + h * 16) * 10 + (col - nb * 80) / 8) * 32 + lane : ~0u;
                }
                const uint32_t ta = sb + O_WO + w * 8192 + (lane & 7) * 64 + (((lane >> 3) ^ (lane >> 1)) & 3) * 16;
#pragma unroll 2
                for (int i = 0; i < 16; i++) {
                    uint32_t r[4];
                    ldsm4t(r, ta + i * 512);
#pragma unroll
                    for (int q = 0; q < 4; q++) {
                        if (off[q] != ~0u) ((uint32_t*)g_wot)[off[q] + i * 320] = r[q];
                        cs[q] += fabsf(bf_lo(r[q])) + fabsf(bf_hi(r[q]));
                    }
                }
                float cm = 0.f;
#pragma unroll
                for (int q = 0; q < 4; q++) {
                    cs[q] += __shfl_xor_sync(~0u, cs[q], 1); cs[q] += __shfl_xor_sync(~0u, cs[q], 2);
                    cm = fmaxf(cm, cs[q]);
                }
                const uint32_t n1 = __reduce_max_sync(~0u, __float_as_uint(cm));
                if (lane == 0) g_co[h * 32 + c * 8 + w] = __uint_as_float(n1);
            }
            mbar_wait(sb + B_W, 0);
            uint32_t v[2];
            lds64(v, sb + O_WMX + (lane < 24 ? lane : 0) * 8);
            const bool mine = (lane >> 3) < 3 && ((lane >> 4) == 1) == (c == 2);
            ma = __reduce_max_sync(~0u, mine ? v[0] : 0u); mb = __reduce_max_sync(~0u, mine ? v[1] : 0u);
            if (c == 2) ma = mb = max(ma, mb);
            fa = __uint_as_float(ma << 16); fb = __uint_as_float(mb << 16);
            if (tid == 0) {
                if (c != 1) g_wmx[h * 3 + c] = fa;
                if (c == 0) g_wmx[h * 3 + 1] = fb;
            }
        } else {
            fa = __ldcg(g_wmx + h * 3 + (c == 2 ? 2 : 0)); fb = __ldcg(g_wmx + h * 3 + (c == 2 ? 2 : 1));
            asm volatile("barrier.cluster.wait.aligned;" ::: "memory");
        }
        if (layer == TLL) TL(49);
        float ia, ib;
        const float sa = pow2_scale(fa, 6, &ia), sc_b = pow2_scale(fb, 6, &ib);
        sl = __uint_as_float(uni(__float_as_uint(ia * ib * (0.08838834764831845f * 1.4426950408889634f))));
        const uint32_t pa = pack_bf(sa, sa), pb = pack_bf(sc_b, sc_b);
        const int ahead = layer == 0 ? 20 : WDEPTH;
        auto convert = [&](int lo) {
#pragma unroll 1
            for (int i = lo; i < lo + 10; i++) {
                issue(i + ahead);
                cp_wait<WDEPTH>();
                const uint32_t d = dst + (i < 19 ? i * 8192 : O_LAST);
                uint32_t u[8];
                lds128(u, d); lds128(u + 4, d + 2048);
#pragma unroll
                for (int q = 0; q < 8; q++)
                    asm("{.reg .b32 m,l,u; mul.rn.bf16x2 m,%0,%1; shl.b32 l,m,16; and.b32 u,m,0xffff0000; cvt.rn.f16x2.f32 %0,u,l;}" : "+r"(u[q]) : "r"(q < 4 ? pa : pb));
                sts128(d, u[0], u[1], u[2], u[3]); sts128(d + 2048, u[4], u[5], u[6], u[7]);
            }
            bar_sync(6 + wg, 128);
        };
        const uint32_t s0 = src + wg * 2048, s1 = src + 2048 - wg * 2048;
        convert(0);
#pragma unroll
        for (int i = 0; i < 10; i++) { ldsm4t(A0[i], s0 + i * 8192); ldsm4t(A1[i], s1 + i * 8192); }
        if (layer == TLL) TL(50);
        convert(10);
#pragma unroll
        for (int i = 10; i < 20; i++) { ldsm4t(A0[i], s0 + (i < 19 ? i * 8192 : O_LAST)); ldsm4t(A1[i], s1 + (i < 19 ? i * 8192 : O_LAST)); }
        if (layer == TLL) TL(53);
        bar_arrive(9, 288);
        bar_sync(4, 288);
        asm volatile("barrier.cluster.arrive.relaxed.aligned;" ::: "memory");
    }
    const uint32_t idn = (lane >> 3) == (lane & 3) ? ((lane & 4) ? 0x3c000000u : 0x3c00u) : 0u;
    float invM = g_invM0;
    char* redp = red_base() + (size_t)layer * 32 * 32768 + w * 2048 + (lane >> 4) * 1024 + ((lane >> 3) & 1) * 256 + (lane & 7) * 16;
    const uint32_t ro2 = uni((w >> 1) * 4096 + 128), rown = uni(c == 2 ? ro2 : c * 16384);
    const uint32_t L16 = lane * 16, L8 = lane * 8, L4 = lane * 4;
    const uint32_t xch0 = uni(sb + O_XCH + t0 * 1024), xch1 = uni(sb + O_XCH + t1 * 1024);
    const uint32_t qo0 = uni(sb + O_QKP + (w & 3) * 1024 + (wg ? 768 : 0)), qp0 = uni(qo0 + (wg ? 128 : 256));
    const uint32_t qo1 = uni(sb + O_QKP + (w & 3) * 1024 + (wg ? 128 : 512)), qp1 = uni(qo1 + (wg ? 256 : 128));
    const uint32_t vo1 = uni(qo1 + (wg ? -128 : 256)), vp1 = uni(qp1 + (wg ? -128 : 256));
    const uint32_t msr = uni(sb + O_MS + wg * 5376);
    const uint32_t msw = uni(msr + ((w >> 1) & 1) * 896 + (w & 1) * 512), msh = uni(msr + ((w >> 1) & 1) * 896 + 384 + (w & 1) * 2);
    const uint32_t sco = uni(sb + O_SC + c * 768 + (w & 3) * 256);
    const uint32_t woa = sb + O_WO + w * 8192 + (lane >> 4) * 512 + (lane & 7) * 64 + (((lane >> 3) ^ (lane >> 1)) & 1) * 16 + ((lane >> 2) & 1) * 32;
    const uint32_t w512 = uni(sb + w * 512), w128 = uni(sb + w * 128);
    const uint32_t pd0 = uni(mapa(sb, c == 2 ? 0 : 2) - sb), pd1 = uni(mapa(sb, c == 1 ? 0 : 1) - sb);
    const bool scw = c < 2 && w >= 4 && w <= 6;
    uint32_t sn = uni(sb + O_STG + (c == 2 ? 8192 : 0) + t1 * 1024);
    uint32_t ka = uni(sb + (w == 6 ? O_QKP + 512 : O_STG + 4096 + (w & 1) * 512));
    uint32_t vs = uni(sb + O_VM + t1 * 256);
    uint32_t va = uni(sb + O_STG + 8192 + w * 2048), vr = uni(sb + O_VM + w * 512);
    const uint32_t sn2 = uni(2 * sn - 16384), ka2 = uni(2 * ka - (w == 6 ? 0 : 16384)), vs2 = uni(2 * vs + 2048), va2 = uni(2 * va - 16384),
                   vr2 = uni(2 * vr + 2048);
    uint32_t xd = uni((uint32_t)mkdesc(sb + O_XS + wg * 20480, 512, 128, 0));
    const uint32_t xd2 = uni(2 * xd + 2560);

    uint32_t wp[2 * NPERM + 1][4];
    sfor<NPERM>([&](auto I) { constexpr int i = I; ldsm4t(wp[2 * i], woa + i * 1024); ldsm4t(wp[2 * i + 1], (woa ^ 32) + i * 1024); });
    auto wo_fetch = [&](uint32_t (&wo)[16][4], auto I) {
        constexpr int i = I;
        if constexpr (i < NPERM) {
#pragma unroll
            for (int q = 0; q < 4; q++) { wo[i][q] = wp[2 * i][q]; wo[8 + i][q] = wp[2 * i + 1][q]; }
        } else { ldsm4t(wo[i], woa + i * 1024); ldsm4t(wo[8 + i], (woa ^ 32) + i * 1024); }
    };
    if (layer == TLL) TL(32);
    float b0[16], b1[16];
    mbar_wait(sb + B_XF, 0);
    if (layer == TLL) TL(33);
    tok_issue<0, NTB>(A0, A1, b0, b1, xd, zero);
    tok_give(b0, L16, xch0);
    tok_issue<NTB, 40>(A0, A1, b0, b1, xd, zero);
    bar_sync(4, 256);
    wg_wait<0>();
    {
        uint32_t e[2][4];
        lds128_u<0>(e[0], L16, xch1); lds128_u<512>(e[1], L16, xch1);
        tok_finish(b1, e, L16, sn, idn);
    }
    sn = sn2 - sn; xd = xd2 - xd;
    bar_sync(5, 288);
    asm volatile("barrier.cluster.wait.aligned;" ::: "memory");
    if (layer == TLL) TL(34);
    mbar_wait(sb + B_XF + 8, 0);
    if (layer == TLL) TL(35);
    tok_issue<0, NTA>(A0, A1, b0, b1, xd, zero);
    uint32_t tr = clock32() - RDELAY;

#pragma unroll 1
    for (int st = 0;; st++) {
        uint4 mv[3];
        asm volatile("{.reg .pred p; .reg .b32 t;\n"
                     "mov.b32 %0,0; mov.b32 %1,0; mov.b32 %2,0; mov.b32 %3,0; mov.b32 %4,0; mov.b32 %5,0; mov.b32 %6,0; mov.b32 %7,0;\n"
                     "mov.b32 %8,0; mov.b32 %9,0; mov.b32 %10,0; mov.b32 %11,0;\n"
                     "T_LOOP: mov.u32 t,%%clock; sub.u32 t,t,%14; setp.ge.u32 p,t,%15;\n"
                     "@p ld.relaxed.gpu.global.v4.u32 {%0,%1,%2,%3},[%12]; @p ld.relaxed.gpu.global.v4.u32 {%4,%5,%6,%7},[%12+16384];\n"
                     "@p ld.relaxed.gpu.global.v4.u32 {%8,%9,%10,%11},[%13];\n"
                     "@!p bra T_LOOP;}"
                     : "=r"(mv[0].x), "=r"(mv[0].y), "=r"(mv[0].z), "=r"(mv[0].w), "=r"(mv[1].x), "=r"(mv[1].y), "=r"(mv[1].z), "=r"(mv[1].w),
                       "=r"(mv[2].x), "=r"(mv[2].y), "=r"(mv[2].z), "=r"(mv[2].w)
                     : "l"(redp), "l"(redp + ro2), "r"(tr), "n"(RDELAY) : "memory");
        STAMP(10);
        tok_issue<NTA, NTB>(A0, A1, b0, b1, xd, zero);
        tok_give(b0, L16, xch0);
        tok_issue<NTB, 40>(A0, A1, b0, b1, xd, zero);
        xd = xd2 - xd;
        STAMP(9);
        if (zero >> 30) break;
        asm volatile("{.reg .pred p; .reg .b32 a,h,t,n; .reg .b16 l,u; .reg .b64 q;\n"
                     "add.u32 a,%12,%13; add.u32 h,%12,%14; mov.u32 n,0;\n"
                     "M_LOOP:\n .pragma \"nounroll\";\n"
                     "st.shared.b32 [a],%0; st.shared.b32 [a+128],%1; st.shared.b32 [a+256],%2; mov.b32 {l,u},%3; st.shared.b16 [h],l;\n"
                     "st.shared.b32 [a+1792],%4; st.shared.b32 [a+1920],%5; st.shared.b32 [a+2048],%6; mov.b32 {l,u},%7; st.shared.b16 [h+1792],l;\n"
                     "st.shared.b32 [a+3584],%8; st.shared.b32 [a+3712],%9; st.shared.b32 [a+3840],%10; mov.b32 {l,u},%11; st.shared.b16 [h+3584],l;\n"
                     "lop3.b32 t,%3,%7,0x50000000,0x7e; lop3.b32 t,t,%11,0x50000000,0xf6; setp.gt.u32 p,t,0xffff;\n"
                     "vote.sync.any.pred p,p,-1; add.u32 n,n,1; setp.lt.and.u32 p,n,%17,p; @!p bra M_DONE;\n"
                     "ld.relaxed.gpu.global.v4.u32 {%0,%1,%2,%3},[%15]; ld.relaxed.gpu.global.v4.u32 {%4,%5,%6,%7},[%15+16384];\n"
                     "cvt.u64.u32 q,%16; add.u64 q,q,%15; ld.relaxed.gpu.global.v4.u32 {%8,%9,%10,%11},[q];\n"
                     "bra M_LOOP;\n"
                     "M_DONE:}"
                     : "+r"(mv[0].x), "+r"(mv[0].y), "+r"(mv[0].z), "+r"(mv[0].w), "+r"(mv[1].x), "+r"(mv[1].y), "+r"(mv[1].z), "+r"(mv[1].w),
                       "+r"(mv[2].x), "+r"(mv[2].y), "+r"(mv[2].z), "+r"(mv[2].w)
                     : "r"(L4), "r"(msw), "r"(msh), "l"(redp), "r"(ro2), "n"(SPIN_LIM) : "memory");
        bar_sync(3, 256);
        STAMP(0);
        uint32_t e[2][4];
        float f1[4];
        {
            uint32_t b[10][4];
            float acc[4][4];
#pragma unroll
            for (int i = 0; i < 4; i++) acc[i][0] = acc[i][1] = acc[i][2] = acc[i][3] = 0.f;
            auto ld = [&](auto I) { constexpr int i = I; ldsm4t_u<i * 512>(b[i], L16, msr); };
            auto mm = [&](auto I) {
                constexpr int i = I;
                mma_f16(acc[0], A0[2 * i], b[i][0], b[i][1]); mma_f16(acc[2], A1[2 * i], b[i][0], b[i][1]);
                mma_f16(acc[1], A0[2 * i + 1], b[i][2], b[i][3]); mma_f16(acc[3], A1[2 * i + 1], b[i][2], b[i][3]);
            };
            ld(IC<0>()); ld(IC<1>()); ld(IC<2>()); ld(IC<3>());
            sts32_u<O_MX>(L4, w128,
                          habsmax(habsmax(habsmax(habsmax(mv[0].x, mv[0].y), habsmax(mv[0].z, mv[1].x)), habsmax(habsmax(mv[1].y, mv[1].z), mv[2].x)),
                                  habsmax(habsmax(mv[2].y, mv[2].z), habsmax(habsmax(mv[0].w, mv[1].w), mv[2].w) & 0xffffu)));
            wg_wait<0>();
            ld(IC<4>()); mm(IC<0>()); ld(IC<5>()); mm(IC<1>()); ld(IC<6>()); mm(IC<2>());
            ld(IC<7>()); mm(IC<3>()); ld(IC<8>()); mm(IC<4>()); ld(IC<9>()); mm(IC<5>());
            lds128_u<0>(e[0], L16, xch1); lds128_u<512>(e[1], L16, xch1);
            mm(IC<6>()); mm(IC<7>()); mm(IC<8>()); mm(IC<9>());
            const uint32_t u0 = pack_bf((acc[0][0] + acc[1][0]) * invM, (acc[0][1] + acc[1][1]) * invM);
            const uint32_t u1 = pack_bf((acc[0][2] + acc[1][2]) * invM, (acc[0][3] + acc[1][3]) * invM);
#pragma unroll
            for (int i = 0; i < 4; i++) f1[i] = (acc[2][i] + acc[3][i]) * invM;
            sts32_u<0>(L4, qo0, u0); sts32_u<0>(L4, qp0, u1); sts32_u<0>(L4, qo1, pack_bf(f1[0], f1[1])); sts32_u<0>(L4, qp1, pack_bf(f1[2], f1[3]));
        }
        STAMP(1);
        bar_sync(1, 320);
        if (__builtin_expect(scw, 1)) {
            float a[4][4];
#pragma unroll
            for (int i = 0; i < 4; i++) a[i][0] = a[i][1] = a[i][2] = a[i][3] = 0.f;
            uint32_t q[4][4], k[4][4];
            sfor<4>([&](auto I) {
                constexpr int i = I;
                ldsm4t_u<O_QKP + i * 1024>(q[i], L16, sb); ldsm4t_u<i * 1024>(k[i], L16, ka);
            });
#pragma unroll
            for (int i = 0; i < 4; i++) {
                mma_bf(a[i & 1], q[i][0], q[i][1], q[i][2], q[i][3], k[i][0], k[i][1]);
                mma_bf(a[2 + (i & 1)], q[i][0], q[i][1], q[i][2], q[i][3], k[i][2], k[i][3]);
            }
            const float mk = w == 6 ? 1.f : 0.f;
            const float x0 = (a[0][0] + a[0][2]) + (a[1][0] + a[1][2]), x1 = (a[0][1] + a[0][3]) + (a[1][1] + a[1][3]);
            const float y0 = (a[2][0] + a[2][2]) + (a[3][0] + a[3][2]), y1 = (a[2][1] + a[2][3]) + (a[3][1] + a[3][3]);
            st_share2(L8, sco, sb + B_S, pd0, pd1, pack_bf(fmaf(y0, mk, x0) * sl, fmaf(y1, mk, x1) * sl), pack_bf(y0 * sl, y1 * sl));
        }
        if (c == 2) {
            const uint32_t x = lds32_u<0>(L4, vo1), y = lds32_u<0>(L4, vp1);
            st_share2(L8, vs, sb + B_S, pd0, pd1, pack_bf(f1[0] + bf_lo(x), f1[1] + bf_hi(x)), pack_bf(f1[2] + bf_lo(y), f1[3] + bf_hi(y)));
        }
        STAMP(3);
        if (st == NSEG - 1) break;
        tok_finish(b1, e, L16, sn, idn);
        redp += (st & 1) ? 32768 - 512 : 512;
        if (wg == 0) {
            uint32_t wo[16][4], vx[2][2][4], vm[2][2];
            ldsm4_u<0>(vx[0][0], L16, va); ldsm4_u<512>(vx[0][1], L16, va); ldsm4_u<1024>(vx[1][0], L16, va); ldsm4_u<1536>(vx[1][1], L16, va);
            sfor<NWO0>([&](auto I) { wo_fetch(wo, I); });
            mbar_wait(sb + B_S, st & 1);
            STAMP(4);
            uint32_t s[5];
            {
                uint32_t p[2][5];
                sfor<2>([&](auto R) {
                    constexpr int r = R;
                    lds64_u<O_SC + r * 768>(p[r], L8, sb); lds64_u<O_SC + r * 768 + 256>(p[r] + 2, L8, sb); p[r][4] = lds32_u<O_SC + r * 768 + 512>(L8, sb);
                });
#pragma unroll
                for (int j = 0; j < 5; j++) s[j] = badd(p[0][j], p[1][j]);
            }
            lds64_u<0>(vm[0], L8, vr); lds64_u<256>(vm[1], L8, vr);
            uint32_t mm = bmax(bmax(bmax(s[0], s[1]), bmax(s[2], s[3])), s[4]);
            mm = bmax(bmax(mm, __shfl_xor_sync(~0u, mm, 1)), bmax(__shfl_xor_sync(~0u, mm, 2), __shfl_xor_sync(~0u, mm, 3)));
            const float m = fmaxf(bf_lo(mm), bf_hi(mm));
            float o0[4] = {0.f, 0.f, 0.f, 0.f}, o1[4] = {0.f, 0.f, 0.f, 0.f}, d[10];
#pragma unroll
            for (int j = 0; j < 5; j++) { d[2 * j] = bf_lo(s[j]) - m; d[2 * j + 1] = bf_hi(s[j]) - m; }
#pragma unroll
            for (int j = 0; j < 10; j++) d[(j + 8) % 10] = ex2(d[(j + 8) % 10]);
            float sum = ((d[8] + d[9]) + (d[0] + d[1])) + ((d[2] + d[3]) + (d[4] + d[5])) + (d[6] + d[7]);
            const uint32_t p4 = pack_bf(d[8], d[9]), p0 = pack_bf(d[0], d[1]), p1 = pack_bf(d[2], d[3]), p2 = pack_bf(d[4], d[5]), p3 = pack_bf(d[6], d[7]);
            mma_bf8(o0, vm[0][0], vm[0][1], p4);
            mma_bf8(o1, vm[1][0], vm[1][1], p4);
            mma_bf(o0, vx[0][0][0], vx[0][0][1], vx[0][0][2], vx[0][0][3], p0, p1);
            mma_bf(o1, vx[1][0][0], vx[1][0][1], vx[1][0][2], vx[1][0][3], p0, p1);
            mma_bf(o0, vx[0][1][0], vx[0][1][1], vx[0][1][2], vx[0][1][3], p2, p3);
            mma_bf(o1, vx[1][1][0], vx[1][1][1], vx[1][1][2], vx[1][1][3], p2, p3);
            sfor<NWO0B - NWO0>([&](auto I) { constexpr int i = I; wo_fetch(wo, IC<NWO0 + i>()); });
            sum += __shfl_xor_sync(~0u, sum, 1);
            sum += __shfl_xor_sync(~0u, sum, 2);
            sts32_u<O_OS>(L4, w512, pack_bf(o0[0], o0[1])); sts32_u<O_OS + 128>(L4, w512, pack_bf(o0[2], o0[3]));
            sts32_u<O_OS + 256>(L4, w512, pack_bf(o1[0], o1[1])); sts32_u<O_OS + 384>(L4, w512, pack_bf(o1[2], o1[3]));
            sts32_u<O_SUM>(lane & 28, sb, __float_as_uint(sum));
            STAMP(5);
            invM = mem_out<NWO0B>(sb, L16, L8, wo, woa, redp + rown, w & 1);
            tr = clock32();

        } else {
            uint32_t wo[16][4];
            sfor<NWO1>([&](auto I) { wo_fetch(wo, I); });
            invM = mem_out<NWO1>(sb, L16, L8, wo, woa, redp + rown, w & 1);
            tr = clock32();

        }
        STAMP(7);
        tok_issue<0, NTA>(A0, A1, b0, b1, xd, zero);
        sn = sn2 - sn; ka = ka2 - ka; vs = vs2 - vs; va = va2 - va; vr = vr2 - vr;
        STAMP(8);
    }
    if (layer == TLL) TL(40);
    bar_arrive(8, 320);
    tid = read_tid(); lane = tid & 31;
    float acc[40];
    const int nc = c == 2 ? 10 : 11;
    const int mb = 28 + (h >> 3), nj = c == 2 ? 1 : 2;
    uint32_t rv[2][2];
    const size_t go = ((size_t)(mb * 64 + (w & 3) * 16 + (lane >> 2)) * 640 + (h & 7) * 80 + (wg * 5 + c * 2) * 8 + (lane & 3) * 2) >> 1;
#pragma unroll
    for (int u = 0; u < 4; u++) rv[u >> 1][u & 1] = (u >> 1) < nj ? __ldcg((const uint32_t*)res + go + (u >> 1) * 4 + (u & 1) * 2560) : 0u;
#pragma unroll 1
    for (int k = 0; k < nc; k++) {
        mbar_wait(sb + T_FB + (k % 7) * 8, k >= 7);
        mbar_wait(sb + T_FA + (k & 3) * 8, (k >> 2) & 1);
        if (layer == TLL && k == 0) TL(41);
        const uint64_t da = mkdesc(sb + O_MS + (k & 3) * 16384 + wg * 8192, 1024, 128, 0), db = mkdesc(sb + tail_b(k) + wg * 10240, 1280, 128, 0);
        wg_fence();
#pragma unroll
        for (int q = 0; q < 4; q++) wg_n80_ss(acc, da + q * 128, db + q * 160, k | q);
        wg_commit();
        if (k > 0) {
            wg_wait<1>();
            if (lane == 0) { mbar_arrive(sb + T_EA + ((k - 1) & 3) * 8); if (k <= 4) mbar_arrive(sb + T_EB + (k - 1) * 8); }
        }
    }
    if (layer == TLL) TL(52);
    wg_wait<0>();
    asm volatile("barrier.cluster.arrive.relaxed.aligned; barrier.cluster.wait.aligned;" ::: "memory");
    const uint32_t ra = sb + O_XS + tid * 16, rb = sb + O_MS + tid * 16;
#pragma unroll
    for (int j = 0; j < 5; j++) {
        const float* q = acc + 4 * j;
        sts128(rb + j * 4096, __float_as_uint(wg ? q[0] : q[20]), __float_as_uint(wg ? q[1] : q[21]), __float_as_uint(wg ? q[2] : q[22]), __float_as_uint(wg ? q[3] : q[23]));
    }
    bar_sync(4, 256);
#pragma unroll
    for (int j = 0; j < 5; j++) {
        const float* q = acc + 4 * j;
        uint32_t p[4];
        lds128(p, sb + O_MS + (tid ^ 128) * 16 + j * 4096);
        asm volatile("st.async.shared::cluster.mbarrier::complete_tx::bytes.v4.f32 [%0],{%1,%2,%3,%4},[%5];" ::"r"(mapa(ra + c * 8192 + (j & 1) * 4096, j >> 1)),
                     "f"((wg ? q[20] : q[0]) + __uint_as_float(p[0])), "f"((wg ? q[21] : q[1]) + __uint_as_float(p[1])),
                     "f"((wg ? q[22] : q[2]) + __uint_as_float(p[2])), "f"((wg ? q[23] : q[3]) + __uint_as_float(p[3])), "r"(mapa(sb + T_RED, j >> 1)) : "memory");
    }
    mbar_wait(sb + T_RED, 0);
#pragma unroll 1
    for (int u = 0; u < nj; u++) {
        uint32_t p[3][4];
#pragma unroll
        for (int q = 0; q < 3; q++) lds128(p[q], ra + q * 8192 + u * 4096);
        float y[4];
#pragma unroll
        for (int i = 0; i < 4; i++) y[i] = __uint_as_float(p[0][i]) + __uint_as_float(p[1][i]) + __uint_as_float(p[2][i]);
        ((uint32_t*)out)[go + u * 4] = bfma(pack_bf(y[0], y[1]), 0x3f803f80u, u ? rv[1][0] : rv[0][0]);
        ((uint32_t*)out)[go + u * 4 + 2560] = bfma(pack_bf(y[2], y[3]), 0x3f803f80u, u ? rv[1][1] : rv[0][1]);
    }
    __syncwarp();
    if (layer == 0 && lane == 0) red_release(g_flag + F_R + mb);
    TL(layer == 0 ? 15 : 29);
    asm volatile("barrier.cluster.arrive.relaxed.aligned; barrier.cluster.wait.aligned;" ::: "memory");
}

__device__ __forceinline__ void tail_load_b(const uint32_t sb, const int h, const int c, const int k) {
    mbar_expect(sb + T_FB + (k % 7) * 8, 20480);
    bulk_g2s(sb + tail_b(k), (const char*)g_wot + (size_t)((h & 7) * GNC + c * 11 + k) * 20480, 20480, sb + T_FB + (k % 7) * 8);
}
template <int layer> __device__ __forceinline__ void chain_aux(const uint32_t sb, const int c, const int h, const int nact) {
    const int tid = read_tid(), w = __shfl_sync(~0u, tid >> 5, 0), lane = tid & 31;
    if (w == 8) {
        mbar_init(sb + O_BAR + lane * 8, lane == 2 ? (c == 2 ? 9 : 4) : (lane >= 16 && lane < 20) || (lane >= 27 && lane < 31) ? 8 : 1);
        asm volatile("fence.mbarrier_init.release.cluster;" ::: "memory");
        fence_async_smem();
        __syncwarp();
    }
    {
        uint4* z = (uint4*)red_base() + layer * 65536;
#pragma unroll 1
        for (int i = blockIdx.x * 128 + tid - 256; i < 65536; i += 96 * 128)
            if (i >= 2048 || (i & 32)) z[i] = make_uint4(0, 0, 0, 0);
    }
    if (w == 8 && lane == 0) {
        mbar_expect(sb + B_S, s_tx(c));
        mbar_expect(sb + B_W, 192);
        mbar_expect(sb + T_RED, (c == 2 ? 1 : 2) * 3 * 4096);
        if (layer == 1) prefetch_l2(red_base() + 32 * 32768 + blockIdx.x * 1024, 1024);
        if (layer == 0) wait_flag<400>(g_ready, NSETUP);
    }
    __syncwarp();
    cluster_sync_full();
    asm volatile("barrier.cluster.arrive.relaxed.aligned;" ::: "memory");
    pdl_wait();
    if (w == 11 && lane == 0) red_relaxed(g_flag + F_X + layer * 128 + 65);
    Flag* flag = g_flag + layer * NSEG * 32 + h;
    const Flag* xflag = g_flag + F_X + layer * 128;
    char* const it0 = g_item + (size_t)h * 32768;
    if (w == 8) {
#pragma unroll 1
        for (int n = 0; n < 3; n++) {
            wait_flag<100>(xflag + (n >> 1), 4);
            fence_async_glb();
            if (n == 0) { bar_sync(4, 288); fence_async_smem(); }
            if (lane == 0 && n < 2) {
                mbar_expect(sb + B_XF + n * 8, 40960);
                bulk_g2s(sb + O_XS + n * 40960, (const char*)g_xn + n * 40960, 40960, sb + B_XF + n * 8);
            }
            __syncwarp();
        }
#pragma unroll 1
        for (int n = 0; n < NSEG; n++) {
            const int np = n & 1;
            if (n == 0) { wait_flag<100>(g_flag + F_W + layer * 128, 96); bar_sync(5, 288); } else bar_sync(2, 352);
            if (n == 1) TL(12 + layer * 14);
            if (n == 63) TL(13 + layer * 14);
            if (lane == 0 && n == NSEG - 1) mbar_arrive(sb + B_STG + 8);
            if (lane == 0 && n < NSEG - 1) {
                const uint32_t vs = sb + O_STG + 8192 - np * 16384, vb = sb + B_VX + np * 8;
                if (c == 2) {
                    fence_async_smem();
                    bulk_s2s(mapa(vs, 0), vs, 8192, mapa(vb, 0));
                    bulk_s2s(mapa(vs, 1), vs, 8192, mapa(vb, 1));
                } else mbar_expect(vb, 8192);
                if (n == 0) { mbar_expect(sb + B_XF, 40960); bulk_g2s(sb + O_XS, (const char*)g_xn + 2 * 40960, 40960, sb + B_XF); }
                if (n == h * 3 + c && !np && n + 6 < NSEG) prefetch_l2(red_base() + (size_t)(layer * 32 + (n >> 1) + 3) * 32768, 32768);
            }
            __syncwarp();
        }
    } else if (w == 11) {
        float cvo;
        {
            auto max8 = [&](const float* p) {
                const float4 u = ((const float4*)p)[0], v = ((const float4*)p)[1];
                return fmaxf(fmaxf(fmaxf(u.x, u.y), fmaxf(u.z, u.w)), fmaxf(fmaxf(v.x, v.y), fmaxf(v.z, v.w)));
            };
            wait_flag<300>(g_flag + F_W + layer * 128, 96);
            const float* pc = g_co + lane * 32;
            float a = 640.f * __ldcg(g_wmx + lane * 3 + 2), o = fmaxf(fmaxf(max8(pc), max8(pc + 8)), max8(pc + 16));
#pragma unroll 1
            for (int s = 16; s; s >>= 1) { a = fmaxf(a, __shfl_xor_sync(~0u, a, s)); o += __shfl_xor_sync(~0u, o, s); }
            cvo = a * o * 2.f;
        }
        float invM = g_invM0;
        float iv;
        weight_scale(h, 2, &iv);
        const uint32_t L16 = sb + lane * 16 + O_MX;
#pragma unroll 1
        for (int st = 0; st < NSEG; st++) {
            bar_sync(1, 320);
            if (st == NSEG - 1) break;
            if (lane == 0) mbar_arrive(sb + B_STG + (st & 1) * 8);
            uint32_t u[2][4];
            lds128(u[0], L16); lds128(u[1], L16 + 512);
            uint32_t mx = habsmax(habsmax(habsmax(u[0][0], u[0][1]), habsmax(u[0][2], u[0][3])), habsmax(habsmax(u[1][0], u[1][1]), habsmax(u[1][2], u[1][3])));
            mx = __reduce_max_sync(~0u, max(mx & 0x7fffu, (mx >> 16) & 0x7fffu));
            const float bound = fmaxf(__half2float(__ushort_as_half((unsigned short)mx)) * invM, 25.5f) * cvo;
            const float sc = pow2_scale(bound, 15, &invM);
            sts64(sb + O_SCL, __float_as_uint(sc * iv), __float_as_uint(invM));
            bar_arrive(2, 352);
        }
    } else if (w == 10) {
        bar_sync(9, 288);
        if (lane == 0) red_release(g_flag + F_W + layer * 128);
        if (lane == 0) {
#pragma unroll 1
            for (int n = 0; n < NSEG; n++) {
                mbar_sleep(sb + B_STG + (n & 1) * 8, (n >> 1) & 1);
                fence_async_smem();
                const uint32_t stg = sb + O_STG - (n & 1) * 16384;
                char* it = it0 + (size_t)(n % RING) * 32 * 32768;
                bulk_s2g(it + c * 8192, stg + (c == 2 ? 8192 : 0), 8192);
                bulk_commit();
                if (n + 1 >= RING && n + 1 < NSEG) wait_flag(flag - (RING - 1) * 32, 7);
                bulk_wait0();
                mbar_arrive(sb + B_FREE + (n & 1) * 8);
                fence_async_glb();
                red_relaxed(flag);
                flag += 32;
            }
        }
    } else {
        bool allx = false;
#pragma unroll 1
        for (int st = 0; st < NSEG; st++) {
            const int par = st & 1;
            char* const it = it0 + (size_t)(st % RING) * 32 * 32768;
            if (lane == 0 && !allx && st + 3 < NSEG) {
                allx = ld_acquire(xflag + 64) >= nact;
                if (!allx) wait_flag(st + 4 < NSEG ? xflag + ((st + 3) >> 1) : xflag + 64, st + 4 < NSEG ? 4 : nact);
                fence_async_glb();
            }
            __syncwarp();
            if (st < NSEG - 1 && c < 2) mbar_sleep(sb + B_VX + par * 8, (st >> 1) & 1);
            if (st < NSEG - 2) mbar_sleep(sb + B_XF + par * 8, ((st >> 1) + 1) & 1);
            bar_sync(1, 320);
            if (lane == 0 && st + 3 < NSEG) {
                mbar_expect(sb + B_XF + (par ^ 1) * 8, 40960);
                bulk_g2s_last(sb + O_XS + (par ^ 1) * 40960, (const char*)g_xn + (size_t)(st + 3) * 40960, 40960, sb + B_XF + (par ^ 1) * 8);
            } else if (lane == 0 && st < NSEG - 1) {
                tail_load_b(sb, h, c, (par ^ 1) * 2); tail_load_b(sb, h, c, (par ^ 1) * 2 + 1);
            }
            __syncwarp();
            if (lane == 0 && c < 2) {
                fence_async_smem();
#pragma unroll 1
                for (int i = 0; i < 4; i++) bulk_s2g(it + 24576 + (c * 4 + i) * 512, sb + O_QKP + i * 1024 + 512, 512);
                bulk_commit();
                asm volatile("cp.async.bulk.wait_group.read 0;" ::: "memory");
            }
            __syncwarp();
            if (st < NSEG - 1) bar_arrive(2, 352);
            mbar_sleep(sb + B_S, par);
            __syncwarp();
            if (lane == 0) {
                if (st < NSEG - 1) mbar_expect(sb + B_S, s_tx(c));
                if (c == 2) { fence_async_smem(); bulk_s2g(it + 28672, sb + O_VM + par * 2048, 2048); bulk_commit(); }
                if (st == NSEG - 1) asm volatile("cp.async.bulk.wait_group.read 0;" ::: "memory");
            }
            __syncwarp();
            if (st == NSEG - 1) bar_arrive(8, 320);
            if (lane == 0) { bulk_wait0(); fence_async_glb(); red_relaxed(flag); }
            __syncwarp();
            mbar_sleep(sb + B_FREE + par * 8, (st >> 1) & 1);
            flag += 32;
        }
    }
    __syncwarp();
    const int nc = c == 2 ? 10 : 11;
    if (w == 10) {
        bar_sync(8, 320);
        if (lane == 0) {
            if (layer == 1 && blockIdx.x == 0) g_ready[0].v = 0;
            fence_async_smem();
            __nanosleep(TDELAY);
            wait_flag(xflag + 64, nact);
            wait_flag<50>(g_flag + F_O + layer * 32 + 28 + (h >> 3), 64);
            fence_async_glb();
#pragma unroll 1
            for (int k = 0; k < nc; k++) {
                if (k >= 4) mbar_sleep(sb + T_EA + (k & 3) * 8, ((k >> 2) - 1) & 1);
                mbar_expect(sb + T_FA + (k & 3) * 8, 16384);
                bulk_g2s_last(sb + O_MS + (k & 3) * 16384, (const char*)g_O + (size_t)((28 + (h >> 3)) * GNC + c * 11 + k) * 16384, 16384, sb + T_FA + (k & 3) * 8);
            }
        }
    } else if (w == 9 && lane == 0) {
        __nanosleep(TDELAY);
#pragma unroll 1
        for (int k = 4; k < nc; k++) {
            if (k >= 7) mbar_sleep(sb + T_EB + (k - 7) * 8, 0);
            tail_load_b(sb, h, c, k);
        }
    }
    __syncwarp();
    asm volatile("barrier.cluster.wait.aligned;" ::: "memory");
    asm volatile("barrier.cluster.arrive.relaxed.aligned; barrier.cluster.wait.aligned;" ::: "memory");
    asm volatile("barrier.cluster.arrive.relaxed.aligned; barrier.cluster.wait.aligned;" ::: "memory");
}

constexpr int RI_A = 0, RI_TAB = 81920, RI_STG = RI_TAB + 82 * 768;
constexpr int RI_RES = RI_STG + 25600, RI_ST = RI_RES + 2 * 64 * 336;
constexpr int HB_A = G_BAR + 64, HB_AFREE = HB_A + 32, HB_LN = HB_A + 40, HB_FULL = HB_A + 64, HB_DONE = HB_FULL + 48, HB_FREE = HB_DONE + 48;
constexpr int HP_SMEM = HB_FREE + 48;
static_assert(G_BAR >= RI_ST + 2048, "helper shared-memory map");
#define IDL 280
#define ITEM_NS 60
#define PFW_AT 28
#define PFW_NS 150
__device__ __forceinline__ void helper_aux(const uint32_t sb, const int j, const int nh, const int na, const int nbh, const int layer, const bf16* Wq,
                                           const bf16* Wk, const bf16* Wv, const bf16* Wo) {
    const int w = threadIdx.x >> 5, lane = threadIdx.x & 31, p = w - 8;
    if (lane == 0 && j < (nh & ~3)) {
        int n = 0;
        for (int a = j >> 2; a < 32; a += nh >> 2, n++) {
            if (n == 0) continue;
            mbar_wait(sb + HB_AFREE, (n - 1) & 1);
            mbar_expect(sb + HB_A + p * 8, 20480);
            bulk_g2s_last(sb + RI_A + p * 20480, (const char*)g_YT + (size_t)a * 81920 + p * 20480, 20480, sb + HB_A + p * 8);
            if (p == 0) { mbar_wait(sb + HB_LN, (n - 1) & 1); red_release(g_flag + F_X + layer * 128 + a - (nh >> 2)); }
        }
        if (p == 0) { mbar_wait(sb + HB_LN, (n - 1) & 1); red_release(g_flag + F_X + layer * 128 + (j >> 2) + (n - 1) * (nh >> 2)); }
    }
    __syncwarp();
    if (layer == 0 && w == 8 && lane == 0) wait_flag<400>(g_flag + F_W, 96);
    __syncwarp();
    bar_sync(3, 384);
    if (p == 3 && lane == 0 && j < (nh & ~3)) red_release(g_flag + F_X + layer * 128 + 64);
    fence_async_smem();
    Flag* oflag = g_flag + F_O + layer * 32;
    if (j < na) {
        int sl = p & 1, ph = 1;
        for (int idx = j + (p & 1) * na; idx < NSEG * 32 && p >= 2 && lane == 0; idx += 2 * na) {
            mbar_wait(sb + HB_DONE + sl * 8, ph ^ 1);
            mbar_arrive(sb + HB_FREE + sl * 8);
            red_release(oflag + (idx >> 6));
            atomicAdd(&g_flag[layer * NSEG * 32 + idx].v, 1u);
            sl += 2;
            if (sl >= 6) { sl -= 6; ph ^= 1; }
        }
        for (int idx = j + p * na; idx < NSEG * 32 && p < 2 && lane == 0; idx += 2 * na) {
            mbar_wait(sb + HB_FREE + sl * 8, ph);
            wait_flag<ITEM_NS>(g_flag + layer * NSEG * 32 + idx, 6);
            fence_async_glb();
            if (idx < (NSEG - 2) * 32) __nanosleep(IDL);
            mbar_expect(sb + HB_FULL + sl * 8, 30720);
            bulk_g2s(sb + sl * 30720, g_item + (size_t)(idx % (RING * 32)) * 32768, 30720, sb + HB_FULL + sl * 8);
            sl += 2;
            if (sl >= 6) { sl -= 6; ph ^= 1; }
        }
    } else if (lane == 0 && p == 3) {
        if (layer == 0) {
            wait_flag<1000>(oflag + PFW_AT, 64);
            const int np = nh - na;
#pragma unroll 1
            for (int i = j - na; i < 1280; i += np) {
                const bf16* W = i < 320 ? Wq : i < 640 ? Wk : i < 960 ? Wv : Wo;
                prefetch_l2((const char*)W + (size_t)(i % 320) * 16384, 16384);
                __nanosleep(PFW_NS);
            }
#pragma unroll 1
            for (int i = j - na; i < 205; i += np) {
                const char* p_ = i < 160 ? (const char*)g_Wf + i * 16384 : i < 165 ? (const char*)g_stat + (i - 144) * 16384
                               : i < 167 ? (const char*)g_ctab + (i - 165) * 8192 : (const char*)(g_flag + NFLAG) - (i - 166) * 16384;
                prefetch_l2(p_, 16384);
                __nanosleep(PFW_NS);
            }
            if (j - na < 16) prefetch_l2(g_rtab + (j - na) * (RF_A / 4), RF_A / 4);
#pragma unroll 1
            for (int i = j - na; i < 130; i += np) { prefetch_l2((const char*)g_xb + i * 16384, 16384); __nanosleep(PFW_NS); }
        }
    } else if (lane == 0) {
        if (p == 2) wait_flag<500>(g_flag + F_X + layer * 128 + 64, nh & ~3);
        int c0 = 0;
        for (int mb = (j - na) >> 3; mb < nbh; mb += (nh - na) >> 3, c0 += GNC) {
            if (p < 2) wait_flag<300>(oflag + 2 * mb + p, 64);
            fence_async_glb();
            oproj_load(sb, p, mb, (j - na) & 7, c0, nh - na < 24 ? 0 : mb == nbh - 1 ? GPACE2 : GPACE);
        }
    }
}
__device__ __forceinline__ void helper_mma(char* sm, const int jh, const int nh, const int na, const int nbh, const int layer, const bf16* res, bf16* x,
                                           bf16* out) {
    const uint32_t sb = smem_u32(sm);
    const int tid = threadIdx.x, w = tid >> 5, lane = tid & 31, g = lane >> 2, t = lane & 3;
    const bool act = jh < (nh & ~3);
    const int j4 = jh & 3;
    const int fr = tid & 63, rg = w >> 1;
    auto chunk0 = [&](int u) { return u == 0 ? 5 * j4 : u == 1 ? 75 - 5 * j4 : u == 2 ? 40 + 5 * j4 : 35 - 5 * j4; };
    const int gr = tid / 20, gq_ = tid - gr * 20, go = gr * 80 + chunk0(gq_ / 5) + gq_ % 5;
    const uint32_t gs = sb + RI_RES + gr * 336 + gq_ * 16;
    auto residual = [&](int a, int n) {
#pragma unroll 1
        for (int r = 0; r < 64 - gr && tid < 240 && a < 32; r += 12) cp_async16(gs + (n & 1) * 21504 + r * 336, (const uint4*)res + (a * 64 + r) * 80 + go);
        cp_commit();
    };
    if (act) {
        if (tid < 240) {
            const int k0 = tid / 48, n = tid - k0 * 48;
            const float d = (float)(40 * j4 + n), amp = 2.f * 0.03952847075210474f;
#pragma unroll 4
            for (int u = 0; u < 16; u++)
                *(uint4*)(sm + RI_TAB + (tid + u * 240) * 16) = cos_row8(fmaf((float)((k0 + (u & 3) * 5) * 16 + ((u >> 2) & 1)), d, (float)((u & 8) * 20)), 2.f * d, amp);
            if (tid < 96) *(uint4*)(sm + RI_TAB + (3840 + tid) * 16) = make_uint4(k0 == 0 ? pack_h((n & 1) ? -amp : amp, 0.f) : 0u, 0, 0, 0);
        }
        fence_async_smem();
        residual(jh >> 2, 0);
    }
    bar_sync(1, 384);
    if (layer == TLL) TL(36);
    if (act) {
        const float4 wm = ((const float4*)g_wmax)[lane];
        const int wg = w >> 2;
        int n = 0;
#pragma unroll 1
        for (int a = jh >> 2; a < 32; a += nh >> 2, n++) {
            float acc[2][24];
            uint64_t da = mkdesc(sb + RI_A + wg * 40960, 1024, 1024, 1), db = mkdesc(sb + RI_TAB + wg * 30720, 768, 128, 0);
#pragma unroll
            for (int gq = 0; gq < 2; gq++) {
                mbar_wait(sb + HB_A + (wg * 2 + gq) * 8, n & 1);
                if (layer == TLL && n == TLN && gq == 0) TL(45);
                wg_fence();
#pragma unroll 5
                for (int k = 0; k < 10; k++) { wg_n48_ss_ta(acc[gq], da, db, k); da += 128; db += 96; }
                wg_commit();
            }
            if (wg == 0) {
                mbar_wait(sb + HB_A + 16, n & 1);
                wg_fence();
                wg_n48_ss_ta(acc[0], da, db + 20 * 96, 1);
                wg_commit();
            }
            float inv;
            pow2_scale(__uint_as_float(__reduce_max_sync(~0u, __float_as_uint(fmaxf(fmaxf(wm.x, wm.y), fmaxf(wm.z, wm.w))))), 0, &inv);
            const uint32_t ysc = pack_bf(inv, inv);
            wg_wait<0>();
            if (layer == TLL && n == TLN) TL(46);
            if (lane == 0) mbar_arrive(sb + HB_AFREE);
            const uint32_t ad = sb + RI_STG + ((w & 3) * 16 + (lane & 15)) * 400 + (lane >> 4) * 96 + wg * 192;
#pragma unroll
            for (int q = 0; q < 6; q++) {
                const float *e = acc[0] + q * 4, *o = acc[1] + q * 4;
                stsm4(ad + q * 16, pack_h(e[0] + o[0], e[1] + o[1]), pack_h(e[2] + o[2], e[3] + o[3]), pack_h(e[0] - o[0], e[1] - o[1]), pack_h(e[2] - o[2], e[3] - o[3]));
            }
            cp_wait<0>();
            bar_sync(4, 256);
            const uint32_t xa = sb + RI_RES + (n & 1) * 21504 + fr * 336 + rg * 80, sg = (rg & 1) ? 0xbc00bc00u : 0x3c003c00u;
            float sum = 0.f, sq = 0.f;
            uint32_t ya = sb + RI_STG + fr * 400 + (rg >> 1) * 96 + ((rg & 1) ? 64 : 0), carry;
            asm("fma.rn.f16x2 %0,%1,%2,%3;" : "=r"(carry) : "r"(lds32(ya + 208)), "r"(sg), "r"(lds32(ya + 16)));
#pragma unroll 1
            for (int ch = 0; ch < 5; ch++, ya += (rg & 1) ? -16 : 16) {
                uint32_t y[4], z[4], xr[4];
                lds128(y, ya); lds128(z, ya + 192); lds128(xr, xa + ch * 16);
#pragma unroll
                for (int q = 0; q < 4; q++) asm("fma.rn.f16x2 %0,%1,%2,%0;" : "+r"(y[q]) : "r"(z[q]), "r"(sg));
                if (rg & 1) {
                    const uint32_t y0 = y[0], y1 = y[1];
                    y[0] = __byte_perm(carry, y[3], 0x7610); y[1] = __byte_perm(y[3], y[2], 0x7610);
                    y[3] = __byte_perm(y1, y0, 0x7610); y[2] = __byte_perm(y[2], y1, 0x7610);
                    carry = y0;
                }
#pragma unroll
                for (int q = 0; q < 4; q++) {
                    const float2 yf = __half22float2(*(const __half2*)&y[q]);
                    xr[q] = bfma(pack_bf(yf.x, yf.y), ysc, xr[q]);
                    const float e = bf_lo(xr[q]), f = bf_hi(xr[q]);
                    sum += e + f; sq = fmaf(e, e, fmaf(f, f, sq));
                }
                sts128(xa + ch * 16, xr[0], xr[1], xr[2], xr[3]);
            }
            uint2* stat = g_stat + (size_t)(layer * 32 + a) * 1024 + rg * 64 + fr;
            asm volatile("st.relaxed.gpu.global.v2.u32 [%0],{%1,%2};" ::"l"(stat + j4 * 256), "r"(__float_as_uint(sum)), "r"(__float_as_uint(sq) | 0x80000000u) : "memory");
            if (layer == TLL && n == TLN) TL(47);
            uint32_t s0[3], s1[3];
            int lim = 0;
            do {
#pragma unroll
                for (int q = 0; q < 3; q++)
                    asm volatile("ld.relaxed.gpu.global.v2.u32 {%0,%1},[%2];" : "=r"(s0[q]), "=r"(s1[q]) : "l"(stat + ((j4 + 1 + q) & 3) * 256) : "memory");
            } while (__any_sync(~0u, (int)(s1[0] & s1[1] & s1[2]) >= 0) && ++lim < SPIN_LIM);
#pragma unroll
            for (int q = 0; q < 3; q++) { sum += __uint_as_float(s0[q]); sq -= __uint_as_float(s1[q]); }
            sts64(sb + RI_ST + tid * 8, __float_as_uint(sum), __float_as_uint(sq));
            bar_sync(4, 256);
            if (layer == TLL && n == TLN) TL(48);
#pragma unroll
            for (int q = 1; q < 4; q++) {
                uint32_t st2[2];
                lds64(st2, sb + RI_ST + ((tid + q * 64) & 255) * 8);
                sum += __uint_as_float(st2[0]); sq += __uint_as_float(st2[1]);
            }
            const float mean = sum * (1.f / 640.f), r = rsqrtf(fmaxf(fmaf(-mean, mean, sq * (1.f / 640.f)), 0.f) + 1e-5f), off = -mean * r;
            uint4* dst = (uint4*)g_xn + ((size_t)(2 * a + (w & 1)) * 80 + chunk0(rg)) * 32 + lane;
#pragma unroll
            for (int i = 0; i < 5; i++) {
                uint32_t u[4];
                lds128(u, xa + i * 16);
                dst[i * 32] = make_uint4(pack_h(fmaf(bf_lo(u[0]), r, off), fmaf(bf_hi(u[0]), r, off)), pack_h(fmaf(bf_lo(u[1]), r, off), fmaf(bf_hi(u[1]), r, off)),
                                         pack_h(fmaf(bf_lo(u[2]), r, off), fmaf(bf_hi(u[2]), r, off)), pack_h(fmaf(bf_lo(u[3]), r, off), fmaf(bf_hi(u[3]), r, off)));
            }
            __syncwarp();
            if (lane == 0) mbar_arrive(sb + HB_LN);
            if (layer == TLL) TL(37);
            if (layer == TLL && n == TLN) TL(44);
            residual(a + (nh >> 2), n + 1);
#pragma unroll 2
            for (int rr = 0; rr < 64 - gr && tid < 240; rr += 12) {
                uint32_t v[4];
                lds128(v, gs + (n & 1) * 21504 + rr * 336);
                ((uint4*)x)[(a * 64 + rr) * 80 + go] = make_uint4(v[0], v[1], v[2], v[3]);
            }
        }
    }
    bar_sync(3, 384);
    if (layer == TLL) TL(38);
    if (jh >= na) {
        int c0 = 0;
#pragma unroll 1
        for (int mb = (jh - na) >> 3; mb < nbh; mb += (nh - na) >> 3, c0 += GNC) oproj_mma(sb, mb, (jh - na) & 7, c0, x, out, layer);
        if (layer == TLL) TL(42);
        return;
    }
    const int p = w >> 1, mi = w & 1;
    int slot = p, ph = 0;
    for (int idx = jh + p * na; idx < NSEG * 32; idx += 4 * na) {
        const uint32_t it = sb + slot * 30720 + lane * 16;
        float iq, ik, iv;
        weight_scale(idx & 31, 0, &iq); weight_scale(idx & 31, 1, &ik); weight_scale(idx & 31, 2, &iv);
        bar_sync(6 + p, 64);
        mbar_wait(sb + HB_DONE + slot * 8, ph ^ 1);
        mbar_wait(sb + HB_FULL + slot * 8, ph);
        if (layer == TLL && idx >= 63 * 32) TL(55);
        float s[6][4];
#pragma unroll
        for (int i = 0; i < 6; i++) s[i][0] = s[i][1] = s[i][2] = s[i][3] = 0.f;
#pragma unroll
        for (int e = 0; e < 8; e++) {
            uint32_t q[4], k[4];
            ldsm4t(q, it + (e >> 2) * 8192 + (e & 3) * 1024 + mi * 512);
            ldsm4t(k, it + 24576 + e * 512);
            mma_bf(s[4], q[0], q[2], q[1], q[3], k[0], k[1]);
            mma_bf(s[5], q[0], q[2], q[1], q[3], k[2], k[3]);
            ldsm4t(k, it + (e >> 2) * 8192 + 4096 + (e & 3) * 1024);
            mma_bf(s[0], q[0], q[2], q[1], q[3], k[0], k[1]);
            mma_bf(s[1], q[0], q[2], q[1], q[3], k[2], k[3]);
            if (mi) {
                ldsm4t(k, it + (e >> 2) * 8192 + 4096 + (e & 3) * 1024 + 512);
                mma_bf(s[2], q[0], q[2], q[1], q[3], k[0], k[1]);
                mma_bf(s[3], q[0], q[2], q[1], q[3], k[2], k[3]);
            }
        }
#pragma unroll
        for (int q = 0; q < 4; q++) s[4][q] += s[5][q];
        const int seg = idx >> 5, h = idx & 31;
        const float sl = iq * ik * (0.08838834764831845f * 1.4426950408889634f);
        float mx[2] = {-3.0e38f, -3.0e38f};
#pragma unroll
        for (int i = 0; i < 5; i++)
#pragma unroll
            for (int q = 0; q < 4; q++) {
                const bool ok = i == 4 || (i * 8 + 2 * t + (q & 1)) <= (mi * 16 + g + (q >> 1) * 8);
                s[i][q] = ok ? s[i][q] * sl : -1.0e9f * 1.4426950408889634f;
                mx[q >> 1] = fmaxf(mx[q >> 1], s[i][q]);
            }
        float sum[2] = {0.f, 0.f};
#pragma unroll
        for (int r = 0; r < 2; r++) {
            mx[r] = fmaxf(mx[r], __shfl_xor_sync(~0u, mx[r], 1));
            mx[r] = fmaxf(mx[r], __shfl_xor_sync(~0u, mx[r], 2));
        }
#pragma unroll
        for (int i = 0; i < 5; i++)
#pragma unroll
            for (int q = 0; q < 4; q++) { s[i][q] = ex2(s[i][q] - mx[q >> 1]); sum[q >> 1] += s[i][q]; }
#pragma unroll
        for (int r = 0; r < 2; r++) {
            sum[r] += __shfl_xor_sync(~0u, sum[r], 1);
            sum[r] += __shfl_xor_sync(~0u, sum[r], 2);
            sum[r] = iv * rcp(sum[r]);
        }
        uint32_t pp[5][2];
#pragma unroll
        for (int i = 0; i < 5; i++) { pp[i][0] = pack_bf(s[i][0] * sum[0], s[i][1] * sum[0]); pp[i][1] = pack_bf(s[i][2] * sum[1], s[i][3] * sum[1]); }
        uint32_t* o = (uint32_t*)g_O + (((size_t)(seg >> 1) * 512 + h * 16) * 8 + (seg & 1) * 4 + mi * 2) * 32 + lane;
#pragma unroll
        for (int e = 0; e < 8; e++) {
            float o0[4] = {0.f, 0.f, 0.f, 0.f}, o1[4] = {0.f, 0.f, 0.f, 0.f};
            uint32_t v[4];
            lds64(v, it - lane * 8 + 28672 + e * 256);
            mma_bf8(o0, pp[4][0], pp[4][1], v[0]);
            mma_bf8(o1, pp[4][0], pp[4][1], v[1]);
            ldsm4(v, it + 16384 + e * 1024);
            mma_bf(o0, pp[0][0], pp[0][1], pp[1][0], pp[1][1], v[0], v[2]);
            mma_bf(o1, pp[0][0], pp[0][1], pp[1][0], pp[1][1], v[1], v[3]);
            ldsm4(v, it + 16384 + e * 1024 + 512);
            mma_bf(o0, pp[2][0], pp[2][1], pp[3][0], pp[3][1], v[0], v[2]);
            mma_bf(o1, pp[2][0], pp[2][1], pp[3][0], pp[3][1], v[1], v[3]);
            o[(2 * e) * 256] = pack_bf(o0[0], o0[1]); o[(2 * e) * 256 + 32] = pack_bf(o0[2], o0[3]);
            o[(2 * e + 1) * 256] = pack_bf(o1[0], o1[1]); o[(2 * e + 1) * 256 + 32] = pack_bf(o1[2], o1[3]);
        }
        __syncwarp();
        if (lane == 0) mbar_arrive(sb + HB_DONE + slot * 8);
        slot += 4;
        if (slot >= 6) { slot -= 6; ph ^= 1; }
    }
    if (layer == TLL) TL(39);
}

template <int layer> __global__ void __cluster_dims__(3, 1, 1) __launch_bounds__(384, 1)
k_chain(const int nact, const uint32_t zero, const bf16* __restrict__ Wq, const bf16* __restrict__ Wk, const bf16* __restrict__ Wv,
        const bf16* __restrict__ Wo, const bf16* res, bf16* out) {
    extern __shared__ __align__(1024) char sm[];
    const uint32_t sb = smem_u32(sm);
    const int b = blockIdx.x, h = b / 3, c = b - h * 3;
    pdl_go();
    if (threadIdx.x >= 256) {
        asm volatile("setmaxnreg.dec.sync.aligned.u32 24;");
        TL(11 + layer * 14);
        chain_aux<layer>(sb, c, h, nact);
    } else {
        asm volatile("setmaxnreg.inc.sync.aligned.u32 240;");
        chain_mma<layer>(sb, c, h, zero, Wq, Wk, Wv, Wo, res, out);
    }
}
__global__ void __launch_bounds__(384, 1) k_help(const bf16* res, bf16* x, bf16* out, const int layer, const int na, const int nbh, const int zero, const bf16* Wq,
                                                  const bf16* Wk, const bf16* Wv, const bf16* Wo) {
    extern __shared__ __align__(1024) char sm[];
    if (layer == TLL) TL(51);
    pdl_go();
    if (threadIdx.x >= 256) {
        const uint32_t sb = smem_u32(sm);
        const int p = (threadIdx.x >> 5) - 8, i = (threadIdx.x & 31) * 4 + p;
        if (i < 34) mbar_init(sb + G_BAR + i * 8, i < 4 ? 3 : i < 8 || i == 12 || i == 13 ? 8 : i >= 22 && i < 28 ? 2 : 1);
        fence_async_smem();
        wait_flag<100>(g_flag + F_X + layer * 128 + 65, 1);
        fence_async_glb();
        if (i == 8 + p && blockIdx.x < (gridDim.x & ~3)) {
            mbar_expect(sb + HB_A + p * 8, 20480);
            bulk_g2s(sb + RI_A + p * 20480, (const char*)g_YT + (size_t)(blockIdx.x >> 2) * 81920 + p * 20480, 20480, sb + HB_A + p * 8);
        }
        __syncwarp();
        bar_sync(2, 128);
        bar_arrive(1, 384);
    }
    if (threadIdx.x + zero >= 256) helper_aux(smem_u32(sm), blockIdx.x, gridDim.x, na, nbh, layer, Wq, Wk, Wv, Wo);
    else helper_mma(sm, blockIdx.x, gridDim.x, na, nbh, layer, res, x, out);
    __syncwarp();
    if (blockIdx.x == 0) pdl_wait();
}

#define COL_PAD 15872
template <class... P, class... A>
void launch_pdl(void (*k)(P...), int grid, int block, int smem, cudaStream_t st, A... args) {
    cudaLaunchConfig_t cfg = {};
    cfg.gridDim = dim3(grid); cfg.blockDim = dim3(block); cfg.dynamicSmemBytes = smem; cfg.stream = st;
    cudaLaunchAttribute at[1];
    at[0].id = cudaLaunchAttributeProgrammaticStreamSerialization; at[0].val.programmaticStreamSerializationAllowed = 1;
    cfg.attrs = at;
    cfg.numAttrs = 1;
    cudaLaunchKernelEx(&cfg, k, args...);
}

}

extern "C" void kernel_launch(void* const* d_in, const int* in_sizes, int n_in, void* d_out, int out_size) {
    const bf16* x = (const bf16*)d_in[0];
    const bf16* wr = (const bf16*)d_in[1];
    const bf16* wi = (const bf16*)d_in[2];
    const bf16* mem0 = (const bf16*)d_in[4];
    const bf16* Wq = (const bf16*)d_in[5];
    const bf16* Wk = (const bf16*)d_in[6];
    const bf16* Wv = (const bf16*)d_in[7];
    const bf16* Wo = (const bf16*)d_in[8];
    bf16* out = (bf16*)d_out;
    static int nhelp = 0;
    static bf16 *xa, *xb;
    static cudaStream_t s1;
    static cudaEvent_t ev_fork, ev_join;
    if (!nhelp) {
        cudaStreamCreateWithFlags(&s1, cudaStreamNonBlocking);
        cudaEventCreateWithFlags(&ev_fork, cudaEventDisableTiming);
        cudaEventCreateWithFlags(&ev_join, cudaEventDisableTiming);
        cudaFuncSetAttribute(k_setup, cudaFuncAttributeMaxDynamicSharedMemorySize, SU_SMEM);
        cudaFuncSetAttribute(k_rowf<0>, cudaFuncAttributeMaxDynamicSharedMemorySize, RF_SMEM);
        cudaFuncSetAttribute(k_rowf<1>, cudaFuncAttributeMaxDynamicSharedMemorySize, RF_SMEM);
        cudaFuncSetAttribute(k_col, cudaFuncAttributeMaxDynamicSharedMemorySize, COL_PAD);
        cudaFuncSetAttribute(k_chain<0>, cudaFuncAttributeMaxDynamicSharedMemorySize, CH_SMEM);
        cudaFuncSetAttribute(k_chain<1>, cudaFuncAttributeMaxDynamicSharedMemorySize, CH_SMEM);
        cudaFuncSetAttribute(k_setup, cudaFuncAttributePreferredSharedMemoryCarveout, 100);
        cudaFuncSetAttribute(k_rowf<0>, cudaFuncAttributePreferredSharedMemoryCarveout, 100);
        cudaFuncSetAttribute(k_rowf<1>, cudaFuncAttributePreferredSharedMemoryCarveout, 100);
        cudaFuncSetAttribute(k_col, cudaFuncAttributePreferredSharedMemoryCarveout, 100);
        cudaFuncSetAttribute(k_chain<0>, cudaFuncAttributePreferredSharedMemoryCarveout, 100);
        cudaFuncSetAttribute(k_chain<1>, cudaFuncAttributePreferredSharedMemoryCarveout, 100);
        cudaFuncSetAttribute(k_help, cudaFuncAttributeMaxDynamicSharedMemorySize, HP_SMEM);
        cudaFuncSetAttribute(k_help, cudaFuncAttributePreferredSharedMemoryCarveout, 100);
        int dev = 0, sms = 0;
        cudaGetDevice(&dev);
        cudaDeviceGetAttribute(&sms, cudaDevAttrMultiProcessorCount, dev);
        nhelp = sms - 96 < 12 ? 12 : sms - 96;
        cudaGetSymbolAddress((void**)&xa, g_xa);
        cudaGetSymbolAddress((void**)&xb, g_xb);
    }
    const int na = nhelp - (nhelp >= 36 ? 24 : nhelp >= 28 ? 16 : 8), nbh = 14;
    cudaStream_t s0 = cudaStreamPerThread;
    cudaEventRecord(ev_fork, s0);
    cudaStreamWaitEvent(s1, ev_fork, 0);
    k_rowf<1><<<(96 + nhelp) & ~1, 256, RF_SMEM, s0>>>(x);
    k_setup<<<NSETUP, 256, SU_SMEM, s1>>>(wr, wi, mem0);
    cudaEventRecord(ev_join, s1);
#define NLAYER 2
    for (int l = 0; l < NLAYER; l++) {
        const bf16* xin = l == 0 ? x : xb;
        if (l == 1) launch_pdl(k_rowf<0>, 128, 256, RF_SMEM, s0, xin);
        launch_pdl(k_col, 321, 128, l == 0 ? 0 : COL_PAD, s0, (int)(l == 0));
        launch_pdl(l == 0 ? k_chain<0> : k_chain<1>, 96, 384, CH_SMEM, s0, nhelp & ~3, 0u, Wq, Wk, Wv, Wo, (const bf16*)xa, l == 0 ? xb : out);
        launch_pdl(k_help, nhelp, 384, HP_SMEM, s0, xin, xa, l == 0 ? xb : out, l, na, nbh, 0, Wq, Wk, Wv, Wo);
    }
    cudaStreamWaitEvent(s0, ev_join, 0);
}
```

```cpp
#include <cuda_runtime.h>
#include <cuda_bf16.h>
#include <cuda_fp16.h>
#include <stdint.h>
#include <string.h>

namespace {

typedef __nv_bfloat16 bf16;
constexpr int S_ = 2048, D_ = 640, NSEG = 64;
constexpr int SPIN_LIM = 1 << 13;

__device__ float                  g_wmx[96];
__device__ __align__(1024) bf16   g_wot[4096 * 640];
__device__ __align__(16) float    g_co[1024];
__device__ __align__(256) uint2   g_stat[2 * 32 * 16 * 64];
__device__ float                  g_invM0;
__device__ __align__(16) float    g_wmax[128];
__device__ __align__(1024) char   g_redraw[65 * 32768];
constexpr int F_X = 2 * NSEG * 32, F_O = F_X + 2 * 128, NFLAG = F_O + 128, RING = 8;
constexpr int F_W = F_X + 66;
constexpr int F_R = F_O + 64;
constexpr int NSETUP = 131;
struct __align__(256) Flag { unsigned v; };
__device__ Flag                   g_flag[NFLAG];
__device__ Flag                   g_ready[1];
__device__ __align__(1024) char   g_item[RING * 32 * 32768];
__device__ __align__(1024) bf16   g_O[S_ * 4096];
__device__ __align__(1024) __half g_xn[S_ * D_];
__device__ __align__(1024) bf16   g_xa[S_ * D_];
__device__ __align__(1024) bf16   g_xb[S_ * D_];
__device__ __align__(1024) __half g_UT[D_ * S_];
__device__ __align__(1024) __half g_YT[D_ * S_];
__device__ __align__(1024) __half g_ctab[64 * 128 + 64 * 64];
__device__ __align__(1024) uint32_t g_Wf[321 * 2048];

#define TL(i)
#define TLN 0
#define TLL 1
#define CK(i)
__device__ __forceinline__ uint32_t smem_u32(const void* p) { return (uint32_t)__cvta_generic_to_shared(p); }
__device__ __forceinline__ uint32_t mapa(uint32_t a, uint32_t r) { uint32_t o; asm("mapa.shared::cluster.u32 %0,%1,%2;" : "=r"(o) : "r"(a), "r"(r)); return o; }
__device__ __forceinline__ void mbar_init(uint32_t a, int c) { asm volatile("mbarrier.init.shared::cta.b64 [%0],%1;" ::"r"(a), "r"(c) : "memory"); }
__device__ __forceinline__ void mbar_expect(uint32_t a, int bytes) { asm volatile("mbarrier.arrive.expect_tx.shared::cta.b64 _,[%0],%1;" ::"r"(a), "r"(bytes) : "memory"); }
__device__ __forceinline__ void mbar_arrive(uint32_t a) { asm volatile("mbarrier.arrive.shared::cta.b64 _,[%0];" ::"r"(a) : "memory"); }
__device__ __forceinline__ bool mbar_try(uint32_t a, uint32_t par) {
    uint32_t p;
    asm volatile("{.reg .pred q; mbarrier.try_wait.parity.shared::cta.b64 q,[%1],%2; selp.u32 %0,1,0,q;}" : "=r"(p) : "r"(a), "r"(par) : "memory");
    return p;
}
__device__ __forceinline__ void mbar_wait(uint32_t a, uint32_t par) {
    if (!mbar_try(a, par)) {
        int lim = 0;
        while (!mbar_try(a, par) && ++lim < SPIN_LIM) {}
    }
}
__device__ __forceinline__ void mbar_sleep(uint32_t a, uint32_t par) {
    asm volatile("{.reg .pred q; .reg .u32 n; mov.u32 n,0;\n"
                 "W_LOOP: mbarrier.try_wait.parity.shared::cta.b64 q,[%0],%1,%2; add.u32 n,n,1; setp.lt.and.u32 q,n,%3,!q; @q bra W_LOOP;}"
                 ::"r"(a), "r"(par), "n"(20000), "n"(SPIN_LIM) : "memory");
}
__device__ __forceinline__ void bar_arrive(int id, int n) { asm volatile("bar.arrive %0,%1;" ::"r"(id), "r"(n) : "memory"); }
__device__ __forceinline__ uint32_t clock32() { uint32_t c; asm volatile("mov.u32 %0,%%clock;" : "=r"(c)); return c; }
__device__ __forceinline__ uint32_t read_tid() { uint32_t v; asm volatile("mov.u32 %0,%%tid.x;" : "=r"(v)); return v; }
__device__ __forceinline__ void bar_sync(int id, int n) { asm volatile("bar.sync %0,%1;" ::"r"(id), "r"(n) : "memory"); }
__device__ __forceinline__ void fence_async_smem() { asm volatile("fence.proxy.async.shared::cta;" ::: "memory"); }
__device__ __forceinline__ void fence_async_glb() { asm volatile("fence.proxy.async.global;" ::: "memory"); }
__device__ __forceinline__ void cluster_sync_full() { asm volatile("barrier.cluster.arrive.aligned; barrier.cluster.wait.aligned;" ::: "memory"); }
__device__ __forceinline__ void bulk_g2s(uint32_t dst, const void* src, int bytes, uint32_t mb) {
    asm volatile("cp.async.bulk.shared::cluster.global.mbarrier::complete_tx::bytes [%0],[%1],%2,[%3];" ::"r"(dst), "l"(src), "r"(bytes), "r"(mb) : "memory");
}
__device__ __forceinline__ void bulk_g2s_last(uint32_t dst, const void* src, int bytes, uint32_t mb) {
    asm volatile("{.reg .b64 p; createpolicy.fractional.L2::evict_first.b64 p, 1.0;\n"
                 "cp.async.bulk.shared::cluster.global.mbarrier::complete_tx::bytes.L2::cache_hint [%0],[%1],%2,[%3],p;}"
                 ::"r"(dst), "l"(src), "r"(bytes), "r"(mb) : "memory");
}
__device__ __forceinline__ void bulk_s2s(uint32_t dst, uint32_t src, int bytes, uint32_t mb) {
    asm volatile("cp.async.bulk.shared::cluster.shared::cta.mbarrier::complete_tx::bytes [%0],[%1],%2,[%3];" ::"r"(dst), "r"(src), "r"(bytes), "r"(mb) : "memory");
}
__device__ __forceinline__ void bulk_s2g(void* dst, uint32_t src, int bytes) {
    asm volatile("cp.async.bulk.global.shared::cta.bulk_group [%0],[%1],%2;" ::"l"(dst), "r"(src), "r"(bytes) : "memory");
}
__device__ __forceinline__ void cp_async16(uint32_t dst, const void* src, uint32_t bytes = 16) {
    asm volatile("cp.async.cg.shared.global [%0],[%1],16,%2;" ::"r"(dst), "l"(src), "r"(bytes) : "memory");
}
__device__ __forceinline__ void cp_commit() { asm volatile("cp.async.commit_group;" ::: "memory"); }
template <int N> __device__ __forceinline__ void cp_wait() { asm volatile("cp.async.wait_group %0;" ::"n"(N) : "memory"); }
__device__ __forceinline__ void bulk_commit() { asm volatile("cp.async.bulk.commit_group;" ::: "memory"); }
__device__ __forceinline__ void bulk_wait0() { asm volatile("cp.async.bulk.wait_group 0;" ::: "memory"); }
__device__ __forceinline__ void ldsm4(uint32_t* r, uint32_t a) {
    asm volatile("ldmatrix.sync.aligned.m8n8.x4.shared.b16 {%0,%1,%2,%3},[%4];" : "=r"(r[0]), "=r"(r[1]), "=r"(r[2]), "=r"(r[3]) : "r"(a) : "memory");
}
__device__ __forceinline__ void ldsm4t(uint32_t* r, uint32_t a) {
    asm volatile("ldmatrix.sync.aligned.m8n8.x4.trans.shared.b16 {%0,%1,%2,%3},[%4];" : "=r"(r[0]), "=r"(r[1]), "=r"(r[2]), "=r"(r[3]) : "r"(a) : "memory");
}
__device__ __forceinline__ void stsm4(uint32_t a, uint32_t r0, uint32_t r1, uint32_t r2, uint32_t r3) {
    asm volatile("stmatrix.sync.aligned.m8n8.x4.shared.b16 [%0],{%1,%2,%3,%4};" ::"r"(a), "r"(r0), "r"(r1), "r"(r2), "r"(r3) : "memory");
}
__device__ __forceinline__ void stsm4t(uint32_t a, uint32_t r0, uint32_t r1, uint32_t r2, uint32_t r3) {
    asm volatile("stmatrix.sync.aligned.m8n8.x4.trans.shared.b16 [%0],{%1,%2,%3,%4};" ::"r"(a), "r"(r0), "r"(r1), "r"(r2), "r"(r3) : "memory");
}
__device__ __forceinline__ void lds128(uint32_t* r, uint32_t a) {
    asm volatile("ld.shared.v4.b32 {%0,%1,%2,%3},[%4];" : "=r"(r[0]), "=r"(r[1]), "=r"(r[2]), "=r"(r[3]) : "r"(a) : "memory");
}
__device__ __forceinline__ void lds64(uint32_t* r, uint32_t a) {
    asm volatile("ld.shared.v2.b32 {%0,%1},[%2];" : "=r"(r[0]), "=r"(r[1]) : "r"(a) : "memory");
}
__device__ __forceinline__ uint32_t lds32(uint32_t a) { uint32_t v; asm volatile("ld.shared.b32 %0,[%1];" : "=r"(v) : "r"(a) : "memory"); return v; }
__device__ __forceinline__ void sts128(uint32_t a, uint32_t r0, uint32_t r1, uint32_t r2, uint32_t r3) {
    asm volatile("st.shared.v4.b32 [%0],{%1,%2,%3,%4};" ::"r"(a), "r"(r0), "r"(r1), "r"(r2), "r"(r3) : "memory");
}
__device__ __forceinline__ void sts64(uint32_t a, uint32_t v0, uint32_t v1) { asm volatile("st.shared.v2.b32 [%0],{%1,%2};" ::"r"(a), "r"(v0), "r"(v1) : "memory"); }
[[maybe_unused]] __device__ __forceinline__ void sts32(uint32_t a, uint32_t v) { asm volatile("st.shared.b32 [%0],%1;" ::"r"(a), "r"(v) : "memory"); }
#define AU_(op) "{.reg .u32 t; add.u32 t,%4,%5; " op " {%0,%1,%2,%3},[t+%6];}"
template <int I> __device__ __forceinline__ void ldsm4_u(uint32_t* r, uint32_t a, uint32_t u) {
    asm volatile(AU_("ldmatrix.sync.aligned.m8n8.x4.shared.b16") : "=r"(r[0]), "=r"(r[1]), "=r"(r[2]), "=r"(r[3]) : "r"(a), "r"(u), "n"(I) : "memory");
}
template <int I> __device__ __forceinline__ void ldsm4t_u(uint32_t* r, uint32_t a, uint32_t u) {
    asm volatile(AU_("ldmatrix.sync.aligned.m8n8.x4.trans.shared.b16") : "=r"(r[0]), "=r"(r[1]), "=r"(r[2]), "=r"(r[3]) : "r"(a), "r"(u), "n"(I) : "memory");
}
template <int I> __device__ __forceinline__ void lds128_u(uint32_t* r, uint32_t a, uint32_t u) {
    asm volatile(AU_("ld.shared.v4.b32") : "=r"(r[0]), "=r"(r[1]), "=r"(r[2]), "=r"(r[3]) : "r"(a), "r"(u), "n"(I) : "memory");
}
template <int I> __device__ __forceinline__ void lds64_u(uint32_t* r, uint32_t a, uint32_t u) {
    asm volatile("{.reg .u32 t; add.u32 t,%2,%3; ld.shared.v2.b32 {%0,%1},[t+%4];}" : "=r"(r[0]), "=r"(r[1]) : "r"(a), "r"(u), "n"(I) : "memory");
}
template <int I> __device__ __forceinline__ uint32_t lds32_u(uint32_t a, uint32_t u) {
    uint32_t v;
    asm volatile("{.reg .u32 t; add.u32 t,%1,%2; ld.shared.b32 %0,[t+%3];}" : "=r"(v) : "r"(a), "r"(u), "n"(I) : "memory");
    return v;
}
template <int I> __device__ __forceinline__ void sts64_u(uint32_t a, uint32_t u, uint32_t v0, uint32_t v1) {
    asm volatile("{.reg .u32 t; add.u32 t,%0,%1; st.shared.v2.b32 [t+%2],{%3,%4};}" ::"r"(a), "r"(u), "n"(I), "r"(v0), "r"(v1) : "memory");
}
template <int I> __device__ __forceinline__ void sts32_u(uint32_t a, uint32_t u, uint32_t v) {
    asm volatile("{.reg .u32 t; add.u32 t,%0,%1; st.shared.b32 [t+%2],%3;}" ::"r"(a), "r"(u), "n"(I), "r"(v) : "memory");
}
template <int I> __device__ __forceinline__ void sts16_u(uint32_t a, uint32_t u, uint32_t v) {
    asm volatile("{.reg .u32 t; add.u32 t,%0,%1; st.shared.b16 [t+%2],%3;}" ::"r"(a), "r"(u), "n"(I), "h"((unsigned short)v) : "memory");
}
template <int I> __device__ __forceinline__ void sts128_u(uint32_t a, uint32_t u, uint32_t r0, uint32_t r1, uint32_t r2, uint32_t r3) {
    asm volatile("{.reg .u32 t; add.u32 t,%0,%1; st.shared.v4.b32 [t+%2],{%3,%4,%5,%6};}" ::"r"(a), "r"(u), "n"(I), "r"(r0), "r"(r1), "r"(r2), "r"(r3) : "memory");
}
template <int I> __device__ __forceinline__ void stsm4_u(uint32_t a, uint32_t u, uint32_t r0, uint32_t r1, uint32_t r2, uint32_t r3) {
    asm volatile("{.reg .u32 t; add.u32 t,%0,%1; stmatrix.sync.aligned.m8n8.x4.shared.b16 [t+%2],{%3,%4,%5,%6};}"
                 ::"r"(a), "r"(u), "n"(I), "r"(r0), "r"(r1), "r"(r2), "r"(r3) : "memory");
}
__device__ __forceinline__ void st_share2(uint32_t a, uint32_t u, uint32_t mb, uint32_t d0, uint32_t d1, uint32_t v0, uint32_t v1) {
    asm volatile("{.reg .pred p; .reg .u32 t,x,y; add.u32 t,%0,%1;\n"
                 "add.u32 x,t,%3; add.u32 y,%2,%3; st.async.shared::cluster.mbarrier::complete_tx::bytes.v2.b32 [x],{%5,%6},[y];\n"
                 "add.u32 x,t,%4; add.u32 y,%2,%4; st.async.shared::cluster.mbarrier::complete_tx::bytes.v2.b32 [x],{%5,%6},[y];\n"
                 "st.shared.v2.b32 [t],{%5,%6}; bar.warp.sync -1; setp.eq.u32 p,%0,0; @p mbarrier.arrive.shared::cta.b64 _,[%2];}"
                 ::"r"(a), "r"(u), "r"(mb), "r"(d0), "r"(d1), "r"(v0), "r"(v1) : "memory");
}
template <int V> struct IC { __host__ __device__ constexpr operator int() const { return V; } };
template <int N, class F> __device__ __forceinline__ void sfor(F f) {
    if constexpr (N > 0) { sfor<N - 1>(f); f(IC<N - 1>()); }
}
__device__ __forceinline__ void mma_f16(float* d, const uint32_t* a, uint32_t b0, uint32_t b1) {
    asm volatile("mma.sync.aligned.m16n8k16.row.col.f32.f16.f16.f32 {%0,%1,%2,%3},{%4,%5,%6,%7},{%8,%9},{%0,%1,%2,%3};"
                 : "+f"(d[0]), "+f"(d[1]), "+f"(d[2]), "+f"(d[3]) : "r"(a[0]), "r"(a[1]), "r"(a[2]), "r"(a[3]), "r"(b0), "r"(b1));
}
__device__ __forceinline__ void mma_bf(float* d, uint32_t a0, uint32_t a1, uint32_t a2, uint32_t a3, uint32_t b0, uint32_t b1) {
    asm volatile("mma.sync.aligned.m16n8k16.row.col.f32.bf16.bf16.f32 {%0,%1,%2,%3},{%4,%5,%6,%7},{%8,%9},{%0,%1,%2,%3};"
                 : "+f"(d[0]), "+f"(d[1]), "+f"(d[2]), "+f"(d[3]) : "r"(a0), "r"(a1), "r"(a2), "r"(a3), "r"(b0), "r"(b1));
}
__device__ __forceinline__ void mma_bf8(float* d, uint32_t a0, uint32_t a1, uint32_t b0) {
    asm volatile("mma.sync.aligned.m16n8k8.row.col.f32.bf16.bf16.f32 {%0,%1,%2,%3},{%4,%5},{%6},{%0,%1,%2,%3};"
                 : "+f"(d[0]), "+f"(d[1]), "+f"(d[2]), "+f"(d[3]) : "r"(a0), "r"(a1), "r"(b0));
}
__device__ __forceinline__ uint32_t pack_bf(float lo, float hi) { uint32_t r; asm("cvt.rn.bf16x2.f32 %0,%1,%2;" : "=r"(r) : "f"(hi), "f"(lo)); return r; }
__device__ __forceinline__ uint32_t pack_h(float lo, float hi) { uint32_t r; asm("cvt.rn.f16x2.f32 %0,%1,%2;" : "=r"(r) : "f"(hi), "f"(lo)); return r; }
__device__ __forceinline__ float bf_lo(uint32_t v) { return __uint_as_float(v << 16); }
__device__ __forceinline__ float bf_hi(uint32_t v) { return __uint_as_float(v & 0xffff0000u); }
__device__ __forceinline__ uint32_t bfma(uint32_t a, uint32_t b, uint32_t c) { uint32_t r; asm("fma.rn.bf16x2 %0,%1,%2,%3;" : "=r"(r) : "r"(a), "r"(b), "r"(c)); return r; }
__device__ __forceinline__ uint4 add_bf8(const uint4 x, const uint32_t* y, const uint32_t k = 0x3f803f80u) {
    return make_uint4(bfma(y[0], k, x.x), bfma(y[1], k, x.y), bfma(y[2], k, x.z), bfma(y[3], k, x.w));
}
__device__ __forceinline__ float ex2(float x) { float r; asm("ex2.approx.ftz.f32 %0,%1;" : "=f"(r) : "f"(x)); return r; }
__device__ __forceinline__ float rcp(float x) { float r; asm("rcp.approx.ftz.f32 %0,%1;" : "=f"(r) : "f"(x)); return r; }
__device__ __forceinline__ void wg_fence() { asm volatile("wgmma.fence.sync.aligned;" ::: "memory"); }
__device__ __forceinline__ void wg_commit() { asm volatile("wgmma.commit_group.sync.aligned;" ::: "memory"); }
template <int N> __device__ __forceinline__ void wg_wait() { asm volatile("wgmma.wait_group.sync.aligned %0;" ::"n"(N) : "memory"); }
__device__ __forceinline__ uint64_t mkdesc(uint32_t a, uint32_t lbo, uint32_t sbo, uint32_t sw) {
    return (uint64_t)((a & 0x3FFFF) >> 4) | ((uint64_t)(lbo >> 4) << 16) | ((uint64_t)(sbo >> 4) << 32) | ((uint64_t)sw << 62);
}
#define F4(d, i) "+f"(d[i]), "+f"(d[i + 1]), "+f"(d[i + 2]), "+f"(d[i + 3])
#define F8(d, i) F4(d, i), F4(d, i + 4)
#define F16(d, i) F8(d, i), F8(d, i + 8)
template <int OFF, int SC> __device__ __forceinline__ void wg_n32_x(float* d, const uint32_t* a, uint32_t lo) {
    asm volatile("{.reg .pred p; .reg .b32 l; .reg .b64 q; setp.ne.b32 p,%22,0; add.u32 l,%20,%21; mov.b64 q,{l,8};\n"
                 "wgmma.mma_async.sync.aligned.m64n32k16.f32.f16.f16 "
                 "{%0,%1,%2,%3,%4,%5,%6,%7,%8,%9,%10,%11,%12,%13,%14,%15},{%16,%17,%18,%19},q,p,1,1,0;}"
                 : F16(d, 0) : "r"(a[0]), "r"(a[1]), "r"(a[2]), "r"(a[3]), "r"(lo), "n"(OFF), "n"(SC));
}
__device__ __forceinline__ void wg_n128_rs(float* d, const uint32_t* a, uint64_t db, int sc) {
    asm volatile("{.reg .pred p; setp.ne.b32 p,%69,0; wgmma.mma_async.sync.aligned.m64n128k16.f32.f16.f16 "
                 "{%0,%1,%2,%3,%4,%5,%6,%7,%8,%9,%10,%11,%12,%13,%14,%15,%16,%17,%18,%19,%20,%21,%22,%23,%24,%25,%26,%27,%28,%29,%30,%31,"
                 "%32,%33,%34,%35,%36,%37,%38,%39,%40,%41,%42,%43,%44,%45,%46,%47,%48,%49,%50,%51,%52,%53,%54,%55,%56,%57,%58,%59,%60,%61,%62,%63},"
                 "{%64,%65,%66,%67},%68,p,1,1,0;}"
                 : F16(d, 0), F16(d, 16), F16(d, 32), F16(d, 48) : "r"(a[0]), "r"(a[1]), "r"(a[2]), "r"(a[3]), "l"(db), "r"(sc));
}
#define N80_REGS "{%0,%1,%2,%3,%4,%5,%6,%7,%8,%9,%10,%11,%12,%13,%14,%15,%16,%17,%18,%19,%20,%21,%22,%23,%24,%25,%26,%27,%28,%29,%30,%31,%32,%33,%34,%35,%36,%37,%38,%39}"
__device__ __forceinline__ void wg_n80_ss(float* d, uint64_t da, uint64_t db, int sc) {
    asm volatile("{.reg .pred p; setp.ne.b32 p,%42,0; wgmma.mma_async.sync.aligned.m64n80k16.f32.bf16.bf16 " N80_REGS ",%40,%41,p,1,1,0,0;}"
                 : F16(d, 0), F16(d, 16), F8(d, 32) : "l"(da), "l"(db), "r"(sc));
}
__device__ __forceinline__ void wg_n88_ss(float* d, uint64_t da, uint64_t db, int sc) {
    asm volatile("{.reg .pred p; setp.ne.b32 p,%46,0; wgmma.mma_async.sync.aligned.m64n88k16.f32.f16.f16 "
                 "{%0,%1,%2,%3,%4,%5,%6,%7,%8,%9,%10,%11,%12,%13,%14,%15,%16,%17,%18,%19,%20,%21,%22,%23,%24,%25,%26,%27,%28,%29,%30,%31,"
                 "%32,%33,%34,%35,%36,%37,%38,%39,%40,%41,%42,%43},%44,%45,p,1,1,0,0;}"
                 : F16(d, 0), F16(d, 16), F8(d, 32), F4(d, 40) : "l"(da), "l"(db), "r"(sc));
}
__device__ __forceinline__ void wg_n48_ss_ta(float* d, uint64_t da, uint64_t db, int sc) {
    asm volatile("{.reg .pred p; setp.ne.b32 p,%26,0; wgmma.mma_async.sync.aligned.m64n48k16.f32.f16.f16 "
                 "{%0,%1,%2,%3,%4,%5,%6,%7,%8,%9,%10,%11,%12,%13,%14,%15,%16,%17,%18,%19,%20,%21,%22,%23},%24,%25,p,1,1,1,0;}"
                 : F16(d, 0), F8(d, 16) : "l"(da), "l"(db), "r"(sc));
}
template <int TA> __device__ __forceinline__ void wg_n64_ss_tb(float* d, uint64_t da, uint64_t db, int sc) {
    asm volatile("{.reg .pred p; setp.ne.b32 p,%34,0; wgmma.mma_async.sync.aligned.m64n64k16.f32.f16.f16 "
                 "{%0,%1,%2,%3,%4,%5,%6,%7,%8,%9,%10,%11,%12,%13,%14,%15,%16,%17,%18,%19,%20,%21,%22,%23,%24,%25,%26,%27,%28,%29,%30,%31},"
                 "%32,%33,p,1,1,%35,1;}"
                 : F16(d, 0), F16(d, 16) : "l"(da), "l"(db), "r"(sc), "n"(TA));
}
__device__ __forceinline__ void pdl_wait() { asm volatile("griddepcontrol.wait;" ::: "memory"); }
__device__ __forceinline__ void pdl_go() { asm volatile("griddepcontrol.launch_dependents;" ::: "memory"); }
__device__ __forceinline__ float cos640(float p) {
    const float q = fmaf(p, 0.0015625f, 12582912.f) - 12582912.f;
    return __cosf(fmaf(q, -640.f, p) * 0.009817477042468103f);
}
__device__ __forceinline__ uint4 cos_row8(float p0, float step, float amp = 1.f) {
    float v[8];
    const float k = 2.f * cos640(step);
    v[0] = amp * cos640(p0); v[1] = amp * cos640(p0 + step);
#pragma unroll
    for (int i = 2; i < 8; i++) v[i] = fmaf(k, v[i - 1], -v[i - 2]);
    return make_uint4(pack_h(v[0], v[1]), pack_h(v[2], v[3]), pack_h(v[4], v[5]), pack_h(v[6], v[7]));
}
__device__ __forceinline__ float wfilter_max(int lane) {
    float m = fmaxf(fmaxf(g_wmax[lane], g_wmax[lane + 32]), fmaxf(g_wmax[lane + 64], g_wmax[lane + 96]));
    return __uint_as_float(__reduce_max_sync(~0u, __float_as_uint(m)));
}
__device__ __forceinline__ unsigned ld_acquire(const Flag* p) { unsigned v; asm volatile("ld.acquire.gpu.global.u32 %0,[%1];" : "=r"(v) : "l"(p) : "memory"); return v; }
#define POLL_NS 200
template <int NS = POLL_NS> __device__ __forceinline__ void wait_flag(const Flag* p, unsigned v) {
    if (ld_acquire(p) >= v) return;
    unsigned x;
    int lim = 0;
    do {
        __nanosleep(NS);
        asm volatile("ld.relaxed.gpu.global.u32 %0,[%1];" : "=r"(x) : "l"(p) : "memory");
    } while (x < v && ++lim < SPIN_LIM);
    ld_acquire(p);
}
__device__ __forceinline__ void prefetch_l2(const void* p, int bytes) { asm volatile("cp.async.bulk.prefetch.L2.global [%0],%1;" ::"l"(p), "r"(bytes) : "memory"); }
__device__ __forceinline__ void red_release(Flag* p) { asm volatile("red.release.gpu.global.add.u32 [%0],1;" ::"l"(p) : "memory"); }
__device__ __forceinline__ void red_relaxed(Flag* p) { asm volatile("red.relaxed.gpu.global.add.u32 [%0],1;" ::"l"(p) : "memory"); }
__device__ __forceinline__ void red_h8(void* p, uint32_t a, uint32_t b, uint32_t c, uint32_t d) {
    asm volatile("red.relaxed.gpu.global.add.noftz.v4.f16x2 [%0],{%1,%2,%3,%4};" ::"l"(p), "r"(a), "r"(b), "r"(c), "r"(d) : "memory");
}
__device__ __forceinline__ float pow2_scale(float bound, int top, float* inv) {
    int e = (int)((__float_as_uint(bound) >> 23) & 0xff) - 126;
    int k = top - e;
    k = max(-100, min(100, k));
    *inv = __uint_as_float((uint32_t)(127 - k) << 23);
    return __uint_as_float((uint32_t)(127 + k) << 23);
}
__device__ __forceinline__ char* red_base() { return (char*)(((uintptr_t)g_redraw + 32767) & ~(uintptr_t)32767); }

__device__ __forceinline__ void setup_a(char* sm, const int b, const bf16* __restrict__ wr, const bf16* __restrict__ wi) {
    const int tid = threadIdx.x, lane = tid & 31;
    const uint32_t sb = smem_u32(sm);
    auto row_byte = [&](int q) { return ((b >> 2) + 32 * ((q >> 1) * 8 + 2 * (b & 3) + (q & 1))) * 642; };
#pragma unroll 1
    for (int r = tid >> 5; r < 32; r += 8) {
        const char* src = (const char*)(r < 16 ? wr : wi) + (row_byte(r & 15) & ~15);
        cp_async16(sb + r * 672 + lane * 16, src + lane * 16);
        if (lane < 9) cp_async16(sb + r * 672 + 512 + lane * 16, src + 512 + lane * 16);
    }
    ((uint4*)g_stat)[b * 256 + tid] = make_uint4(0, 0, 0, 0);
    if (tid < 2 * (NFLAG / 128)) ((uint4*)(g_flag + b * (NFLAG / 128) + (tid >> 1)))[tid & 1] = make_uint4(0, 0, 0, 0);
    if (tid < 12) {
        const int i = b * 12 + tid;
        const int f = ((i >> 4) & 3) * 8 + (i & 7), im = (i >> 3) & 1, part = (i >> 8) & 1;
        ((uint4*)g_ctab)[i] = cos_row8((float)(i < 1024 ? (i >> 7) * 80 * (i & 63) + ((i & 64) ? 480 : 0) : ((i >> 6) & 3) * 160 * f + (im == part ? 0 : im ? 160 : 480)),
                                       (float)(i < 1024 ? 10 * (i & 63) : 20 * f));
    }
    asm volatile("cp.async.wait_all;" ::: "memory");
    __syncthreads();
    const int q0 = (tid & 3) * 4;
    const char* rp[4];
#pragma unroll
    for (int u = 0; u < 4; u++) rp[u] = sm + (q0 + u) * 672 + (row_byte(q0 + u) & 15);
    uint32_t mx = 0;
#pragma unroll 2
    for (int c = tid >> 2; c < 321; c += 64) {
        uint32_t v[4];
#pragma unroll
        for (int u = 0; u < 4; u++) {
            v[u] = ((const unsigned short*)rp[u])[c] | ((uint32_t)((const unsigned short*)(rp[u] + 16 * 672))[c] << 16);
            mx = __vmaxu2(mx, v[u] & 0x7fff7fffu);
        }
        ((uint4*)g_Wf)[(size_t)c * 512 + b * 4 + ((tid ^ (b >> 1)) & 3)] = make_uint4(v[0], v[1], v[2], v[3]);
    }
    mx = __reduce_max_sync(~0u, max(mx & 0xffffu, mx >> 16));
    __syncthreads();
    if (lane == 0) ((uint32_t*)sm)[tid >> 5] = mx;
    __syncthreads();
    if (tid < 32) {
        mx = __reduce_max_sync(~0u, ((uint32_t*)sm)[lane & 7]);
        if (tid == 0) g_wmax[b] = __uint_as_float(mx << 16);
    }
}
__device__ __forceinline__ void setup_b(const int b, const bf16* __restrict__ mem0) {
    const int tid = threadIdx.x;
    uint4* z = (uint4*)red_base();
    if (b < 3) {
        const int w = tid >> 5, lane = tid & 31, p = b * 2 + ((w >> 1) & 1), odd = w & 1;
        uint32_t mx = 0;
#pragma unroll 4
        for (int i = lane; i < 640; i += 32) {
            const uint4 u = ((const uint4*)mem0)[i];
            mx = __vmaxu2(__vmaxu2(mx, u.x & 0x7fff7fffu), __vmaxu2(__vmaxu2(u.y & 0x7fff7fffu, u.z & 0x7fff7fffu), u.w & 0x7fff7fffu));
        }
        float inv, v[7];
        const float sc = pow2_scale(__uint_as_float(__reduce_max_sync(~0u, max(mx & 0xffffu, mx >> 16)) << 16), 14, &inv);
        if (tid == 0) g_invM0 = inv;
#pragma unroll
        for (int j = 0; j < 7; j++) {
            const int r = p * 56 + (j < 6 ? odd * 32 + (j >> 1) * 8 : 24) + (lane >> 2), mr = 2 * (lane & 3) + (j < 6 ? (j & 1) : odd);
            v[j] = r < 320 ? __bfloat162float(mem0[mr * 640 + (w >> 2) * 320 + r]) * sc : 0.f;
        }
        const int off = w * 2048 + (lane >> 4) * 1024 + ((lane >> 3) & 1) * 256 + (lane & 7) * 16 + (b == 2 ? (w >> 1) * 4096 + 128 : b * 16384);
        const uint4 u = make_uint4(pack_h(v[0], v[1]), pack_h(v[2], v[3]), pack_h(v[4], v[5]), pack_h(v[6], 32.f));
        z[off >> 4] = u; z[65536 + (off >> 4)] = u;
    }
}

#define SU_PAD 40960
constexpr int SU_SMEM = SU_PAD;
__global__ void __launch_bounds__(256, 4) k_setup(const bf16* __restrict__ wr, const bf16* __restrict__ wi, const bf16* __restrict__ mem0) {
    extern __shared__ __align__(1024) char sm[];
    TL(0);
    if (blockIdx.x >= 128) setup_b(blockIdx.x - 128, mem0);
    else setup_a(sm, blockIdx.x, wr, wi);
    __syncthreads();
    if (threadIdx.x == 0) red_release(g_ready);
    TL(1);
}
__device__ __forceinline__ float weight_scale(int h, int ty, float* inv) { return pow2_scale(__ldcg(g_wmx + h * 3 + ty), 6, inv); }

#define STR_(x) #x
#define STR(x) STR_(x)
#define RF_U 1
constexpr int RF_A = 22 * 2816, RF_X = RF_A + 22 * 1024, RF_BAR = RF_X + 64 * 1344, RF_SMEM = RF_BAR + 80;
__device__ __align__(1024) char g_rtab[4 * RF_A];
template <int first> __global__ void __cluster_dims__(2, 1, 1) __launch_bounds__(256, 2) k_rowf(const bf16* x) {
    extern __shared__ __align__(1024) char sm[];
    TL(first ? 2 : 16);
    const int tid = threadIdx.x, w = tid >> 5, lane = tid & 31, g = lane >> 2, t = lane & 3;
    if (blockIdx.x >= 128) { __nanosleep(2500); return; }
    const int a = first ? blockIdx.x >> 2 : 31 - (blockIdx.x >> 2), gq = blockIdx.x & 3;
    if (!first) pdl_go();
    const uint32_t sb = smem_u32(sm), mb = sb + RF_BAR + w * 8;
    if (lane == 0) {
        mbar_init(mb, 1);
        asm volatile("fence.mbarrier_init.release.cluster;" ::: "memory");
        if (!first && w == 0) {
            mbar_init(sb + RF_BAR + 64, 1);
            fence_async_smem();
            mbar_expect(sb + RF_BAR + 64, RF_A);
            bulk_g2s(sb, g_rtab + gq * RF_A, RF_A, sb + RF_BAR + 64);
        }
    }
    if (lane == 0) mbar_expect(mb, 8 * 1280);
    __syncwarp();
    asm volatile("barrier.cluster.arrive.relaxed.aligned; barrier.cluster.wait.aligned;" ::: "memory");
    if (!first) {
        if (lane == 0) wait_flag<100>(g_flag + F_R + a, a < 28 ? 32 : 192);
        __syncwarp();
        fence_async_glb();
    }
    TL(first ? 3 : 17);
    if (lane < 4)
        asm volatile("cp.async.bulk.shared::cluster.global.mbarrier::complete_tx::bytes.multicast::cluster [%0],[%1],1280,[%2],%3;"
                     ::"r"(sb + RF_X + (w * 8 + (gq & 1) * 4 + lane) * 1344), "l"(x + (size_t)(a * 64 + w * 8 + (gq & 1) * 4 + lane) * 640), "r"(mb),
                     "h"((unsigned short)3) : "memory");
    __syncwarp();
    if (first) pdl_go();
    if (first) {
#pragma unroll 3
        for (int id = tid; id < 22 * 176; id += 256) {
            const int kg = id / 176, n = id - kg * 176;
            const float c = (float)(2 * n + (gq & 1));
            *(uint4*)(sm + id * 16) = cos_row8(fmaf((float)(kg * 8), c, (float)((gq & 2) * 80)), c, 0.03952847075210474f);
        }
    }
    mbar_wait(mb, 0);
    const uint32_t row = sb + RF_X + (w * 8 + g) * 1344;
    float st[4][4] = {};
#pragma unroll 1
    for (int i = 0; i < 20; i += 4) {
        uint32_t u[4][4];
#pragma unroll
        for (int q = 0; q < 4; q++) lds128(u[q], row + (4 * (i + q) + t) * 16);
#pragma unroll
        for (int q = 0; q < 4; q++) {
            mma_bf(st[(q & 1) * 2], u[q][0], 0x3f803f80u, u[q][1], 0x3f803f80u, u[q][0], u[q][1]);
            mma_bf(st[(q & 1) * 2 + 1], u[q][2], 0x3f803f80u, u[q][3], 0x3f803f80u, u[q][2], u[q][3]);
        }
    }
#pragma unroll
    for (int q = 0; q < 4; q++) { st[0][q] += st[2][q]; st[1][q] += st[3][q]; }
    const float sq = __shfl_sync(~0u, (g & 1) ? st[0][1] + st[1][1] : st[0][0] + st[1][0], g * 4 + (g >> 1));
    const float mean = __shfl_sync(~0u, (g & 1) ? st[0][3] + st[1][3] : st[0][2] + st[1][2], g * 4 + (g >> 1)) * (1.f / 640.f);
    const float r = rsqrtf(fmaxf(fmaf(-mean, mean, sq * (1.f / 640.f)), 0.f) + 1e-5f), off = gq == 0 ? -4.f * mean * r : 0.f;
    const float r1 = (gq == 1 || gq == 2) ? -r : r, r2 = (gq & 1) ? -r : r, r3 = gq >= 2 ? -r : r;
    const uint32_t aa = sb + RF_A + w * 128 + g * 16;
    auto el = [&](int d) { unsigned short v; asm volatile("ld.shared.u16 %0,[%1];" : "=h"(v) : "r"(row + d * 2)); return __uint_as_float((uint32_t)v << 16); };
_Pragma(STR(unroll RF_U))
    for (int i = 0; i < 5; i++) {
        const int ch = t + 4 * i;
        uint32_t u[4][4];
        lds128(u[0], row + ch * 16); lds128(u[1], row + (39 - ch) * 16); lds128(u[2], row + (40 + ch) * 16); lds128(u[3], row + (79 - ch) * 16);
        const float nb0 = el(320 - 8 * ch), nb1 = el(ch ? 640 - 8 * ch : 0);
        float o[8];
#pragma unroll
        for (int q = 0; q < 8; q++) {
            const int m = (8 - q) >> 1;
            const float e0 = (q & 1) ? bf_hi(u[0][q >> 1]) : bf_lo(u[0][q >> 1]), e2 = (q & 1) ? bf_hi(u[2][q >> 1]) : bf_lo(u[2][q >> 1]);
            const float e1 = q == 0 ? nb0 : (q & 1) ? bf_hi(u[1][m & 3]) : bf_lo(u[1][m & 3]), e3 = q == 0 ? nb1 : (q & 1) ? bf_hi(u[3][m & 3]) : bf_lo(u[3][m & 3]);
            o[q] = fmaf(e3, r3, fmaf(e2, r2, fmaf(e1, r1, fmaf(e0, r, off))));
        }
        if (ch == 0) o[0] *= 0.5f;
        sts128(aa + ch * 1024, pack_h(o[0], o[1]), pack_h(o[2], o[3]), pack_h(o[4], o[5]), pack_h(o[6], o[7]));
    }
    if (t < 2) sts128(aa + (20 + t) * 1024, t == 0 ? pack_h(fmaf(el(480), r2, fmaf(el(160), r, 0.5f * off)), 0.f) : 0u, 0u, 0u, 0u);
    fence_async_smem();
    __syncthreads();
    if (!first) mbar_wait(sb + RF_BAR + 64, 0);
    else if (a == 0 && tid == 0) { bulk_s2g(g_rtab + gq * RF_A, sb, RF_A); bulk_commit(); }
    const int wg = w >> 2;
    float acc[44];
    uint64_t da = mkdesc(sb + RF_A, 1024, 128, 0), db = mkdesc(sb + wg * 1408, 2816, 128, 0);
    wg_fence();
#pragma unroll 1
    for (int k = 0; k < 11; k++) { wg_n88_ss(acc, da, db, k); da += 128; db += 352; }
    wg_commit(); wg_wait<0>();
    const uint32_t stg = sb + RF_X + wg * 96 * 144;
#pragma unroll
    for (int j = 0; j < 12; j += 2) {
        const int m = lane >> 3, j1 = j < 10 ? j + 1 : j;
        stsm4t(stg + ((j + (m >> 1)) * 8 + (lane & 7)) * 144 + ((w & 3) * 16 + (m & 1) * 8) * 2, pack_h(acc[j * 4], acc[j * 4 + 1]),
               pack_h(acc[j * 4 + 2], acc[j * 4 + 3]), pack_h(acc[j1 * 4], acc[j1 * 4 + 1]), pack_h(acc[j1 * 4 + 2], acc[j1 * 4 + 3]));
    }
    bar_sync(1 + wg, 128);
#pragma unroll 3
    for (int rr = (tid & 127) >> 3; rr < 88; rr += 16) {
        const int ch = tid & 7, c = 2 * (wg * 88 + rr) + (gq & 1);
        if (c <= 320 - (gq >> 1) && (c | (gq ^ 2))) {
            uint32_t u[4];
            lds128(u, stg + rr * 144 + ch * 16);
            ((uint4*)g_UT)[((size_t)(c == 320 ? 1 : 2 * c + (gq >> 1)) * 32 + a) * 8 + (ch ^ (a & 7))] = make_uint4(u[0], u[1], u[2], u[3]);
        }
    }
    if (first && blockIdx.x < 4 && tid == 0) asm volatile("cp.async.bulk.wait_group.read 0;" ::: "memory");
    TL(first ? 4 : 18);
}

constexpr int GST = 4, GSTB = 32768 + 20480, GNC = 32;
constexpr int G_BAR = GST * GSTB + 3072;
#define GPACE 1100
#define GPACE2 650
__device__ __forceinline__ void oproj_load(const uint32_t sb, const int op, const int mb, const int nb, const int c0, const uint32_t pace) {
    const int by = op == 2 ? 20480 : 16384;
    const char* src = op == 2 ? (const char*)g_wot + (size_t)nb * GNC * 20480 : (const char*)g_O + (size_t)(2 * mb + op) * GNC * 16384;
    uint32_t t0 = clock32() - pace + op * (pace / 3);
#pragma unroll 1
    for (int c = c0; c < c0 + GNC; c++, src += by) {
        const int st = c % GST;
        if (c >= GST) mbar_wait(sb + G_BAR + (GST + st) * 8, ((c / GST) - 1) & 1);
        while (clock32() - t0 < pace) {}
        t0 = clock32();
        const int by_ = by;
        mbar_expect(sb + G_BAR + st * 8, by_);
        if (op == 2) bulk_g2s(sb + st * GSTB + 32768, src, by_, sb + G_BAR + st * 8);
        else bulk_g2s_last(sb + st * GSTB + op * 16384, src, by_, sb + G_BAR + st * 8);
    }
}
__device__ __forceinline__ void oproj_mma(const uint32_t sb, const int mb, const int nb, const int c0, const bf16* res, bf16* out, const int layer) {
    const int w = threadIdx.x >> 5, lane = threadIdx.x & 31, wg = w >> 2;
    float acc[40];
    uint4 rv[5];
#pragma unroll 1
    for (int c = c0; c < c0 + GNC; c++) {
        const int st = c % GST;
        mbar_wait(sb + G_BAR + st * 8, (c / GST) & 1);
        const uint32_t d = sb + st * GSTB;
        wg_fence();
#pragma unroll
        for (int k = 0; k < 8; k++)
            wg_n80_ss(acc, mkdesc(d + wg * 16384 + k * 2048, 1024, 128, 0), mkdesc(d + 32768 + k * 2560, 1280, 128, 0), (c - c0) | k);
        wg_commit();
        if (c > c0) {
            wg_wait<1>();
            if (lane == 0) mbar_arrive(sb + G_BAR + (GST + (c - 1) % GST) * 8);
        }
    }
#pragma unroll
    for (int i = 0; i < 5; i++) {
        const int id = i * 32 + lane, r = id / 10;
        rv[i] = __ldcg((const uint4*)res + (size_t)(mb * 128 + w * 16 + r) * 80 + nb * 10 + id - r * 10);
    }
    wg_wait<0>();
    bar_sync(5, 256);
    const uint32_t stg = sb + (GST - 1) * GSTB + w * 16 * 176;
#pragma unroll
    for (int j = 0; j < 5; j++)
        stsm4(stg + (lane & 15) * 176 + (2 * j + (lane >> 4)) * 16, pack_bf(acc[j * 8], acc[j * 8 + 1]), pack_bf(acc[j * 8 + 2], acc[j * 8 + 3]),
              pack_bf(acc[j * 8 + 4], acc[j * 8 + 5]), pack_bf(acc[j * 8 + 6], acc[j * 8 + 7]));
    __syncwarp();
#pragma unroll
    for (int i = 0; i < 5; i++) {
        const int id = i * 32 + lane, r = id / 10, ch = id - r * 10;
        uint32_t y[4];
        lds128(y, stg + r * 176 + ch * 16);
        ((uint4*)out)[(size_t)(mb * 128 + w * 16 + r) * 80 + nb * 10 + ch] = add_bf8(rv[i], y);
    }
    fence_async_smem();
    __syncwarp();
    if (lane == 0) {
        mbar_arrive(sb + G_BAR + (2 * GST - 1) * 8);
        if (layer == 0) red_release(g_flag + F_R + 2 * mb + wg);
    }
}

__global__ void __launch_bounds__(128, 4) k_col(const int first) {
    __shared__ __align__(1024) char sz[8192];
    __shared__ __align__(1024) char stab[24576];
    __shared__ __align__(1024) char swf[8192];
    __shared__ __align__(8) uint64_t bar[2];
    const int tid = threadIdx.x, wl = tid >> 5, lane = tid & 31, g = lane >> 2, t = lane & 3;
    const int c = blockIdx.x;
    TL(first ? 5 : 19);
    const bool realc = c == 0 || c == 320;
    const uint32_t z = smem_u32(sz), b2 = smem_u32(stab), a1 = b2 + 16384, wf = smem_u32(swf), mb = smem_u32(bar);
    if (tid == 0) { mbar_init(mb, 1); mbar_init(mb + 8, 1); fence_async_smem(); }
    if (realc) {
        for (int i = tid; i < 256; i += 128) sts128(z + 4096 + i * 16, 0, 0, 0, 0);
        fence_async_smem();
    }
    const int k1 = wl * 8 + g;
    float tc[16], ts[16];
#pragma unroll
    for (int j = 0; j < 16; j++) {
        const int p = ((j >> 1) * 8 + 2 * t + (j & 1)) * k1;
        __sincosf((float)(p - 1024) * 0.003067961575771282f, &ts[j], &tc[j]);
        ts[j] = -ts[j]; tc[j] = -tc[j];
    }
    if (first && tid == 32) { wait_flag<400>(g_ready, NSETUP); fence_async_glb(); }
    __syncthreads();
    if (tid == 32) {
        mbar_expect(mb + 8, 24576 + 8192);
        bulk_g2s(b2, g_ctab, 24576, mb + 8);
        bulk_g2s(wf, g_Wf + (size_t)c * 2048, 8192, mb + 8);
    }
    float inv;
    const float wsc = pow2_scale(wfilter_max(lane), 0, &inv) * (realc ? 0.0625f : 0.125f);
    pdl_wait();
    TL(first ? 6 : 20);
    if (tid == 0) {
        const int by = realc ? 4096 : 8192;
        mbar_expect(mb, by);
        bulk_g2s_last(z, (const char*)g_UT + (size_t)(c == 320 ? 1 : 2 * c) * 4096, by, mb);
    }
    pdl_go();
    mbar_wait(mb + 8, 0);
    mbar_wait(mb, 0);
    float d[64];
    uint32_t a[4][4];
    wg_fence();
#pragma unroll
    for (int ks = 0; ks < 4; ks++) wg_n64_ss_tb<0>(d, mkdesc(a1 + ks * 2048, 1024, 128, 0), mkdesc(z + ks * 2048, 1024, 1024, 1), ks);
    wg_commit(); wg_wait<0>();
    const float r32 = 0.17677669529663687f;
#pragma unroll
    for (int j = 0; j < 8; j++) {
        float yr[2], yi[2];
#pragma unroll
        for (int e = 0; e < 2; e++) {
            const float re = d[j * 4 + e] * r32, im = d[j * 4 + 2 + e] * r32, cc = tc[j * 2 + e], ss = ts[j * 2 + e];
            yr[e] = re * cc + im * ss; yi[e] = im * cc - re * ss;
        }
        a[j >> 1][(j & 1) * 2] = pack_h(yr[0], yr[1]); a[j >> 1][(j & 1) * 2 + 1] = pack_h(yi[0], yi[1]);
    }
    wg_fence();
#pragma unroll
    for (int ks = 0; ks < 4; ks++) wg_n128_rs(d, a[ks], mkdesc(b2 + ks * 4096, 2048, 128, 0), ks);
    wg_commit(); wg_wait<0>();
#pragma unroll
    for (int q = 0; q < 4; q++) {
        uint32_t wv[4];
        lds128(wv, wf + tid * 64 + ((q ^ (tid >> 1)) & 3) * 16);
#pragma unroll
        for (int jj = 0; jj < 2; jj++) {
            const int j = 2 * q + jj;
            float yr[2], yi[2];
#pragma unroll
            for (int e = 0; e < 2; e++) {
                const float xr = d[j * 4 + e] + d[32 + j * 4 + 2 + e], xi = d[j * 4 + 2 + e] - d[32 + j * 4 + e];
                const float fr = bf_lo(wv[jj * 2 + e]) * wsc, fi = bf_hi(wv[jj * 2 + e]) * wsc;
                yr[e] = xr * fr - xi * fi; yi[e] = xr * fi + xi * fr;
            }
            a[q][jj * 2] = pack_h(yr[0], yr[1]); a[q][jj * 2 + 1] = pack_h(yi[0], yi[1]);
        }
    }
    wg_fence();
#pragma unroll
    for (int ks = 0; ks < 4; ks++) wg_n128_rs(d, a[ks], mkdesc(b2 + ks * 4096, 2048, 128, 0), ks);
    wg_commit(); wg_wait<0>();
#pragma unroll
    for (int j = 0; j < 8; j++) {
        float yr[2], yi[2];
#pragma unroll
        for (int e = 0; e < 2; e++) {
            const float vr = (d[j * 4 + e] - d[32 + j * 4 + 2 + e]) * 0.125f, vi = (d[j * 4 + 2 + e] + d[32 + j * 4 + e]) * 0.125f;
            const float cc = tc[j * 2 + e], ss = ts[j * 2 + e];
            yr[e] = vr * cc - vi * ss; yi[e] = vi * cc + vr * ss;
        }
        a[j >> 1][(j & 1) * 2] = pack_h(yr[0], yr[1]); a[j >> 1][(j & 1) * 2 + 1] = pack_h(yi[0], yi[1]);
    }
    __syncthreads();
    const int mm = lane >> 3, rr = lane & 7;
    const uint32_t rowo = (wl * 16 + (mm & 1) * 8 + rr) * 128;
#pragma unroll
    for (int q = 0; q < 4; q++) stsm4(z + rowo + (((2 * q + (mm >> 1)) ^ rr) << 4), a[q][0], a[q][1], a[q][2], a[q][3]);
    fence_async_smem();
    __syncthreads();
    wg_fence();
#pragma unroll
    for (int ks = 0; ks < 4; ks++) wg_n64_ss_tb<1>(d, mkdesc(a1 + ks * 256, 128, 1024, 0), mkdesc(z + ks * 2048, 1024, 1024, 1), ks);
    wg_commit(); wg_wait<0>();
#pragma unroll
    for (int q = 0; q < 4; q++)
        stsm4(wf + rowo + (((2 * q + (mm >> 1)) ^ rr) << 4), pack_h(d[q * 8] * r32, d[q * 8 + 1] * r32), pack_h(d[q * 8 + 2] * r32, d[q * 8 + 3] * r32),
              pack_h(d[q * 8 + 4] * r32, d[q * 8 + 5] * r32), pack_h(d[q * 8 + 6] * r32, d[q * 8 + 7] * r32));
    __syncwarp();
    if (!(realc && wl >= 2)) {
        const int kk = c == 320 ? 320 : (c & 1) * 160 + (c >> 1) + (wl >> 1) * 320;
#pragma unroll
        for (int i = 0; i < 4; i++) {
            const int r = wl * 16 + i * 4 + (lane >> 3), ch = lane & 7;
            uint32_t v[4];
            lds128(v, wf + r * 128 + ((ch ^ (r & 7)) << 4));
            ((uint4*)g_YT)[((size_t)(r & 31) * 640 + kk) * 8 + (ch ^ (kk & 7))] = make_uint4(v[0], v[1], v[2], v[3]);
        }
    }
    TL(first ? 7 : 21);
}

constexpr int O_XS = 0;
constexpr int O_MS = 81920;
constexpr int O_QKP = O_MS + 10752;
constexpr int O_VM = O_QKP + 4096;
constexpr int O_SC = O_VM + 4096;
constexpr int O_OS = O_SC + 1536;
constexpr int O_XCH = O_OS + 2048;
constexpr int O_SUM = O_XCH + 8192;
constexpr int O_MX = O_SUM + 256;
constexpr int O_STG = O_MS + 65536 - 8192;
static_assert(O_STG - 16384 >= O_MX + 1024, "shared-memory map");
constexpr int O_WO = O_STG + 16384;
constexpr int O_SCL = O_WO + 65536;
constexpr int O_BAR = O_SCL + 64;
constexpr int B_XF = O_BAR, B_S = O_BAR + 16, B_VX = O_BAR + 32, B_STG = O_BAR + 48, B_FREE = O_BAR + 72;
constexpr int T_FA = O_BAR + 96, T_EA = T_FA + 32, T_FB = T_EA + 32, T_EB = T_FB + 56, T_RED = T_EB + 32;
constexpr int O_WMX = O_BAR + 512, B_W = O_BAR + 64;
constexpr int O_LAST = (O_WMX + 192 + 1023) / 1024 * 1024;
constexpr int CH_SMEM = O_LAST + 8192;
static_assert(O_WO == 19 * 8192, "weight staging");
__device__ __forceinline__ uint32_t tail_b(int c) { return c % 7 < 4 ? O_XS + (c % 7) * 20480 : O_WO + (c % 7 - 4) * 20480; }
__device__ __forceinline__ int s_tx(int c) { return c == 2 ? 2 * 768 : 768 + 2048; }

#define NPERM 1
#define NWO0 1
#define NWO0B 4
#define NWO1 6
#define LASTS 1
#define TDELAY 800
#define WDEPTH 6
#define RDELAY 580

#define STAMP(i)

#define NTA 23
#define NTB 26
template <int LO, int HI>
__device__ __forceinline__ void tok_issue(const uint32_t (&A0)[20][4], const uint32_t (&A1)[20][4], float (&b0)[16], float (&b1)[16], uint32_t xd,
                                          const uint32_t zero) {
    if (LO == 0) wg_fence();
    sfor<HI - LO>([&](auto I) {
        constexpr int i = LO + I;
        if constexpr (i < 20) wg_n32_x<i * 64, i>(b0, A0[i], xd); else wg_n32_x<(i - 20) * 64, i - 20>(b1, A1[i - 20], xd + zero);
        if constexpr (i == 19 || i == NTB - 1 || i == 39) wg_commit();
    });
}
__device__ __forceinline__ void tok_give(const float (&b0)[16], const uint32_t L16, const uint32_t xch0) {
    wg_wait<1>();
    sfor<2>([&](auto I) {
        constexpr int i = I;
        sts128_u<i * 512>(L16, xch0, pack_h(b0[8 * i], b0[8 * i + 1]), pack_h(b0[8 * i + 2], b0[8 * i + 3]), pack_h(b0[8 * i + 4], b0[8 * i + 5]),
                          pack_h(b0[8 * i + 6], b0[8 * i + 7]));
    });
}
__device__ __forceinline__ void tok_finish(float (&b1)[16], const uint32_t (&e)[2][4], const uint32_t L16, const uint32_t dst, const uint32_t idn) {
#pragma unroll
    for (int j = 0; j < 4; j++)
        asm volatile("mma.sync.aligned.m16n8k8.row.col.f32.f16.f16.f32 {%0,%1,%2,%3},{%4,%5},{%6},{%0,%1,%2,%3};"
                     : F4(b1, 4 * j) : "r"(e[j >> 1][(j & 1) * 2]), "r"(e[j >> 1][(j & 1) * 2 + 1]), "r"(idn));
    stsm4_u<0>(L16, dst, pack_bf(b1[0], b1[1]), pack_bf(b1[2], b1[3]), pack_bf(b1[4], b1[5]), pack_bf(b1[6], b1[7]));
    stsm4_u<512>(L16, dst, pack_bf(b1[8], b1[9]), pack_bf(b1[10], b1[11]), pack_bf(b1[12], b1[13]), pack_bf(b1[14], b1[15]));
}
__device__ __forceinline__ uint32_t uni(uint32_t v) { return __shfl_sync(~0u, v, 0); }
__device__ __forceinline__ uint32_t badd(uint32_t a, uint32_t b) { uint32_t r; asm("add.rn.bf16x2 %0,%1,%2;" : "=r"(r) : "r"(a), "r"(b)); return r; }
__device__ __forceinline__ uint32_t bmax(uint32_t a, uint32_t b) { uint32_t r; asm("max.bf16x2 %0,%1,%2;" : "=r"(r) : "r"(a), "r"(b)); return r; }
__device__ __forceinline__ uint32_t babsmax(uint32_t a, uint32_t b) { uint32_t r; asm("max.xorsign.abs.bf16x2 %0,%1,%2;" : "=r"(r) : "r"(a), "r"(b)); return r; }
__device__ __forceinline__ uint32_t habsmax(uint32_t a, uint32_t b) { uint32_t r; asm("max.xorsign.abs.f16x2 %0,%1,%2;" : "=r"(r) : "r"(a), "r"(b)); return r; }

template <int NPF>
__device__ __forceinline__ float mem_out(const uint32_t sb, const uint32_t L16, const uint32_t L8, uint32_t (&wo)[16][4], const uint32_t woa,
                                         char* dst, const bool odd) {
    bar_sync(2, 352);
    float a[4][4];
#pragma unroll
    for (int i = 0; i < 4; i++) a[i][0] = a[i][1] = a[i][2] = a[i][3] = 0.f;
    uint32_t ob[4][4], sm_[2], sc[2];
    sfor<8>([&](auto I) {
        constexpr int i = I;
        if constexpr (!(i & 1)) ldsm4t_u<O_OS + (i >> 1) * 512>(ob[i >> 1], L16, sb);
        if constexpr (i >= NPF) { ldsm4t(wo[i], woa + i * 1024); ldsm4t(wo[8 + i], (woa ^ 32) + i * 1024); }
    });
    lds64_u<O_SUM>(sm_, L8 & 24, sb); lds64(sc, sb + O_SCL);
#pragma unroll
    for (int i = 0; i < 8; i++) {
        mma_bf(a[i & 1], wo[i][0], wo[i][1], wo[i][2], wo[i][3], ob[i >> 1][(i & 1) * 2], ob[i >> 1][(i & 1) * 2 + 1]);
        mma_bf(a[2 + (i & 1)], wo[8 + i][0], wo[8 + i][1], wo[8 + i][2], wo[8 + i][3], ob[i >> 1][(i & 1) * 2], ob[i >> 1][(i & 1) * 2 + 1]);
    }
    const float f0 = rcp(__uint_as_float(sm_[0])) * __uint_as_float(sc[0]), f1 = rcp(__uint_as_float(sm_[1])) * __uint_as_float(sc[0]);
    red_h8(dst, pack_h((a[0][0] + a[1][0]) * f0, (a[0][1] + a[1][1]) * f1), pack_h((a[0][2] + a[1][2]) * f0, (a[0][3] + a[1][3]) * f1),
           pack_h((a[2][0] + a[3][0]) * f0, (a[2][1] + a[3][1]) * f1), pack_h(odd ? (a[2][3] + a[3][3]) * f1 : (a[2][2] + a[3][2]) * f0, 1.f));
    return __uint_as_float(sc[1]);
}

template <int layer> __device__ __forceinline__ void chain_mma(const uint32_t sb, const int c, const int h, const uint32_t zero, const bf16* __restrict__ Wq,
                                          const bf16* __restrict__ Wk, const bf16* __restrict__ Wv, const bf16* __restrict__ Wo,
                                          const bf16* res, bf16* out) {
    int tid = read_tid(), lane = tid & 31;
    const int w = __shfl_sync(~0u, tid >> 5, 0), wg = w >> 2;
    [[maybe_unused]] const int cta = h * 3 + c;
    uint32_t A0[20][4], A1[20][4];
    const int t0 = (w & 3) + wg * 4, t1 = t0 ^ 4;
    float sl;
    {
        const int tl = tid & 127, r = tl >> 3, ch = tl & 7;
        const size_t so = (size_t)(wg * 320 + r) * 4096 + h * 128 + ch * 8;
        const bf16 *wa = (c == 2 ? Wv : Wq + c * 64) + so, *wb = (c == 2 ? Wv + 64 : Wk + c * 64) + so;
        const uint32_t ring = sb + wg * 4096;
        const uint32_t dst = ring + r * 128 + ((ch ^ r) & 7) * 16;
        const uint32_t src = ring + ((lane & 7) + (lane >> 4) * 8) * 128 + ((((w & 3) * 2 + ((lane >> 3) & 1)) ^ lane) & 7) * 16;
        const int q4 = lane & 3, gr = (c * 2 + ((w >> 1) & 1)) * 56 + (q4 == 3 ? 24 : (w & 1) * 32 + q4 * 8);
        const bf16* wo_ = Wo + (size_t)(h * 128 + (lane >> 2)) * 640 + wg * 320 + min(gr, 312);
        const uint32_t wdst = sb + O_WO + w * 8192 + (lane >> 2) * 64 + ((q4 ^ (lane >> 3)) & 3) * 16;
        auto issue = [&](int i) {
            if (i < 20) {
                const uint32_t d = dst + (i < 19 ? i * 8192 : O_LAST);
                cp_async16(d, wa + (size_t)i * 65536); cp_async16(d + 2048, wb + (size_t)i * 65536);
                if (i < 16) cp_async16(wdst + i * 512, wo_ + i * 5120, gr < 320 ? 16 : 0);
            }
            cp_commit();
        };
#pragma unroll 1
        for (int i = 0; i < WDEPTH; i++) issue(i);
        asm volatile("barrier.cluster.arrive.relaxed.aligned;" ::: "memory");
        float fa, fb;
        if (layer == 0) {
            uint32_t ma = 0, mb = 0;
#pragma unroll 1
            for (int i = 0; i < 20; i++) {
                issue(i + WDEPTH);
                cp_wait<WDEPTH>();
                const uint32_t d = dst + (i < 19 ? i * 8192 : O_LAST);
                uint32_t u[8];
                lds128(u, d); lds128(u + 4, d + 2048);
                ma = babsmax(babsmax(ma, babsmax(u[0], u[1])), babsmax(u[2], u[3])); mb = babsmax(babsmax(mb, babsmax(u[4], u[5])), babsmax(u[6], u[7]));
            }
            ma = __reduce_max_sync(~0u, max(ma & 0x7fffu, (ma >> 16) & 0x7fffu)); mb = __reduce_max_sync(~0u, max(mb & 0x7fffu, (mb >> 16) & 0x7fffu));
            asm volatile("barrier.cluster.wait.aligned;" ::: "memory");
            if (lane < 3)
                asm volatile("st.async.shared::cluster.mbarrier::complete_tx::bytes.v2.b32 [%0],{%1,%2},[%3];"
                             ::"r"(mapa(sb + O_WMX + (c * 8 + w) * 8, lane)), "r"(ma), "r"(mb), "r"(mapa(sb + B_W, lane)) : "memory");
            __syncwarp();
            {
                uint32_t off[4];
                float cs[4] = {0.f, 0.f, 0.f, 0.f};
#pragma unroll
                for (int q = 0; q < 4; q++) {
                    const int g_ = (c * 2 + ((w >> 1) & 1)) * 56 + (q == 3 ? 24 : (w & 1) * 32 + q * 8), col = wg * 320 + g_, nb = col / 80;
                    off[q] = g_ < 320 && !(q == 3 && (w & 1)) ? ((nb * 512 + h * 16) * 10 + (col - nb * 80) / 8) * 32 + lane : ~0u;
                }
                const uint32_t ta = sb + O_WO + w * 8192 + (lane & 7) * 64 + (((lane >> 3) ^ (lane >> 1)) & 3) * 16;
#pragma unroll 2
                for (int i = 0; i < 16; i++) {
                    uint32_t r[4];
                    ldsm4t(r, ta + i * 512);
#pragma unroll
                    for (int q = 0; q < 4; q++) {
                        if (off[q] != ~0u) ((uint32_t*)g_wot)[off[q] + i * 320] = r[q];
                        cs[q] += fabsf(bf_lo(r[q])) + fabsf(bf_hi(r[q]));
                    }
                }
                float cm = 0.f;
#pragma unroll
                for (int q = 0; q < 4; q++) {
                    cs[q] += __shfl_xor_sync(~0u, cs[q], 1); cs[q] += __shfl_xor_sync(~0u, cs[q], 2);
                    cm = fmaxf(cm, cs[q]);
                }
                const uint32_t n1 = __reduce_max_sync(~0u, __float_as_uint(cm));
                if (lane == 0) g_co[h * 32 + c * 8 + w] = __uint_as_float(n1);
            }
            mbar_wait(sb + B_W, 0);
            uint32_t v[2];
            lds64(v, sb + O_WMX + (lane < 24 ? lane : 0) * 8);
            const bool mine = (lane >> 3) < 3 && ((lane >> 4) == 1) == (c == 2);
            ma = __reduce_max_sync(~0u, mine ? v[0] : 0u); mb = __reduce_max_sync(~0u, mine ? v[1] : 0u);
            if (c == 2) ma = mb = max(ma, mb);
            fa = __uint_as_float(ma << 16); fb = __uint_as_float(mb << 16);
            if (tid == 0) {
                if (c != 1) g_wmx[h * 3 + c] = fa;
                if (c == 0) g_wmx[h * 3 + 1] = fb;
            }
        } else {
            fa = __ldcg(g_wmx + h * 3 + (c == 2 ? 2 : 0)); fb = __ldcg(g_wmx + h * 3 + (c == 2 ? 2 : 1));
            asm volatile("barrier.cluster.wait.aligned;" ::: "memory");
        }
        if (layer == TLL) TL(49);
        float ia, ib;
        const float sa = pow2_scale(fa, 6, &ia), sc_b = pow2_scale(fb, 6, &ib);
        sl = __uint_as_float(uni(__float_as_uint(ia * ib * (0.08838834764831845f * 1.4426950408889634f))));
        const uint32_t pa = pack_bf(sa, sa), pb = pack_bf(sc_b, sc_b);
        const int ahead = layer == 0 ? 20 : WDEPTH;
        auto convert = [&](int lo) {
#pragma unroll 1
            for (int i = lo; i < lo + 10; i++) {
                issue(i + ahead);
                cp_wait<WDEPTH>();
                const uint32_t d = dst + (i < 19 ? i * 8192 : O_LAST);
                uint32_t u[8];
                lds128(u, d); lds128(u + 4, d + 2048);
#pragma unroll
                for (int q = 0; q < 8; q++)
                    asm("{.reg .b32 m,l,u; mul.rn.bf16x2 m,%0,%1; shl.b32 l,m,16; and.b32 u,m,0xffff0000; cvt.rn.f16x2.f32 %0,u,l;}" : "+r"(u[q]) : "r"(q < 4 ? pa : pb));
                sts128(d, u[0], u[1], u[2], u[3]); sts128(d + 2048, u[4], u[5], u[6], u[7]);
            }
            bar_sync(6 + wg, 128);
        };
        const uint32_t s0 = src + wg * 2048, s1 = src + 2048 - wg * 2048;
        convert(0);
#pragma unroll
        for (int i = 0; i < 10; i++) { ldsm4t(A0[i], s0 + i * 8192); ldsm4t(A1[i], s1 + i * 8192); }
        if (layer == TLL) TL(50);
        convert(10);
#pragma unroll
        for (int i = 10; i < 20; i++) { ldsm4t(A0[i], s0 + (i < 19 ? i * 8192 : O_LAST)); ldsm4t(A1[i], s1 + (i < 19 ? i * 8192 : O_LAST)); }
        if (layer == TLL) TL(53);
        bar_arrive(9, 288);
        bar_sync(4, 288);
        asm volatile("barrier.cluster.arrive.relaxed.aligned;" ::: "memory");
    }
    const uint32_t idn = (lane >> 3) == (lane & 3) ? ((lane & 4) ? 0x3c000000u : 0x3c00u) : 0u;
    float invM = g_invM0;
    char* redp = red_base() + (size_t)layer * 32 * 32768 + w * 2048 + (lane >> 4) * 1024 + ((lane >> 3) & 1) * 256 + (lane & 7) * 16;
    const uint32_t ro2 = uni((w >> 1) * 4096 + 128), rown = uni(c == 2 ? ro2 : c * 16384);
    const uint32_t L16 = lane * 16, L8 = lane * 8, L4 = lane * 4;
    const uint32_t xch0 = uni(sb + O_XCH + t0 * 1024), xch1 = uni(sb + O_XCH + t1 * 1024);
    const uint32_t qo0 = uni(sb + O_QKP + (w & 3) * 1024 + (wg ? 768 : 0)), qp0 = uni(qo0 + (wg ? 128 : 256));
    const uint32_t qo1 = uni(sb + O_QKP + (w & 3) * 1024 + (wg ? 128 : 512)), qp1 = uni(qo1 + (wg ? 256 : 128));
    const uint32_t vo1 = uni(qo1 + (wg ? -128 : 256)), vp1 = uni(qp1 + (wg ? -128 : 256));
    const uint32_t msr = uni(sb + O_MS + wg * 5376);
    const uint32_t msw = uni(msr + ((w >> 1) & 1) * 896 + (w & 1) * 512), msh = uni(msr + ((w >> 1) & 1) * 896 + 384 + (w & 1) * 2);
    const uint32_t sco = uni(sb + O_SC + c * 768 + (w & 3) * 256);
    const uint32_t woa = sb + O_WO + w * 8192 + (lane >> 4) * 512 + (lane & 7) * 64 + (((lane >> 3) ^ (lane >> 1)) & 1) * 16 + ((lane >> 2) & 1) * 32;
    const uint32_t w512 = uni(sb + w * 512), w128 = uni(sb + w * 128);
    const uint32_t pd0 = uni(mapa(sb, c == 2 ? 0 : 2) - sb), pd1 = uni(mapa(sb, c == 1 ? 0 : 1) - sb);
    const bool scw = c < 2 && w >= 4 && w <= 6;
    uint32_t sn = uni(sb + O_STG + (c == 2 ? 8192 : 0) + t1 * 1024);
    uint32_t ka = uni(sb + (w == 6 ? O_QKP + 512 : O_STG + 4096 + (w & 1) * 512));
    uint32_t vs = uni(sb + O_VM + t1 * 256);
    uint32_t va = uni(sb + O_STG + 8192 + w * 2048), vr = uni(sb + O_VM + w * 512);
    const uint32_t sn2 = uni(2 * sn - 16384), ka2 = uni(2 * ka - (w == 6 ? 0 : 16384)), vs2 = uni(2 * vs + 2048), va2 = uni(2 * va - 16384),
                   vr2 = uni(2 * vr + 2048);
    uint32_t xd = uni((uint32_t)mkdesc(sb + O_XS + wg * 20480, 512, 128, 0));
    const uint32_t xd2 = uni(2 * xd + 2560);

    uint32_t wp[2 * NPERM + 1][4];
    sfor<NPERM>([&](auto I) { constexpr int i = I; ldsm4t(wp[2 * i], woa + i * 1024); ldsm4t(wp[2 * i + 1], (woa ^ 32) + i * 1024); });
    auto wo_fetch = [&](uint32_t (&wo)[16][4], auto I) {
        constexpr int i = I;
        if constexpr (i < NPERM) {
#pragma unroll
            for (int q = 0; q < 4; q++) { wo[i][q] = wp[2 * i][q]; wo[8 + i][q] = wp[2 * i + 1][q]; }
        } else { ldsm4t(wo[i], woa + i * 1024); ldsm4t(wo[8 + i], (woa ^ 32) + i * 1024); }
    };
    if (layer == TLL) TL(32);
    float b0[16], b1[16];
    mbar_wait(sb + B_XF, 0);
    if (layer == TLL) TL(33);
    tok_issue<0, NTB>(A0, A1, b0, b1, xd, zero);
    tok_give(b0, L16, xch0);
    tok_issue<NTB, 40>(A0, A1, b0, b1, xd, zero);
    bar_sync(4, 256);
    wg_wait<0>();
    {
        uint32_t e[2][4];
        lds128_u<0>(e[0], L16, xch1); lds128_u<512>(e[1], L16, xch1);
        tok_finish(b1, e, L16, sn, idn);
    }
    sn = sn2 - sn; xd = xd2 - xd;
    bar_sync(5, 288);
    asm volatile("barrier.cluster.wait.aligned;" ::: "memory");
    if (layer == TLL) TL(34);
    mbar_wait(sb + B_XF + 8, 0);
    if (layer == TLL) TL(35);
    tok_issue<0, NTA>(A0, A1, b0, b1, xd, zero);
    uint32_t tr = clock32() - RDELAY;

#pragma unroll 1
    for (int st = 0;; st++) {
        uint4 mv[3];
        asm volatile("{.reg .pred p; .reg .b32 t;\n"
                     "mov.b32 %0,0; mov.b32 %1,0; mov.b32 %2,0; mov.b32 %3,0; mov.b32 %4,0; mov.b32 %5,0; mov.b32 %6,0; mov.b32 %7,0;\n"
                     "mov.b32 %8,0; mov.b32 %9,0; mov.b32 %10,0; mov.b32 %11,0;\n"
                     "T_LOOP: mov.u32 t,%%clock; sub.u32 t,t,%14; setp.ge.u32 p,t,%15;\n"
                     "@p ld.relaxed.gpu.global.v4.u32 {%0,%1,%2,%3},[%12]; @p ld.relaxed.gpu.global.v4.u32 {%4,%5,%6,%7},[%12+16384];\n"
                     "@p ld.relaxed.gpu.global.v4.u32 {%8,%9,%10,%11},[%13];\n"
                     "@!p bra T_LOOP;}"
                     : "=r"(mv[0].x), "=r"(mv[0].y), "=r"(mv[0].z), "=r"(mv[0].w), "=r"(mv[1].x), "=r"(mv[1].y), "=r"(mv[1].z), "=r"(mv[1].w),
                       "=r"(mv[2].x), "=r"(mv[2].y), "=r"(mv[2].z), "=r"(mv[2].w)
                     : "l"(redp), "l"(redp + ro2), "r"(tr), "n"(RDELAY) : "memory");
        STAMP(10);
        tok_issue<NTA, NTB>(A0, A1, b0, b1, xd, zero);
        tok_give(b0, L16, xch0);
        tok_issue<NTB, 40>(A0, A1, b0, b1, xd, zero);
        xd = xd2 - xd;
        STAMP(9);
        if (zero >> 30) break;
        asm volatile("{.reg .pred p; .reg .b32 a,h,t,n; .reg .b16 l,u; .reg .b64 q;\n"
                     "add.u32 a,%12,%13; add.u32 h,%12,%14; mov.u32 n,0;\n"
                     "M_LOOP:\n .pragma \"nounroll\";\n"
                     "st.shared.b32 [a],%0; st.shared.b32 [a+128],%1; st.shared.b32 [a+256],%2; mov.b32 {l,u},%3; st.shared.b16 [h],l;\n"
                     "st.shared.b32 [a+1792],%4; st.shared.b32 [a+1920],%5; st.shared.b32 [a+2048],%6; mov.b32 {l,u},%7; st.shared.b16 [h+1792],l;\n"
                     "st.shared.b32 [a+3584],%8; st.shared.b32 [a+3712],%9; st.shared.b32 [a+3840],%10; mov.b32 {l,u},%11; st.shared.b16 [h+3584],l;\n"
                     "lop3.b32 t,%3,%7,0x50000000,0x7e; lop3.b32 t,t,%11,0x50000000,0xf6; setp.gt.u32 p,t,0xffff;\n"
                     "vote.sync.any.pred p,p,-1; add.u32 n,n,1; setp.lt.and.u32 p,n,%17,p; @!p bra M_DONE;\n"
                     "ld.relaxed.gpu.global.v4.u32 {%0,%1,%2,%3},[%15]; ld.relaxed.gpu.global.v4.u32 {%4,%5,%6,%7},[%15+16384];\n"
                     "cvt.u64.u32 q,%16; add.u64 q,q,%15; ld.relaxed.gpu.global.v4.u32 {%8,%9,%10,%11},[q];\n"
                     "bra M_LOOP;\n"
                     "M_DONE:}"
                     : "+r"(mv[0].x), "+r"(mv[0].y), "+r"(mv[0].z), "+r"(mv[0].w), "+r"(mv[1].x), "+r"(mv[1].y), "+r"(mv[1].z), "+r"(mv[1].w),
                       "+r"(mv[2].x), "+r"(mv[2].y), "+r"(mv[2].z), "+r"(mv[2].w)
                     : "r"(L4), "r"(msw), "r"(msh), "l"(redp), "r"(ro2), "n"(SPIN_LIM) : "memory");
        bar_sync(3, 256);
        STAMP(0);
        uint32_t e[2][4];
        float f1[4];
        {
            uint32_t b[10][4];
            float acc[4][4];
#pragma unroll
            for (int i = 0; i < 4; i++) acc[i][0] = acc[i][1] = acc[i][2] = acc[i][3] = 0.f;
            auto ld = [&](auto I) { constexpr int i = I; ldsm4t_u<i * 512>(b[i], L16, msr); };
            auto mm = [&](auto I) {
                constexpr int i = I;
                mma_f16(acc[0], A0[2 * i], b[i][0], b[i][1]); mma_f16(acc[2], A1[2 * i], b[i][0], b[i][1]);
                mma_f16(acc[1], A0[2 * i + 1], b[i][2], b[i][3]); mma_f16(acc[3], A1[2 * i + 1], b[i][2], b[i][3]);
            };
            ld(IC<0>()); ld(IC<1>()); ld(IC<2>()); ld(IC<3>());
            sts32_u<O_MX>(L4, w128,
                          habsmax(habsmax(habsmax(habsmax(mv[0].x, mv[0].y), habsmax(mv[0].z, mv[1].x)), habsmax(habsmax(mv[1].y, mv[1].z), mv[2].x)),
                                  habsmax(habsmax(mv[2].y, mv[2].z), habsmax(habsmax(mv[0].w, mv[1].w), mv[2].w) & 0xffffu)));
            wg_wait<0>();
            ld(IC<4>()); mm(IC<0>()); ld(IC<5>()); mm(IC<1>()); ld(IC<6>()); mm(IC<2>());
            ld(IC<7>()); mm(IC<3>()); ld(IC<8>()); mm(IC<4>()); ld(IC<9>()); mm(IC<5>());
            lds128_u<0>(e[0], L16, xch1); lds128_u<512>(e[1], L16, xch1);
            mm(IC<6>()); mm(IC<7>()); mm(IC<8>()); mm(IC<9>());
            const uint32_t u0 = pack_bf((acc[0][0] + acc[1][0]) * invM, (acc[0][1] + acc[1][1]) * invM);
            const uint32_t u1 = pack_bf((acc[0][2] + acc[1][2]) * invM, (acc[0][3] + acc[1][3]) * invM);
#pragma unroll
            for (int i = 0; i < 4; i++) f1[i] = (acc[2][i] + acc[3][i]) * invM;
            sts32_u<0>(L4, qo0, u0); sts32_u<0>(L4, qp0, u1); sts32_u<0>(L4, qo1, pack_bf(f1[0], f1[1])); sts32_u<0>(L4, qp1, pack_bf(f1[2], f1[3]));
        }
        STAMP(1);
        bar_sync(1, 320);
        if (__builtin_expect(scw, 1)) {
            float a[4][4];
#pragma unroll
            for (int i = 0; i < 4; i++) a[i][0] = a[i][1] = a[i][2] = a[i][3] = 0.f;
            uint32_t q[4][4], k[4][4];
            sfor<4>([&](auto I) {
                constexpr int i = I;
                ldsm4t_u<O_QKP + i * 1024>(q[i], L16, sb); ldsm4t_u<i * 1024>(k[i], L16, ka);
            });
#pragma unroll
            for (int i = 0; i < 4; i++) {
                mma_bf(a[i & 1], q[i][0], q[i][1], q[i][2], q[i][3], k[i][0], k[i][1]);
                mma_bf(a[2 + (i & 1)], q[i][0], q[i][1], q[i][2], q[i][3], k[i][2], k[i][3]);
            }
            const float mk = w == 6 ? 1.f : 0.f;
            const float x0 = (a[0][0] + a[0][2]) + (a[1][0] + a[1][2]), x1 = (a[0][1] + a[0][3]) + (a[1][1] + a[1][3]);
            const float y0 = (a[2][0] + a[2][2]) + (a[3][0] + a[3][2]), y1 = (a[2][1] + a[2][3]) + (a[3][1] + a[3][3]);
            st_share2(L8, sco, sb + B_S, pd0, pd1, pack_bf(fmaf(y0, mk, x0) * sl, fmaf(y1, mk, x1) * sl), pack_bf(y0 * sl, y1 * sl));
        }
        if (c == 2) {
            const uint32_t x = lds32_u<0>(L4, vo1), y = lds32_u<0>(L4, vp1);
            st_share2(L8, vs, sb + B_S, pd0, pd1, pack_bf(f1[0] + bf_lo(x), f1[1] + bf_hi(x)), pack_bf(f1[2] + bf_lo(y), f1[3] + bf_hi(y)));
        }
        STAMP(3);
        if (st == NSEG - 1) break;
        tok_finish(b1, e, L16, sn, idn);
        redp += (st & 1) ? 32768 - 512 : 512;
        if (wg == 0) {
            uint32_t wo[16][4], vx[2][2][4], vm[2][2];
            ldsm4_u<0>(vx[0][0], L16, va); ldsm4_u<512>(vx[0][1], L16, va); ldsm4_u<1024>(vx[1][0], L16, va); ldsm4_u<1536>(vx[1][1], L16, va);
            sfor<NWO0>([&](auto I) { wo_fetch(wo, I); });
            mbar_wait(sb + B_S, st & 1);
            STAMP(4);
            uint32_t s[5];
            {
                uint32_t p[2][5];
                sfor<2>([&](auto R) {
                    constexpr int r = R;
                    lds64_u<O_SC + r * 768>(p[r], L8, sb); lds64_u<O_SC + r * 768 + 256>(p[r] + 2, L8, sb); p[r][4] = lds32_u<O_SC + r * 768 + 512>(L8, sb);
                });
#pragma unroll
                for (int j = 0; j < 5; j++) s[j] = badd(p[0][j], p[1][j]);
            }
            lds64_u<0>(vm[0], L8, vr); lds64_u<256>(vm[1], L8, vr);
            uint32_t mm = bmax(bmax(bmax(s[0], s[1]), bmax(s[2], s[3])), s[4]);
            mm = bmax(bmax(mm, __shfl_xor_sync(~0u, mm, 1)), bmax(__shfl_xor_sync(~0u, mm, 2), __shfl_xor_sync(~0u, mm, 3)));
            const float m = fmaxf(bf_lo(mm), bf_hi(mm));
            float o0[4] = {0.f, 0.f, 0.f, 0.f}, o1[4] = {0.f, 0.f, 0.f, 0.f}, d[10];
#pragma unroll
            for (int j = 0; j < 5; j++) { d[2 * j] = bf_lo(s[j]) - m; d[2 * j + 1] = bf_hi(s[j]) - m; }
#pragma unroll
            for (int j = 0; j < 10; j++) d[(j + 8) % 10] = ex2(d[(j + 8) % 10]);
            float sum = ((d[8] + d[9]) + (d[0] + d[1])) + ((d[2] + d[3]) + (d[4] + d[5])) + (d[6] + d[7]);
            const uint32_t p4 = pack_bf(d[8], d[9]), p0 = pack_bf(d[0], d[1]), p1 = pack_bf(d[2], d[3]), p2 = pack_bf(d[4], d[5]), p3 = pack_bf(d[6], d[7]);
            mma_bf8(o0, vm[0][0], vm[0][1], p4);
            mma_bf8(o1, vm[1][0], vm[1][1], p4);
            mma_bf(o0, vx[0][0][0], vx[0][0][1], vx[0][0][2], vx[0][0][3], p0, p1);
            mma_bf(o1, vx[1][0][0], vx[1][0][1], vx[1][0][2], vx[1][0][3], p0, p1);
            mma_bf(o0, vx[0][1][0], vx[0][1][1], vx[0][1][2], vx[0][1][3], p2, p3);
            mma_bf(o1, vx[1][1][0], vx[1][1][1], vx[1][1][2], vx[1][1][3], p2, p3);
            sfor<NWO0B - NWO0>([&](auto I) { constexpr int i = I; wo_fetch(wo, IC<NWO0 + i>()); });
            sum += __shfl_xor_sync(~0u, sum, 1);
            sum += __shfl_xor_sync(~0u, sum, 2);
            sts32_u<O_OS>(L4, w512, pack_bf(o0[0], o0[1])); sts32_u<O_OS + 128>(L4, w512, pack_bf(o0[2], o0[3]));
            sts32_u<O_OS + 256>(L4, w512, pack_bf(o1[0], o1[1])); sts32_u<O_OS + 384>(L4, w512, pack_bf(o1[2], o1[3]));
            sts32_u<O_SUM>(lane & 28, sb, __float_as_uint(sum));
            STAMP(5);
            invM = mem_out<NWO0B>(sb, L16, L8, wo, woa, redp + rown, w & 1);
            tr = clock32();

        } else {
            uint32_t wo[16][4];
            sfor<NWO1>([&](auto I) { wo_fetch(wo, I); });
            invM = mem_out<NWO1>(sb, L16, L8, wo, woa, redp + rown, w & 1);
            tr = clock32();

        }
        STAMP(7);
        tok_issue<0, NTA>(A0, A1, b0, b1, xd, zero);
        sn = sn2 - sn; ka = ka2 - ka; vs = vs2 - vs; va = va2 - va; vr = vr2 - vr;
        STAMP(8);
    }
    if (layer == TLL) TL(40);
    bar_arrive(8, 320);
    tid = read_tid(); lane = tid & 31;
    float acc[40];
    const int nc = c == 2 ? 10 : 11;
    const int mb = 28 + (h >> 3), nj = c == 2 ? 1 : 2;
    uint32_t rv[2][2];
    const size_t go = ((size_t)(mb * 64 + (w & 3) * 16 + (lane >> 2)) * 640 + (h & 7) * 80 + (wg * 5 + c * 2) * 8 + (lane & 3) * 2) >> 1;
#pragma unroll
    for (int u = 0; u < 4; u++) rv[u >> 1][u & 1] = (u >> 1) < nj ? __ldcg((const uint32_t*)res + go + (u >> 1) * 4 + (u & 1) * 2560) : 0u;
#pragma unroll 1
    for (int k = 0; k < nc; k++) {
        mbar_wait(sb + T_FB + (k % 7) * 8, k >= 7);
        mbar_wait(sb + T_FA + (k & 3) * 8, (k >> 2) & 1);
        if (layer == TLL && k == 0) TL(41);
        const uint64_t da = mkdesc(sb + O_MS + (k & 3) * 16384 + wg * 8192, 1024, 128, 0), db = mkdesc(sb + tail_b(k) + wg * 10240, 1280, 128, 0);
        wg_fence();
#pragma unroll
        for (int q = 0; q < 4; q++) wg_n80_ss(acc, da + q * 128, db + q * 160, k | q);
        wg_commit();
        if (k > 0) {
            wg_wait<1>();
            if (lane == 0) { mbar_arrive(sb + T_EA + ((k - 1) & 3) * 8); if (k <= 4) mbar_arrive(sb + T_EB + (k - 1) * 8); }
        }
    }
    if (layer == TLL) TL(52);
    wg_wait<0>();
    asm volatile("barrier.cluster.arrive.relaxed.aligned; barrier.cluster.wait.aligned;" ::: "memory");
    const uint32_t ra = sb + O_XS + tid * 16, rb = sb + O_MS + tid * 16;
#pragma unroll
    for (int j = 0; j < 5; j++) {
        const float* q = acc + 4 * j;
        sts128(rb + j * 4096, __float_as_uint(wg ? q[0] : q[20]), __float_as_uint(wg ? q[1] : q[21]), __float_as_uint(wg ? q[2] : q[22]), __float_as_uint(wg ? q[3] : q[23]));
    }
    bar_sync(4, 256);
#pragma unroll
    for (int j = 0; j < 5; j++) {
        const float* q = acc + 4 * j;
        uint32_t p[4];
        lds128(p, sb + O_MS + (tid ^ 128) * 16 + j * 4096);
        asm volatile("st.async.shared::cluster.mbarrier::complete_tx::bytes.v4.f32 [%0],{%1,%2,%3,%4},[%5];" ::"r"(mapa(ra + c * 8192 + (j & 1) * 4096, j >> 1)),
                     "f"((wg ? q[20] : q[0]) + __uint_as_float(p[0])), "f"((wg ? q[21] : q[1]) + __uint_as_float(p[1])),
                     "f"((wg ? q[22] : q[2]) + __uint_as_float(p[2])), "f"((wg ? q[23] : q[3]) + __uint_as_float(p[3])), "r"(mapa(sb + T_RED, j >> 1)) : "memory");
    }
    mbar_wait(sb + T_RED, 0);
#pragma unroll 1
    for (int u = 0; u < nj; u++) {
        uint32_t p[3][4];
#pragma unroll
        for (int q = 0; q < 3; q++) lds128(p[q], ra + q * 8192 + u * 4096);
        float y[4];
#pragma unroll
        for (int i = 0; i < 4; i++) y[i] = __uint_as_float(p[0][i]) + __uint_as_float(p[1][i]) + __uint_as_float(p[2][i]);
        ((uint32_t*)out)[go + u * 4] = bfma(pack_bf(y[0], y[1]), 0x3f803f80u, u ? rv[1][0] : rv[0][0]);
        ((uint32_t*)out)[go + u * 4 + 2560] = bfma(pack_bf(y[2], y[3]), 0x3f803f80u, u ? rv[1][1] : rv[0][1]);
    }
    __syncwarp();
    if (layer == 0 && lane == 0) red_release(g_flag + F_R + mb);
    TL(layer == 0 ? 15 : 29);
    asm volatile("barrier.cluster.arrive.relaxed.aligned; barrier.cluster.wait.aligned;" ::: "memory");
}

__device__ __forceinline__ void tail_load_b(const uint32_t sb, const int h, const int c, const int k) {
    mbar_expect(sb + T_FB + (k % 7) * 8, 20480);
    bulk_g2s(sb + tail_b(k), (const char*)g_wot + (size_t)((h & 7) * GNC + c * 11 + k) * 20480, 20480, sb + T_FB + (k % 7) * 8);
}
template <int layer> __device__ __forceinline__ void chain_aux(const uint32_t sb, const int c, const int h, const int nact) {
    const int tid = read_tid(), w = __shfl_sync(~0u, tid >> 5, 0), lane = tid & 31;
    if (w == 8) {
        mbar_init(sb + O_BAR + lane * 8, lane == 2 ? (c == 2 ? 9 : 4) : (lane >= 16 && lane < 20) || (lane >= 27 && lane < 31) ? 8 : 1);
        asm volatile("fence.mbarrier_init.release.cluster;" ::: "memory");
        fence_async_smem();
        __syncwarp();
    }
    {
        uint4* z = (uint4*)red_base() + layer * 65536;
#pragma unroll 1
        for (int i = blockIdx.x * 128 + tid - 256; i < 65536; i += 96 * 128)
            if (i >= 2048 || (i & 32)) z[i] = make_uint4(0, 0, 0, 0);
    }
    if (w == 8 && lane == 0) {
        mbar_expect(sb + B_S, s_tx(c));
        mbar_expect(sb + B_W, 192);
        mbar_expect(sb + T_RED, (c == 2 ? 1 : 2) * 3 * 4096);
        if (layer == 1) prefetch_l2(red_base() + 32 * 32768 + blockIdx.x * 1024, 1024);
        if (layer == 0) wait_flag<400>(g_ready, NSETUP);
    }
    __syncwarp();
    cluster_sync_full();
    asm volatile("barrier.cluster.arrive.relaxed.aligned;" ::: "memory");
    pdl_wait();
    if (w == 11 && lane == 0) red_relaxed(g_flag + F_X + layer * 128 + 65);
    Flag* flag = g_flag + layer * NSEG * 32 + h;
    const Flag* xflag = g_flag + F_X + layer * 128;
    char* const it0 = g_item + (size_t)h * 32768;
    if (w == 8) {
#pragma unroll 1
        for (int n = 0; n < 3; n++) {
            wait_flag<100>(xflag + (n >> 1), 4);
            fence_async_glb();
            if (n == 0) { bar_sync(4, 288); fence_async_smem(); }
            if (lane == 0 && n < 2) {
                mbar_expect(sb + B_XF + n * 8, 40960);
                bulk_g2s(sb + O_XS + n * 40960, (const char*)g_xn + n * 40960, 40960, sb + B_XF + n * 8);
            }
            __syncwarp();
        }
#pragma unroll 1
        for (int n = 0; n < NSEG; n++) {
            const int np = n & 1;
            if (n == 0) { wait_flag<100>(g_flag + F_W + layer * 128, 96); bar_sync(5, 288); } else bar_sync(2, 352);
            if (n == 1) TL(12 + layer * 14);
            if (n == 63) TL(13 + layer * 14);
            if (lane == 0 && n == NSEG - 1) mbar_arrive(sb + B_STG + 8);
            if (lane == 0 && n < NSEG - 1) {
                const uint32_t vs = sb + O_STG + 8192 - np * 16384, vb = sb + B_VX + np * 8;
                if (c == 2) {
                    fence_async_smem();
                    bulk_s2s(mapa(vs, 0), vs, 8192, mapa(vb, 0));
                    bulk_s2s(mapa(vs, 1), vs, 8192, mapa(vb, 1));
                } else mbar_expect(vb, 8192);
                if (n == 0) { mbar_expect(sb + B_XF, 40960); bulk_g2s(sb + O_XS, (const char*)g_xn + 2 * 40960, 40960, sb + B_XF); }
                if (n == h * 3 + c && !np && n + 6 < NSEG) prefetch_l2(red_base() + (size_t)(layer * 32 + (n >> 1) + 3) * 32768, 32768);
            }
            __syncwarp();
        }
    } else if (w == 11) {
        float cvo;
        {
            auto max8 = [&](const float* p) {
                const float4 u = ((const float4*)p)[0], v = ((const float4*)p)[1];
                return fmaxf(fmaxf(fmaxf(u.x, u.y), fmaxf(u.z, u.w)), fmaxf(fmaxf(v.x, v.y), fmaxf(v.z, v.w)));
            };
            wait_flag<300>(g_flag + F_W + layer * 128, 96);
            const float* pc = g_co + lane * 32;
            float a = 640.f * __ldcg(g_wmx + lane * 3 + 2), o = fmaxf(fmaxf(max8(pc), max8(pc + 8)), max8(pc + 16));
#pragma unroll 1
            for (int s = 16; s; s >>= 1) { a = fmaxf(a, __shfl_xor_sync(~0u, a, s)); o += __shfl_xor_sync(~0u, o, s); }
            cvo = a * o * 2.f;
        }
        float invM = g_invM0;
        float iv;
        weight_scale(h, 2, &iv);
        const uint32_t L16 = sb + lane * 16 + O_MX;
#pragma unroll 1
        for (int st = 0; st < NSEG; st++) {
            bar_sync(1, 320);
            if (st == NSEG - 1) break;
            if (lane == 0) mbar_arrive(sb + B_STG + (st & 1) * 8);
            uint32_t u[2][4];
            lds128(u[0], L16); lds128(u[1], L16 + 512);
            uint32_t mx = habsmax(habsmax(habsmax(u[0][0], u[0][1]), habsmax(u[0][2], u[0][3])), habsmax(habsmax(u[1][0], u[1][1]), habsmax(u[1][2], u[1][3])));
            mx = __reduce_max_sync(~0u, max(mx & 0x7fffu, (mx >> 16) & 0x7fffu));
            const float bound = fmaxf(__half2float(__ushort_as_half((unsigned short)mx)) * invM, 25.5f) * cvo;
            const float sc = pow2_scale(bound, 15, &invM);
            sts64(sb + O_SCL, __float_as_uint(sc * iv), __float_as_uint(invM));
            bar_arrive(2, 352);
        }
    } else if (w == 10) {
        bar_sync(9, 288);
        if (lane == 0) red_release(g_flag + F_W + layer * 128);
        if (lane == 0) {
#pragma unroll 1
            for (int n = 0; n < NSEG; n++) {
                mbar_sleep(sb + B_STG + (n & 1) * 8, (n >> 1) & 1);
                fence_async_smem();
                const uint32_t stg = sb + O_STG - (n & 1) * 16384;
                char* it = it0 + (size_t)(n % RING) * 32 * 32768;
                bulk_s2g(it + c * 8192, stg + (c == 2 ? 8192 : 0), 8192);
                bulk_commit();
                if (n + 1 >= RING && n + 1 < NSEG) wait_flag(flag - (RING - 1) * 32, 7);
                bulk_wait0();
                mbar_arrive(sb + B_FREE + (n & 1) * 8);
                fence_async_glb();
                red_relaxed(LASTS && n == NSEG - 1 ? g_flag + F_X + layer * 128 + 32 + h : flag);
                flag += 32;
            }
        }
    } else {
        bool allx = false;
#pragma unroll 1
        for (int st = 0; st < NSEG; st++) {
            const int par = st & 1;
            char* const it = it0 + (size_t)(st % RING) * 32 * 32768;
            if (lane == 0 && !allx && st + 3 < NSEG) {
                allx = ld_acquire(xflag + 64) >= nact;
                if (!allx) wait_flag(st + 4 < NSEG ? xflag + ((st + 3) >> 1) : xflag + 64, st + 4 < NSEG ? 4 : nact);
                fence_async_glb();
            }
            __syncwarp();
            if (st < NSEG - 1 && c < 2) mbar_sleep(sb + B_VX + par * 8, (st >> 1) & 1);
            if (st < NSEG - 2) mbar_sleep(sb + B_XF + par * 8, ((st >> 1) + 1) & 1);
            bar_sync(1, 320);
            if (lane == 0 && st + 3 < NSEG) {
                mbar_expect(sb + B_XF + (par ^ 1) * 8, 40960);
                bulk_g2s_last(sb + O_XS + (par ^ 1) * 40960, (const char*)g_xn + (size_t)(st + 3) * 40960, 40960, sb + B_XF + (par ^ 1) * 8);
            } else if (lane == 0 && st < NSEG - 1) {
                tail_load_b(sb, h, c, (par ^ 1) * 2); tail_load_b(sb, h, c, (par ^ 1) * 2 + 1);
            }
            __syncwarp();
            if (lane == 0 && c < 2) {
                fence_async_smem();
#pragma unroll 1
                for (int i = 0; i < 4; i++) bulk_s2g(it + 24576 + (c * 4 + i) * 512, sb + O_QKP + i * 1024 + 512, 512);
                bulk_commit();
                asm volatile("cp.async.bulk.wait_group.read 0;" ::: "memory");
            }
            __syncwarp();
            if (st < NSEG - 1) bar_arrive(2, 352);
            mbar_sleep(sb + B_S, par);
            __syncwarp();
            if (lane == 0) {
                if (st < NSEG - 1) mbar_expect(sb + B_S, s_tx(c));
                if (c == 2) { fence_async_smem(); bulk_s2g(it + 28672, sb + O_VM + par * 2048, 2048); bulk_commit(); }
                if (st == NSEG - 1) asm volatile("cp.async.bulk.wait_group.read 0;" ::: "memory");
            }
            __syncwarp();
            if (st == NSEG - 1) bar_arrive(8, 320);
            if (lane == 0) { bulk_wait0(); fence_async_glb(); red_relaxed(flag); }
            __syncwarp();
            mbar_sleep(sb + B_FREE + par * 8, (st >> 1) & 1);
            flag += 32;
        }
    }
    __syncwarp();
    const int nc = c == 2 ? 10 : 11;
    if (w == 10) {
        bar_sync(8, 320);
        if (lane == 0) {
            if (layer == 1 && blockIdx.x == 0) g_ready[0].v = 0;
            fence_async_smem();
            __nanosleep(TDELAY);
            wait_flag(xflag + 64, nact);
            wait_flag<50>(g_flag + F_O + layer * 32 + 28 + (h >> 3), 64);
            fence_async_glb();
#pragma unroll 1
            for (int k = 0; k < nc; k++) {
                if (k >= 4) mbar_sleep(sb + T_EA + (k & 3) * 8, ((k >> 2) - 1) & 1);
                mbar_expect(sb + T_FA + (k & 3) * 8, 16384);
                bulk_g2s_last(sb + O_MS + (k & 3) * 16384, (const char*)g_O + (size_t)((28 + (h >> 3)) * GNC + c * 11 + k) * 16384, 16384, sb + T_FA + (k & 3) * 8);
            }
        }
    } else if (w == 9 && lane == 0) {
        __nanosleep(TDELAY);
#pragma unroll 1
        for (int k = 4; k < nc; k++) {
            if (k >= 7) mbar_sleep(sb + T_EB + (k - 7) * 8, 0);
            tail_load_b(sb, h, c, k);
        }
    }
    __syncwarp();
    asm volatile("barrier.cluster.wait.aligned;" ::: "memory");
    asm volatile("barrier.cluster.arrive.relaxed.aligned; barrier.cluster.wait.aligned;" ::: "memory");
    asm volatile("barrier.cluster.arrive.relaxed.aligned; barrier.cluster.wait.aligned;" ::: "memory");
}

constexpr int RI_A = 0, RI_TAB = 81920, RI_STG = RI_TAB + 82 * 768;
constexpr int RI_RES = RI_STG + 25600, RI_ST = RI_RES + 2 * 64 * 336;
constexpr int HB_A = G_BAR + 64, HB_AFREE = HB_A + 32, HB_LN = HB_A + 40, HB_FULL = HB_A + 64, HB_DONE = HB_FULL + 48, HB_FREE = HB_DONE + 48;
constexpr int HP_SMEM = HB_FREE + 48;
static_assert(G_BAR >= RI_ST + 2048, "helper shared-memory map");
#define IDL 280
#define ITEM_NS 60
#define PFW_AT 28
#define PFW_NS 150
__device__ __forceinline__ void helper_aux(const uint32_t sb, const int j, const int nh, const int na, const int nbh, const int layer, const bf16* Wq,
                                           const bf16* Wk, const bf16* Wv, const bf16* Wo) {
    const int w = threadIdx.x >> 5, lane = threadIdx.x & 31, p = w - 8;
    if (lane == 0 && j < (nh & ~3)) {
        int n = 0;
        for (int a = j >> 2; a < 32; a += nh >> 2, n++) {
            if (n == 0) continue;
            mbar_wait(sb + HB_AFREE, (n - 1) & 1);
            mbar_expect(sb + HB_A + p * 8, 20480);
            bulk_g2s_last(sb + RI_A + p * 20480, (const char*)g_YT + (size_t)a * 81920 + p * 20480, 20480, sb + HB_A + p * 8);
            if (p == 0) { mbar_wait(sb + HB_LN, (n - 1) & 1); red_release(g_flag + F_X + layer * 128 + a - (nh >> 2)); }
        }
        if (p == 0) { mbar_wait(sb + HB_LN, (n - 1) & 1); red_release(g_flag + F_X + layer * 128 + (j >> 2) + (n - 1) * (nh >> 2)); }
    }
    __syncwarp();
    if (layer == 0 && w == 8 && lane == 0) wait_flag<400>(g_flag + F_W, 96);
    __syncwarp();
    bar_sync(3, 384);
    if (p == 3 && lane == 0 && j < (nh & ~3)) red_release(g_flag + F_X + layer * 128 + 64);
    fence_async_smem();
    Flag* oflag = g_flag + F_O + layer * 32;
    if (j < na) {
        int sl = p & 1, ph = 1;
        for (int idx = j + (p & 1) * na; idx < NSEG * 32 && p >= 2 && lane == 0; idx += 2 * na) {
            mbar_wait(sb + HB_DONE + sl * 8, ph ^ 1);
            mbar_arrive(sb + HB_FREE + sl * 8);
            red_release(oflag + (idx >> 6));
            atomicAdd(&g_flag[layer * NSEG * 32 + idx].v, 1u);
            sl += 2;
            if (sl >= 6) { sl -= 6; ph ^= 1; }
        }
        for (int idx = j + p * na; idx < NSEG * 32 && p < 2 && lane == 0; idx += 2 * na) {
            mbar_wait(sb + HB_FREE + sl * 8, ph);
            if (LASTS && idx >= (NSEG - 1) * 32) {
                const char* src = g_item + (size_t)(idx % (RING * 32)) * 32768;
                wait_flag<ITEM_NS>(g_flag + F_X + layer * 128 + 32 + (idx & 31), 3);
                fence_async_glb();
                mbar_expect(sb + HB_FULL + sl * 8, 30720);
                bulk_g2s(sb + sl * 30720, src, 24576, sb + HB_FULL + sl * 8);
                wait_flag<30>(g_flag + layer * NSEG * 32 + idx, 3);
                fence_async_glb();
                bulk_g2s(sb + sl * 30720 + 24576, src + 24576, 6144, sb + HB_FULL + sl * 8);
                sl += 2;
                if (sl >= 6) { sl -= 6; ph ^= 1; }
                continue;
            }
            wait_flag<ITEM_NS>(g_flag + layer * NSEG * 32 + idx, 6);
            fence_async_glb();
            if (idx < (NSEG - 2) * 32) __nanosleep(IDL);
            mbar_expect(sb + HB_FULL + sl * 8, 30720);
            bulk_g2s(sb + sl * 30720, g_item + (size_t)(idx % (RING * 32)) * 32768, 30720, sb + HB_FULL + sl * 8);
            sl += 2;
            if (sl >= 6) { sl -= 6; ph ^= 1; }
        }
    } else if (lane == 0 && p == 3) {
        if (layer == 0) {
            wait_flag<1000>(oflag + PFW_AT, 64);
            const int np = nh - na;
#pragma unroll 1
            for (int i = j - na; i < 1280; i += np) {
                const bf16* W = i < 320 ? Wq : i < 640 ? Wk : i < 960 ? Wv : Wo;
                prefetch_l2((const char*)W + (size_t)(i % 320) * 16384, 16384);
                __nanosleep(PFW_NS);
            }
#pragma unroll 1
            for (int i = j - na; i < 205; i += np) {
                const char* p_ = i < 160 ? (const char*)g_Wf + i * 16384 : i < 165 ? (const char*)g_stat + (i - 144) * 16384
                               : i < 167 ? (const char*)g_ctab + (i - 165) * 8192 : (const char*)(g_flag + NFLAG) - (i - 166) * 16384;
                prefetch_l2(p_, 16384);
                __nanosleep(PFW_NS);
            }
            if (j - na < 16) prefetch_l2(g_rtab + (j - na) * (RF_A / 4), RF_A / 4);
#pragma unroll 1
            for (int i = j - na; i < 130; i += np) { prefetch_l2((const char*)g_xb + i * 16384, 16384); __nanosleep(PFW_NS); }
        }
    } else if (lane == 0) {
        if (p == 2) wait_flag<500>(g_flag + F_X + layer * 128 + 64, nh & ~3);
        int c0 = 0;
        for (int mb = (j - na) >> 3; mb < nbh; mb += (nh - na) >> 3, c0 += GNC) {
            if (p < 2) wait_flag<300>(oflag + 2 * mb + p, 64);
            fence_async_glb();
            oproj_load(sb, p, mb, (j - na) & 7, c0, nh - na < 24 ? 0 : mb == nbh - 1 ? GPACE2 : GPACE);
        }
    }
}
__device__ __forceinline__ void helper_mma(char* sm, const int jh, const int nh, const int na, const int nbh, const int layer, const bf16* res, bf16* x,
                                           bf16* out) {
    const uint32_t sb = smem_u32(sm);
    const int tid = threadIdx.x, w = tid >> 5, lane = tid & 31, g = lane >> 2, t = lane & 3;
    const bool act = jh < (nh & ~3);
    const int j4 = jh & 3;
    const int fr = tid & 63, rg = w >> 1;
    auto chunk0 = [&](int u) { return u == 0 ? 5 * j4 : u == 1 ? 75 - 5 * j4 : u == 2 ? 40 + 5 * j4 : 35 - 5 * j4; };
    const int gr = tid / 20, gq_ = tid - gr * 20, go = gr * 80 + chunk0(gq_ / 5) + gq_ % 5;
    const uint32_t gs = sb + RI_RES + gr * 336 + gq_ * 16;
    auto residual = [&](int a, int n) {
#pragma unroll 1
        for (int r = 0; r < 64 - gr && tid < 240 && a < 32; r += 12) cp_async16(gs + (n & 1) * 21504 + r * 336, (const uint4*)res + (a * 64 + r) * 80 + go);
        cp_commit();
    };
    if (act) {
        if (tid < 240) {
            const int k0 = tid / 48, n = tid - k0 * 48;
            const float d = (float)(40 * j4 + n), amp = 2.f * 0.03952847075210474f;
#pragma unroll 4
            for (int u = 0; u < 16; u++)
                *(uint4*)(sm + RI_TAB + (tid + u * 240) * 16) = cos_row8(fmaf((float)((k0 + (u & 3) * 5) * 16 + ((u >> 2) & 1)), d, (float)((u & 8) * 20)), 2.f * d, amp);
            if (tid < 96) *(uint4*)(sm + RI_TAB + (3840 + tid) * 16) = make_uint4(k0 == 0 ? pack_h((n & 1) ? -amp : amp, 0.f) : 0u, 0, 0, 0);
        }
        fence_async_smem();
        residual(jh >> 2, 0);
    }
    bar_sync(1, 384);
    if (layer == TLL) TL(36);
    if (act) {
        const float4 wm = ((const float4*)g_wmax)[lane];
        const int wg = w >> 2;
        int n = 0;
#pragma unroll 1
        for (int a = jh >> 2; a < 32; a += nh >> 2, n++) {
            float acc[2][24];
            uint64_t da = mkdesc(sb + RI_A + wg * 40960, 1024, 1024, 1), db = mkdesc(sb + RI_TAB + wg * 30720, 768, 128, 0);
#pragma unroll
            for (int gq = 0; gq < 2; gq++) {
                mbar_wait(sb + HB_A + (wg * 2 + gq) * 8, n & 1);
                if (layer == TLL && n == TLN && gq == 0) TL(45);
                wg_fence();
#pragma unroll 5
                for (int k = 0; k < 10; k++) { wg_n48_ss_ta(acc[gq], da, db, k); da += 128; db += 96; }
                wg_commit();
            }
            if (wg == 0) {
                mbar_wait(sb + HB_A + 16, n & 1);
                wg_fence();
                wg_n48_ss_ta(acc[0], da, db + 20 * 96, 1);
                wg_commit();
            }
            float inv;
            pow2_scale(__uint_as_float(__reduce_max_sync(~0u, __float_as_uint(fmaxf(fmaxf(wm.x, wm.y), fmaxf(wm.z, wm.w))))), 0, &inv);
            const uint32_t ysc = pack_bf(inv, inv);
            wg_wait<0>();
            if (layer == TLL && n == TLN) TL(46);
            if (lane == 0) mbar_arrive(sb + HB_AFREE);
            const uint32_t ad = sb + RI_STG + ((w & 3) * 16 + (lane & 15)) * 400 + (lane >> 4) * 96 + wg * 192;
#pragma unroll
            for (int q = 0; q < 6; q++) {
                const float *e = acc[0] + q * 4, *o = acc[1] + q * 4;
                stsm4(ad + q * 16, pack_h(e[0] + o[0], e[1] + o[1]), pack_h(e[2] + o[2], e[3] + o[3]), pack_h(e[0] - o[0], e[1] - o[1]), pack_h(e[2] - o[2], e[3] - o[3]));
            }
            cp_wait<0>();
            bar_sync(4, 256);
            const uint32_t xa = sb + RI_RES + (n & 1) * 21504 + fr * 336 + rg * 80, sg = (rg & 1) ? 0xbc00bc00u : 0x3c003c00u;
            float sum = 0.f, sq = 0.f;
            uint32_t ya = sb + RI_STG + fr * 400 + (rg >> 1) * 96 + ((rg & 1) ? 64 : 0), carry;
            asm("fma.rn.f16x2 %0,%1,%2,%3;" : "=r"(carry) : "r"(lds32(ya + 208)), "r"(sg), "r"(lds32(ya + 16)));
#pragma unroll 1
            for (int ch = 0; ch < 5; ch++, ya += (rg & 1) ? -16 : 16) {
                uint32_t y[4], z[4], xr[4];
                lds128(y, ya); lds128(z, ya + 192); lds128(xr, xa + ch * 16);
#pragma unroll
                for (int q = 0; q < 4; q++) asm("fma.rn.f16x2 %0,%1,%2,%0;" : "+r"(y[q]) : "r"(z[q]), "r"(sg));
                if (rg & 1) {
                    const uint32_t y0 = y[0], y1 = y[1];
                    y[0] = __byte_perm(carry, y[3], 0x7610); y[1] = __byte_perm(y[3], y[2], 0x7610);
                    y[3] = __byte_perm(y1, y0, 0x7610); y[2] = __byte_perm(y[2], y1, 0x7610);
                    carry = y0;
                }
#pragma unroll
                for (int q = 0; q < 4; q++) {
                    const float2 yf = __half22float2(*(const __half2*)&y[q]);
                    xr[q] = bfma(pack_bf(yf.x, yf.y), ysc, xr[q]);
                    const float e = bf_lo(xr[q]), f = bf_hi(xr[q]);
                    sum += e + f; sq = fmaf(e, e, fmaf(f, f, sq));
                }
                sts128(xa + ch * 16, xr[0], xr[1], xr[2], xr[3]);
            }
            uint2* stat = g_stat + (size_t)(layer * 32 + a) * 1024 + rg * 64 + fr;
            asm volatile("st.relaxed.gpu.global.v2.u32 [%0],{%1,%2};" ::"l"(stat + j4 * 256), "r"(__float_as_uint(sum)), "r"(__float_as_uint(sq) | 0x80000000u) : "memory");
            if (layer == TLL && n == TLN) TL(47);
            uint32_t s0[3], s1[3];
            int lim = 0;
            do {
#pragma unroll
                for (int q = 0; q < 3; q++)
                    asm volatile("ld.relaxed.gpu.global.v2.u32 {%0,%1},[%2];" : "=r"(s0[q]), "=r"(s1[q]) : "l"(stat + ((j4 + 1 + q) & 3) * 256) : "memory");
            } while (__any_sync(~0u, (int)(s1[0] & s1[1] & s1[2]) >= 0) && ++lim < SPIN_LIM);
#pragma unroll
            for (int q = 0; q < 3; q++) { sum += __uint_as_float(s0[q]); sq -= __uint_as_float(s1[q]); }
            sts64(sb + RI_ST + tid * 8, __float_as_uint(sum), __float_as_uint(sq));
            bar_sync(4, 256);
            if (layer == TLL && n == TLN) TL(48);
#pragma unroll
            for (int q = 1; q < 4; q++) {
                uint32_t st2[2];
                lds64(st2, sb + RI_ST + ((tid + q * 64) & 255) * 8);
                sum += __uint_as_float(st2[0]); sq += __uint_as_float(st2[1]);
            }
            const float mean = sum * (1.f / 640.f), r = rsqrtf(fmaxf(fmaf(-mean, mean, sq * (1.f / 640.f)), 0.f) + 1e-5f), off = -mean * r;
            uint4* dst = (uint4*)g_xn + ((size_t)(2 * a + (w & 1)) * 80 + chunk0(rg)) * 32 + lane;
#pragma unroll
            for (int i = 0; i < 5; i++) {
                uint32_t u[4];
                lds128(u, xa + i * 16);
                dst[i * 32] = make_uint4(pack_h(fmaf(bf_lo(u[0]), r, off), fmaf(bf_hi(u[0]), r, off)), pack_h(fmaf(bf_lo(u[1]), r, off), fmaf(bf_hi(u[1]), r, off)),
                                         pack_h(fmaf(bf_lo(u[2]), r, off), fmaf(bf_hi(u[2]), r, off)), pack_h(fmaf(bf_lo(u[3]), r, off), fmaf(bf_hi(u[3]), r, off)));
            }
            __syncwarp();
            if (lane == 0) mbar_arrive(sb + HB_LN);
            if (layer == TLL) TL(37);
            if (layer == TLL && n == TLN) TL(44);
            residual(a + (nh >> 2), n + 1);
#pragma unroll 2
            for (int rr = 0; rr < 64 - gr && tid < 240; rr += 12) {
                uint32_t v[4];
                lds128(v, gs + (n & 1) * 21504 + rr * 336);
                ((uint4*)x)[(a * 64 + rr) * 80 + go] = make_uint4(v[0], v[1], v[2], v[3]);
            }
        }
    }
    bar_sync(3, 384);
    if (layer == TLL) TL(38);
    if (jh >= na) {
        int c0 = 0;
#pragma unroll 1
        for (int mb = (jh - na) >> 3; mb < nbh; mb += (nh - na) >> 3, c0 += GNC) oproj_mma(sb, mb, (jh - na) & 7, c0, x, out, layer);
        if (layer == TLL) TL(42);
        return;
    }
    const int p = w >> 1, mi = w & 1;
    int slot = p, ph = 0;
    for (int idx = jh + p * na; idx < NSEG * 32; idx += 4 * na) {
        const uint32_t it = sb + slot * 30720 + lane * 16;
        float iq, ik, iv;
        weight_scale(idx & 31, 0, &iq); weight_scale(idx & 31, 1, &ik); weight_scale(idx & 31, 2, &iv);
        bar_sync(6 + p, 64);
        mbar_wait(sb + HB_DONE + slot * 8, ph ^ 1);
        mbar_wait(sb + HB_FULL + slot * 8, ph);
        if (layer == TLL && idx >= 63 * 32) TL(55);
        float s[6][4];
#pragma unroll
        for (int i = 0; i < 6; i++) s[i][0] = s[i][1] = s[i][2] = s[i][3] = 0.f;
#pragma unroll
        for (int e = 0; e < 8; e++) {
            uint32_t q[4], k[4];
            ldsm4t(q, it + (e >> 2) * 8192 + (e & 3) * 1024 + mi * 512);
            ldsm4t(k, it + 24576 + e * 512);
            mma_bf(s[4], q[0], q[2], q[1], q[3], k[0], k[1]);
            mma_bf(s[5], q[0], q[2], q[1], q[3], k[2], k[3]);
            ldsm4t(k, it + (e >> 2) * 8192 + 4096 + (e & 3) * 1024);
            mma_bf(s[0], q[0], q[2], q[1], q[3], k[0], k[1]);
            mma_bf(s[1], q[0], q[2], q[1], q[3], k[2], k[3]);
            if (mi) {
                ldsm4t(k, it + (e >> 2) * 8192 + 4096 + (e & 3) * 1024 + 512);
                mma_bf(s[2], q[0], q[2], q[1], q[3], k[0], k[1]);
                mma_bf(s[3], q[0], q[2], q[1], q[3], k[2], k[3]);
            }
        }
#pragma unroll
        for (int q = 0; q < 4; q++) s[4][q] += s[5][q];
        const int seg = idx >> 5, h = idx & 31;
        const float sl = iq * ik * (0.08838834764831845f * 1.4426950408889634f);
        float mx[2] = {-3.0e38f, -3.0e38f};
#pragma unroll
        for (int i = 0; i < 5; i++)
#pragma unroll
            for (int q = 0; q < 4; q++) {
                const bool ok = i == 4 || (i * 8 + 2 * t + (q & 1)) <= (mi * 16 + g + (q >> 1) * 8);
                s[i][q] = ok ? s[i][q] * sl : -1.0e9f * 1.4426950408889634f;
                mx[q >> 1] = fmaxf(mx[q >> 1], s[i][q]);
            }
        float sum[2] = {0.f, 0.f};
#pragma unroll
        for (int r = 0; r < 2; r++) {
            mx[r] = fmaxf(mx[r], __shfl_xor_sync(~0u, mx[r], 1));
            mx[r] = fmaxf(mx[r], __shfl_xor_sync(~0u, mx[r], 2));
        }
#pragma unroll
        for (int i = 0; i < 5; i++)
#pragma unroll
            for (int q = 0; q < 4; q++) { s[i][q] = ex2(s[i][q] - mx[q >> 1]); sum[q >> 1] += s[i][q]; }
#pragma unroll
        for (int r = 0; r < 2; r++) {
            sum[r] += __shfl_xor_sync(~0u, sum[r], 1);
            sum[r] += __shfl_xor_sync(~0u, sum[r], 2);
            sum[r] = iv * rcp(sum[r]);
        }
        uint32_t pp[5][2];
#pragma unroll
        for (int i = 0; i < 5; i++) { pp[i][0] = pack_bf(s[i][0] * sum[0], s[i][1] * sum[0]); pp[i][1] = pack_bf(s[i][2] * sum[1], s[i][3] * sum[1]); }
        uint32_t* o = (uint32_t*)g_O + (((size_t)(seg >> 1) * 512 + h * 16) * 8 + (seg & 1) * 4 + mi * 2) * 32 + lane;
#pragma unroll
        for (int e = 0; e < 8; e++) {
            float o0[4] = {0.f, 0.f, 0.f, 0.f}, o1[4] = {0.f, 0.f, 0.f, 0.f};
            uint32_t v[4];
            lds64(v, it - lane * 8 + 28672 + e * 256);
            mma_bf8(o0, pp[4][0], pp[4][1], v[0]);
            mma_bf8(o1, pp[4][0], pp[4][1], v[1]);
            ldsm4(v, it + 16384 + e * 1024);
            mma_bf(o0, pp[0][0], pp[0][1], pp[1][0], pp[1][1], v[0], v[2]);
            mma_bf(o1, pp[0][0], pp[0][1], pp[1][0], pp[1][1], v[1], v[3]);
            ldsm4(v, it + 16384 + e * 1024 + 512);
            mma_bf(o0, pp[2][0], pp[2][1], pp[3][0], pp[3][1], v[0], v[2]);
            mma_bf(o1, pp[2][0], pp[2][1], pp[3][0], pp[3][1], v[1], v[3]);
            o[(2 * e) * 256] = pack_bf(o0[0], o0[1]); o[(2 * e) * 256 + 32] = pack_bf(o0[2], o0[3]);
            o[(2 * e + 1) * 256] = pack_bf(o1[0], o1[1]); o[(2 * e + 1) * 256 + 32] = pack_bf(o1[2], o1[3]);
        }
        __syncwarp();
        if (lane == 0) mbar_arrive(sb + HB_DONE + slot * 8);
        slot += 4;
        if (slot >= 6) { slot -= 6; ph ^= 1; }
    }
    if (layer == TLL) TL(39);
}

template <int layer> __global__ void __cluster_dims__(3, 1, 1) __launch_bounds__(384, 1)
k_chain(const int nact, const uint32_t zero, const bf16* __restrict__ Wq, const bf16* __restrict__ Wk, const bf16* __restrict__ Wv,
        const bf16* __restrict__ Wo, const bf16* res, bf16* out) {
    extern __shared__ __align__(1024) char sm[];
    const uint32_t sb = smem_u32(sm);
    const int b = blockIdx.x, h = b / 3, c = b - h * 3;
    pdl_go();
    if (threadIdx.x >= 256) {
        asm volatile("setmaxnreg.dec.sync.aligned.u32 24;");
        TL(11 + layer * 14);
        chain_aux<layer>(sb, c, h, nact);
    } else {
        asm volatile("setmaxnreg.inc.sync.aligned.u32 240;");
        chain_mma<layer>(sb, c, h, zero, Wq, Wk, Wv, Wo, res, out);
    }
}
__global__ void __launch_bounds__(384, 1) k_help(const bf16* res, bf16* x, bf16* out, const int layer, const int na, const int nbh, const int zero, const bf16* Wq,
                                                  const bf16* Wk, const bf16* Wv, const bf16* Wo) {
    extern __shared__ __align__(1024) char sm[];
    if (layer == TLL) TL(51);
    pdl_go();
    if (threadIdx.x >= 256) {
        const uint32_t sb = smem_u32(sm);
        const int p = (threadIdx.x >> 5) - 8, i = (threadIdx.x & 31) * 4 + p;
        if (i < 34) mbar_init(sb + G_BAR + i * 8, i < 4 ? 3 : i < 8 || i == 12 || i == 13 ? 8 : i >= 22 && i < 28 ? 2 : 1);
        fence_async_smem();
        wait_flag<100>(g_flag + F_X + layer * 128 + 65, 1);
        fence_async_glb();
        if (i == 8 + p && blockIdx.x < (gridDim.x & ~3)) {
            mbar_expect(sb + HB_A + p * 8, 20480);
            bulk_g2s(sb + RI_A + p * 20480, (const char*)g_YT + (size_t)(blockIdx.x >> 2) * 81920 + p * 20480, 20480, sb + HB_A + p * 8);
        }
        __syncwarp();
        bar_sync(2, 128);
        bar_arrive(1, 384);
    }
    if (threadIdx.x + zero >= 256) helper_aux(smem_u32(sm), blockIdx.x, gridDim.x, na, nbh, layer, Wq, Wk, Wv, Wo);
    else helper_mma(sm, blockIdx.x, gridDim.x, na, nbh, layer, res, x, out);
    __syncwarp();
    if (blockIdx.x == 0) pdl_wait();
}

#define COL_PAD 15872
template <class... P, class... A>
void launch_pdl(void (*k)(P...), int grid, int block, int smem, cudaStream_t st, A... args) {
    cudaLaunchConfig_t cfg = {};
    cfg.gridDim = dim3(grid); cfg.blockDim = dim3(block); cfg.dynamicSmemBytes = smem; cfg.stream = st;
    cudaLaunchAttribute at[1];
    at[0].id = cudaLaunchAttributeProgrammaticStreamSerialization; at[0].val.programmaticStreamSerializationAllowed = 1;
    cfg.attrs = at;
    cfg.numAttrs = 1;
    cudaLaunchKernelEx(&cfg, k, args...);
}

}

extern "C" void kernel_launch(void* const* d_in, const int* in_sizes, int n_in, void* d_out, int out_size) {
    const bf16* x = (const bf16*)d_in[0];
    const bf16* wr = (const bf16*)d_in[1];
    const bf16* wi = (const bf16*)d_in[2];
    const bf16* mem0 = (const bf16*)d_in[4];
    const bf16* Wq = (const bf16*)d_in[5];
    const bf16* Wk = (const bf16*)d_in[6];
    const bf16* Wv = (const bf16*)d_in[7];
    const bf16* Wo = (const bf16*)d_in[8];
    bf16* out = (bf16*)d_out;
    static int nhelp = 0;
    static bf16 *xa, *xb;
    static cudaStream_t s1;
    static cudaEvent_t ev_fork, ev_join;
    if (!nhelp) {
        cudaStreamCreateWithFlags(&s1, cudaStreamNonBlocking);
        cudaEventCreateWithFlags(&ev_fork, cudaEventDisableTiming);
        cudaEventCreateWithFlags(&ev_join, cudaEventDisableTiming);
        cudaFuncSetAttribute(k_setup, cudaFuncAttributeMaxDynamicSharedMemorySize, SU_SMEM);
        cudaFuncSetAttribute(k_rowf<0>, cudaFuncAttributeMaxDynamicSharedMemorySize, RF_SMEM);
        cudaFuncSetAttribute(k_rowf<1>, cudaFuncAttributeMaxDynamicSharedMemorySize, RF_SMEM);
        cudaFuncSetAttribute(k_col, cudaFuncAttributeMaxDynamicSharedMemorySize, COL_PAD);
        cudaFuncSetAttribute(k_chain<0>, cudaFuncAttributeMaxDynamicSharedMemorySize, CH_SMEM);
        cudaFuncSetAttribute(k_chain<1>, cudaFuncAttributeMaxDynamicSharedMemorySize, CH_SMEM);
        cudaFuncSetAttribute(k_setup, cudaFuncAttributePreferredSharedMemoryCarveout, 100);
        cudaFuncSetAttribute(k_rowf<0>, cudaFuncAttributePreferredSharedMemoryCarveout, 100);
        cudaFuncSetAttribute(k_rowf<1>, cudaFuncAttributePreferredSharedMemoryCarveout, 100);
        cudaFuncSetAttribute(k_col, cudaFuncAttributePreferredSharedMemoryCarveout, 100);
        cudaFuncSetAttribute(k_chain<0>, cudaFuncAttributePreferredSharedMemoryCarveout, 100);
        cudaFuncSetAttribute(k_chain<1>, cudaFuncAttributePreferredSharedMemoryCarveout, 100);
        cudaFuncSetAttribute(k_help, cudaFuncAttributeMaxDynamicSharedMemorySize, HP_SMEM);
        cudaFuncSetAttribute(k_help, cudaFuncAttributePreferredSharedMemoryCarveout, 100);
        int dev = 0, sms = 0;
        cudaGetDevice(&dev);
        cudaDeviceGetAttribute(&sms, cudaDevAttrMultiProcessorCount, dev);
        nhelp = sms - 96 < 12 ? 12 : sms - 96;
        cudaGetSymbolAddress((void**)&xa, g_xa);
        cudaGetSymbolAddress((void**)&xb, g_xb);
    }
    const int na = nhelp - (nhelp >= 36 ? 24 : nhelp >= 28 ? 16 : 8), nbh = 14;
    cudaStream_t s0 = cudaStreamPerThread;
    cudaEventRecord(ev_fork, s0);
    cudaStreamWaitEvent(s1, ev_fork, 0);
    k_rowf<1><<<(96 + nhelp) & ~1, 256, RF_SMEM, s0>>>(x);
    k_setup<<<NSETUP, 256, SU_SMEM, s1>>>(wr, wi, mem0);
    cudaEventRecord(ev_join, s1);
#define NLAYER 2
    for (int l = 0; l < NLAYER; l++) {
        const bf16* xin = l == 0 ? x : xb;
        if (l == 1) launch_pdl(k_rowf<0>, 128, 256, RF_SMEM, s0, xin);
        launch_pdl(k_col, 321, 128, l == 0 ? 0 : COL_PAD, s0, (int)(l == 0));
        launch_pdl(l == 0 ? k_chain<0> : k_chain<1>, 96, 384, CH_SMEM, s0, nhelp & ~3, 0u, Wq, Wk, Wv, Wo, (const bf16*)xa, l == 0 ? xb : out);
        launch_pdl(k_help, nhelp, 384, HP_SMEM, s0, xin, xa, l == 0 ? xb : out, l, na, nbh, 0, Wq, Wk, Wv, Wo);
    }
    cudaStreamWaitEvent(s0, ev_join, 0);
}
```

```cpp
#include <cuda_runtime.h>
#include <cuda_bf16.h>
#include <cuda_fp16.h>
#include <stdint.h>
#include <string.h>

namespace {

typedef __nv_bfloat16 bf16;
constexpr int S_ = 2048, D_ = 640, NSEG = 64;
constexpr int SPIN_LIM = 1 << 13;

__device__ float                  g_wmx[96];
__device__ __align__(1024) bf16   g_wot[4096 * 640];
__device__ __align__(16) float    g_co[1024];
__device__ __align__(256) uint2   g_stat[2 * 32 * 16 * 64];
__device__ float                  g_invM0;
__device__ __align__(16) float    g_wmax[128];
__device__ __align__(1024) char   g_redraw[65 * 32768];
constexpr int F_X = 2 * NSEG * 32, F_O = F_X + 2 * 128, NFLAG = F_O + 128, RING = 8;
constexpr int F_W = F_X + 66;
constexpr int F_R = F_O + 64;
constexpr int NSETUP = 131;
struct __align__(256) Flag { unsigned v; };
__device__ Flag                   g_flag[NFLAG];
__device__ Flag                   g_ready[1];
__device__ __align__(1024) char   g_item[RING * 32 * 32768];
__device__ __align__(1024) bf16   g_O[S_ * 4096];
__device__ __align__(1024) __half g_xn[S_ * D_];
__device__ __align__(1024) bf16   g_xa[S_ * D_];
__device__ __align__(1024) bf16   g_xb[S_ * D_];
__device__ __align__(1024) __half g_UT[D_ * S_];
__device__ __align__(1024) __half g_YT[D_ * S_];
__device__ __align__(1024) __half g_ctab[64 * 128 + 64 * 64];
__device__ __align__(1024) uint32_t g_Wf[321 * 2048];

#define TL(i)
#define TLN 0
#define TLL 1
#define CK(i)
__device__ __forceinline__ uint32_t smem_u32(const void* p) { return (uint32_t)__cvta_generic_to_shared(p); }
__device__ __forceinline__ uint32_t mapa(uint32_t a, uint32_t r) { uint32_t o; asm("mapa.shared::cluster.u32 %0,%1,%2;" : "=r"(o) : "r"(a), "r"(r)); return o; }
__device__ __forceinline__ void mbar_init(uint32_t a, int c) { asm volatile("mbarrier.init.shared::cta.b64 [%0],%1;" ::"r"(a), "r"(c) : "memory"); }
__device__ __forceinline__ void mbar_expect(uint32_t a, int bytes) { asm volatile("mbarrier.arrive.expect_tx.shared::cta.b64 _,[%0],%1;" ::"r"(a), "r"(bytes) : "memory"); }
__device__ __forceinline__ void mbar_arrive(uint32_t a) { asm volatile("mbarrier.arrive.shared::cta.b64 _,[%0];" ::"r"(a) : "memory"); }
__device__ __forceinline__ bool mbar_try(uint32_t a, uint32_t par) {
    uint32_t p;
    asm volatile("{.reg .pred q; mbarrier.try_wait.parity.shared::cta.b64 q,[%1],%2; selp.u32 %0,1,0,q;}" : "=r"(p) : "r"(a), "r"(par) : "memory");
    return p;
}
__device__ __forceinline__ void mbar_wait(uint32_t a, uint32_t par) {
    if (!mbar_try(a, par)) {
        int lim = 0;
        while (!mbar_try(a, par) && ++lim < SPIN_LIM) {}
    }
}
__device__ __forceinline__ void mbar_sleep(uint32_t a, uint32_t par) {
    asm volatile("{.reg .pred q; .reg .u32 n; mov.u32 n,0;\n"
                 "W_LOOP: mbarrier.try_wait.parity.shared::cta.b64 q,[%0],%1,%2; add.u32 n,n,1; setp.lt.and.u32 q,n,%3,!q; @q bra W_LOOP;}"
                 ::"r"(a), "r"(par), "n"(20000), "n"(SPIN_LIM) : "memory");
}
__device__ __forceinline__ void bar_arrive(int id, int n) { asm volatile("bar.arrive %0,%1;" ::"r"(id), "r"(n) : "memory"); }
__device__ __forceinline__ uint32_t clock32() { uint32_t c; asm volatile("mov.u32 %0,%%clock;" : "=r"(c)); return c; }
__device__ __forceinline__ uint32_t read_tid() { uint32_t v; asm volatile("mov.u32 %0,%%tid.x;" : "=r"(v)); return v; }
__device__ __forceinline__ void bar_sync(int id, int n) { asm volatile("bar.sync %0,%1;" ::"r"(id), "r"(n) : "memory"); }
__device__ __forceinline__ void fence_async_smem() { asm volatile("fence.proxy.async.shared::cta;" ::: "memory"); }
__device__ __forceinline__ void fence_async_glb() { asm volatile("fence.proxy.async.global;" ::: "memory"); }
__device__ __forceinline__ void cluster_sync_full() { asm volatile("barrier.cluster.arrive.aligned; barrier.cluster.wait.aligned;" ::: "memory"); }
__device__ __forceinline__ void bulk_g2s(uint32_t dst, const void* src, int bytes, uint32_t mb) {
    asm volatile("cp.async.bulk.shared::cluster.global.mbarrier::complete_tx::bytes [%0],[%1],%2,[%3];" ::"r"(dst), "l"(src), "r"(bytes), "r"(mb) : "memory");
}
__device__ __forceinline__ void bulk_g2s_last(uint32_t dst, const void* src, int bytes, uint32_t mb) {
    asm volatile("{.reg .b64 p; createpolicy.fractional.L2::evict_first.b64 p, 1.0;\n"
                 "cp.async.bulk.shared::cluster.global.mbarrier::complete_tx::bytes.L2::cache_hint [%0],[%1],%2,[%3],p;}"
                 ::"r"(dst), "l"(src), "r"(bytes), "r"(mb) : "memory");
}
__device__ __forceinline__ void bulk_s2s(uint32_t dst, uint32_t src, int bytes, uint32_t mb) {
    asm volatile("cp.async.bulk.shared::cluster.shared::cta.mbarrier::complete_tx::bytes [%0],[%1],%2,[%3];" ::"r"(dst), "r"(src), "r"(bytes), "r"(mb) : "memory");
}
__device__ __forceinline__ void bulk_s2g(void* dst, uint32_t src, int bytes) {
    asm volatile("cp.async.bulk.global.shared::cta.bulk_group [%0],[%1],%2;" ::"l"(dst), "r"(src), "r"(bytes) : "memory");
}
__device__ __forceinline__ void cp_async16(uint32_t dst, const void* src, uint32_t bytes = 16) {
    asm volatile("cp.async.cg.shared.global [%0],[%1],16,%2;" ::"r"(dst), "l"(src), "r"(bytes) : "memory");
}
__device__ __forceinline__ void cp_commit() { asm volatile("cp.async.commit_group;" ::: "memory"); }
template <int N> __device__ __forceinline__ void cp_wait() { asm volatile("cp.async.wait_group %0;" ::"n"(N) : "memory"); }
__device__ __forceinline__ void bulk_commit() { asm volatile("cp.async.bulk.commit_group;" ::: "memory"); }
__device__ __forceinline__ void bulk_wait0() { asm volatile("cp.async.bulk.wait_group 0;" ::: "memory"); }
__device__ __forceinline__ void ldsm4(uint32_t* r, uint32_t a) {
    asm volatile("ldmatrix.sync.aligned.m8n8.x4.shared.b16 {%0,%1,%2,%3},[%4];" : "=r"(r[0]), "=r"(r[1]), "=r"(r[2]), "=r"(r[3]) : "r"(a) : "memory");
}
__device__ __forceinline__ void ldsm4t(uint32_t* r, uint32_t a) {
    asm volatile("ldmatrix.sync.aligned.m8n8.x4.trans.shared.b16 {%0,%1,%2,%3},[%4];" : "=r"(r[0]), "=r"(r[1]), "=r"(r[2]), "=r"(r[3]) : "r"(a) : "memory");
}
__device__ __forceinline__ void stsm4(uint32_t a, uint32_t r0, uint32_t r1, uint32_t r2, uint32_t r3) {
    asm volatile("stmatrix.sync.aligned.m8n8.x4.shared.b16 [%0],{%1,%2,%3,%4};" ::"r"(a), "r"(r0), "r"(r1), "r"(r2), "r"(r3) : "memory");
}
__device__ __forceinline__ void stsm4t(uint32_t a, uint32_t r0, uint32_t r1, uint32_t r2, uint32_t r3) {
    asm volatile("stmatrix.sync.aligned.m8n8.x4.trans.shared.b16 [%0],{%1,%2,%3,%4};" ::"r"(a), "r"(r0), "r"(r1), "r"(r2), "r"(r3) : "memory");
}
__device__ __forceinline__ void lds128(uint32_t* r, uint32_t a) {
    asm volatile("ld.shared.v4.b32 {%0,%1,%2,%3},[%4];" : "=r"(r[0]), "=r"(r[1]), "=r"(r[2]), "=r"(r[3]) : "r"(a) : "memory");
}
__device__ __forceinline__ void lds64(uint32_t* r, uint32_t a) {
    asm volatile("ld.shared.v2.b32 {%0,%1},[%2];" : "=r"(r[0]), "=r"(r[1]) : "r"(a) : "memory");
}
__device__ __forceinline__ uint32_t lds32(uint32_t a) { uint32_t v; asm volatile("ld.shared.b32 %0,[%1];" : "=r"(v) : "r"(a) : "memory"); return v; }
__device__ __forceinline__ void sts128(uint32_t a, uint32_t r0, uint32_t r1, uint32_t r2, uint32_t r3) {
    asm volatile("st.shared.v4.b32 [%0],{%1,%2,%3,%4};" ::"r"(a), "r"(r0), "r"(r1), "r"(r2), "r"(r3) : "memory");
}
__device__ __forceinline__ void sts64(uint32_t a, uint32_t v0, uint32_t v1) { asm volatile("st.shared.v2.b32 [%0],{%1,%2};" ::"r"(a), "r"(v0), "r"(v1) : "memory"); }
[[maybe_unused]] __device__ __forceinline__ void sts32(uint32_t a, uint32_t v) { asm volatile("st.shared.b32 [%0],%1;" ::"r"(a), "r"(v) : "memory"); }
#define AU_(op) "{.reg .u32 t; add.u32 t,%4,%5; " op " {%0,%1,%2,%3},[t+%6];}"
template <int I> __device__ __forceinline__ void ldsm4_u(uint32_t* r, uint32_t a, uint32_t u) {
    asm volatile(AU_("ldmatrix.sync.aligned.m8n8.x4.shared.b16") : "=r"(r[0]), "=r"(r[1]), "=r"(r[2]), "=r"(r[3]) : "r"(a), "r"(u), "n"(I) : "memory");
}
template <int I> __device__ __forceinline__ void ldsm4t_u(uint32_t* r, uint32_t a, uint32_t u) {
    asm volatile(AU_("ldmatrix.sync.aligned.m8n8.x4.trans.shared.b16") : "=r"(r[0]), "=r"(r[1]), "=r"(r[2]), "=r"(r[3]) : "r"(a), "r"(u), "n"(I) : "memory");
}
template <int I> __device__ __forceinline__ void lds128_u(uint32_t* r, uint32_t a, uint32_t u) {
    asm volatile(AU_("ld.shared.v4.b32") : "=r"(r[0]), "=r"(r[1]), "=r"(r[2]), "=r"(r[3]) : "r"(a), "r"(u), "n"(I) : "memory");
}
template <int I> __device__ __forceinline__ void lds64_u(uint32_t* r, uint32_t a, uint32_t u) {
    asm volatile("{.reg .u32 t; add.u32 t,%2,%3; ld.shared.v2.b32 {%0,%1},[t+%4];}" : "=r"(r[0]), "=r"(r[1]) : "r"(a), "r"(u), "n"(I) : "memory");
}
template <int I> __device__ __forceinline__ uint32_t lds32_u(uint32_t a, uint32_t u) {
    uint32_t v;
    asm volatile("{.reg .u32 t; add.u32 t,%1,%2; ld.shared.b32 %0,[t+%3];}" : "=r"(v) : "r"(a), "r"(u), "n"(I) : "memory");
    return v;
}
template <int I> __device__ __forceinline__ void sts64_u(uint32_t a, uint32_t u, uint32_t v0, uint32_t v1) {
    asm volatile("{.reg .u32 t; add.u32 t,%0,%1; st.shared.v2.b32 [t+%2],{%3,%4};}" ::"r"(a), "r"(u), "n"(I), "r"(v0), "r"(v1) : "memory");
}
template <int I> __device__ __forceinline__ void sts32_u(uint32_t a, uint32_t u, uint32_t v) {
    asm volatile("{.reg .u32 t; add.u32 t,%0,%1; st.shared.b32 [t+%2],%3;}" ::"r"(a), "r"(u), "n"(I), "r"(v) : "memory");
}
template <int I> __device__ __forceinline__ void sts16_u(uint32_t a, uint32_t u, uint32_t v) {
    asm volatile("{.reg .u32 t; add.u32 t,%0,%1; st.shared.b16 [t+%2],%3;}" ::"r"(a), "r"(u), "n"(I), "h"((unsigned short)v) : "memory");
}
template <int I> __device__ __forceinline__ void sts128_u(uint32_t a, uint32_t u, uint32_t r0, uint32_t r1, uint32_t r2, uint32_t r3) {
    asm volatile("{.reg .u32 t; add.u32 t,%0,%1; st.shared.v4.b32 [t+%2],{%3,%4,%5,%6};}" ::"r"(a), "r"(u), "n"(I), "r"(r0), "r"(r1), "r"(r2), "r"(r3) : "memory");
}
template <int I> __device__ __forceinline__ void stsm4_u(uint32_t a, uint32_t u, uint32_t r0, uint32_t r1, uint32_t r2, uint32_t r3) {
    asm volatile("{.reg .u32 t; add.u32 t,%0,%1; stmatrix.sync.aligned.m8n8.x4.shared.b16 [t+%2],{%3,%4,%5,%6};}"
                 ::"r"(a), "r"(u), "n"(I), "r"(r0), "r"(r1), "r"(r2), "r"(r3) : "memory");
}
__device__ __forceinline__ void st_share2(uint32_t a, uint32_t u, uint32_t mb, uint32_t d0, uint32_t d1, uint32_t v0, uint32_t v1) {
    asm volatile("{.reg .pred p; .reg .u32 t,x,y; add.u32 t,%0,%1;\n"
                 "add.u32 x,t,%3; add.u32 y,%2,%3; st.async.shared::cluster.mbarrier::complete_tx::bytes.v2.b32 [x],{%5,%6},[y];\n"
                 "add.u32 x,t,%4; add.u32 y,%2,%4; st.async.shared::cluster.mbarrier::complete_tx::bytes.v2.b32 [x],{%5,%6},[y];\n"
                 "st.shared.v2.b32 [t],{%5,%6}; bar.warp.sync -1; setp.eq.u32 p,%0,0; @p mbarrier.arrive.shared::cta.b64 _,[%2];}"
                 ::"r"(a), "r"(u), "r"(mb), "r"(d0), "r"(d1), "r"(v0), "r"(v1) : "memory");
}
template <int V> struct IC { __host__ __device__ constexpr operator int() const { return V; } };
template <int N, class F> __device__ __forceinline__ void sfor(F f) {
    if constexpr (N > 0) { sfor<N - 1>(f); f(IC<N - 1>()); }
}
__device__ __forceinline__ void mma_f16(float* d, const uint32_t* a, uint32_t b0, uint32_t b1) {
    asm volatile("mma.sync.aligned.m16n8k16.row.col.f32.f16.f16.f32 {%0,%1,%2,%3},{%4,%5,%6,%7},{%8,%9},{%0,%1,%2,%3};"
                 : "+f"(d[0]), "+f"(d[1]), "+f"(d[2]), "+f"(d[3]) : "r"(a[0]), "r"(a[1]), "r"(a[2]), "r"(a[3]), "r"(b0), "r"(b1));
}
__device__ __forceinline__ void mma_bf(float* d, uint32_t a0, uint32_t a1, uint32_t a2, uint32_t a3, uint32_t b0, uint32_t b1) {
    asm volatile("mma.sync.aligned.m16n8k16.row.col.f32.bf16.bf16.f32 {%0,%1,%2,%3},{%4,%5,%6,%7},{%8,%9},{%0,%1,%2,%3};"
                 : "+f"(d[0]), "+f"(d[1]), "+f"(d[2]), "+f"(d[3]) : "r"(a0), "r"(a1), "r"(a2), "r"(a3), "r"(b0), "r"(b1));
}
__device__ __forceinline__ void mma_bf8(float* d, uint32_t a0, uint32_t a1, uint32_t b0) {
    asm volatile("mma.sync.aligned.m16n8k8.row.col.f32.bf16.bf16.f32 {%0,%1,%2,%3},{%4,%5},{%6},{%0,%1,%2,%3};"
                 : "+f"(d[0]), "+f"(d[1]), "+f"(d[2]), "+f"(d[3]) : "r"(a0), "r"(a1), "r"(b0));
}
__device__ __forceinline__ uint32_t pack_bf(float lo, float hi) { uint32_t r; asm("cvt.rn.bf16x2.f32 %0,%1,%2;" : "=r"(r) : "f"(hi), "f"(lo)); return r; }
__device__ __forceinline__ uint32_t pack_h(float lo, float hi) { uint32_t r; asm("cvt.rn.f16x2.f32 %0,%1,%2;" : "=r"(r) : "f"(hi), "f"(lo)); return r; }
__device__ __forceinline__ float bf_lo(uint32_t v) { return __uint_as_float(v << 16); }
__device__ __forceinline__ float bf_hi(uint32_t v) { return __uint_as_float(v & 0xffff0000u); }
__device__ __forceinline__ uint32_t bfma(uint32_t a, uint32_t b, uint32_t c) { uint32_t r; asm("fma.rn.bf16x2 %0,%1,%2,%3;" : "=r"(r) : "r"(a), "r"(b), "r"(c)); return r; }
__device__ __forceinline__ uint4 add_bf8(const uint4 x, const uint32_t* y, const uint32_t k = 0x3f803f80u) {
    return make_uint4(bfma(y[0], k, x.x), bfma(y[1], k, x.y), bfma(y[2], k, x.z), bfma(y[3], k, x.w));
}
__device__ __forceinline__ float ex2(float x) { float r; asm("ex2.approx.ftz.f32 %0,%1;" : "=f"(r) : "f"(x)); return r; }
__device__ __forceinline__ float rcp(float x) { float r; asm("rcp.approx.ftz.f32 %0,%1;" : "=f"(r) : "f"(x)); return r; }
__device__ __forceinline__ void wg_fence() { asm volatile("wgmma.fence.sync.aligned;" ::: "memory"); }
__device__ __forceinline__ void wg_commit() { asm volatile("wgmma.commit_group.sync.aligned;" ::: "memory"); }
template <int N> __device__ __forceinline__ void wg_wait() { asm volatile("wgmma.wait_group.sync.aligned %0;" ::"n"(N) : "memory"); }
__device__ __forceinline__ uint64_t mkdesc(uint32_t a, uint32_t lbo, uint32_t sbo, uint32_t sw) {
    return (uint64_t)((a & 0x3FFFF) >> 4) | ((uint64_t)(lbo >> 4) << 16) | ((uint64_t)(sbo >> 4) << 32) | ((uint64_t)sw << 62);
}
#define F4(d, i) "+f"(d[i]), "+f"(d[i + 1]), "+f"(d[i + 2]), "+f"(d[i + 3])
#define F8(d, i) F4(d, i), F4(d, i + 4)
#define F16(d, i) F8(d, i), F8(d, i + 8)
template <int OFF, int SC> __device__ __forceinline__ void wg_n32_x(float* d, const uint32_t* a, uint32_t lo) {
    asm volatile("{.reg .pred p; .reg .b32 l; .reg .b64 q; setp.ne.b32 p,%22,0; add.u32 l,%20,%21; mov.b64 q,{l,8};\n"
                 "wgmma.mma_async.sync.aligned.m64n32k16.f32.f16.f16 "
                 "{%0,%1,%2,%3,%4,%5,%6,%7,%8,%9,%10,%11,%12,%13,%14,%15},{%16,%17,%18,%19},q,p,1,1,0;}"
                 : F16(d, 0) : "r"(a[0]), "r"(a[1]), "r"(a[2]), "r"(a[3]), "r"(lo), "n"(OFF), "n"(SC));
}
__device__ __forceinline__ void wg_n128_rs(float* d, const uint32_t* a, uint64_t db, int sc) {
    asm volatile("{.reg .pred p; setp.ne.b32 p,%69,0; wgmma.mma_async.sync.aligned.m64n128k16.f32.f16.f16 "
                 "{%0,%1,%2,%3,%4,%5,%6,%7,%8,%9,%10,%11,%12,%13,%14,%15,%16,%17,%18,%19,%20,%21,%22,%23,%24,%25,%26,%27,%28,%29,%30,%31,"
                 "%32,%33,%34,%35,%36,%37,%38,%39,%40,%41,%42,%43,%44,%45,%46,%47,%48,%49,%50,%51,%52,%53,%54,%55,%56,%57,%58,%59,%60,%61,%62,%63},"
                 "{%64,%65,%66,%67},%68,p,1,1,0;}"
                 : F16(d, 0), F16(d, 16), F16(d, 32), F16(d, 48) : "r"(a[0]), "r"(a[1]), "r"(a[2]), "r"(a[3]), "l"(db), "r"(sc));
}
#define N80_REGS "{%0,%1,%2,%3,%4,%5,%6,%7,%8,%9,%10,%11,%12,%13,%14,%15,%16,%17,%18,%19,%20,%21,%22,%23,%24,%25,%26,%27,%28,%29,%30,%31,%32,%33,%34,%35,%36,%37,%38,%39}"
__device__ __forceinline__ void wg_n80_ss(float* d, uint64_t da, uint64_t db, int sc) {
    asm volatile("{.reg .pred p; setp.ne.b32 p,%42,0; wgmma.mma_async.sync.aligned.m64n80k16.f32.bf16.bf16 " N80_REGS ",%40,%41,p,1,1,0,0;}"
                 : F16(d, 0), F16(d, 16), F8(d, 32) : "l"(da), "l"(db), "r"(sc));
}
__device__ __forceinline__ void wg_n88_ss(float* d, uint64_t da, uint64_t db, int sc) {
    asm volatile("{.reg .pred p; setp.ne.b32 p,%46,0; wgmma.mma_async.sync.aligned.m64n88k16.f32.f16.f16 "
                 "{%0,%1,%2,%3,%4,%5,%6,%7,%8,%9,%10,%11,%12,%13,%14,%15,%16,%17,%18,%19,%20,%21,%22,%23,%24,%25,%26,%27,%28,%29,%30,%31,"
                 "%32,%33,%34,%35,%36,%37,%38,%39,%40,%41,%42,%43},%44,%45,p,1,1,0,0;}"
                 : F16(d, 0), F16(d, 16), F8(d, 32), F4(d, 40) : "l"(da), "l"(db), "r"(sc));
}
__device__ __forceinline__ void wg_n48_ss_ta(float* d, uint64_t da, uint64_t db, int sc) {
    asm volatile("{.reg .pred p; setp.ne.b32 p,%26,0; wgmma.mma_async.sync.aligned.m64n48k16.f32.f16.f16 "
                 "{%0,%1,%2,%3,%4,%5,%6,%7,%8,%9,%10,%11,%12,%13,%14,%15,%16,%17,%18,%19,%20,%21,%22,%23},%24,%25,p,1,1,1,0;}"
                 : F16(d, 0), F8(d, 16) : "l"(da), "l"(db), "r"(sc));
}
template <int TA> __device__ __forceinline__ void wg_n64_ss_tb(float* d, uint64_t da, uint64_t db, int sc) {
    asm volatile("{.reg .pred p; setp.ne.b32 p,%34,0; wgmma.mma_async.sync.aligned.m64n64k16.f32.f16.f16 "
                 "{%0,%1,%2,%3,%4,%5,%6,%7,%8,%9,%10,%11,%12,%13,%14,%15,%16,%17,%18,%19,%20,%21,%22,%23,%24,%25,%26,%27,%28,%29,%30,%31},"
                 "%32,%33,p,1,1,%35,1;}"
                 : F16(d, 0), F16(d, 16) : "l"(da), "l"(db), "r"(sc), "n"(TA));
}
__device__ __forceinline__ void pdl_wait() { asm volatile("griddepcontrol.wait;" ::: "memory"); }
__device__ __forceinline__ void pdl_go() { asm volatile("griddepcontrol.launch_dependents;" ::: "memory"); }
__device__ __forceinline__ float cos640(float p) {
    const float q = fmaf(p, 0.0015625f, 12582912.f) - 12582912.f;
    return __cosf(fmaf(q, -640.f, p) * 0.009817477042468103f);
}
__device__ __forceinline__ uint4 cos_row8(float p0, float step, float amp = 1.f) {
    float v[8];
    const float k = 2.f * cos640(step);
    v[0] = amp * cos640(p0); v[1] = amp * cos640(p0 + step);
#pragma unroll
    for (int i = 2; i < 8; i++) v[i] = fmaf(k, v[i - 1], -v[i - 2]);
    return make_uint4(pack_h(v[0], v[1]), pack_h(v[2], v[3]), pack_h(v[4], v[5]), pack_h(v[6], v[7]));
}
__device__ __forceinline__ float wfilter_max(int lane) {
    float m = fmaxf(fmaxf(g_wmax[lane], g_wmax[lane + 32]), fmaxf(g_wmax[lane + 64], g_wmax[lane + 96]));
    return __uint_as_float(__reduce_max_sync(~0u, __float_as_uint(m)));
}
__device__ __forceinline__ unsigned ld_acquire(const Flag* p) { unsigned v; asm volatile("ld.acquire.gpu.global.u32 %0,[%1];" : "=r"(v) : "l"(p) : "memory"); return v; }
#define POLL_NS 200
template <int NS = POLL_NS> __device__ __forceinline__ void wait_flag(const Flag* p, unsigned v) {
    if (ld_acquire(p) >= v) return;
    unsigned x;
    int lim = 0;
    do {
        __nanosleep(NS);
        asm volatile("ld.relaxed.gpu.global.u32 %0,[%1];" : "=r"(x) : "l"(p) : "memory");
    } while (x < v && ++lim < SPIN_LIM);
    ld_acquire(p);
}
__device__ __forceinline__ void prefetch_l2(const void* p, int bytes) { asm volatile("cp.async.bulk.prefetch.L2.global [%0],%1;" ::"l"(p), "r"(bytes) : "memory"); }
__device__ __forceinline__ void red_release(Flag* p) { asm volatile("red.release.gpu.global.add.u32 [%0],1;" ::"l"(p) : "memory"); }
__device__ __forceinline__ void red_relaxed(Flag* p) { asm volatile("red.relaxed.gpu.global.add.u32 [%0],1;" ::"l"(p) : "memory"); }
__device__ __forceinline__ void red_h8(void* p, uint32_t a, uint32_t b, uint32_t c, uint32_t d) {
    asm volatile("red.relaxed.gpu.global.add.noftz.v4.f16x2 [%0],{%1,%2,%3,%4};" ::"l"(p), "r"(a), "r"(b), "r"(c), "r"(d) : "memory");
}
__device__ __forceinline__ float pow2_scale(float bound, int top, float* inv) {
    int e = (int)((__float_as_uint(bound) >> 23) & 0xff) - 126;
    int k = top - e;
    k = max(-100, min(100, k));
    *inv = __uint_as_float((uint32_t)(127 - k) << 23);
    return __uint_as_float((uint32_t)(127 + k) << 23);
}
__device__ __forceinline__ char* red_base() { return (char*)(((uintptr_t)g_redraw + 32767) & ~(uintptr_t)32767); }

__device__ __forceinline__ void setup_a(char* sm, const int b, const bf16* __restrict__ wr, const bf16* __restrict__ wi) {
    const int tid = threadIdx.x, lane = tid & 31;
    const uint32_t sb = smem_u32(sm);
    auto row_byte = [&](int q) { return ((b >> 2) + 32 * ((q >> 1) * 8 + 2 * (b & 3) + (q & 1))) * 642; };
#pragma unroll 1
    for (int r = tid >> 5; r < 32; r += 8) {
        const char* src = (const char*)(r < 16 ? wr : wi) + (row_byte(r & 15) & ~15);
        cp_async16(sb + r * 672 + lane * 16, src + lane * 16);
        if (lane < 9) cp_async16(sb + r * 672 + 512 + lane * 16, src + 512 + lane * 16);
    }
    ((uint4*)g_stat)[b * 256 + tid] = make_uint4(0, 0, 0, 0);
    if (tid < 2 * (NFLAG / 128)) ((uint4*)(g_flag + b * (NFLAG / 128) + (tid >> 1)))[tid & 1] = make_uint4(0, 0, 0, 0);
    if (tid < 12) {
        const int i = b * 12 + tid;
        const int f = ((i >> 4) & 3) * 8 + (i & 7), im = (i >> 3) & 1, part = (i >> 8) & 1;
        ((uint4*)g_ctab)[i] = cos_row8((float)(i < 1024 ? (i >> 7) * 80 * (i & 63) + ((i & 64) ? 480 : 0) : ((i >> 6) & 3) * 160 * f + (im == part ? 0 : im ? 160 : 480)),
                                       (float)(i < 1024 ? 10 * (i & 63) : 20 * f));
    }
    asm volatile("cp.async.wait_all;" ::: "memory");
    __syncthreads();
    const int q0 = (tid & 3) * 4;
    const char* rp[4];
#pragma unroll
    for (int u = 0; u < 4; u++) rp[u] = sm + (q0 + u) * 672 + (row_byte(q0 + u) & 15);
    uint32_t mx = 0;
#pragma unroll 2
    for (int c = tid >> 2; c < 321; c += 64) {
        uint32_t v[4];
#pragma unroll
        for (int u = 0; u < 4; u++) {
            v[u] = ((const unsigned short*)rp[u])[c] | ((uint32_t)((const unsigned short*)(rp[u] + 16 * 672))[c] << 16);
            mx = __vmaxu2(mx, v[u] & 0x7fff7fffu);
        }
        ((uint4*)g_Wf)[(size_t)c * 512 + b * 4 + ((tid ^ (b >> 1)) & 3)] = make_uint4(v[0], v[1], v[2], v[3]);
    }
    mx = __reduce_max_sync(~0u, max(mx & 0xffffu, mx >> 16));
    __syncthreads();
    if (lane == 0) ((uint32_t*)sm)[tid >> 5] = mx;
    __syncthreads();
    if (tid < 32) {
        mx = __reduce_max_sync(~0u, ((uint32_t*)sm)[lane & 7]);
        if (tid == 0) g_wmax[b] = __uint_as_float(mx << 16);
    }
}
__device__ __forceinline__ void setup_b(const int b, const bf16* __restrict__ mem0) {
    const int tid = threadIdx.x;
    uint4* z = (uint4*)red_base();
    if (b < 3) {
        const int w = tid >> 5, lane = tid & 31, p = b * 2 + ((w >> 1) & 1), odd = w & 1;
        uint32_t mx = 0;
#pragma unroll 4
        for (int i = lane; i < 640; i += 32) {
            const uint4 u = ((const uint4*)mem0)[i];
            mx = __vmaxu2(__vmaxu2(mx, u.x & 0x7fff7fffu), __vmaxu2(__vmaxu2(u.y & 0x7fff7fffu, u.z & 0x7fff7fffu), u.w & 0x7fff7fffu));
        }
        float inv, v[7];
        const float sc = pow2_scale(__uint_as_float(__reduce_max_sync(~0u, max(mx & 0xffffu, mx >> 16)) << 16), 14, &inv);
        if (tid == 0) g_invM0 = inv;
#pragma unroll
        for (int j = 0; j < 7; j++) {
            const int r = p * 56 + (j < 6 ? odd * 32 + (j >> 1) * 8 : 24) + (lane >> 2), mr = 2 * (lane & 3) + (j < 6 ? (j & 1) : odd);
            v[j] = r < 320 ? __bfloat162float(mem0[mr * 640 + (w >> 2) * 320 + r]) * sc : 0.f;
        }
        const int off = w * 2048 + (lane >> 4) * 1024 + ((lane >> 3) & 1) * 256 + (lane & 7) * 16 + (b == 2 ? (w >> 1) * 4096 + 128 : b * 16384);
        const uint4 u = make_uint4(pack_h(v[0], v[1]), pack_h(v[2], v[3]), pack_h(v[4], v[5]), pack_h(v[6], 32.f));
        z[off >> 4] = u; z[65536 + (off >> 4)] = u;
    }
}

#define SU_PAD 40960
constexpr int SU_SMEM = SU_PAD;
__global__ void __launch_bounds__(256, 4) k_setup(const bf16* __restrict__ wr, const bf16* __restrict__ wi, const bf16* __restrict__ mem0) {
    extern __shared__ __align__(1024) char sm[];
    TL(0);
    if (blockIdx.x >= 128) setup_b(blockIdx.x - 128, mem0);
    else setup_a(sm, blockIdx.x, wr, wi);
    __syncthreads();
    if (threadIdx.x == 0) red_release(g_ready);
    TL(1);
}
__device__ __forceinline__ float weight_scale(int h, int ty, float* inv) { return pow2_scale(__ldcg(g_wmx + h * 3 + ty), 6, inv); }

#define STR_(x) #x
#define STR(x) STR_(x)
#define RF_U 1
constexpr int RF_A = 22 * 2816, RF_X = RF_A + 22 * 1024, RF_BAR = RF_X + 64 * 1344, RF_SMEM = RF_BAR + 80;
__device__ __align__(1024) char g_rtab[4 * RF_A];
template <int first> __global__ void __cluster_dims__(2, 1, 1) __launch_bounds__(256, 2) k_rowf(const bf16* x) {
    extern __shared__ __align__(1024) char sm[];
    TL(first ? 2 : 16);
    const int tid = threadIdx.x, w = tid >> 5, lane = tid & 31, g = lane >> 2, t = lane & 3;
    if (blockIdx.x >= 128) { __nanosleep(2500); return; }
    const int a = first ? blockIdx.x >> 2 : 31 - (blockIdx.x >> 2), gq = blockIdx.x & 3;
    if (!first) pdl_go();
    const uint32_t sb = smem_u32(sm), mb = sb + RF_BAR + w * 8;
    if (lane == 0) {
        mbar_init(mb, 1);
        asm volatile("fence.mbarrier_init.release.cluster;" ::: "memory");
        if (!first && w == 0) {
            mbar_init(sb + RF_BAR + 64, 1);
            fence_async_smem();
            mbar_expect(sb + RF_BAR + 64, RF_A);
            bulk_g2s(sb, g_rtab + gq * RF_A, RF_A, sb + RF_BAR + 64);
        }
    }
    if (lane == 0) mbar_expect(mb, 8 * 1280);
    __syncwarp();
    asm volatile("barrier.cluster.arrive.relaxed.aligned; barrier.cluster.wait.aligned;" ::: "memory");
    if (!first) {
        if (lane == 0) wait_flag<100>(g_flag + F_R + a, a < 28 ? 32 : 192);
        __syncwarp();
        fence_async_glb();
    }
    TL(first ? 3 : 17);
    if (lane < 4)
        asm volatile("cp.async.bulk.shared::cluster.global.mbarrier::complete_tx::bytes.multicast::cluster [%0],[%1],1280,[%2],%3;"
                     ::"r"(sb + RF_X + (w * 8 + (gq & 1) * 4 + lane) * 1344), "l"(x + (size_t)(a * 64 + w * 8 + (gq & 1) * 4 + lane) * 640), "r"(mb),
                     "h"((unsigned short)3) : "memory");
    __syncwarp();
    if (first) pdl_go();
    if (first) {
#pragma unroll 3
        for (int id = tid; id < 22 * 176; id += 256) {
            const int kg = id / 176, n = id - kg * 176;
            const float c = (float)(2 * n + (gq & 1));
            *(uint4*)(sm + id * 16) = cos_row8(fmaf((float)(kg * 8), c, (float)((gq & 2) * 80)), c, 0.03952847075210474f);
        }
    }
    mbar_wait(mb, 0);
    const uint32_t row = sb + RF_X + (w * 8 + g) * 1344;
    float st[4][4] = {};
#pragma unroll 1
    for (int i = 0; i < 20; i += 4) {
        uint32_t u[4][4];
#pragma unroll
        for (int q = 0; q < 4; q++) lds128(u[q], row + (4 * (i + q) + t) * 16);
#pragma unroll
        for (int q = 0; q < 4; q++) {
            mma_bf(st[(q & 1) * 2], u[q][0], 0x3f803f80u, u[q][1], 0x3f803f80u, u[q][0], u[q][1]);
            mma_bf(st[(q & 1) * 2 + 1], u[q][2], 0x3f803f80u, u[q][3], 0x3f803f80u, u[q][2], u[q][3]);
        }
    }
#pragma unroll
    for (int q = 0; q < 4; q++) { st[0][q] += st[2][q]; st[1][q] += st[3][q]; }
    const float sq = __shfl_sync(~0u, (g & 1) ? st[0][1] + st[1][1] : st[0][0] + st[1][0], g * 4 + (g >> 1));
    const float mean = __shfl_sync(~0u, (g & 1) ? st[0][3] + st[1][3] : st[0][2] + st[1][2], g * 4 + (g >> 1)) * (1.f / 640.f);
    const float r = rsqrtf(fmaxf(fmaf(-mean, mean, sq * (1.f / 640.f)), 0.f) + 1e-5f), off = gq == 0 ? -4.f * mean * r : 0.f;
    const float r1 = (gq == 1 || gq == 2) ? -r : r, r2 = (gq & 1) ? -r : r, r3 = gq >= 2 ? -r : r;
    const uint32_t aa = sb + RF_A + w * 128 + g * 16;
    auto el = [&](int d) { unsigned short v; asm volatile("ld.shared.u16 %0,[%1];" : "=h"(v) : "r"(row + d * 2)); return __uint_as_float((uint32_t)v << 16); };
_Pragma(STR(unroll RF_U))
    for (int i = 0; i < 5; i++) {
        const int ch = t + 4 * i;
        uint32_t u[4][4];
        lds128(u[0], row + ch * 16); lds128(u[1], row + (39 - ch) * 16); lds128(u[2], row + (40 + ch) * 16); lds128(u[3], row + (79 - ch) * 16);
        const float nb0 = el(320 - 8 * ch), nb1 = el(ch ? 640 - 8 * ch : 0);
        float o[8];
#pragma unroll
        for (int q = 0; q < 8; q++) {
            const int m = (8 - q) >> 1;
            const float e0 = (q & 1) ? bf_hi(u[0][q >> 1]) : bf_lo(u[0][q >> 1]), e2 = (q & 1) ? bf_hi(u[2][q >> 1]) : bf_lo(u[2][q >> 1]);
            const float e1 = q == 0 ? nb0 : (q & 1) ? bf_hi(u[1][m & 3]) : bf_lo(u[1][m & 3]), e3 = q == 0 ? nb1 : (q & 1) ? bf_hi(u[3][m & 3]) : bf_lo(u[3][m & 3]);
            o[q] = fmaf(e3, r3, fmaf(e2, r2, fmaf(e1, r1, fmaf(e0, r, off))));
        }
        if (ch == 0) o[0] *= 0.5f;
        sts128(aa + ch * 1024, pack_h(o[0], o[1]), pack_h(o[2], o[3]), pack_h(o[4], o[5]), pack_h(o[6], o[7]));
    }
    if (t < 2) sts128(aa + (20 + t) * 1024, t == 0 ? pack_h(fmaf(el(480), r2, fmaf(el(160), r, 0.5f * off)), 0.f) : 0u, 0u, 0u, 0u);
    fence_async_smem();
    __syncthreads();
    if (!first) mbar_wait(sb + RF_BAR + 64, 0);
    else if (a == 0 && tid == 0) { bulk_s2g(g_rtab + gq * RF_A, sb, RF_A); bulk_commit(); }
    const int wg = w >> 2;
    float acc[44];
    uint64_t da = mkdesc(sb + RF_A, 1024, 128, 0), db = mkdesc(sb + wg * 1408, 2816, 128, 0);
    wg_fence();
#pragma unroll 1
    for (int k = 0; k < 11; k++) { wg_n88_ss(acc, da, db, k); da += 128; db += 352; }
    wg_commit(); wg_wait<0>();
    const uint32_t stg = sb + RF_X + wg * 96 * 144;
#pragma unroll
    for (int j = 0; j < 12; j += 2) {
        const int m = lane >> 3, j1 = j < 10 ? j + 1 : j;
        stsm4t(stg + ((j + (m >> 1)) * 8 + (lane & 7)) * 144 + ((w & 3) * 16 + (m & 1) * 8) * 2, pack_h(acc[j * 4], acc[j * 4 + 1]),
               pack_h(acc[j * 4 + 2], acc[j * 4 + 3]), pack_h(acc[j1 * 4], acc[j1 * 4 + 1]), pack_h(acc[j1 * 4 + 2], acc[j1 * 4 + 3]));
    }
    bar_sync(1 + wg, 128);
#pragma unroll 3
    for (int rr = (tid & 127) >> 3; rr < 88; rr += 16) {
        const int ch = tid & 7, c = 2 * (wg * 88 + rr) + (gq & 1);
        if (c <= 320 - (gq >> 1) && (c | (gq ^ 2))) {
            uint32_t u[4];
            lds128(u, stg + rr * 144 + ch * 16);
            ((uint4*)g_UT)[((size_t)(c == 320 ? 1 : 2 * c + (gq >> 1)) * 32 + a) * 8 + (ch ^ (a & 7))] = make_uint4(u[0], u[1], u[2], u[3]);
        }
    }
    if (first && blockIdx.x < 4 && tid == 0) asm volatile("cp.async.bulk.wait_group.read 0;" ::: "memory");
    TL(first ? 4 : 18);
}

constexpr int GST = 4, GSTB = 32768 + 20480, GNC = 32;
constexpr int G_BAR = GST * GSTB + 3072;
#define GPACE 1100
#define GPACE2 650
__device__ __forceinline__ void oproj_load(const uint32_t sb, const int op, const int mb, const int nb, const int c0, const uint32_t pace) {
    const int by = op == 2 ? 20480 : 16384;
    const char* src = op == 2 ? (const char*)g_wot + (size_t)nb * GNC * 20480 : (const char*)g_O + (size_t)(2 * mb + op) * GNC * 16384;
    uint32_t t0 = clock32() - pace + op * (pace / 3);
#pragma unroll 1
    for (int c = c0; c < c0 + GNC; c++, src += by) {
        const int st = c % GST;
        if (c >= GST) mbar_wait(sb + G_BAR + (GST + st) * 8, ((c / GST) - 1) & 1);
        while (clock32() - t0 < pace) {}
        t0 = clock32();
        const int by_ = by;
        mbar_expect(sb + G_BAR + st * 8, by_);
        if (op == 2) bulk_g2s(sb + st * GSTB + 32768, src, by_, sb + G_BAR + st * 8);
        else bulk_g2s_last(sb + st * GSTB + op * 16384, src, by_, sb + G_BAR + st * 8);
    }
}
__device__ __forceinline__ void oproj_mma(const uint32_t sb, const int mb, const int nb, const int c0, const bf16* res, bf16* out, const int layer) {
    const int w = threadIdx.x >> 5, lane = threadIdx.x & 31, wg = w >> 2;
    float acc[40];
    uint4 rv[5];
#pragma unroll 1
    for (int c = c0; c < c0 + GNC; c++) {
        const int st = c % GST;
        mbar_wait(sb + G_BAR + st * 8, (c / GST) & 1);
        const uint32_t d = sb + st * GSTB;
        wg_fence();
#pragma unroll
        for (int k = 0; k < 8; k++)
            wg_n80_ss(acc, mkdesc(d + wg * 16384 + k * 2048, 1024, 128, 0), mkdesc(d + 32768 + k * 2560, 1280, 128, 0), (c - c0) | k);
        wg_commit();
        if (c > c0) {
            wg_wait<1>();
            if (lane == 0) mbar_arrive(sb + G_BAR + (GST + (c - 1) % GST) * 8);
        }
    }
#pragma unroll
    for (int i = 0; i < 5; i++) {
        const int id = i * 32 + lane, r = id / 10;
        rv[i] = __ldcg((const uint4*)res + (size_t)(mb * 128 + w * 16 + r) * 80 + nb * 10 + id - r * 10);
    }
    wg_wait<0>();
    bar_sync(5, 256);
    const uint32_t stg = sb + (GST - 1) * GSTB + w * 16 * 176;
#pragma unroll
    for (int j = 0; j < 5; j++)
        stsm4(stg + (lane & 15) * 176 + (2 * j + (lane >> 4)) * 16, pack_bf(acc[j * 8], acc[j * 8 + 1]), pack_bf(acc[j * 8 + 2], acc[j * 8 + 3]),
              pack_bf(acc[j * 8 + 4], acc[j * 8 + 5]), pack_bf(acc[j * 8 + 6], acc[j * 8 + 7]));
    __syncwarp();
#pragma unroll
    for (int i = 0; i < 5; i++) {
        const int id = i * 32 + lane, r = id / 10, ch = id - r * 10;
        uint32_t y[4];
        lds128(y, stg + r * 176 + ch * 16);
        ((uint4*)out)[(size_t)(mb * 128 + w * 16 + r) * 80 + nb * 10 + ch] = add_bf8(rv[i], y);
    }
    fence_async_smem();
    __syncwarp();
    if (lane == 0) {
        mbar_arrive(sb + G_BAR + (2 * GST - 1) * 8);
        if (layer == 0) red_release(g_flag + F_R + 2 * mb + wg);
    }
}

__global__ void __launch_bounds__(128, 4) k_col(const int first) {
    __shared__ __align__(1024) char sz[8192];
    __shared__ __align__(1024) char stab[24576];
    __shared__ __align__(1024) char swf[8192];
    __shared__ __align__(8) uint64_t bar[2];
    const int tid = threadIdx.x, wl = tid >> 5, lane = tid & 31, g = lane >> 2, t = lane & 3;
    const int c = blockIdx.x;
    TL(first ? 5 : 19);
    const bool realc = c == 0 || c == 320;
    const uint32_t z = smem_u32(sz), b2 = smem_u32(stab), a1 = b2 + 16384, wf = smem_u32(swf), mb = smem_u32(bar);
    if (tid == 0) { mbar_init(mb, 1); mbar_init(mb + 8, 1); fence_async_smem(); }
    if (realc) {
        for (int i = tid; i < 256; i += 128) sts128(z + 4096 + i * 16, 0, 0, 0, 0);
        fence_async_smem();
    }
    const int k1 = wl * 8 + g;
    float tc[16], ts[16];
#pragma unroll
    for (int j = 0; j < 16; j++) {
        const int p = ((j >> 1) * 8 + 2 * t + (j & 1)) * k1;
        __sincosf((float)(p - 1024) * 0.003067961575771282f, &ts[j], &tc[j]);
        ts[j] = -ts[j]; tc[j] = -tc[j];
    }
    if (first && tid == 32) { wait_flag<400>(g_ready, NSETUP); fence_async_glb(); }
    __syncthreads();
    if (tid == 32) {
        mbar_expect(mb + 8, 24576 + 8192);
        bulk_g2s(b2, g_ctab, 24576, mb + 8);
        bulk_g2s(wf, g_Wf + (size_t)c * 2048, 8192, mb + 8);
    }
    float inv;
    const float wsc = pow2_scale(wfilter_max(lane), 0, &inv) * (realc ? 0.0625f : 0.125f);
    pdl_wait();
    TL(first ? 6 : 20);
    if (tid == 0) {
        const int by = realc ? 4096 : 8192;
        mbar_expect(mb, by);
        bulk_g2s_last(z, (const char*)g_UT + (size_t)(c == 320 ? 1 : 2 * c) * 4096, by, mb);
    }
    pdl_go();
    mbar_wait(mb + 8, 0);
    mbar_wait(mb, 0);
    float d[64];
    uint32_t a[4][4];
    wg_fence();
#pragma unroll
    for (int ks = 0; ks < 4; ks++) wg_n64_ss_tb<0>(d, mkdesc(a1 + ks * 2048, 1024, 128, 0), mkdesc(z + ks * 2048, 1024, 1024, 1), ks);
    wg_commit(); wg_wait<0>();
    const float r32 = 0.17677669529663687f;
#pragma unroll
    for (int j = 0; j < 8; j++) {
        float yr[2], yi[2];
#pragma unroll
        for (int e = 0; e < 2; e++) {
            const float re = d[j * 4 + e] * r32, im = d[j * 4 + 2 + e] * r32, cc = tc[j * 2 + e], ss = ts[j * 2 + e];
            yr[e] = re * cc + im * ss; yi[e] = im * cc - re * ss;
        }
        a[j >> 1][(j & 1) * 2] = pack_h(yr[0], yr[1]); a[j >> 1][(j & 1) * 2 + 1] = pack_h(yi[0], yi[1]);
    }
    wg_fence();
#pragma unroll
    for (int ks = 0; ks < 4; ks++) wg_n128_rs(d, a[ks], mkdesc(b2 + ks * 4096, 2048, 128, 0), ks);
    wg_commit(); wg_wait<0>();
#pragma unroll
    for (int q = 0; q < 4; q++) {
        uint32_t wv[4];
        lds128(wv, wf + tid * 64 + ((q ^ (tid >> 1)) & 3) * 16);
#pragma unroll
        for (int jj = 0; jj < 2; jj++) {
            const int j = 2 * q + jj;
            float yr[2], yi[2];
#pragma unroll
            for (int e = 0; e < 2; e++) {
                const float xr = d[j * 4 + e] + d[32 + j * 4 + 2 + e], xi = d[j * 4 + 2 + e] - d[32 + j * 4 + e];
                const float fr = bf_lo(wv[jj * 2 + e]) * wsc, fi = bf_hi(wv[jj * 2 + e]) * wsc;
                yr[e] = xr * fr - xi * fi; yi[e] = xr * fi + xi * fr;
            }
            a[q][jj * 2] = pack_h(yr[0], yr[1]); a[q][jj * 2 + 1] = pack_h(yi[0], yi[1]);
        }
    }
    wg_fence();
#pragma unroll
    for (int ks = 0; ks < 4; ks++) wg_n128_rs(d, a[ks], mkdesc(b2 + ks * 4096, 2048, 128, 0), ks);
    wg_commit(); wg_wait<0>();
#pragma unroll
    for (int j = 0; j < 8; j++) {
        float yr[2], yi[2];
#pragma unroll
        for (int e = 0; e < 2; e++) {
            const float vr = (d[j * 4 + e] - d[32 + j * 4 + 2 + e]) * 0.125f, vi = (d[j * 4 + 2 + e] + d[32 + j * 4 + e]) * 0.125f;
            const float cc = tc[j * 2 + e], ss = ts[j * 2 + e];
            yr[e] = vr * cc - vi * ss; yi[e] = vi * cc + vr * ss;
        }
        a[j >> 1][(j & 1) * 2] = pack_h(yr[0], yr[1]); a[j >> 1][(j & 1) * 2 + 1] = pack_h(yi[0], yi[1]);
    }
    __syncthreads();
    const int mm = lane >> 3, rr = lane & 7;
    const uint32_t rowo = (wl * 16 + (mm & 1) * 8 + rr) * 128;
#pragma unroll
    for (int q = 0; q < 4; q++) stsm4(z + rowo + (((2 * q + (mm >> 1)) ^ rr) << 4), a[q][0], a[q][1], a[q][2], a[q][3]);
    fence_async_smem();
    __syncthreads();
    wg_fence();
#pragma unroll
    for (int ks = 0; ks < 4; ks++) wg_n64_ss_tb<1>(d, mkdesc(a1 + ks * 256, 128, 1024, 0), mkdesc(z + ks * 2048, 1024, 1024, 1), ks);
    wg_commit(); wg_wait<0>();
#pragma unroll
    for (int q = 0; q < 4; q++)
        stsm4(wf + rowo + (((2 * q + (mm >> 1)) ^ rr) << 4), pack_h(d[q * 8] * r32, d[q * 8 + 1] * r32), pack_h(d[q * 8 + 2] * r32, d[q * 8 + 3] * r32),
              pack_h(d[q * 8 + 4] * r32, d[q * 8 + 5] * r32), pack_h(d[q * 8 + 6] * r32, d[q * 8 + 7] * r32));
    __syncwarp();
    if (!(realc && wl >= 2)) {
        const int kk = c == 320 ? 320 : (c & 1) * 160 + (c >> 1) + (wl >> 1) * 320;
#pragma unroll
        for (int i = 0; i < 4; i++) {
            const int r = wl * 16 + i * 4 + (lane >> 3), ch = lane & 7;
            uint32_t v[4];
            lds128(v, wf + r * 128 + ((ch ^ (r & 7)) << 4));
            ((uint4*)g_YT)[((size_t)(r & 31) * 640 + kk) * 8 + (ch ^ (kk & 7))] = make_uint4(v[0], v[1], v[2], v[3]);
        }
    }
    TL(first ? 7 : 21);
}

constexpr int O_XS = 0;
constexpr int O_MS = 81920;
constexpr int O_QKP = O_MS + 10752;
constexpr int O_VM = O_QKP + 4096;
constexpr int O_SC = O_VM + 4096;
constexpr int O_OS = O_SC + 1536;
constexpr int O_XCH = O_OS + 2048;
constexpr int O_SUM = O_XCH + 8192;
constexpr int O_MX = O_SUM + 256;
constexpr int O_STG = O_MS + 65536 - 8192;
static_assert(O_STG - 16384 >= O_MX + 1024, "shared-memory map");
constexpr int O_WO = O_STG + 16384;
constexpr int O_SCL = O_WO + 65536;
constexpr int O_BAR = O_SCL + 64;
constexpr int B_XF = O_BAR, B_S = O_BAR + 16, B_VX = O_BAR + 32, B_STG = O_BAR + 48, B_FREE = O_BAR + 72;
constexpr int T_FA = O_BAR + 96, T_EA = T_FA + 32, T_FB = T_EA + 32, T_EB = T_FB + 56, T_RED = T_EB + 32;
constexpr int O_WMX = O_BAR + 512, B_W = O_BAR + 64;
constexpr int O_LAST = (O_WMX + 192 + 1023) / 1024 * 1024;
constexpr int CH_SMEM = O_LAST + 8192;
static_assert(O_WO == 19 * 8192, "weight staging");
__device__ __forceinline__ uint32_t tail_b(int c) { return c % 7 < 4 ? O_XS + (c % 7) * 20480 : O_WO + (c % 7 - 4) * 20480; }
__device__ __forceinline__ int s_tx(int c) { return c == 2 ? 2 * 768 : 768 + 2048; }

#define NPERM 1
#define NWO0 1
#define NWO0B 4
#define NWO1 6
#define EN 25
#define VXN 100
#define TDELAY 300
#define WDEPTH 6
#define RDELAY 570

#define STAMP(i)

#define NTA 23
#define NTB 26
template <int LO, int HI>
__device__ __forceinline__ void tok_issue(const uint32_t (&A0)[20][4], const uint32_t (&A1)[20][4], float (&b0)[16], float (&b1)[16], uint32_t xd,
                                          const uint32_t zero) {
    if (LO == 0) wg_fence();
    sfor<HI - LO>([&](auto I) {
        constexpr int i = LO + I;
        if constexpr (i < 20) wg_n32_x<i * 64, i>(b0, A0[i], xd); else wg_n32_x<(i - 20) * 64, i - 20>(b1, A1[i - 20], xd + zero);
        if constexpr (i == 19 || i == NTB - 1 || i == 39) wg_commit();
    });
}
__device__ __forceinline__ void tok_give(const float (&b0)[16], const uint32_t L16, const uint32_t xch0) {
    wg_wait<1>();
    sfor<2>([&](auto I) {
        constexpr int i = I;
        sts128_u<i * 512>(L16, xch0, pack_h(b0[8 * i], b0[8 * i + 1]), pack_h(b0[8 * i + 2], b0[8 * i + 3]), pack_h(b0[8 * i + 4], b0[8 * i + 5]),
                          pack_h(b0[8 * i + 6], b0[8 * i + 7]));
    });
}
__device__ __forceinline__ void tok_finish(float (&b1)[16], const uint32_t (&e)[2][4], const uint32_t L16, const uint32_t dst, const uint32_t idn) {
#pragma unroll
    for (int j = 0; j < 4; j++)
        asm volatile("mma.sync.aligned.m16n8k8.row.col.f32.f16.f16.f32 {%0,%1,%2,%3},{%4,%5},{%6},{%0,%1,%2,%3};"
                     : F4(b1, 4 * j) : "r"(e[j >> 1][(j & 1) * 2]), "r"(e[j >> 1][(j & 1) * 2 + 1]), "r"(idn));
    stsm4_u<0>(L16, dst, pack_bf(b1[0], b1[1]), pack_bf(b1[2], b1[3]), pack_bf(b1[4], b1[5]), pack_bf(b1[6], b1[7]));
    stsm4_u<512>(L16, dst, pack_bf(b1[8], b1[9]), pack_bf(b1[10], b1[11]), pack_bf(b1[12], b1[13]), pack_bf(b1[14], b1[15]));
}
__device__ __forceinline__ uint32_t uni(uint32_t v) { return __shfl_sync(~0u, v, 0); }
__device__ __forceinline__ uint32_t badd(uint32_t a, uint32_t b) { uint32_t r; asm("add.rn.bf16x2 %0,%1,%2;" : "=r"(r) : "r"(a), "r"(b)); return r; }
__device__ __forceinline__ uint32_t bmax(uint32_t a, uint32_t b) { uint32_t r; asm("max.bf16x2 %0,%1,%2;" : "=r"(r) : "r"(a), "r"(b)); return r; }
__device__ __forceinline__ uint32_t babsmax(uint32_t a, uint32_t b) { uint32_t r; asm("max.xorsign.abs.bf16x2 %0,%1,%2;" : "=r"(r) : "r"(a), "r"(b)); return r; }
__device__ __forceinline__ uint32_t habsmax(uint32_t a, uint32_t b) { uint32_t r; asm("max.xorsign.abs.f16x2 %0,%1,%2;" : "=r"(r) : "r"(a), "r"(b)); return r; }

template <int NPF>
__device__ __forceinline__ float mem_out(const uint32_t sb, const uint32_t L16, const uint32_t L8, uint32_t (&wo)[16][4], const uint32_t woa,
                                         char* dst, const bool odd) {
    bar_sync(2, 352);
    float a[4][4];
#pragma unroll
    for (int i = 0; i < 4; i++) a[i][0] = a[i][1] = a[i][2] = a[i][3] = 0.f;
    uint32_t ob[4][4], sm_[2], sc[2];
    sfor<8>([&](auto I) {
        constexpr int i = I;
        if constexpr (!(i & 1)) ldsm4t_u<O_OS + (i >> 1) * 512>(ob[i >> 1], L16, sb);
        if constexpr (i >= NPF) { ldsm4t(wo[i], woa + i * 1024); ldsm4t(wo[8 + i], (woa ^ 32) + i * 1024); }
    });
    lds64_u<O_SUM>(sm_, L8 & 24, sb); lds64(sc, sb + O_SCL);
#pragma unroll
    for (int i = 0; i < 8; i++) {
        mma_bf(a[i & 1], wo[i][0], wo[i][1], wo[i][2], wo[i][3], ob[i >> 1][(i & 1) * 2], ob[i >> 1][(i & 1) * 2 + 1]);
        mma_bf(a[2 + (i & 1)], wo[8 + i][0], wo[8 + i][1], wo[8 + i][2], wo[8 + i][3], ob[i >> 1][(i & 1) * 2], ob[i >> 1][(i & 1) * 2 + 1]);
    }
    const float f0 = rcp(__uint_as_float(sm_[0])) * __uint_as_float(sc[0]), f1 = rcp(__uint_as_float(sm_[1])) * __uint_as_float(sc[0]);
    red_h8(dst, pack_h((a[0][0] + a[1][0]) * f0, (a[0][1] + a[1][1]) * f1), pack_h((a[0][2] + a[1][2]) * f0, (a[0][3] + a[1][3]) * f1),
           pack_h((a[2][0] + a[3][0]) * f0, (a[2][1] + a[3][1]) * f1), pack_h(odd ? (a[2][3] + a[3][3]) * f1 : (a[2][2] + a[3][2]) * f0, 1.f));
    return __uint_as_float(sc[1]);
}

template <int NE>
__device__ __forceinline__ void tok_attention(const uint32_t qk, const uint32_t dq, const uint32_t km, const uint32_t dk, const uint32_t vt, const uint32_t vm,
                                              const int e0, const int mi, const int lane, const int seg, const int h, const float iqk, const float iv) {
    const int g = lane >> 2, t = lane & 3;
    float s[6][4];
#pragma unroll
    for (int i = 0; i < 6; i++) s[i][0] = s[i][1] = s[i][2] = s[i][3] = 0.f;
#pragma unroll
    for (int e = 0; e < 8; e++) {
        uint32_t q[4], k[4];
        ldsm4t(q, qk + (e >> 2) * dq + (e & 3) * 1024 + mi * 512);
        ldsm4t(k, km + (e >> 2) * dk + (e & 3) * 512);
        mma_bf(s[4], q[0], q[2], q[1], q[3], k[0], k[1]);
        mma_bf(s[5], q[0], q[2], q[1], q[3], k[2], k[3]);
        ldsm4t(k, qk + (e >> 2) * dq + 4096 + (e & 3) * 1024);
        mma_bf(s[0], q[0], q[2], q[1], q[3], k[0], k[1]);
        mma_bf(s[1], q[0], q[2], q[1], q[3], k[2], k[3]);
        if (mi) {
            ldsm4t(k, qk + (e >> 2) * dq + 4096 + (e & 3) * 1024 + 512);
            mma_bf(s[2], q[0], q[2], q[1], q[3], k[0], k[1]);
            mma_bf(s[3], q[0], q[2], q[1], q[3], k[2], k[3]);
        }
    }
#pragma unroll
    for (int q = 0; q < 4; q++) s[4][q] += s[5][q];
    const float sl = iqk * (0.08838834764831845f * 1.4426950408889634f);
    float mx[2] = {-3.0e38f, -3.0e38f};
#pragma unroll
    for (int i = 0; i < 5; i++)
#pragma unroll
        for (int q = 0; q < 4; q++) {
            const bool ok = i == 4 || (i * 8 + 2 * t + (q & 1)) <= (mi * 16 + g + (q >> 1) * 8);
            s[i][q] = ok ? s[i][q] * sl : -1.0e9f * 1.4426950408889634f;
            mx[q >> 1] = fmaxf(mx[q >> 1], s[i][q]);
        }
    float sum[2] = {0.f, 0.f};
#pragma unroll
    for (int r = 0; r < 2; r++) {
        mx[r] = fmaxf(mx[r], __shfl_xor_sync(~0u, mx[r], 1));
        mx[r] = fmaxf(mx[r], __shfl_xor_sync(~0u, mx[r], 2));
    }
#pragma unroll
    for (int i = 0; i < 5; i++)
#pragma unroll
        for (int q = 0; q < 4; q++) { s[i][q] = ex2(s[i][q] - mx[q >> 1]); sum[q >> 1] += s[i][q]; }
#pragma unroll
    for (int r = 0; r < 2; r++) {
        sum[r] += __shfl_xor_sync(~0u, sum[r], 1);
        sum[r] += __shfl_xor_sync(~0u, sum[r], 2);
        sum[r] = iv * rcp(sum[r]);
    }
    uint32_t pp[5][2];
#pragma unroll
    for (int i = 0; i < 5; i++) { pp[i][0] = pack_bf(s[i][0] * sum[0], s[i][1] * sum[0]); pp[i][1] = pack_bf(s[i][2] * sum[1], s[i][3] * sum[1]); }
    uint32_t* o = (uint32_t*)g_O + (((size_t)(seg >> 1) * 512 + h * 16) * 8 + (seg & 1) * 4 + mi * 2) * 32 + lane;
#pragma unroll
    for (int u = 0; u < NE; u++) {
        const int e = e0 + u;
        float o0[4] = {0.f, 0.f, 0.f, 0.f}, o1[4] = {0.f, 0.f, 0.f, 0.f};
        uint32_t v[4];
        lds64(v, vm + e * 256);
        mma_bf8(o0, pp[4][0], pp[4][1], v[0]);
        mma_bf8(o1, pp[4][0], pp[4][1], v[1]);
        ldsm4(v, vt + e * 1024);
        mma_bf(o0, pp[0][0], pp[0][1], pp[1][0], pp[1][1], v[0], v[2]);
        mma_bf(o1, pp[0][0], pp[0][1], pp[1][0], pp[1][1], v[1], v[3]);
        ldsm4(v, vt + e * 1024 + 512);
        mma_bf(o0, pp[2][0], pp[2][1], pp[3][0], pp[3][1], v[0], v[2]);
        mma_bf(o1, pp[2][0], pp[2][1], pp[3][0], pp[3][1], v[1], v[3]);
        o[(2 * e) * 256] = pack_bf(o0[0], o0[1]); o[(2 * e) * 256 + 32] = pack_bf(o0[2], o0[3]);
        o[(2 * e + 1) * 256] = pack_bf(o1[0], o1[1]); o[(2 * e + 1) * 256 + 32] = pack_bf(o1[2], o1[3]);
    }
}

__device__ __forceinline__
void attend_last(const uint32_t sb, const int layer) {
    const int tid = read_tid(), ln = tid & 31, w = tid >> 5;
    int h;
    asm volatile("mov.u32 %0,%%clusterid.x;" : "=r"(h));
    float iq, ik, iv;
    weight_scale(h, 0, &iq); weight_scale(h, 1, &ik); weight_scale(h, 2, &iv);
    mbar_wait(sb + B_S, (NSEG - 1) & 1);
    mbar_wait(sb + B_VX + 8, 0);
    if (w == 0 && ln < 2)
        asm volatile("mbarrier.arrive.relaxed.cluster.shared::cluster.b64 _,[%0];" ::"r"(mapa(sb + B_STG + 8, ln)) : "memory");
    tok_attention<2>(sb + O_STG - 16384 + ln * 16, 16384, sb + O_LAST + ln * 16, 2048, sb + O_STG + 8192 - 16384 + ln * 16, sb + O_VM + 2048 + ln * 8,
                     (w >> 1) * 2, w & 1, ln, NSEG - 1, h, iq * ik, iv);
    __syncwarp();
    if (ln == 0) red_release(g_flag + F_O + layer * 32 + 31);
}

template <int layer> __device__ __forceinline__ void chain_mma(const uint32_t sb, const int c, const int h, const uint32_t zero, const bf16* __restrict__ Wq,
                                          const bf16* __restrict__ Wk, const bf16* __restrict__ Wv, const bf16* __restrict__ Wo,
                                          const bf16* res, bf16* out) {
    int tid = read_tid(), lane = tid & 31;
    const int w = __shfl_sync(~0u, tid >> 5, 0), wg = w >> 2;
    [[maybe_unused]] const int cta = h * 3 + c;
    uint32_t A0[20][4], A1[20][4];
    const int t0 = (w & 3) + wg * 4, t1 = t0 ^ 4;
    float sl;
    {
        const int tl = tid & 127, r = tl >> 3, ch = tl & 7;
        const size_t so = (size_t)(wg * 320 + r) * 4096 + h * 128 + ch * 8;
        const bf16 *wa = (c == 2 ? Wv : Wq + c * 64) + so, *wb = (c == 2 ? Wv + 64 : Wk + c * 64) + so;
        const uint32_t ring = sb + wg * 4096;
        const uint32_t dst = ring + r * 128 + ((ch ^ r) & 7) * 16;
        const uint32_t src = ring + ((lane & 7) + (lane >> 4) * 8) * 128 + ((((w & 3) * 2 + ((lane >> 3) & 1)) ^ lane) & 7) * 16;
        const int q4 = lane & 3, gr = (c * 2 + ((w >> 1) & 1)) * 56 + (q4 == 3 ? 24 : (w & 1) * 32 + q4 * 8);
        const bf16* wo_ = Wo + (size_t)(h * 128 + (lane >> 2)) * 640 + wg * 320 + min(gr, 312);
        const uint32_t wdst = sb + O_WO + w * 8192 + (lane >> 2) * 64 + ((q4 ^ (lane >> 3)) & 3) * 16;
        auto issue = [&](int i) {
            if (i < 20) {
                const uint32_t d = dst + (i < 19 ? i * 8192 : O_LAST);
                cp_async16(d, wa + (size_t)i * 65536); cp_async16(d + 2048, wb + (size_t)i * 65536);
                if (i < 16) cp_async16(wdst + i * 512, wo_ + i * 5120, gr < 320 ? 16 : 0);
            }
            cp_commit();
        };
#pragma unroll 1
        for (int i = 0; i < WDEPTH; i++) issue(i);
        asm volatile("barrier.cluster.arrive.relaxed.aligned;" ::: "memory");
        float fa, fb;
        if (layer == 0) {
            uint32_t ma = 0, mb = 0;
#pragma unroll 1
            for (int i = 0; i < 20; i++) {
                issue(i + WDEPTH);
                cp_wait<WDEPTH>();
                const uint32_t d = dst + (i < 19 ? i * 8192 : O_LAST);
                uint32_t u[8];
                lds128(u, d); lds128(u + 4, d + 2048);
                ma = babsmax(babsmax(ma, babsmax(u[0], u[1])), babsmax(u[2], u[3])); mb = babsmax(babsmax(mb, babsmax(u[4], u[5])), babsmax(u[6], u[7]));
            }
            ma = __reduce_max_sync(~0u, max(ma & 0x7fffu, (ma >> 16) & 0x7fffu)); mb = __reduce_max_sync(~0u, max(mb & 0x7fffu, (mb >> 16) & 0x7fffu));
            asm volatile("barrier.cluster.wait.aligned;" ::: "memory");
            if (lane < 3)
                asm volatile("st.async.shared::cluster.mbarrier::complete_tx::bytes.v2.b32 [%0],{%1,%2},[%3];"
                             ::"r"(mapa(sb + O_WMX + (c * 8 + w) * 8, lane)), "r"(ma), "r"(mb), "r"(mapa(sb + B_W, lane)) : "memory");
            __syncwarp();
            {
                uint32_t off[4];
                float cs[4] = {0.f, 0.f, 0.f, 0.f};
#pragma unroll
                for (int q = 0; q < 4; q++) {
                    const int g_ = (c * 2 + ((w >> 1) & 1)) * 56 + (q == 3 ? 24 : (w & 1) * 32 + q * 8), col = wg * 320 + g_, nb = col / 80;
                    off[q] = g_ < 320 && !(q == 3 && (w & 1)) ? ((nb * 512 + h * 16) * 10 + (col - nb * 80) / 8) * 32 + lane : ~0u;
                }
                const uint32_t ta = sb + O_WO + w * 8192 + (lane & 7) * 64 + (((lane >> 3) ^ (lane >> 1)) & 3) * 16;
#pragma unroll 2
                for (int i = 0; i < 16; i++) {
                    uint32_t r[4];
                    ldsm4t(r, ta + i * 512);
#pragma unroll
                    for (int q = 0; q < 4; q++) {
                        if (off[q] != ~0u) ((uint32_t*)g_wot)[off[q] + i * 320] = r[q];
                        cs[q] += fabsf(bf_lo(r[q])) + fabsf(bf_hi(r[q]));
                    }
                }
                float cm = 0.f;
#pragma unroll
                for (int q = 0; q < 4; q++) {
                    cs[q] += __shfl_xor_sync(~0u, cs[q], 1); cs[q] += __shfl_xor_sync(~0u, cs[q], 2);
                    cm = fmaxf(cm, cs[q]);
                }
                const uint32_t n1 = __reduce_max_sync(~0u, __float_as_uint(cm));
                if (lane == 0) g_co[h * 32 + c * 8 + w] = __uint_as_float(n1);
            }
            mbar_wait(sb + B_W, 0);
            uint32_t v[2];
            lds64(v, sb + O_WMX + (lane < 24 ? lane : 0) * 8);
            const bool mine = (lane >> 3) < 3 && ((lane >> 4) == 1) == (c == 2);
            ma = __reduce_max_sync(~0u, mine ? v[0] : 0u); mb = __reduce_max_sync(~0u, mine ? v[1] : 0u);
            if (c == 2) ma = mb = max(ma, mb);
            fa = __uint_as_float(ma << 16); fb = __uint_as_float(mb << 16);
            if (tid == 0) {
                if (c != 1) g_wmx[h * 3 + c] = fa;
                if (c == 0) g_wmx[h * 3 + 1] = fb;
            }
        } else {
            fa = __ldcg(g_wmx + h * 3 + (c == 2 ? 2 : 0)); fb = __ldcg(g_wmx + h * 3 + (c == 2 ? 2 : 1));
            asm volatile("barrier.cluster.wait.aligned;" ::: "memory");
        }
        if (layer == TLL) TL(49);
        float ia, ib;
        const float sa = pow2_scale(fa, 6, &ia), sc_b = pow2_scale(fb, 6, &ib);
        sl = __uint_as_float(uni(__float_as_uint(ia * ib * (0.08838834764831845f * 1.4426950408889634f))));
        const uint32_t pa = pack_bf(sa, sa), pb = pack_bf(sc_b, sc_b);
        const int ahead = layer == 0 ? 20 : WDEPTH;
        auto convert = [&](int lo) {
#pragma unroll 1
            for (int i = lo; i < lo + 10; i++) {
                issue(i + ahead);
                cp_wait<WDEPTH>();
                const uint32_t d = dst + (i < 19 ? i * 8192 : O_LAST);
                uint32_t u[8];
                lds128(u, d); lds128(u + 4, d + 2048);
#pragma unroll
                for (int q = 0; q < 8; q++)
                    asm("{.reg .b32 m,l,u; mul.rn.bf16x2 m,%0,%1; shl.b32 l,m,16; and.b32 u,m,0xffff0000; cvt.rn.f16x2.f32 %0,u,l;}" : "+r"(u[q]) : "r"(q < 4 ? pa : pb));
                sts128(d, u[0], u[1], u[2], u[3]); sts128(d + 2048, u[4], u[5], u[6], u[7]);
            }
            bar_sync(6 + wg, 128);
        };
        const uint32_t s0 = src + wg * 2048, s1 = src + 2048 - wg * 2048;
        convert(0);
#pragma unroll
        for (int i = 0; i < 10; i++) { ldsm4t(A0[i], s0 + i * 8192); ldsm4t(A1[i], s1 + i * 8192); }
        if (layer == TLL) TL(50);
        convert(10);
#pragma unroll
        for (int i = 10; i < 20; i++) { ldsm4t(A0[i], s0 + (i < 19 ? i * 8192 : O_LAST)); ldsm4t(A1[i], s1 + (i < 19 ? i * 8192 : O_LAST)); }
        if (layer == TLL) TL(53);
        bar_arrive(9, 288);
        bar_sync(4, 288);
        asm volatile("barrier.cluster.arrive.relaxed.aligned;" ::: "memory");
    }
    const uint32_t idn = (lane >> 3) == (lane & 3) ? ((lane & 4) ? 0x3c000000u : 0x3c00u) : 0u;
    float invM = g_invM0;
    char* redp = red_base() + (size_t)layer * 32 * 32768 + w * 2048 + (lane >> 4) * 1024 + ((lane >> 3) & 1) * 256 + (lane & 7) * 16;
    const uint32_t ro2 = uni((w >> 1) * 4096 + 128), rown = uni(c == 2 ? ro2 : c * 16384);
    const uint32_t L16 = lane * 16, L8 = lane * 8, L4 = lane * 4;
    const uint32_t xch0 = uni(sb + O_XCH + t0 * 1024), xch1 = uni(sb + O_XCH + t1 * 1024);
    const uint32_t qo0 = uni(sb + O_QKP + (w & 3) * 1024 + (wg ? 768 : 0)), qp0 = uni(qo0 + (wg ? 128 : 256));
    const uint32_t qo1 = uni(sb + O_QKP + (w & 3) * 1024 + (wg ? 128 : 512)), qp1 = uni(qo1 + (wg ? 256 : 128));
    const uint32_t vo1 = uni(qo1 + (wg ? -128 : 256)), vp1 = uni(qp1 + (wg ? -128 : 256));
    const uint32_t msr = uni(sb + O_MS + wg * 5376);
    const uint32_t msw = uni(msr + ((w >> 1) & 1) * 896 + (w & 1) * 512), msh = uni(msr + ((w >> 1) & 1) * 896 + 384 + (w & 1) * 2);
    const uint32_t sco = uni(sb + O_SC + c * 768 + (w & 3) * 256);
    const uint32_t woa = sb + O_WO + w * 8192 + (lane >> 4) * 512 + (lane & 7) * 64 + (((lane >> 3) ^ (lane >> 1)) & 1) * 16 + ((lane >> 2) & 1) * 32;
    const uint32_t w512 = uni(sb + w * 512), w128 = uni(sb + w * 128);
    const uint32_t pd0 = uni(mapa(sb, c == 2 ? 0 : 2) - sb), pd1 = uni(mapa(sb, c == 1 ? 0 : 1) - sb);
    const bool scw = c < 2 && w >= 4 && w <= 6;
    uint32_t sn = uni(sb + O_STG + (c == 2 ? 8192 : 0) + t1 * 1024);
    uint32_t ka = uni(sb + (w == 6 ? O_QKP + 512 : O_STG + 4096 + (w & 1) * 512));
    uint32_t vs = uni(sb + O_VM + t1 * 256);
    uint32_t va = uni(sb + O_STG + 8192 + w * 2048), vr = uni(sb + O_VM + w * 512);
    const uint32_t sn2 = uni(2 * sn - 16384), ka2 = uni(2 * ka - (w == 6 ? 0 : 16384)), vs2 = uni(2 * vs + 2048), va2 = uni(2 * va - 16384),
                   vr2 = uni(2 * vr + 2048);
    uint32_t xd = uni((uint32_t)mkdesc(sb + O_XS + wg * 20480, 512, 128, 0));
    const uint32_t xd2 = uni(2 * xd + 2560);

    uint32_t wp[2 * NPERM + 1][4];
    sfor<NPERM>([&](auto I) { constexpr int i = I; ldsm4t(wp[2 * i], woa + i * 1024); ldsm4t(wp[2 * i + 1], (woa ^ 32) + i * 1024); });
    auto wo_fetch = [&](uint32_t (&wo)[16][4], auto I) {
        constexpr int i = I;
        if constexpr (i < NPERM) {
#pragma unroll
            for (int q = 0; q < 4; q++) { wo[i][q] = wp[2 * i][q]; wo[8 + i][q] = wp[2 * i + 1][q]; }
        } else { ldsm4t(wo[i], woa + i * 1024); ldsm4t(wo[8 + i], (woa ^ 32) + i * 1024); }
    };
    if (layer == TLL) TL(32);
    float b0[16], b1[16];
    mbar_wait(sb + B_XF, 0);
    if (layer == TLL) TL(33);
    tok_issue<0, NTB>(A0, A1, b0, b1, xd, zero);
    tok_give(b0, L16, xch0);
    tok_issue<NTB, 40>(A0, A1, b0, b1, xd, zero);
    bar_sync(4, 256);
    wg_wait<0>();
    {
        uint32_t e[2][4];
        lds128_u<0>(e[0], L16, xch1); lds128_u<512>(e[1], L16, xch1);
        tok_finish(b1, e, L16, sn, idn);
    }
    sn = sn2 - sn; xd = xd2 - xd;
    bar_sync(5, 288);
    asm volatile("barrier.cluster.wait.aligned;" ::: "memory");
    if (layer == TLL) TL(34);
    mbar_wait(sb + B_XF + 8, 0);
    if (layer == TLL) TL(35);
    tok_issue<0, NTA>(A0, A1, b0, b1, xd, zero);
    uint32_t tr = clock32() - RDELAY;

#pragma unroll 1
    for (int st = 0;; st++) {
        uint4 mv[3];
        asm volatile("{.reg .pred p; .reg .b32 t;\n"
                     "mov.b32 %0,0; mov.b32 %1,0; mov.b32 %2,0; mov.b32 %3,0; mov.b32 %4,0; mov.b32 %5,0; mov.b32 %6,0; mov.b32 %7,0;\n"
                     "mov.b32 %8,0; mov.b32 %9,0; mov.b32 %10,0; mov.b32 %11,0;\n"
                     "T_LOOP: mov.u32 t,%%clock; sub.u32 t,t,%14; setp.ge.u32 p,t,%15;\n"
                     "@p ld.relaxed.gpu.global.v4.u32 {%0,%1,%2,%3},[%12]; @p ld.relaxed.gpu.global.v4.u32 {%4,%5,%6,%7},[%12+16384];\n"
                     "@p ld.relaxed.gpu.global.v4.u32 {%8,%9,%10,%11},[%13];\n"
                     "@!p bra T_LOOP;}"
                     : "=r"(mv[0].x), "=r"(mv[0].y), "=r"(mv[0].z), "=r"(mv[0].w), "=r"(mv[1].x), "=r"(mv[1].y), "=r"(mv[1].z), "=r"(mv[1].w),
                       "=r"(mv[2].x), "=r"(mv[2].y), "=r"(mv[2].z), "=r"(mv[2].w)
                     : "l"(redp), "l"(redp + ro2), "r"(tr), "n"(RDELAY) : "memory");
        STAMP(10);
        tok_issue<NTA, NTB>(A0, A1, b0, b1, xd, zero);
        tok_give(b0, L16, xch0);
        tok_issue<NTB, 40>(A0, A1, b0, b1, xd, zero);
        xd = xd2 - xd;
        STAMP(9);
        if (zero >> 30) break;
        asm volatile("{.reg .pred p; .reg .b32 a,h,t,n; .reg .b16 l,u; .reg .b64 q;\n"
                     "add.u32 a,%12,%13; add.u32 h,%12,%14; mov.u32 n,0;\n"
                     "M_LOOP:\n .pragma \"nounroll\";\n"
                     "st.shared.b32 [a],%0; st.shared.b32 [a+128],%1; st.shared.b32 [a+256],%2; mov.b32 {l,u},%3; st.shared.b16 [h],l;\n"
                     "st.shared.b32 [a+1792],%4; st.shared.b32 [a+1920],%5; st.shared.b32 [a+2048],%6; mov.b32 {l,u},%7; st.shared.b16 [h+1792],l;\n"
                     "st.shared.b32 [a+3584],%8; st.shared.b32 [a+3712],%9; st.shared.b32 [a+3840],%10; mov.b32 {l,u},%11; st.shared.b16 [h+3584],l;\n"
                     "lop3.b32 t,%3,%7,0x50000000,0x7e; lop3.b32 t,t,%11,0x50000000,0xf6; setp.gt.u32 p,t,0xffff;\n"
                     "vote.sync.any.pred p,p,-1; add.u32 n,n,1; setp.lt.and.u32 p,n,%17,p; @!p bra M_DONE;\n"
                     "ld.relaxed.gpu.global.v4.u32 {%0,%1,%2,%3},[%15]; ld.relaxed.gpu.global.v4.u32 {%4,%5,%6,%7},[%15+16384];\n"
                     "cvt.u64.u32 q,%16; add.u64 q,q,%15; ld.relaxed.gpu.global.v4.u32 {%8,%9,%10,%11},[q];\n"
                     "bra M_LOOP;\n"
                     "M_DONE:}"
                     : "+r"(mv[0].x), "+r"(mv[0].y), "+r"(mv[0].z), "+r"(mv[0].w), "+r"(mv[1].x), "+r"(mv[1].y), "+r"(mv[1].z), "+r"(mv[1].w),
                       "+r"(mv[2].x), "+r"(mv[2].y), "+r"(mv[2].z), "+r"(mv[2].w)
                     : "r"(L4), "r"(msw), "r"(msh), "l"(redp), "r"(ro2), "n"(SPIN_LIM) : "memory");
        bar_sync(3, 256);
        STAMP(0);
        uint32_t e[2][4];
        float f1[4];
        {
            uint32_t b[10][4];
            float acc[4][4];
#pragma unroll
            for (int i = 0; i < 4; i++) acc[i][0] = acc[i][1] = acc[i][2] = acc[i][3] = 0.f;
            auto ld = [&](auto I) { constexpr int i = I; ldsm4t_u<i * 512>(b[i], L16, msr); };
            auto mm = [&](auto I) {
                constexpr int i = I;
                mma_f16(acc[0], A0[2 * i], b[i][0], b[i][1]); mma_f16(acc[2], A1[2 * i], b[i][0], b[i][1]);
                mma_f16(acc[1], A0[2 * i + 1], b[i][2], b[i][3]); mma_f16(acc[3], A1[2 * i + 1], b[i][2], b[i][3]);
            };
            ld(IC<0>()); ld(IC<1>()); ld(IC<2>()); ld(IC<3>());
            sts32_u<O_MX>(L4, w128,
                          habsmax(habsmax(habsmax(habsmax(mv[0].x, mv[0].y), habsmax(mv[0].z, mv[1].x)), habsmax(habsmax(mv[1].y, mv[1].z), mv[2].x)),
                                  habsmax(habsmax(mv[2].y, mv[2].z), habsmax(habsmax(mv[0].w, mv[1].w), mv[2].w) & 0xffffu)));
            wg_wait<0>();
            ld(IC<4>()); mm(IC<0>()); ld(IC<5>()); mm(IC<1>()); ld(IC<6>()); mm(IC<2>());
            ld(IC<7>()); mm(IC<3>()); ld(IC<8>()); mm(IC<4>()); ld(IC<9>()); mm(IC<5>());
            lds128_u<0>(e[0], L16, xch1); lds128_u<512>(e[1], L16, xch1);
            mm(IC<6>()); mm(IC<7>()); mm(IC<8>()); mm(IC<9>());
            const uint32_t u0 = pack_bf((acc[0][0] + acc[1][0]) * invM, (acc[0][1] + acc[1][1]) * invM);
            const uint32_t u1 = pack_bf((acc[0][2] + acc[1][2]) * invM, (acc[0][3] + acc[1][3]) * invM);
#pragma unroll
            for (int i = 0; i < 4; i++) f1[i] = (acc[2][i] + acc[3][i]) * invM;
            sts32_u<0>(L4, qo0, u0); sts32_u<0>(L4, qp0, u1); sts32_u<0>(L4, qo1, pack_bf(f1[0], f1[1])); sts32_u<0>(L4, qp1, pack_bf(f1[2], f1[3]));
        }
        STAMP(1);
        bar_sync(1, 320);
        if (__builtin_expect(scw, 1)) {
            float a[4][4];
#pragma unroll
            for (int i = 0; i < 4; i++) a[i][0] = a[i][1] = a[i][2] = a[i][3] = 0.f;
            uint32_t q[4][4], k[4][4];
            sfor<4>([&](auto I) {
                constexpr int i = I;
                ldsm4t_u<O_QKP + i * 1024>(q[i], L16, sb); ldsm4t_u<i * 1024>(k[i], L16, ka);
            });
#pragma unroll
            for (int i = 0; i < 4; i++) {
                mma_bf(a[i & 1], q[i][0], q[i][1], q[i][2], q[i][3], k[i][0], k[i][1]);
                mma_bf(a[2 + (i & 1)], q[i][0], q[i][1], q[i][2], q[i][3], k[i][2], k[i][3]);
            }
            const float mk = w == 6 ? 1.f : 0.f;
            const float x0 = (a[0][0] + a[0][2]) + (a[1][0] + a[1][2]), x1 = (a[0][1] + a[0][3]) + (a[1][1] + a[1][3]);
            const float y0 = (a[2][0] + a[2][2]) + (a[3][0] + a[3][2]), y1 = (a[2][1] + a[2][3]) + (a[3][1] + a[3][3]);
            st_share2(L8, sco, sb + B_S, pd0, pd1, pack_bf(fmaf(y0, mk, x0) * sl, fmaf(y1, mk, x1) * sl), pack_bf(y0 * sl, y1 * sl));
        }
        if (c == 2) {
            const uint32_t x = lds32_u<0>(L4, vo1), y = lds32_u<0>(L4, vp1);
            st_share2(L8, vs, sb + B_S, pd0, pd1, pack_bf(f1[0] + bf_lo(x), f1[1] + bf_hi(x)), pack_bf(f1[2] + bf_lo(y), f1[3] + bf_hi(y)));
        }
        STAMP(3);
        if (st == NSEG - 1) break;
        tok_finish(b1, e, L16, sn, idn);
        redp += (st & 1) ? 32768 - 512 : 512;
        if (wg == 0) {
            uint32_t wo[16][4], vx[2][2][4], vm[2][2];
            ldsm4_u<0>(vx[0][0], L16, va); ldsm4_u<512>(vx[0][1], L16, va); ldsm4_u<1024>(vx[1][0], L16, va); ldsm4_u<1536>(vx[1][1], L16, va);
            sfor<NWO0>([&](auto I) { wo_fetch(wo, I); });
            mbar_wait(sb + B_S, st & 1);
            STAMP(4);
            uint32_t s[5];
            {
                uint32_t p[2][5];
                sfor<2>([&](auto R) {
                    constexpr int r = R;
                    lds64_u<O_SC + r * 768>(p[r], L8, sb); lds64_u<O_SC + r * 768 + 256>(p[r] + 2, L8, sb); p[r][4] = lds32_u<O_SC + r * 768 + 512>(L8, sb);
                });
#pragma unroll
                for (int j = 0; j < 5; j++) s[j] = badd(p[0][j], p[1][j]);
            }
            lds64_u<0>(vm[0], L8, vr); lds64_u<256>(vm[1], L8, vr);
            uint32_t mm = bmax(bmax(bmax(s[0], s[1]), bmax(s[2], s[3])), s[4]);
            mm = bmax(bmax(mm, __shfl_xor_sync(~0u, mm, 1)), bmax(__shfl_xor_sync(~0u, mm, 2), __shfl_xor_sync(~0u, mm, 3)));
            const float m = fmaxf(bf_lo(mm), bf_hi(mm));
            float o0[4] = {0.f, 0.f, 0.f, 0.f}, o1[4] = {0.f, 0.f, 0.f, 0.f}, d[10];
#pragma unroll
            for (int j = 0; j < 5; j++) { d[2 * j] = bf_lo(s[j]) - m; d[2 * j + 1] = bf_hi(s[j]) - m; }
#pragma unroll
            for (int j = 0; j < 10; j++) d[(j + 8) % 10] = ex2(d[(j + 8) % 10]);
            float sum = ((d[8] + d[9]) + (d[0] + d[1])) + ((d[2] + d[3]) + (d[4] + d[5])) + (d[6] + d[7]);
            const uint32_t p4 = pack_bf(d[8], d[9]), p0 = pack_bf(d[0], d[1]), p1 = pack_bf(d[2], d[3]), p2 = pack_bf(d[4], d[5]), p3 = pack_bf(d[6], d[7]);
            mma_bf8(o0, vm[0][0], vm[0][1], p4);
            mma_bf8(o1, vm[1][0], vm[1][1], p4);
            mma_bf(o0, vx[0][0][0], vx[0][0][1], vx[0][0][2], vx[0][0][3], p0, p1);
            mma_bf(o1, vx[1][0][0], vx[1][0][1], vx[1][0][2], vx[1][0][3], p0, p1);
            mma_bf(o0, vx[0][1][0], vx[0][1][1], vx[0][1][2], vx[0][1][3], p2, p3);
            mma_bf(o1, vx[1][1][0], vx[1][1][1], vx[1][1][2], vx[1][1][3], p2, p3);
            sfor<NWO0B - NWO0>([&](auto I) { constexpr int i = I; wo_fetch(wo, IC<NWO0 + i>()); });
            sum += __shfl_xor_sync(~0u, sum, 1);
            sum += __shfl_xor_sync(~0u, sum, 2);
            sts32_u<O_OS>(L4, w512, pack_bf(o0[0], o0[1])); sts32_u<O_OS + 128>(L4, w512, pack_bf(o0[2], o0[3]));
            sts32_u<O_OS + 256>(L4, w512, pack_bf(o1[0], o1[1])); sts32_u<O_OS + 384>(L4, w512, pack_bf(o1[2], o1[3]));
            sts32_u<O_SUM>(lane & 28, sb, __float_as_uint(sum));
            STAMP(5);
            invM = mem_out<NWO0B>(sb, L16, L8, wo, woa, redp + rown, w & 1);
            tr = clock32();

        } else {
            uint32_t wo[16][4];
            sfor<NWO1>([&](auto I) { wo_fetch(wo, I); });
            invM = mem_out<NWO1>(sb, L16, L8, wo, woa, redp + rown, w & 1);
            tr = clock32();

        }
        STAMP(7);
        tok_issue<0, NTA>(A0, A1, b0, b1, xd, zero);
        sn = sn2 - sn; ka = ka2 - ka; vs = vs2 - vs; va = va2 - va; vr = vr2 - vr;
        STAMP(8);
    }
    if (layer == TLL) TL(40);
    if (c == 2) attend_last(sb, layer);
    bar_arrive(8, 320);
    tid = read_tid(); lane = tid & 31;
    float acc[40];
    const int nc = c == 2 ? 10 : 11;
    const int mb = 28 + (h >> 3), nj = c == 2 ? 1 : 2;
    uint32_t rv[2][2];
    const size_t go = ((size_t)(mb * 64 + (w & 3) * 16 + (lane >> 2)) * 640 + (h & 7) * 80 + (wg * 5 + c * 2) * 8 + (lane & 3) * 2) >> 1;
#pragma unroll
    for (int u = 0; u < 4; u++) rv[u >> 1][u & 1] = (u >> 1) < nj ? __ldcg((const uint32_t*)res + go + (u >> 1) * 4 + (u & 1) * 2560) : 0u;
#pragma unroll 1
    for (int k = 0; k < nc; k++) {
        mbar_wait(sb + T_FB + (k % 7) * 8, k >= 7);
        mbar_wait(sb + T_FA + (k & 3) * 8, (k >> 2) & 1);
        if (layer == TLL && k == 0) TL(41);
        const uint64_t da = mkdesc(sb + O_MS + (k & 3) * 16384 + wg * 8192, 1024, 128, 0), db = mkdesc(sb + tail_b(k) + wg * 10240, 1280, 128, 0);
        wg_fence();
#pragma unroll
        for (int q = 0; q < 4; q++) wg_n80_ss(acc, da + q * 128, db + q * 160, k | q);
        wg_commit();
        if (k > 0) {
            wg_wait<1>();
            if (lane == 0) { mbar_arrive(sb + T_EA + ((k - 1) & 3) * 8); if (k <= 4) mbar_arrive(sb + T_EB + (k - 1) * 8); }
        }
    }
    if (layer == TLL) TL(52);
    wg_wait<0>();
    asm volatile("barrier.cluster.arrive.relaxed.aligned; barrier.cluster.wait.aligned;" ::: "memory");
    const uint32_t ra = sb + O_XS + tid * 16, rb = sb + O_MS + tid * 16;
#pragma unroll
    for (int j = 0; j < 5; j++) {
        const float* q = acc + 4 * j;
        sts128(rb + j * 4096, __float_as_uint(wg ? q[0] : q[20]), __float_as_uint(wg ? q[1] : q[21]), __float_as_uint(wg ? q[2] : q[22]), __float_as_uint(wg ? q[3] : q[23]));
    }
    bar_sync(4, 256);
#pragma unroll
    for (int j = 0; j < 5; j++) {
        const float* q = acc + 4 * j;
        uint32_t p[4];
        lds128(p, sb + O_MS + (tid ^ 128) * 16 + j * 4096);
        asm volatile("st.async.shared::cluster.mbarrier::complete_tx::bytes.v4.f32 [%0],{%1,%2,%3,%4},[%5];" ::"r"(mapa(ra + c * 8192 + (j & 1) * 4096, j >> 1)),
                     "f"((wg ? q[20] : q[0]) + __uint_as_float(p[0])), "f"((wg ? q[21] : q[1]) + __uint_as_float(p[1])),
                     "f"((wg ? q[22] : q[2]) + __uint_as_float(p[2])), "f"((wg ? q[23] : q[3]) + __uint_as_float(p[3])), "r"(mapa(sb + T_RED, j >> 1)) : "memory");
    }
    mbar_wait(sb + T_RED, 0);
#pragma unroll 1
    for (int u = 0; u < nj; u++) {
        uint32_t p[3][4];
#pragma unroll
        for (int q = 0; q < 3; q++) lds128(p[q], ra + q * 8192 + u * 4096);
        float y[4];
#pragma unroll
        for (int i = 0; i < 4; i++) y[i] = __uint_as_float(p[0][i]) + __uint_as_float(p[1][i]) + __uint_as_float(p[2][i]);
        ((uint32_t*)out)[go + u * 4] = bfma(pack_bf(y[0], y[1]), 0x3f803f80u, u ? rv[1][0] : rv[0][0]);
        ((uint32_t*)out)[go + u * 4 + 2560] = bfma(pack_bf(y[2], y[3]), 0x3f803f80u, u ? rv[1][1] : rv[0][1]);
    }
    __syncwarp();
    if (layer == 0 && lane == 0) red_release(g_flag + F_R + mb);
    TL(layer == 0 ? 15 : 29);
    asm volatile("barrier.cluster.arrive.relaxed.aligned; barrier.cluster.wait.aligned;" ::: "memory");
}

__device__ __forceinline__ void tail_load_b(const uint32_t sb, const int h, const int c, const int k) {
    mbar_expect(sb + T_FB + (k % 7) * 8, 20480);
    bulk_g2s(sb + tail_b(k), (const char*)g_wot + (size_t)((h & 7) * GNC + c * 11 + k) * 20480, 20480, sb + T_FB + (k % 7) * 8);
}
template <int layer> __device__ __forceinline__ void chain_aux(const uint32_t sb, const int c, const int h, const int nact) {
    const int tid = read_tid(), w = __shfl_sync(~0u, tid >> 5, 0), lane = tid & 31;
    if (w == 8) {
        mbar_init(sb + O_BAR + lane * 8, lane == 2 ? (c == 2 ? 9 : 4) : (lane >= 16 && lane < 20) || (lane >= 27 && lane < 31) ? 8 : 1);
        asm volatile("fence.mbarrier_init.release.cluster;" ::: "memory");
        fence_async_smem();
        __syncwarp();
    }
    {
        uint4* z = (uint4*)red_base() + layer * 65536;
#pragma unroll 1
        for (int i = blockIdx.x * 128 + tid - 256; i < 65536; i += 96 * 128)
            if (i >= 2048 || (i & 32)) z[i] = make_uint4(0, 0, 0, 0);
    }
    if (w == 8 && lane == 0) {
        mbar_expect(sb + B_S, s_tx(c));
        mbar_expect(sb + B_W, 192);
        mbar_expect(sb + T_RED, (c == 2 ? 1 : 2) * 3 * 4096);
        if (layer == 1) prefetch_l2(red_base() + 32 * 32768 + blockIdx.x * 1024, 1024);
        if (layer == 0) wait_flag<400>(g_ready, NSETUP);
    }
    __syncwarp();
    cluster_sync_full();
    asm volatile("barrier.cluster.arrive.relaxed.aligned;" ::: "memory");
    pdl_wait();
    if (w == 11 && lane == 0) red_relaxed(g_flag + F_X + layer * 128 + 65);
    Flag* flag = g_flag + layer * NSEG * 32 + h;
    const Flag* xflag = g_flag + F_X + layer * 128;
    char* const it0 = g_item + (size_t)h * 32768;
    if (w == 8) {
#pragma unroll 1
        for (int n = 0; n < 3; n++) {
            wait_flag<100>(xflag + (n >> 1), 4);
            fence_async_glb();
            if (n == 0) { bar_sync(4, 288); fence_async_smem(); }
            if (lane == 0 && n < 2) {
                mbar_expect(sb + B_XF + n * 8, 40960);
                bulk_g2s(sb + O_XS + n * 40960, (const char*)g_xn + n * 40960, 40960, sb + B_XF + n * 8);
            }
            __syncwarp();
        }
#pragma unroll 1
        for (int n = 0; n < NSEG - 1; n++) {
            const int np = n & 1;
            if (n == 0) { wait_flag<100>(g_flag + F_W + layer * 128, 96); bar_sync(5, 288); } else bar_sync(2, 352);
            if (n == 1) TL(12 + layer * 14);
            if (n == 63) TL(13 + layer * 14);
            if (lane == 0) {
                const uint32_t vs = sb + O_STG + 8192 - np * 16384, vb = sb + B_VX + np * 8;
                if (c == 2) {
                    if (n > 0) __nanosleep(VXN);
                    fence_async_smem();
                    bulk_s2s(mapa(vs, 0), vs, 8192, mapa(vb, 0));
                    bulk_s2s(mapa(vs, 1), vs, 8192, mapa(vb, 1));
                } else mbar_expect(vb, 8192);
                if (n == 0) { mbar_expect(sb + B_XF, 40960); bulk_g2s(sb + O_XS, (const char*)g_xn + 2 * 40960, 40960, sb + B_XF); }
                if (n == h * 3 + c && !np && n + 6 < NSEG) prefetch_l2(red_base() + (size_t)(layer * 32 + (n >> 1) + 3) * 32768, 32768);
            }
            __syncwarp();
        }
        {
            bar_sync(2, 352);
            TL(13 + layer * 14);
            if (lane == 0) {
                if (c == 2) mbar_expect(sb + B_VX + 8, 2 * 8192 + 2 * 2048);
                else {
                    fence_async_smem();
                    bulk_s2s(mapa(sb + O_STG - (c == 0 ? 16384 : 0), 2), sb + O_STG - 16384, 8192, mapa(sb + B_VX + 8, 2));
                }
            }
            __syncwarp();
        }
    } else if (w == 11) {
        float cvo;
        {
            auto max8 = [&](const float* p) {
                const float4 u = ((const float4*)p)[0], v = ((const float4*)p)[1];
                return fmaxf(fmaxf(fmaxf(u.x, u.y), fmaxf(u.z, u.w)), fmaxf(fmaxf(v.x, v.y), fmaxf(v.z, v.w)));
            };
            wait_flag<300>(g_flag + F_W + layer * 128, 96);
            const float* pc = g_co + lane * 32;
            float a = 640.f * __ldcg(g_wmx + lane * 3 + 2), o = fmaxf(fmaxf(max8(pc), max8(pc + 8)), max8(pc + 16));
#pragma unroll 1
            for (int s = 16; s; s >>= 1) { a = fmaxf(a, __shfl_xor_sync(~0u, a, s)); o += __shfl_xor_sync(~0u, o, s); }
            cvo = a * o * 2.f;
        }
        float invM = g_invM0;
        float iv;
        weight_scale(h, 2, &iv);
        const uint32_t L16 = sb + lane * 16 + O_MX;
#pragma unroll 1
        for (int st = 0; st < NSEG; st++) {
            bar_sync(1, 320);
            if (st == NSEG - 1) break;
            if (lane == 0) mbar_arrive(sb + B_STG + (st & 1) * 8);
            uint32_t u[2][4];
            lds128(u[0], L16); lds128(u[1], L16 + 512);
            uint32_t mx = habsmax(habsmax(habsmax(u[0][0], u[0][1]), habsmax(u[0][2], u[0][3])), habsmax(habsmax(u[1][0], u[1][1]), habsmax(u[1][2], u[1][3])));
            mx = __reduce_max_sync(~0u, max(mx & 0x7fffu, (mx >> 16) & 0x7fffu));
            const float bound = fmaxf(__half2float(__ushort_as_half((unsigned short)mx)) * invM, 25.5f) * cvo;
            const float sc = pow2_scale(bound, 15, &invM);
            sts64(sb + O_SCL, __float_as_uint(sc * iv), __float_as_uint(invM));
            bar_arrive(2, 352);
        }
    } else if (w == 10) {
        bar_sync(9, 288);
        if (lane == 0) red_release(g_flag + F_W + layer * 128);
        if (lane == 0) {
#pragma unroll 1
            for (int n = 0; n < NSEG - 1; n++) {
                mbar_sleep(sb + B_STG + (n & 1) * 8, (n >> 1) & 1);
                __nanosleep(EN);
                fence_async_smem();
                const uint32_t stg = sb + O_STG - (n & 1) * 16384;
                char* it = it0 + (size_t)(n % RING) * 32 * 32768;
                bulk_s2g(it + c * 8192, stg + (c == 2 ? 8192 : 0), 8192);
                bulk_commit();
                if (n + 1 >= RING && n + 1 < NSEG) wait_flag(flag - (RING - 1) * 32, 7);
                bulk_wait0();
                mbar_arrive(sb + B_FREE + (n & 1) * 8);
                fence_async_glb();
                red_relaxed(flag);
                flag += 32;
            }
        }
    } else {
        bool allx = false;
#pragma unroll 1
        for (int st = 0; st < NSEG - 1; st++) {
            const int par = st & 1;
            char* const it = it0 + (size_t)(st % RING) * 32 * 32768;
            if (lane == 0 && !allx && st + 3 < NSEG) {
                allx = ld_acquire(xflag + 64) >= nact;
                if (!allx) wait_flag(st + 4 < NSEG ? xflag + ((st + 3) >> 1) : xflag + 64, st + 4 < NSEG ? 4 : nact);
                fence_async_glb();
            }
            __syncwarp();
            if (c < 2) mbar_sleep(sb + B_VX + par * 8, (st >> 1) & 1);
            if (st < NSEG - 2) mbar_sleep(sb + B_XF + par * 8, ((st >> 1) + 1) & 1);
            bar_sync(1, 320);
            if (lane == 0 && st + 3 < NSEG) {
                mbar_expect(sb + B_XF + (par ^ 1) * 8, 40960);
                bulk_g2s_last(sb + O_XS + (par ^ 1) * 40960, (const char*)g_xn + (size_t)(st + 3) * 40960, 40960, sb + B_XF + (par ^ 1) * 8);
            } else if (lane == 0) {
                tail_load_b(sb, h, c, (par ^ 1) * 2); tail_load_b(sb, h, c, (par ^ 1) * 2 + 1);
            }
            __syncwarp();
            if (lane == 0 && c < 2) {
                fence_async_smem();
#pragma unroll 1
                for (int i = 0; i < 4; i++) bulk_s2g(it + 24576 + (c * 4 + i) * 512, sb + O_QKP + i * 1024 + 512, 512);
                bulk_commit();
                asm volatile("cp.async.bulk.wait_group.read 0;" ::: "memory");
            }
            __syncwarp();
            bar_arrive(2, 352);
            mbar_sleep(sb + B_S, par);
            __syncwarp();
            if (lane == 0) {
                mbar_expect(sb + B_S, s_tx(c));
                if (c == 2) { fence_async_smem(); bulk_s2g(it + 28672, sb + O_VM + par * 2048, 2048); bulk_commit(); }
            }
            __syncwarp();
            if (lane == 0) { bulk_wait0(); fence_async_glb(); red_relaxed(flag); }
            __syncwarp();
            mbar_sleep(sb + B_FREE + par * 8, (st >> 1) & 1);
            flag += 32;
        }
        {
            bar_sync(1, 320);
            if (lane == 0 && c < 2) {
                fence_async_smem();
#pragma unroll 1
                for (int i = 0; i < 4; i++)
                    bulk_s2s(mapa(sb + O_LAST + (c * 4 + i) * 512, 2), sb + O_QKP + i * 1024 + 512, 512, mapa(sb + B_VX + 8, 2));
            }
            __syncwarp();
            bar_arrive(8, 320);
        }
    }
    __syncwarp();
    const int nc = c == 2 ? 10 : 11;
    if (w == 10) {
        bar_sync(8, 320);
        if (lane == 0) {
            if (layer == 1 && blockIdx.x == 0) g_ready[0].v = 0;
            if (c < 2) mbar_sleep(sb + B_STG + 8, 1);
            fence_async_smem();
            __nanosleep(TDELAY);
            wait_flag(xflag + 64, nact);
            wait_flag<50>(g_flag + F_O + layer * 32 + 28 + (h >> 3), (h >> 3) == 3 ? 32 + 8 * 32 : 64);
            fence_async_glb();
#pragma unroll 1
            for (int k = 0; k < nc; k++) {
                if (k >= 4) mbar_sleep(sb + T_EA + (k & 3) * 8, ((k >> 2) - 1) & 1);
                mbar_expect(sb + T_FA + (k & 3) * 8, 16384);
                bulk_g2s_last(sb + O_MS + (k & 3) * 16384, (const char*)g_O + (size_t)((28 + (h >> 3)) * GNC + c * 11 + k) * 16384, 16384, sb + T_FA + (k & 3) * 8);
            }
        }
    } else if (w == 9 && lane == 0) {
        __nanosleep(TDELAY);
#pragma unroll 1
        for (int k = 4; k < nc; k++) {
            if (k >= 7) mbar_sleep(sb + T_EB + (k - 7) * 8, 0);
            tail_load_b(sb, h, c, k);
        }
    }
    __syncwarp();
    asm volatile("barrier.cluster.wait.aligned;" ::: "memory");
    asm volatile("barrier.cluster.arrive.relaxed.aligned; barrier.cluster.wait.aligned;" ::: "memory");
    asm volatile("barrier.cluster.arrive.relaxed.aligned; barrier.cluster.wait.aligned;" ::: "memory");
}

constexpr int RI_A = 0, RI_TAB = 81920, RI_STG = RI_TAB + 82 * 768;
constexpr int RI_RES = RI_STG + 25600, RI_ST = RI_RES + 2 * 64 * 336;
constexpr int HB_A = G_BAR + 64, HB_AFREE = HB_A + 32, HB_LN = HB_A + 40, HB_FULL = HB_A + 64, HB_DONE = HB_FULL + 48, HB_FREE = HB_DONE + 48;
constexpr int HP_SMEM = HB_FREE + 48;
static_assert(G_BAR >= RI_ST + 2048, "helper shared-memory map");
#define IDL 280
#define ITEM_NS 60
#define PFW_AT 28
#define PFW_NS 150
__device__ __forceinline__ void helper_aux(const uint32_t sb, const int j, const int nh, const int na, const int nbh, const int layer, const bf16* Wq,
                                           const bf16* Wk, const bf16* Wv, const bf16* Wo) {
    const int w = threadIdx.x >> 5, lane = threadIdx.x & 31, p = w - 8;
    if (lane == 0 && j < (nh & ~3)) {
        int n = 0;
        for (int a = j >> 2; a < 32; a += nh >> 2, n++) {
            if (n == 0) continue;
            mbar_wait(sb + HB_AFREE, (n - 1) & 1);
            mbar_expect(sb + HB_A + p * 8, 20480);
            bulk_g2s_last(sb + RI_A + p * 20480, (const char*)g_YT + (size_t)a * 81920 + p * 20480, 20480, sb + HB_A + p * 8);
            if (p == 0) { mbar_wait(sb + HB_LN, (n - 1) & 1); red_release(g_flag + F_X + layer * 128 + a - (nh >> 2)); }
        }
        if (p == 0) { mbar_wait(sb + HB_LN, (n - 1) & 1); red_release(g_flag + F_X + layer * 128 + (j >> 2) + (n - 1) * (nh >> 2)); }
    }
    __syncwarp();
    if (layer == 0 && w == 8 && lane == 0) wait_flag<400>(g_flag + F_W, 96);
    __syncwarp();
    bar_sync(3, 384);
    if (p == 3 && lane == 0 && j < (nh & ~3)) red_release(g_flag + F_X + layer * 128 + 64);
    fence_async_smem();
    Flag* oflag = g_flag + F_O + layer * 32;
    if (j < na) {
        int sl = p & 1, ph = 1;
        for (int idx = j + (p & 1) * na; idx < (NSEG - 1) * 32 && p >= 2 && lane == 0; idx += 2 * na) {
            mbar_wait(sb + HB_DONE + sl * 8, ph ^ 1);
            mbar_arrive(sb + HB_FREE + sl * 8);
            red_release(oflag + (idx >> 6));
            atomicAdd(&g_flag[layer * NSEG * 32 + idx].v, 1u);
            sl += 2;
            if (sl >= 6) { sl -= 6; ph ^= 1; }
        }
        for (int idx = j + p * na; idx < (NSEG - 1) * 32 && p < 2 && lane == 0; idx += 2 * na) {
            mbar_wait(sb + HB_FREE + sl * 8, ph);
            wait_flag<ITEM_NS>(g_flag + layer * NSEG * 32 + idx, 6);
            fence_async_glb();
            if (idx < (NSEG - 2) * 32) __nanosleep(IDL);
            mbar_expect(sb + HB_FULL + sl * 8, 30720);
            bulk_g2s(sb + sl * 30720, g_item + (size_t)(idx % (RING * 32)) * 32768, 30720, sb + HB_FULL + sl * 8);
            sl += 2;
            if (sl >= 6) { sl -= 6; ph ^= 1; }
        }
    } else if (lane == 0 && p == 3) {
        if (layer == 0) {
            wait_flag<1000>(oflag + PFW_AT, 64);
            const int np = nh - na;
#pragma unroll 1
            for (int i = j - na; i < 1280; i += np) {
                const bf16* W = i < 320 ? Wq : i < 640 ? Wk : i < 960 ? Wv : Wo;
                prefetch_l2((const char*)W + (size_t)(i % 320) * 16384, 16384);
                __nanosleep(PFW_NS);
            }
#pragma unroll 1
            for (int i = j - na; i < 205; i += np) {
                const char* p_ = i < 160 ? (const char*)g_Wf + i * 16384 : i < 165 ? (const char*)g_stat + (i - 144) * 16384
                               : i < 167 ? (const char*)g_ctab + (i - 165) * 8192 : (const char*)(g_flag + NFLAG) - (i - 166) * 16384;
                prefetch_l2(p_, 16384);
                __nanosleep(PFW_NS);
            }
            if (j - na < 16) prefetch_l2(g_rtab + (j - na) * (RF_A / 4), RF_A / 4);
#pragma unroll 1
            for (int i = j - na; i < 130; i += np) { prefetch_l2((const char*)g_xb + i * 16384, 16384); __nanosleep(PFW_NS); }
        }
    } else if (lane == 0) {
        if (p == 2) wait_flag<500>(g_flag + F_X + layer * 128 + 64, nh & ~3);
        int c0 = 0;
        for (int mb = (j - na) >> 3; mb < nbh; mb += (nh - na) >> 3, c0 += GNC) {
            if (p < 2) wait_flag<300>(oflag + 2 * mb + p, 64);
            fence_async_glb();
            oproj_load(sb, p, mb, (j - na) & 7, c0, nh - na < 24 ? 0 : mb == nbh - 1 ? GPACE2 : GPACE);
        }
    }
}
__device__ __forceinline__ void helper_mma(char* sm, const int jh, const int nh, const int na, const int nbh, const int layer, const bf16* res, bf16* x,
                                           bf16* out) {
    const uint32_t sb = smem_u32(sm);
    const int tid = threadIdx.x, w = tid >> 5, lane = tid & 31;
    const bool act = jh < (nh & ~3);
    const int j4 = jh & 3;
    const int fr = tid & 63, rg = w >> 1;
    auto chunk0 = [&](int u) { return u == 0 ? 5 * j4 : u == 1 ? 75 - 5 * j4 : u == 2 ? 40 + 5 * j4 : 35 - 5 * j4; };
    const int gr = tid / 20, gq_ = tid - gr * 20, go = gr * 80 + chunk0(gq_ / 5) + gq_ % 5;
    const uint32_t gs = sb + RI_RES + gr * 336 + gq_ * 16;
    auto residual = [&](int a, int n) {
#pragma unroll 1
        for (int r = 0; r < 64 - gr && tid < 240 && a < 32; r += 12) cp_async16(gs + (n & 1) * 21504 + r * 336, (const uint4*)res + (a * 64 + r) * 80 + go);
        cp_commit();
    };
    if (act) {
        if (tid < 240) {
            const int k0 = tid / 48, n = tid - k0 * 48;
            const float d = (float)(40 * j4 + n), amp = 2.f * 0.03952847075210474f;
#pragma unroll 4
            for (int u = 0; u < 16; u++)
                *(uint4*)(sm + RI_TAB + (tid + u * 240) * 16) = cos_row8(fmaf((float)((k0 + (u & 3) * 5) * 16 + ((u >> 2) & 1)), d, (float)((u & 8) * 20)), 2.f * d, amp);
            if (tid < 96) *(uint4*)(sm + RI_TAB + (3840 + tid) * 16) = make_uint4(k0 == 0 ? pack_h((n & 1) ? -amp : amp, 0.f) : 0u, 0, 0, 0);
        }
        fence_async_smem();
        residual(jh >> 2, 0);
    }
    bar_sync(1, 384);
    if (layer == TLL) TL(36);
    if (act) {
        const float4 wm = ((const float4*)g_wmax)[lane];
        const int wg = w >> 2;
        int n = 0;
#pragma unroll 1
        for (int a = jh >> 2; a < 32; a += nh >> 2, n++) {
            float acc[2][24];
            uint64_t da = mkdesc(sb + RI_A + wg * 40960, 1024, 1024, 1), db = mkdesc(sb + RI_TAB + wg * 30720, 768, 128, 0);
#pragma unroll
            for (int gq = 0; gq < 2; gq++) {
                mbar_wait(sb + HB_A + (wg * 2 + gq) * 8, n & 1);
                if (layer == TLL && n == TLN && gq == 0) TL(45);
                wg_fence();
#pragma unroll 5
                for (int k = 0; k < 10; k++) { wg_n48_ss_ta(acc[gq], da, db, k); da += 128; db += 96; }
                wg_commit();
            }
            if (wg == 0) {
                mbar_wait(sb + HB_A + 16, n & 1);
                wg_fence();
                wg_n48_ss_ta(acc[0], da, db + 20 * 96, 1);
                wg_commit();
            }
            float inv;
            pow2_scale(__uint_as_float(__reduce_max_sync(~0u, __float_as_uint(fmaxf(fmaxf(wm.x, wm.y), fmaxf(wm.z, wm.w))))), 0, &inv);
            const uint32_t ysc = pack_bf(inv, inv);
            wg_wait<0>();
            if (layer == TLL && n == TLN) TL(46);
            if (lane == 0) mbar_arrive(sb + HB_AFREE);
            const uint32_t ad = sb + RI_STG + ((w & 3) * 16 + (lane & 15)) * 400 + (lane >> 4) * 96 + wg * 192;
#pragma unroll
            for (int q = 0; q < 6; q++) {
                const float *e = acc[0] + q * 4, *o = acc[1] + q * 4;
                stsm4(ad + q * 16, pack_h(e[0] + o[0], e[1] + o[1]), pack_h(e[2] + o[2], e[3] + o[3]), pack_h(e[0] - o[0], e[1] - o[1]), pack_h(e[2] - o[2], e[3] - o[3]));
            }
            cp_wait<0>();
            bar_sync(4, 256);
            const uint32_t xa = sb + RI_RES + (n & 1) * 21504 + fr * 336 + rg * 80, sg = (rg & 1) ? 0xbc00bc00u : 0x3c003c00u;
            float sum = 0.f, sq = 0.f;
            uint32_t ya = sb + RI_STG + fr * 400 + (rg >> 1) * 96 + ((rg & 1) ? 64 : 0), carry;
            asm("fma.rn.f16x2 %0,%1,%2,%3;" : "=r"(carry) : "r"(lds32(ya + 208)), "r"(sg), "r"(lds32(ya + 16)));
#pragma unroll 1
            for (int ch = 0; ch < 5; ch++, ya += (rg & 1) ? -16 : 16) {
                uint32_t y[4], z[4], xr[4];
                lds128(y, ya); lds128(z, ya + 192); lds128(xr, xa + ch * 16);
#pragma unroll
                for (int q = 0; q < 4; q++) asm("fma.rn.f16x2 %0,%1,%2,%0;" : "+r"(y[q]) : "r"(z[q]), "r"(sg));
                if (rg & 1) {
                    const uint32_t y0 = y[0], y1 = y[1];
                    y[0] = __byte_perm(carry, y[3], 0x7610); y[1] = __byte_perm(y[3], y[2], 0x7610);
                    y[3] = __byte_perm(y1, y0, 0x7610); y[2] = __byte_perm(y[2], y1, 0x7610);
                    carry = y0;
                }
#pragma unroll
                for (int q = 0; q < 4; q++) {
                    const float2 yf = __half22float2(*(const __half2*)&y[q]);
                    xr[q] = bfma(pack_bf(yf.x, yf.y), ysc, xr[q]);
                    const float e = bf_lo(xr[q]), f = bf_hi(xr[q]);
                    sum += e + f; sq = fmaf(e, e, fmaf(f, f, sq));
                }
                sts128(xa + ch * 16, xr[0], xr[1], xr[2], xr[3]);
            }
            uint2* stat = g_stat + (size_t)(layer * 32 + a) * 1024 + rg * 64 + fr;
            asm volatile("st.relaxed.gpu.global.v2.u32 [%0],{%1,%2};" ::"l"(stat + j4 * 256), "r"(__float_as_uint(sum)), "r"(__float_as_uint(sq) | 0x80000000u) : "memory");
            if (layer == TLL && n == TLN) TL(47);
            uint32_t s0[3], s1[3];
            int lim = 0;
            do {
#pragma unroll
                for (int q = 0; q < 3; q++)
                    asm volatile("ld.relaxed.gpu.global.v2.u32 {%0,%1},[%2];" : "=r"(s0[q]), "=r"(s1[q]) : "l"(stat + ((j4 + 1 + q) & 3) * 256) : "memory");
            } while (__any_sync(~0u, (int)(s1[0] & s1[1] & s1[2]) >= 0) && ++lim < SPIN_LIM);
#pragma unroll
            for (int q = 0; q < 3; q++) { sum += __uint_as_float(s0[q]); sq -= __uint_as_float(s1[q]); }
            sts64(sb + RI_ST + tid * 8, __float_as_uint(sum), __float_as_uint(sq));
            bar_sync(4, 256);
            if (layer == TLL && n == TLN) TL(48);
#pragma unroll
            for (int q = 1; q < 4; q++) {
                uint32_t st2[2];
                lds64(st2, sb + RI_ST + ((tid + q * 64) & 255) * 8);
                sum += __uint_as_float(st2[0]); sq += __uint_as_float(st2[1]);
            }
            const float mean = sum * (1.f / 640.f), r = rsqrtf(fmaxf(fmaf(-mean, mean, sq * (1.f / 640.f)), 0.f) + 1e-5f), off = -mean * r;
            uint4* dst = (uint4*)g_xn + ((size_t)(2 * a + (w & 1)) * 80 + chunk0(rg)) * 32 + lane;
#pragma unroll
            for (int i = 0; i < 5; i++) {
                uint32_t u[4];
                lds128(u, xa + i * 16);
                dst[i * 32] = make_uint4(pack_h(fmaf(bf_lo(u[0]), r, off), fmaf(bf_hi(u[0]), r, off)), pack_h(fmaf(bf_lo(u[1]), r, off), fmaf(bf_hi(u[1]), r, off)),
                                         pack_h(fmaf(bf_lo(u[2]), r, off), fmaf(bf_hi(u[2]), r, off)), pack_h(fmaf(bf_lo(u[3]), r, off), fmaf(bf_hi(u[3]), r, off)));
            }
            __syncwarp();
            if (lane == 0) mbar_arrive(sb + HB_LN);
            if (layer == TLL) TL(37);
            if (layer == TLL && n == TLN) TL(44);
            residual(a + (nh >> 2), n + 1);
#pragma unroll 2
            for (int rr = 0; rr < 64 - gr && tid < 240; rr += 12) {
                uint32_t v[4];
                lds128(v, gs + (n & 1) * 21504 + rr * 336);
                ((uint4*)x)[(a * 64 + rr) * 80 + go] = make_uint4(v[0], v[1], v[2], v[3]);
            }
        }
    }
    bar_sync(3, 384);
    if (layer == TLL) TL(38);
    if (jh >= na) {
        int c0 = 0;
#pragma unroll 1
        for (int mb = (jh - na) >> 3; mb < nbh; mb += (nh - na) >> 3, c0 += GNC) oproj_mma(sb, mb, (jh - na) & 7, c0, x, out, layer);
        if (layer == TLL) TL(42);
        return;
    }
    const int p = w >> 1, mi = w & 1;
    int slot = p, ph = 0;
    for (int idx = jh + p * na; idx < (NSEG - 1) * 32; idx += 4 * na) {
        const uint32_t it = sb + slot * 30720 + lane * 16;
        float iq, ik, iv;
        weight_scale(idx & 31, 0, &iq); weight_scale(idx & 31, 1, &ik); weight_scale(idx & 31, 2, &iv);
        bar_sync(6 + p, 64);
        mbar_wait(sb + HB_DONE + slot * 8, ph ^ 1);
        mbar_wait(sb + HB_FULL + slot * 8, ph);
        if (layer == TLL && idx >= 63 * 32) TL(55);
        tok_attention<8>(it, 8192, it + 24576, 2048, it + 16384, it - lane * 8 + 28672, 0, mi, lane, idx >> 5, idx & 31, iq * ik, iv);
        __syncwarp();
        if (lane == 0) mbar_arrive(sb + HB_DONE + slot * 8);
        slot += 4;
        if (slot >= 6) { slot -= 6; ph ^= 1; }
    }
    if (layer == TLL) TL(39);
}

template <int layer> __global__ void __cluster_dims__(3, 1, 1) __launch_bounds__(384, 1)
k_chain(const int nact, const uint32_t zero, const bf16* __restrict__ Wq, const bf16* __restrict__ Wk, const bf16* __restrict__ Wv,
        const bf16* __restrict__ Wo, const bf16* res, bf16* out) {
    extern __shared__ __align__(1024) char sm[];
    const uint32_t sb = smem_u32(sm);
    const int b = blockIdx.x, h = b / 3, c = b - h * 3;
    pdl_go();
    if (threadIdx.x >= 256) {
        asm volatile("setmaxnreg.dec.sync.aligned.u32 24;");
        TL(11 + layer * 14);
        chain_aux<layer>(sb, c, h, nact);
    } else {
        asm volatile("setmaxnreg.inc.sync.aligned.u32 240;");
        chain_mma<layer>(sb, c, h, zero, Wq, Wk, Wv, Wo, res, out);
    }
}
__global__ void __launch_bounds__(384, 1) k_help(const bf16* res, bf16* x, bf16* out, const int layer, const int na, const int nbh, const int zero, const bf16* Wq,
                                                  const bf16* Wk, const bf16* Wv, const bf16* Wo) {
    extern __shared__ __align__(1024) char sm[];
    if (layer == TLL) TL(51);
    pdl_go();
    if (threadIdx.x >= 256) {
        const uint32_t sb = smem_u32(sm);
        const int p = (threadIdx.x >> 5) - 8, i = (threadIdx.x & 31) * 4 + p;
        if (i < 34) mbar_init(sb + G_BAR + i * 8, i < 4 ? 3 : i < 8 || i == 12 || i == 13 ? 8 : i >= 22 && i < 28 ? 2 : 1);
        fence_async_smem();
        wait_flag<100>(g_flag + F_X + layer * 128 + 65, 1);
        fence_async_glb();
        if (i == 8 + p && blockIdx.x < (gridDim.x & ~3)) {
            mbar_expect(sb + HB_A + p * 8, 20480);
            bulk_g2s(sb + RI_A + p * 20480, (const char*)g_YT + (size_t)(blockIdx.x >> 2) * 81920 + p * 20480, 20480, sb + HB_A + p * 8);
        }
        __syncwarp();
        bar_sync(2, 128);
        bar_arrive(1, 384);
    }
    if (threadIdx.x + zero >= 256) helper_aux(smem_u32(sm), blockIdx.x, gridDim.x, na, nbh, layer, Wq, Wk, Wv, Wo);
    else helper_mma(sm, blockIdx.x, gridDim.x, na, nbh, layer, res, x, out);
    __syncwarp();
    if (blockIdx.x == 0) pdl_wait();
}

#define COL_PAD 15872
template <class... P, class... A>
void launch_pdl(void (*k)(P...), int grid, int block, int smem, cudaStream_t st, A... args) {
    cudaLaunchConfig_t cfg = {};
    cfg.gridDim = dim3(grid); cfg.blockDim = dim3(block); cfg.dynamicSmemBytes = smem; cfg.stream = st;
    cudaLaunchAttribute at[1];
    at[0].id = cudaLaunchAttributeProgrammaticStreamSerialization; at[0].val.programmaticStreamSerializationAllowed = 1;
    cfg.attrs = at;
    cfg.numAttrs = 1;
    cudaLaunchKernelEx(&cfg, k, args...);
}

}

extern "C" void kernel_launch(void* const* d_in, const int* in_sizes, int n_in, void* d_out, int out_size) {
    const bf16* x = (const bf16*)d_in[0];
    const bf16* wr = (const bf16*)d_in[1];
    const bf16* wi = (const bf16*)d_in[2];
    const bf16* mem0 = (const bf16*)d_in[4];
    const bf16* Wq = (const bf16*)d_in[5];
    const bf16* Wk = (const bf16*)d_in[6];
    const bf16* Wv = (const bf16*)d_in[7];
    const bf16* Wo = (const bf16*)d_in[8];
    bf16* out = (bf16*)d_out;
    static int nhelp = 0;
    static bf16 *xa, *xb;
    static cudaStream_t s1;
    static cudaEvent_t ev_fork, ev_join;
    if (!nhelp) {
        cudaStreamCreateWithFlags(&s1, cudaStreamNonBlocking);
        cudaEventCreateWithFlags(&ev_fork, cudaEventDisableTiming);
        cudaEventCreateWithFlags(&ev_join, cudaEventDisableTiming);
        cudaFuncSetAttribute(k_setup, cudaFuncAttributeMaxDynamicSharedMemorySize, SU_SMEM);
        cudaFuncSetAttribute(k_rowf<0>, cudaFuncAttributeMaxDynamicSharedMemorySize, RF_SMEM);
        cudaFuncSetAttribute(k_rowf<1>, cudaFuncAttributeMaxDynamicSharedMemorySize, RF_SMEM);
        cudaFuncSetAttribute(k_col, cudaFuncAttributeMaxDynamicSharedMemorySize, COL_PAD);
        cudaFuncSetAttribute(k_chain<0>, cudaFuncAttributeMaxDynamicSharedMemorySize, CH_SMEM);
        cudaFuncSetAttribute(k_chain<1>, cudaFuncAttributeMaxDynamicSharedMemorySize, CH_SMEM);
        cudaFuncSetAttribute(k_setup, cudaFuncAttributePreferredSharedMemoryCarveout, 100);
        cudaFuncSetAttribute(k_rowf<0>, cudaFuncAttributePreferredSharedMemoryCarveout, 100);
        cudaFuncSetAttribute(k_rowf<1>, cudaFuncAttributePreferredSharedMemoryCarveout, 100);
        cudaFuncSetAttribute(k_col, cudaFuncAttributePreferredSharedMemoryCarveout, 100);
        cudaFuncSetAttribute(k_chain<0>, cudaFuncAttributePreferredSharedMemoryCarveout, 100);
        cudaFuncSetAttribute(k_chain<1>, cudaFuncAttributePreferredSharedMemoryCarveout, 100);
        cudaFuncSetAttribute(k_help, cudaFuncAttributeMaxDynamicSharedMemorySize, HP_SMEM);
        cudaFuncSetAttribute(k_help, cudaFuncAttributePreferredSharedMemoryCarveout, 100);
        int dev = 0, sms = 0;
        cudaGetDevice(&dev);
        cudaDeviceGetAttribute(&sms, cudaDevAttrMultiProcessorCount, dev);
        nhelp = sms - 96 < 12 ? 12 : sms - 96;
        cudaGetSymbolAddress((void**)&xa, g_xa);
        cudaGetSymbolAddress((void**)&xb, g_xb);
    }
    const int na = nhelp - (nhelp >= 36 ? 24 : nhelp >= 28 ? 16 : 8), nbh = 14;
    cudaStream_t s0 = cudaStreamPerThread;
    cudaEventRecord(ev_fork, s0);
    cudaStreamWaitEvent(s1, ev_fork, 0);
    k_rowf<1><<<(96 + nhelp) & ~1, 256, RF_SMEM, s0>>>(x);
    k_setup<<<NSETUP, 256, SU_SMEM, s1>>>(wr, wi, mem0);
    cudaEventRecord(ev_join, s1);
#define NLAYER 2
    for (int l = 0; l < NLAYER; l++) {
        const bf16* xin = l == 0 ? x : xb;
        if (l == 1) launch_pdl(k_rowf<0>, 128, 256, RF_SMEM, s0, xin);
        launch_pdl(k_col, 321, 128, l == 0 ? 0 : COL_PAD, s0, (int)(l == 0));
        launch_pdl(l == 0 ? k_chain<0> : k_chain<1>, 96, 384, CH_SMEM, s0, nhelp & ~3, 0u, Wq, Wk, Wv, Wo, (const bf16*)xa, l == 0 ? xb : out);
        launch_pdl(k_help, nhelp, 384, HP_SMEM, s0, xin, xa, l == 0 ? xb : out, l, na, nbh, 0, Wq, Wk, Wv, Wo);
    }
    cudaStreamWaitEvent(s0, ev_join, 0);
}
```

```cpp
#include <cuda_runtime.h>
#include <cuda_bf16.h>
#include <cuda_fp16.h>
#include <stdint.h>
#include <string.h>

namespace {

typedef __nv_bfloat16 bf16;
constexpr int S_ = 2048, D_ = 640, NSEG = 64;
constexpr int SPIN_LIM = 1 << 13;

__device__ float                  g_wmx[96];
__device__ __align__(1024) bf16   g_wot[4096 * 640];
__device__ __align__(16) float    g_co[1024];
__device__ __align__(256) uint2   g_stat[2 * 32 * 16 * 64];
__device__ float                  g_invM0;
__device__ __align__(16) float    g_wmax[128];
__device__ __align__(1024) char   g_redraw[65 * 32768];
constexpr int F_X = 2 * NSEG * 32, F_O = F_X + 2 * 128, NFLAG = F_O + 128, RING = 8;
constexpr int F_W = F_X + 66;
constexpr int F_R = F_O + 64;
constexpr int NSETUP = 131;
struct __align__(256) Flag { unsigned v; };
__device__ Flag                   g_flag[NFLAG];
__device__ Flag                   g_ready[1];
__device__ __align__(1024) char   g_item[RING * 32 * 32768];
__device__ __align__(1024) bf16   g_O[S_ * 4096];
__device__ __align__(1024) __half g_xn[S_ * D_];
__device__ __align__(1024) bf16   g_xa[S_ * D_];
__device__ __align__(1024) bf16   g_xb[S_ * D_];
__device__ __align__(1024) __half g_UT[D_ * S_];
__device__ __align__(1024) __half g_YT[D_ * S_];
__device__ __align__(1024) __half g_ctab[64 * 128 + 64 * 64];
__device__ __align__(1024) uint32_t g_Wf[321 * 2048];

#define TL(i)
#define TLN 0
#define TLL 1
#define CK(i)
__device__ __forceinline__ uint32_t smem_u32(const void* p) { return (uint32_t)__cvta_generic_to_shared(p); }
__device__ __forceinline__ uint32_t mapa(uint32_t a, uint32_t r) { uint32_t o; asm("mapa.shared::cluster.u32 %0,%1,%2;" : "=r"(o) : "r"(a), "r"(r)); return o; }
__device__ __forceinline__ void mbar_init(uint32_t a, int c) { asm volatile("mbarrier.init.shared::cta.b64 [%0],%1;" ::"r"(a), "r"(c) : "memory"); }
__device__ __forceinline__ void mbar_expect(uint32_t a, int bytes) { asm volatile("mbarrier.arrive.expect_tx.shared::cta.b64 _,[%0],%1;" ::"r"(a), "r"(bytes) : "memory"); }
__device__ __forceinline__ void mbar_arrive(uint32_t a) { asm volatile("mbarrier.arrive.shared::cta.b64 _,[%0];" ::"r"(a) : "memory"); }
__device__ __forceinline__ bool mbar_try(uint32_t a, uint32_t par) {
    uint32_t p;
    asm volatile("{.reg .pred q; mbarrier.try_wait.parity.shared::cta.b64 q,[%1],%2; selp.u32 %0,1,0,q;}" : "=r"(p) : "r"(a), "r"(par) : "memory");
    return p;
}
__device__ __forceinline__ void mbar_wait(uint32_t a, uint32_t par) {
    if (!mbar_try(a, par)) {
        int lim = 0;
        while (!mbar_try(a, par) && ++lim < SPIN_LIM) {}
    }
}
__device__ __forceinline__ void mbar_sleep(uint32_t a, uint32_t par) {
    asm volatile("{.reg .pred q; .reg .u32 n; mov.u32 n,0;\n"
                 "W_LOOP: mbarrier.try_wait.parity.shared::cta.b64 q,[%0],%1,%2; add.u32 n,n,1; setp.lt.and.u32 q,n,%3,!q; @q bra W_LOOP;}"
                 ::"r"(a), "r"(par), "n"(20000), "n"(SPIN_LIM) : "memory");
}
__device__ __forceinline__ void bar_arrive(int id, int n) { asm volatile("bar.arrive %0,%1;" ::"r"(id), "r"(n) : "memory"); }
__device__ __forceinline__ uint32_t clock32() { uint32_t c; asm volatile("mov.u32 %0,%%clock;" : "=r"(c)); return c; }
__device__ __forceinline__ uint32_t read_tid() { uint32_t v; asm volatile("mov.u32 %0,%%tid.x;" : "=r"(v)); return v; }
__device__ __forceinline__ void bar_sync(int id, int n) { asm volatile("bar.sync %0,%1;" ::"r"(id), "r"(n) : "memory"); }
__device__ __forceinline__ void fence_async_smem() { asm volatile("fence.proxy.async.shared::cta;" ::: "memory"); }
__device__ __forceinline__ void fence_async_glb() { asm volatile("fence.proxy.async.global;" ::: "memory"); }
__device__ __forceinline__ void cluster_sync_full() { asm volatile("barrier.cluster.arrive.aligned; barrier.cluster.wait.aligned;" ::: "memory"); }
__device__ __forceinline__ void bulk_g2s(uint32_t dst, const void* src, int bytes, uint32_t mb) {
    asm volatile("cp.async.bulk.shared::cluster.global.mbarrier::complete_tx::bytes [%0],[%1],%2,[%3];" ::"r"(dst), "l"(src), "r"(bytes), "r"(mb) : "memory");
}
__device__ __forceinline__ void bulk_g2s_last(uint32_t dst, const void* src, int bytes, uint32_t mb) {
    asm volatile("{.reg .b64 p; createpolicy.fractional.L2::evict_first.b64 p, 1.0;\n"
                 "cp.async.bulk.shared::cluster.global.mbarrier::complete_tx::bytes.L2::cache_hint [%0],[%1],%2,[%3],p;}"
                 ::"r"(dst), "l"(src), "r"(bytes), "r"(mb) : "memory");
}
__device__ __forceinline__ void bulk_s2s(uint32_t dst, uint32_t src, int bytes, uint32_t mb) {
    asm volatile("cp.async.bulk.shared::cluster.shared::cta.mbarrier::complete_tx::bytes [%0],[%1],%2,[%3];" ::"r"(dst), "r"(src), "r"(bytes), "r"(mb) : "memory");
}
__device__ __forceinline__ void bulk_s2g(void* dst, uint32_t src, int bytes) {
    asm volatile("cp.async.bulk.global.shared::cta.bulk_group [%0],[%1],%2;" ::"l"(dst), "r"(src), "r"(bytes) : "memory");
}
__device__ __forceinline__ void cp_async16(uint32_t dst, const void* src, uint32_t bytes = 16) {
    asm volatile("cp.async.cg.shared.global [%0],[%1],16,%2;" ::"r"(dst), "l"(src), "r"(bytes) : "memory");
}
__device__ __forceinline__ void cp_commit() { asm volatile("cp.async.commit_group;" ::: "memory"); }
template <int N> __device__ __forceinline__ void cp_wait() { asm volatile("cp.async.wait_group %0;" ::"n"(N) : "memory"); }
__device__ __forceinline__ void bulk_commit() { asm volatile("cp.async.bulk.commit_group;" ::: "memory"); }
__device__ __forceinline__ void bulk_wait0() { asm volatile("cp.async.bulk.wait_group 0;" ::: "memory"); }
__device__ __forceinline__ void ldsm4(uint32_t* r, uint32_t a) {
    asm volatile("ldmatrix.sync.aligned.m8n8.x4.shared.b16 {%0,%1,%2,%3},[%4];" : "=r"(r[0]), "=r"(r[1]), "=r"(r[2]), "=r"(r[3]) : "r"(a) : "memory");
}
__device__ __forceinline__ void ldsm4t(uint32_t* r, uint32_t a) {
    asm volatile("ldmatrix.sync.aligned.m8n8.x4.trans.shared.b16 {%0,%1,%2,%3},[%4];" : "=r"(r[0]), "=r"(r[1]), "=r"(r[2]), "=r"(r[3]) : "r"(a) : "memory");
}
__device__ __forceinline__ void stsm4(uint32_t a, uint32_t r0, uint32_t r1, uint32_t r2, uint32_t r3) {
    asm volatile("stmatrix.sync.aligned.m8n8.x4.shared.b16 [%0],{%1,%2,%3,%4};" ::"r"(a), "r"(r0), "r"(r1), "r"(r2), "r"(r3) : "memory");
}
__device__ __forceinline__ void stsm4t(uint32_t a, uint32_t r0, uint32_t r1, uint32_t r2, uint32_t r3) {
    asm volatile("stmatrix.sync.aligned.m8n8.x4.trans.shared.b16 [%0],{%1,%2,%3,%4};" ::"r"(a), "r"(r0), "r"(r1), "r"(r2), "r"(r3) : "memory");
}
__device__ __forceinline__ void lds128(uint32_t* r, uint32_t a) {
    asm volatile("ld.shared.v4.b32 {%0,%1,%2,%3},[%4];" : "=r"(r[0]), "=r"(r[1]), "=r"(r[2]), "=r"(r[3]) : "r"(a) : "memory");
}
__device__ __forceinline__ void lds64(uint32_t* r, uint32_t a) {
    asm volatile("ld.shared.v2.b32 {%0,%1},[%2];" : "=r"(r[0]), "=r"(r[1]) : "r"(a) : "memory");
}
__device__ __forceinline__ uint32_t lds32(uint32_t a) { uint32_t v; asm volatile("ld.shared.b32 %0,[%1];" : "=r"(v) : "r"(a) : "memory"); return v; }
__device__ __forceinline__ void sts128(uint32_t a, uint32_t r0, uint32_t r1, uint32_t r2, uint32_t r3) {
    asm volatile("st.shared.v4.b32 [%0],{%1,%2,%3,%4};" ::"r"(a), "r"(r0), "r"(r1), "r"(r2), "r"(r3) : "memory");
}
__device__ __forceinline__ void sts64(uint32_t a, uint32_t v0, uint32_t v1) { asm volatile("st.shared.v2.b32 [%0],{%1,%2};" ::"r"(a), "r"(v0), "r"(v1) : "memory"); }
[[maybe_unused]] __device__ __forceinline__ void sts32(uint32_t a, uint32_t v) { asm volatile("st.shared.b32 [%0],%1;" ::"r"(a), "r"(v) : "memory"); }
#define AU_(op) "{.reg .u32 t; add.u32 t,%4,%5; " op " {%0,%1,%2,%3},[t+%6];}"
template <int I> __device__ __forceinline__ void ldsm4_u(uint32_t* r, uint32_t a, uint32_t u) {
    asm volatile(AU_("ldmatrix.sync.aligned.m8n8.x4.shared.b16") : "=r"(r[0]), "=r"(r[1]), "=r"(r[2]), "=r"(r[3]) : "r"(a), "r"(u), "n"(I) : "memory");
}
template <int I> __device__ __forceinline__ void ldsm4t_u(uint32_t* r, uint32_t a, uint32_t u) {
    asm volatile(AU_("ldmatrix.sync.aligned.m8n8.x4.trans.shared.b16") : "=r"(r[0]), "=r"(r[1]), "=r"(r[2]), "=r"(r[3]) : "r"(a), "r"(u), "n"(I) : "memory");
}
template <int I> __device__ __forceinline__ void lds128_u(uint32_t* r, uint32_t a, uint32_t u) {
    asm volatile(AU_("ld.shared.v4.b32") : "=r"(r[0]), "=r"(r[1]), "=r"(r[2]), "=r"(r[3]) : "r"(a), "r"(u), "n"(I) : "memory");
}
template <int I> __device__ __forceinline__ void lds64_u(uint32_t* r, uint32_t a, uint32_t u) {
    asm volatile("{.reg .u32 t; add.u32 t,%2,%3; ld.shared.v2.b32 {%0,%1},[t+%4];}" : "=r"(r[0]), "=r"(r[1]) : "r"(a), "r"(u), "n"(I) : "memory");
}
template <int I> __device__ __forceinline__ uint32_t lds32_u(uint32_t a, uint32_t u) {
    uint32_t v;
    asm volatile("{.reg .u32 t; add.u32 t,%1,%2; ld.shared.b32 %0,[t+%3];}" : "=r"(v) : "r"(a), "r"(u), "n"(I) : "memory");
    return v;
}
template <int I> __device__ __forceinline__ void sts64_u(uint32_t a, uint32_t u, uint32_t v0, uint32_t v1) {
    asm volatile("{.reg .u32 t; add.u32 t,%0,%1; st.shared.v2.b32 [t+%2],{%3,%4};}" ::"r"(a), "r"(u), "n"(I), "r"(v0), "r"(v1) : "memory");
}
template <int I> __device__ __forceinline__ void sts32_u(uint32_t a, uint32_t u, uint32_t v) {
    asm volatile("{.reg .u32 t; add.u32 t,%0,%1; st.shared.b32 [t+%2],%3;}" ::"r"(a), "r"(u), "n"(I), "r"(v) : "memory");
}
template <int I> __device__ __forceinline__ void sts16_u(uint32_t a, uint32_t u, uint32_t v) {
    asm volatile("{.reg .u32 t; add.u32 t,%0,%1; st.shared.b16 [t+%2],%3;}" ::"r"(a), "r"(u), "n"(I), "h"((unsigned short)v) : "memory");
}
template <int I> __device__ __forceinline__ void sts128_u(uint32_t a, uint32_t u, uint32_t r0, uint32_t r1, uint32_t r2, uint32_t r3) {
    asm volatile("{.reg .u32 t; add.u32 t,%0,%1; st.shared.v4.b32 [t+%2],{%3,%4,%5,%6};}" ::"r"(a), "r"(u), "n"(I), "r"(r0), "r"(r1), "r"(r2), "r"(r3) : "memory");
}
template <int I> __device__ __forceinline__ void stsm4_u(uint32_t a, uint32_t u, uint32_t r0, uint32_t r1, uint32_t r2, uint32_t r3) {
    asm volatile("{.reg .u32 t; add.u32 t,%0,%1; stmatrix.sync.aligned.m8n8.x4.shared.b16 [t+%2],{%3,%4,%5,%6};}"
                 ::"r"(a), "r"(u), "n"(I), "r"(r0), "r"(r1), "r"(r2), "r"(r3) : "memory");
}
__device__ __forceinline__ void st_share2(uint32_t a, uint32_t u, uint32_t mb, uint32_t d0, uint32_t d1, uint32_t v0, uint32_t v1) {
    asm volatile("{.reg .pred p; .reg .u32 t,x,y; add.u32 t,%0,%1;\n"
                 "add.u32 x,t,%3; add.u32 y,%2,%3; st.async.shared::cluster.mbarrier::complete_tx::bytes.v2.b32 [x],{%5,%6},[y];\n"
                 "add.u32 x,t,%4; add.u32 y,%2,%4; st.async.shared::cluster.mbarrier::complete_tx::bytes.v2.b32 [x],{%5,%6},[y];\n"
                 "st.shared.v2.b32 [t],{%5,%6}; bar.warp.sync -1; setp.eq.u32 p,%0,0; @p mbarrier.arrive.shared::cta.b64 _,[%2];}"
                 ::"r"(a), "r"(u), "r"(mb), "r"(d0), "r"(d1), "r"(v0), "r"(v1) : "memory");
}
template <int V> struct IC { __host__ __device__ constexpr operator int() const { return V; } };
template <int N, class F> __device__ __forceinline__ void sfor(F f) {
    if constexpr (N > 0) { sfor<N - 1>(f); f(IC<N - 1>()); }
}
__device__ __forceinline__ void mma_f16(float* d, const uint32_t* a, uint32_t b0, uint32_t b1) {
    asm volatile("mma.sync.aligned.m16n8k16.row.col.f32.f16.f16.f32 {%0,%1,%2,%3},{%4,%5,%6,%7},{%8,%9},{%0,%1,%2,%3};"
                 : "+f"(d[0]), "+f"(d[1]), "+f"(d[2]), "+f"(d[3]) : "r"(a[0]), "r"(a[1]), "r"(a[2]), "r"(a[3]), "r"(b0), "r"(b1));
}
__device__ __forceinline__ void mma_bf(float* d, uint32_t a0, uint32_t a1, uint32_t a2, uint32_t a3, uint32_t b0, uint32_t b1) {
    asm volatile("mma.sync.aligned.m16n8k16.row.col.f32.bf16.bf16.f32 {%0,%1,%2,%3},{%4,%5,%6,%7},{%8,%9},{%0,%1,%2,%3};"
                 : "+f"(d[0]), "+f"(d[1]), "+f"(d[2]), "+f"(d[3]) : "r"(a0), "r"(a1), "r"(a2), "r"(a3), "r"(b0), "r"(b1));
}
__device__ __forceinline__ void mma_bf8(float* d, uint32_t a0, uint32_t a1, uint32_t b0) {
    asm volatile("mma.sync.aligned.m16n8k8.row.col.f32.bf16.bf16.f32 {%0,%1,%2,%3},{%4,%5},{%6},{%0,%1,%2,%3};"
                 : "+f"(d[0]), "+f"(d[1]), "+f"(d[2]), "+f"(d[3]) : "r"(a0), "r"(a1), "r"(b0));
}
__device__ __forceinline__ uint32_t pack_bf(float lo, float hi) { uint32_t r; asm("cvt.rn.bf16x2.f32 %0,%1,%2;" : "=r"(r) : "f"(hi), "f"(lo)); return r; }
__device__ __forceinline__ uint32_t pack_h(float lo, float hi) { uint32_t r; asm("cvt.rn.f16x2.f32 %0,%1,%2;" : "=r"(r) : "f"(hi), "f"(lo)); return r; }
__device__ __forceinline__ float bf_lo(uint32_t v) { return __uint_as_float(v << 16); }
__device__ __forceinline__ float bf_hi(uint32_t v) { return __uint_as_float(v & 0xffff0000u); }
__device__ __forceinline__ uint32_t bfma(uint32_t a, uint32_t b, uint32_t c) { uint32_t r; asm("fma.rn.bf16x2 %0,%1,%2,%3;" : "=r"(r) : "r"(a), "r"(b), "r"(c)); return r; }
__device__ __forceinline__ uint4 add_bf8(const uint4 x, const uint32_t* y, const uint32_t k = 0x3f803f80u) {
    return make_uint4(bfma(y[0], k, x.x), bfma(y[1], k, x.y), bfma(y[2], k, x.z), bfma(y[3], k, x.w));
}
__device__ __forceinline__ float ex2(float x) { float r; asm("ex2.approx.ftz.f32 %0,%1;" : "=f"(r) : "f"(x)); return r; }
__device__ __forceinline__ float rcp(float x) { float r; asm("rcp.approx.ftz.f32 %0,%1;" : "=f"(r) : "f"(x)); return r; }
__device__ __forceinline__ void wg_fence() { asm volatile("wgmma.fence.sync.aligned;" ::: "memory"); }
__device__ __forceinline__ void wg_commit() { asm volatile("wgmma.commit_group.sync.aligned;" ::: "memory"); }
template <int N> __device__ __forceinline__ void wg_wait() { asm volatile("wgmma.wait_group.sync.aligned %0;" ::"n"(N) : "memory"); }
__device__ __forceinline__ uint64_t mkdesc(uint32_t a, uint32_t lbo, uint32_t sbo, uint32_t sw) {
    return (uint64_t)((a & 0x3FFFF) >> 4) | ((uint64_t)(lbo >> 4) << 16) | ((uint64_t)(sbo >> 4) << 32) | ((uint64_t)sw << 62);
}
#define F4(d, i) "+f"(d[i]), "+f"(d[i + 1]), "+f"(d[i + 2]), "+f"(d[i + 3])
#define F8(d, i) F4(d, i), F4(d, i + 4)
#define F16(d, i) F8(d, i), F8(d, i + 8)
template <int OFF, int SC> __device__ __forceinline__ void wg_n32_x(float* d, const uint32_t* a, uint32_t lo) {
    asm volatile("{.reg .pred p; .reg .b32 l; .reg .b64 q; setp.ne.b32 p,%22,0; add.u32 l,%20,%21; mov.b64 q,{l,8};\n"
                 "wgmma.mma_async.sync.aligned.m64n32k16.f32.f16.f16 "
                 "{%0,%1,%2,%3,%4,%5,%6,%7,%8,%9,%10,%11,%12,%13,%14,%15},{%16,%17,%18,%19},q,p,1,1,0;}"
                 : F16(d, 0) : "r"(a[0]), "r"(a[1]), "r"(a[2]), "r"(a[3]), "r"(lo), "n"(OFF), "n"(SC));
}
__device__ __forceinline__ void wg_n128_rs(float* d, const uint32_t* a, uint64_t db, int sc) {
    asm volatile("{.reg .pred p; setp.ne.b32 p,%69,0; wgmma.mma_async.sync.aligned.m64n128k16.f32.f16.f16 "
                 "{%0,%1,%2,%3,%4,%5,%6,%7,%8,%9,%10,%11,%12,%13,%14,%15,%16,%17,%18,%19,%20,%21,%22,%23,%24,%25,%26,%27,%28,%29,%30,%31,"
                 "%32,%33,%34,%35,%36,%37,%38,%39,%40,%41,%42,%43,%44,%45,%46,%47,%48,%49,%50,%51,%52,%53,%54,%55,%56,%57,%58,%59,%60,%61,%62,%63},"
                 "{%64,%65,%66,%67},%68,p,1,1,0;}"
                 : F16(d, 0), F16(d, 16), F16(d, 32), F16(d, 48) : "r"(a[0]), "r"(a[1]), "r"(a[2]), "r"(a[3]), "l"(db), "r"(sc));
}
#define N80_REGS "{%0,%1,%2,%3,%4,%5,%6,%7,%8,%9,%10,%11,%12,%13,%14,%15,%16,%17,%18,%19,%20,%21,%22,%23,%24,%25,%26,%27,%28,%29,%30,%31,%32,%33,%34,%35,%36,%37,%38,%39}"
__device__ __forceinline__ void wg_n80_ss(float* d, uint64_t da, uint64_t db, int sc) {
    asm volatile("{.reg .pred p; setp.ne.b32 p,%42,0; wgmma.mma_async.sync.aligned.m64n80k16.f32.bf16.bf16 " N80_REGS ",%40,%41,p,1,1,0,0;}"
                 : F16(d, 0), F16(d, 16), F8(d, 32) : "l"(da), "l"(db), "r"(sc));
}
__device__ __forceinline__ void wg_n88_ss(float* d, uint64_t da, uint64_t db, int sc) {
    asm volatile("{.reg .pred p; setp.ne.b32 p,%46,0; wgmma.mma_async.sync.aligned.m64n88k16.f32.f16.f16 "
                 "{%0,%1,%2,%3,%4,%5,%6,%7,%8,%9,%10,%11,%12,%13,%14,%15,%16,%17,%18,%19,%20,%21,%22,%23,%24,%25,%26,%27,%28,%29,%30,%31,"
                 "%32,%33,%34,%35,%36,%37,%38,%39,%40,%41,%42,%43},%44,%45,p,1,1,0,0;}"
                 : F16(d, 0), F16(d, 16), F8(d, 32), F4(d, 40) : "l"(da), "l"(db), "r"(sc));
}
__device__ __forceinline__ void wg_n48_ss_ta(float* d, uint64_t da, uint64_t db, int sc) {
    asm volatile("{.reg .pred p; setp.ne.b32 p,%26,0; wgmma.mma_async.sync.aligned.m64n48k16.f32.f16.f16 "
                 "{%0,%1,%2,%3,%4,%5,%6,%7,%8,%9,%10,%11,%12,%13,%14,%15,%16,%17,%18,%19,%20,%21,%22,%23},%24,%25,p,1,1,1,0;}"
                 : F16(d, 0), F8(d, 16) : "l"(da), "l"(db), "r"(sc));
}
template <int TA> __device__ __forceinline__ void wg_n64_ss_tb(float* d, uint64_t da, uint64_t db, int sc) {
    asm volatile("{.reg .pred p; setp.ne.b32 p,%34,0; wgmma.mma_async.sync.aligned.m64n64k16.f32.f16.f16 "
                 "{%0,%1,%2,%3,%4,%5,%6,%7,%8,%9,%10,%11,%12,%13,%14,%15,%16,%17,%18,%19,%20,%21,%22,%23,%24,%25,%26,%27,%28,%29,%30,%31},"
                 "%32,%33,p,1,1,%35,1;}"
                 : F16(d, 0), F16(d, 16) : "l"(da), "l"(db), "r"(sc), "n"(TA));
}
__device__ __forceinline__ void pdl_wait() { asm volatile("griddepcontrol.wait;" ::: "memory"); }
__device__ __forceinline__ void pdl_go() { asm volatile("griddepcontrol.launch_dependents;" ::: "memory"); }
__device__ __forceinline__ float cos640(float p) {
    const float q = fmaf(p, 0.0015625f, 12582912.f) - 12582912.f;
    return __cosf(fmaf(q, -640.f, p) * 0.009817477042468103f);
}
__device__ __forceinline__ uint4 cos_row8(float p0, float step, float amp = 1.f) {
    float v[8];
    const float k = 2.f * cos640(step);
    v[0] = amp * cos640(p0); v[1] = amp * cos640(p0 + step);
#pragma unroll
    for (int i = 2; i < 8; i++) v[i] = fmaf(k, v[i - 1], -v[i - 2]);
    return make_uint4(pack_h(v[0], v[1]), pack_h(v[2], v[3]), pack_h(v[4], v[5]), pack_h(v[6], v[7]));
}
__device__ __forceinline__ float wfilter_max(int lane) {
    float m = fmaxf(fmaxf(g_wmax[lane], g_wmax[lane + 32]), fmaxf(g_wmax[lane + 64], g_wmax[lane + 96]));
    return __uint_as_float(__reduce_max_sync(~0u, __float_as_uint(m)));
}
__device__ __forceinline__ unsigned ld_acquire(const Flag* p) { unsigned v; asm volatile("ld.acquire.gpu.global.u32 %0,[%1];" : "=r"(v) : "l"(p) : "memory"); return v; }
#define POLL_NS 200
template <int NS = POLL_NS> __device__ __forceinline__ void wait_flag(const Flag* p, unsigned v) {
    if (ld_acquire(p) >= v) return;
    unsigned x;
    int lim = 0;
    do {
        __nanosleep(NS);
        asm volatile("ld.relaxed.gpu.global.u32 %0,[%1];" : "=r"(x) : "l"(p) : "memory");
    } while (x < v && ++lim < SPIN_LIM);
    ld_acquire(p);
}
__device__ __forceinline__ void prefetch_l2(const void* p, int bytes) { asm volatile("cp.async.bulk.prefetch.L2.global [%0],%1;" ::"l"(p), "r"(bytes) : "memory"); }
__device__ __forceinline__ void red_release(Flag* p) { asm volatile("red.release.gpu.global.add.u32 [%0],1;" ::"l"(p) : "memory"); }
__device__ __forceinline__ void red_relaxed(Flag* p) { asm volatile("red.relaxed.gpu.global.add.u32 [%0],1;" ::"l"(p) : "memory"); }
__device__ __forceinline__ void red_h8(void* p, uint32_t a, uint32_t b, uint32_t c, uint32_t d) {
    asm volatile("red.relaxed.gpu.global.add.noftz.v4.f16x2 [%0],{%1,%2,%3,%4};" ::"l"(p), "r"(a), "r"(b), "r"(c), "r"(d) : "memory");
}
__device__ __forceinline__ float pow2_scale(float bound, int top, float* inv) {
    int e = (int)((__float_as_uint(bound) >> 23) & 0xff) - 126;
    int k = top - e;
    k = max(-100, min(100, k));
    *inv = __uint_as_float((uint32_t)(127 - k) << 23);
    return __uint_as_float((uint32_t)(127 + k) << 23);
}
__device__ __forceinline__ char* red_base() { return (char*)(((uintptr_t)g_redraw + 32767) & ~(uintptr_t)32767); }

__device__ __forceinline__ void setup_a(char* sm, const int b, const bf16* __restrict__ wr, const bf16* __restrict__ wi) {
    const int tid = threadIdx.x, lane = tid & 31;
    const uint32_t sb = smem_u32(sm);
    auto row_byte = [&](int q) { return ((b >> 2) + 32 * ((q >> 1) * 8 + 2 * (b & 3) + (q & 1))) * 642; };
#pragma unroll 1
    for (int r = tid >> 5; r < 32; r += 8) {
        const char* src = (const char*)(r < 16 ? wr : wi) + (row_byte(r & 15) & ~15);
        cp_async16(sb + r * 672 + lane * 16, src + lane * 16);
        if (lane < 9) cp_async16(sb + r * 672 + 512 + lane * 16, src + 512 + lane * 16);
    }
    ((uint4*)g_stat)[b * 256 + tid] = make_uint4(0, 0, 0, 0);
    if (tid < 2 * (NFLAG / 128)) ((uint4*)(g_flag + b * (NFLAG / 128) + (tid >> 1)))[tid & 1] = make_uint4(0, 0, 0, 0);
    if (tid < 12) {
        const int i = b * 12 + tid;
        const int f = ((i >> 4) & 3) * 8 + (i & 7), im = (i >> 3) & 1, part = (i >> 8) & 1;
        ((uint4*)g_ctab)[i] = cos_row8((float)(i < 1024 ? (i >> 7) * 80 * (i & 63) + ((i & 64) ? 480 : 0) : ((i >> 6) & 3) * 160 * f + (im == part ? 0 : im ? 160 : 480)),
                                       (float)(i < 1024 ? 10 * (i & 63) : 20 * f));
    }
    asm volatile("cp.async.wait_all;" ::: "memory");
    __syncthreads();
    const int q0 = (tid & 3) * 4;
    const char* rp[4];
#pragma unroll
    for (int u = 0; u < 4; u++) rp[u] = sm + (q0 + u) * 672 + (row_byte(q0 + u) & 15);
    uint32_t mx = 0;
#pragma unroll 2
    for (int c = tid >> 2; c < 321; c += 64) {
        uint32_t v[4];
#pragma unroll
        for (int u = 0; u < 4; u++) {
            v[u] = ((const unsigned short*)rp[u])[c] | ((uint32_t)((const unsigned short*)(rp[u] + 16 * 672))[c] << 16);
            mx = __vmaxu2(mx, v[u] & 0x7fff7fffu);
        }
        ((uint4*)g_Wf)[(size_t)c * 512 + b * 4 + ((tid ^ (b >> 1)) & 3)] = make_uint4(v[0], v[1], v[2], v[3]);
    }
    mx = __reduce_max_sync(~0u, max(mx & 0xffffu, mx >> 16));
    __syncthreads();
    if (lane == 0) ((uint32_t*)sm)[tid >> 5] = mx;
    __syncthreads();
    if (tid < 32) {
        mx = __reduce_max_sync(~0u, ((uint32_t*)sm)[lane & 7]);
        if (tid == 0) g_wmax[b] = __uint_as_float(mx << 16);
    }
}
__device__ __forceinline__ void setup_b(const int b, const bf16* __restrict__ mem0) {
    const int tid = threadIdx.x;
    uint4* z = (uint4*)red_base();
    if (b < 3) {
        const int w = tid >> 5, lane = tid & 31, p = b * 2 + ((w >> 1) & 1), odd = w & 1;
        uint32_t mx = 0;
#pragma unroll 4
        for (int i = lane; i < 640; i += 32) {
            const uint4 u = ((const uint4*)mem0)[i];
            mx = __vmaxu2(__vmaxu2(mx, u.x & 0x7fff7fffu), __vmaxu2(__vmaxu2(u.y & 0x7fff7fffu, u.z & 0x7fff7fffu), u.w & 0x7fff7fffu));
        }
        float inv, v[7];
        const float sc = pow2_scale(__uint_as_float(__reduce_max_sync(~0u, max(mx & 0xffffu, mx >> 16)) << 16), 14, &inv);
        if (tid == 0) g_invM0 = inv;
#pragma unroll
        for (int j = 0; j < 7; j++) {
            const int r = p * 56 + (j < 6 ? odd * 32 + (j >> 1) * 8 : 24) + (lane >> 2), mr = 2 * (lane & 3) + (j < 6 ? (j & 1) : odd);
            v[j] = r < 320 ? __bfloat162float(mem0[mr * 640 + (w >> 2) * 320 + r]) * sc : 0.f;
        }
        const int off = w * 2048 + (lane >> 4) * 1024 + ((lane >> 3) & 1) * 256 + (lane & 7) * 16 + (b == 2 ? (w >> 1) * 4096 + 128 : b * 16384);
        const uint4 u = make_uint4(pack_h(v[0], v[1]), pack_h(v[2], v[3]), pack_h(v[4], v[5]), pack_h(v[6], 32.f));
        z[off >> 4] = u; z[65536 + (off >> 4)] = u;
    }
}

#define SU_PAD 40960
constexpr int SU_SMEM = SU_PAD;
__global__ void __launch_bounds__(256, 4) k_setup(const bf16* __restrict__ wr, const bf16* __restrict__ wi, const bf16* __restrict__ mem0) {
    extern __shared__ __align__(1024) char sm[];
    TL(0);
    if (blockIdx.x >= 128) setup_b(blockIdx.x - 128, mem0);
    else setup_a(sm, blockIdx.x, wr, wi);
    __syncthreads();
    if (threadIdx.x == 0) red_release(g_ready);
    TL(1);
}
__device__ __forceinline__ float weight_scale(int h, int ty, float* inv) { return pow2_scale(__ldcg(g_wmx + h * 3 + ty), 6, inv); }

#define STR_(x) #x
#define STR(x) STR_(x)
#define RF_U 1
constexpr int RF_A = 22 * 2816, RF_X = RF_A + 22 * 1024, RF_BAR = RF_X + 64 * 1344, RF_SMEM = RF_BAR + 80;
__device__ __align__(1024) char g_rtab[4 * RF_A];
template <int first> __global__ void __cluster_dims__(2, 1, 1) __launch_bounds__(256, 2) k_rowf(const bf16* x) {
    extern __shared__ __align__(1024) char sm[];
    TL(first ? 2 : 16);
    const int tid = threadIdx.x, w = tid >> 5, lane = tid & 31, g = lane >> 2, t = lane & 3;
    if (blockIdx.x >= 128) { __nanosleep(2500); return; }
    const int a = first ? blockIdx.x >> 2 : 31 - (blockIdx.x >> 2), gq = blockIdx.x & 3;
    if (!first) pdl_go();
    const uint32_t sb = smem_u32(sm), mb = sb + RF_BAR + w * 8;
    if (lane == 0) {
        mbar_init(mb, 1);
        asm volatile("fence.mbarrier_init.release.cluster;" ::: "memory");
        if (!first && w == 0) {
            mbar_init(sb + RF_BAR + 64, 1);
            fence_async_smem();
            mbar_expect(sb + RF_BAR + 64, RF_A);
            bulk_g2s(sb, g_rtab + gq * RF_A, RF_A, sb + RF_BAR + 64);
        }
    }
    if (lane == 0) mbar_expect(mb, 8 * 1280);
    __syncwarp();
    asm volatile("barrier.cluster.arrive.relaxed.aligned; barrier.cluster.wait.aligned;" ::: "memory");
    if (!first) {
        if (lane == 0) wait_flag<100>(g_flag + F_R + a, a < 28 ? 32 : 192);
        __syncwarp();
        fence_async_glb();
    }
    TL(first ? 3 : 17);
    if (lane < 4)
        asm volatile("cp.async.bulk.shared::cluster.global.mbarrier::complete_tx::bytes.multicast::cluster [%0],[%1],1280,[%2],%3;"
                     ::"r"(sb + RF_X + (w * 8 + (gq & 1) * 4 + lane) * 1344), "l"(x + (size_t)(a * 64 + w * 8 + (gq & 1) * 4 + lane) * 640), "r"(mb),
                     "h"((unsigned short)3) : "memory");
    __syncwarp();
    if (first) pdl_go();
    if (first) {
#pragma unroll 3
        for (int id = tid; id < 22 * 176; id += 256) {
            const int kg = id / 176, n = id - kg * 176;
            const float c = (float)(2 * n + (gq & 1));
            *(uint4*)(sm + id * 16) = cos_row8(fmaf((float)(kg * 8), c, (float)((gq & 2) * 80)), c, 0.03952847075210474f);
        }
    }
    mbar_wait(mb, 0);
    const uint32_t row = sb + RF_X + (w * 8 + g) * 1344;
    float st[4][4] = {};
#pragma unroll 1
    for (int i = 0; i < 20; i += 4) {
        uint32_t u[4][4];
#pragma unroll
        for (int q = 0; q < 4; q++) lds128(u[q], row + (4 * (i + q) + t) * 16);
#pragma unroll
        for (int q = 0; q < 4; q++) {
            mma_bf(st[(q & 1) * 2], u[q][0], 0x3f803f80u, u[q][1], 0x3f803f80u, u[q][0], u[q][1]);
            mma_bf(st[(q & 1) * 2 + 1], u[q][2], 0x3f803f80u, u[q][3], 0x3f803f80u, u[q][2], u[q][3]);
        }
    }
#pragma unroll
    for (int q = 0; q < 4; q++) { st[0][q] += st[2][q]; st[1][q] += st[3][q]; }
    const float sq = __shfl_sync(~0u, (g & 1) ? st[0][1] + st[1][1] : st[0][0] + st[1][0], g * 4 + (g >> 1));
    const float mean = __shfl_sync(~0u, (g & 1) ? st[0][3] + st[1][3] : st[0][2] + st[1][2], g * 4 + (g >> 1)) * (1.f / 640.f);
    const float r = rsqrtf(fmaxf(fmaf(-mean, mean, sq * (1.f / 640.f)), 0.f) + 1e-5f), off = gq == 0 ? -4.f * mean * r : 0.f;
    const float r1 = (gq == 1 || gq == 2) ? -r : r, r2 = (gq & 1) ? -r : r, r3 = gq >= 2 ? -r : r;
    const uint32_t aa = sb + RF_A + w * 128 + g * 16;
    auto el = [&](int d) { unsigned short v; asm volatile("ld.shared.u16 %0,[%1];" : "=h"(v) : "r"(row + d * 2)); return __uint_as_float((uint32_t)v << 16); };
_Pragma(STR(unroll RF_U))
    for (int i = 0; i < 5; i++) {
        const int ch = t + 4 * i;
        uint32_t u[4][4];
        lds128(u[0], row + ch * 16); lds128(u[1], row + (39 - ch) * 16); lds128(u[2], row + (40 + ch) * 16); lds128(u[3], row + (79 - ch) * 16);
        const float nb0 = el(320 - 8 * ch), nb1 = el(ch ? 640 - 8 * ch : 0);
        float o[8];
#pragma unroll
        for (int q = 0; q < 8; q++) {
            const int m = (8 - q) >> 1;
            const float e0 = (q & 1) ? bf_hi(u[0][q >> 1]) : bf_lo(u[0][q >> 1]), e2 = (q & 1) ? bf_hi(u[2][q >> 1]) : bf_lo(u[2][q >> 1]);
            const float e1 = q == 0 ? nb0 : (q & 1) ? bf_hi(u[1][m & 3]) : bf_lo(u[1][m & 3]), e3 = q == 0 ? nb1 : (q & 1) ? bf_hi(u[3][m & 3]) : bf_lo(u[3][m & 3]);
            o[q] = fmaf(e3, r3, fmaf(e2, r2, fmaf(e1, r1, fmaf(e0, r, off))));
        }
        if (ch == 0) o[0] *= 0.5f;
        sts128(aa + ch * 1024, pack_h(o[0], o[1]), pack_h(o[2], o[3]), pack_h(o[4], o[5]), pack_h(o[6], o[7]));
    }
    if (t < 2) sts128(aa + (20 + t) * 1024, t == 0 ? pack_h(fmaf(el(480), r2, fmaf(el(160), r, 0.5f * off)), 0.f) : 0u, 0u, 0u, 0u);
    fence_async_smem();
    __syncthreads();
    if (!first) mbar_wait(sb + RF_BAR + 64, 0);
    else if (a == 0 && tid == 0) { bulk_s2g(g_rtab + gq * RF_A, sb, RF_A); bulk_commit(); }
    const int wg = w >> 2;
    float acc[44];
    uint64_t da = mkdesc(sb + RF_A, 1024, 128, 0), db = mkdesc(sb + wg * 1408, 2816, 128, 0);
    wg_fence();
#pragma unroll 1
    for (int k = 0; k < 11; k++) { wg_n88_ss(acc, da, db, k); da += 128; db += 352; }
    wg_commit(); wg_wait<0>();
    const uint32_t stg = sb + RF_X + wg * 96 * 144;
#pragma unroll
    for (int j = 0; j < 12; j += 2) {
        const int m = lane >> 3, j1 = j < 10 ? j + 1 : j;
        stsm4t(stg + ((j + (m >> 1)) * 8 + (lane & 7)) * 144 + ((w & 3) * 16 + (m & 1) * 8) * 2, pack_h(acc[j * 4], acc[j * 4 + 1]),
               pack_h(acc[j * 4 + 2], acc[j * 4 + 3]), pack_h(acc[j1 * 4], acc[j1 * 4 + 1]), pack_h(acc[j1 * 4 + 2], acc[j1 * 4 + 3]));
    }
    bar_sync(1 + wg, 128);
#pragma unroll 3
    for (int rr = (tid & 127) >> 3; rr < 88; rr += 16) {
        const int ch = tid & 7, c = 2 * (wg * 88 + rr) + (gq & 1);
        if (c <= 320 - (gq >> 1) && (c | (gq ^ 2))) {
            uint32_t u[4];
            lds128(u, stg + rr * 144 + ch * 16);
            ((uint4*)g_UT)[((size_t)(c == 320 ? 1 : 2 * c + (gq >> 1)) * 32 + a) * 8 + (ch ^ (a & 7))] = make_uint4(u[0], u[1], u[2], u[3]);
        }
    }
    if (first && blockIdx.x < 4 && tid == 0) asm volatile("cp.async.bulk.wait_group.read 0;" ::: "memory");
    TL(first ? 4 : 18);
}

constexpr int GST = 4, GSTB = 32768 + 20480, GNC = 32;
constexpr int G_BAR = GST * GSTB + 3072;
#define GPACE 1100
#define GPACE2 650
__device__ __forceinline__ void oproj_load(const uint32_t sb, const int op, const int mb, const int nb, const int c0, const uint32_t pace) {
    const int by = op == 2 ? 20480 : 16384;
    const char* src = op == 2 ? (const char*)g_wot + (size_t)nb * GNC * 20480 : (const char*)g_O + (size_t)(2 * mb + op) * GNC * 16384;
    uint32_t t0 = clock32() - pace + op * (pace / 3);
#pragma unroll 1
    for (int c = c0; c < c0 + GNC; c++, src += by) {
        const int st = c % GST;
        if (c >= GST) mbar_wait(sb + G_BAR + (GST + st) * 8, ((c / GST) - 1) & 1);
        while (clock32() - t0 < pace) {}
        t0 = clock32();
        const int by_ = by;
        mbar_expect(sb + G_BAR + st * 8, by_);
        if (op == 2) bulk_g2s(sb + st * GSTB + 32768, src, by_, sb + G_BAR + st * 8);
        else bulk_g2s_last(sb + st * GSTB + op * 16384, src, by_, sb + G_BAR + st * 8);
    }
}
__device__ __forceinline__ void oproj_mma(const uint32_t sb, const int mb, const int nb, const int c0, const bf16* res, bf16* out, const int layer) {
    const int w = threadIdx.x >> 5, lane = threadIdx.x & 31, wg = w >> 2;
    float acc[40];
    uint4 rv[5];
#pragma unroll 1
    for (int c = c0; c < c0 + GNC; c++) {
        const int st = c % GST;
        mbar_wait(sb + G_BAR + st * 8, (c / GST) & 1);
        const uint32_t d = sb + st * GSTB;
        wg_fence();
#pragma unroll
        for (int k = 0; k < 8; k++)
            wg_n80_ss(acc, mkdesc(d + wg * 16384 + k * 2048, 1024, 128, 0), mkdesc(d + 32768 + k * 2560, 1280, 128, 0), (c - c0) | k);
        wg_commit();
        if (c > c0) {
            wg_wait<1>();
            if (lane == 0) mbar_arrive(sb + G_BAR + (GST + (c - 1) % GST) * 8);
        }
    }
#pragma unroll
    for (int i = 0; i < 5; i++) {
        const int id = i * 32 + lane, r = id / 10;
        rv[i] = __ldcg((const uint4*)res + (size_t)(mb * 128 + w * 16 + r) * 80 + nb * 10 + id - r * 10);
    }
    wg_wait<0>();
    bar_sync(5, 256);
    const uint32_t stg = sb + (GST - 1) * GSTB + w * 16 * 176;
#pragma unroll
    for (int j = 0; j < 5; j++)
        stsm4(stg + (lane & 15) * 176 + (2 * j + (lane >> 4)) * 16, pack_bf(acc[j * 8], acc[j * 8 + 1]), pack_bf(acc[j * 8 + 2], acc[j * 8 + 3]),
              pack_bf(acc[j * 8 + 4], acc[j * 8 + 5]), pack_bf(acc[j * 8 + 6], acc[j * 8 + 7]));
    __syncwarp();
#pragma unroll
    for (int i = 0; i < 5; i++) {
        const int id = i * 32 + lane, r = id / 10, ch = id - r * 10;
        uint32_t y[4];
        lds128(y, stg + r * 176 + ch * 16);
        ((uint4*)out)[(size_t)(mb * 128 + w * 16 + r) * 80 + nb * 10 + ch] = add_bf8(rv[i], y);
    }
    fence_async_smem();
    __syncwarp();
    if (lane == 0) {
        mbar_arrive(sb + G_BAR + (2 * GST - 1) * 8);
        if (layer == 0) red_release(g_flag + F_R + 2 * mb + wg);
    }
}

__global__ void __launch_bounds__(128, 4) k_col(const int first) {
    __shared__ __align__(1024) char sz[8192];
    __shared__ __align__(1024) char stab[24576];
    __shared__ __align__(1024) char swf[8192];
    __shared__ __align__(8) uint64_t bar[2];
    const int tid = threadIdx.x, wl = tid >> 5, lane = tid & 31, g = lane >> 2, t = lane & 3;
    const int c = blockIdx.x;
    TL(first ? 5 : 19);
    const bool realc = c == 0 || c == 320;
    const uint32_t z = smem_u32(sz), b2 = smem_u32(stab), a1 = b2 + 16384, wf = smem_u32(swf), mb = smem_u32(bar);
    if (tid == 0) { mbar_init(mb, 1); mbar_init(mb + 8, 1); fence_async_smem(); }
    if (realc) {
        for (int i = tid; i < 256; i += 128) sts128(z + 4096 + i * 16, 0, 0, 0, 0);
        fence_async_smem();
    }
    const int k1 = wl * 8 + g;
    float tc[16], ts[16];
#pragma unroll
    for (int j = 0; j < 16; j++) {
        const int p = ((j >> 1) * 8 + 2 * t + (j & 1)) * k1;
        __sincosf((float)(p - 1024) * 0.003067961575771282f, &ts[j], &tc[j]);
        ts[j] = -ts[j]; tc[j] = -tc[j];
    }
    if (first && tid == 32) { wait_flag<400>(g_ready, NSETUP); fence_async_glb(); }
    __syncthreads();
    if (tid == 32) {
        mbar_expect(mb + 8, 24576 + 8192);
        bulk_g2s(b2, g_ctab, 24576, mb + 8);
        bulk_g2s(wf, g_Wf + (size_t)c * 2048, 8192, mb + 8);
    }
    float inv;
    const float wsc = pow2_scale(wfilter_max(lane), 0, &inv) * (realc ? 0.0625f : 0.125f);
    pdl_wait();
    TL(first ? 6 : 20);
    if (tid == 0) {
        const int by = realc ? 4096 : 8192;
        mbar_expect(mb, by);
        bulk_g2s_last(z, (const char*)g_UT + (size_t)(c == 320 ? 1 : 2 * c) * 4096, by, mb);
    }
    pdl_go();
    mbar_wait(mb + 8, 0);
    mbar_wait(mb, 0);
    float d[64];
    uint32_t a[4][4];
    wg_fence();
#pragma unroll
    for (int ks = 0; ks < 4; ks++) wg_n64_ss_tb<0>(d, mkdesc(a1 + ks * 2048, 1024, 128, 0), mkdesc(z + ks * 2048, 1024, 1024, 1), ks);
    wg_commit(); wg_wait<0>();
    const float r32 = 0.17677669529663687f;
#pragma unroll
    for (int j = 0; j < 8; j++) {
        float yr[2], yi[2];
#pragma unroll
        for (int e = 0; e < 2; e++) {
            const float re = d[j * 4 + e] * r32, im = d[j * 4 + 2 + e] * r32, cc = tc[j * 2 + e], ss = ts[j * 2 + e];
            yr[e] = re * cc + im * ss; yi[e] = im * cc - re * ss;
        }
        a[j >> 1][(j & 1) * 2] = pack_h(yr[0], yr[1]); a[j >> 1][(j & 1) * 2 + 1] = pack_h(yi[0], yi[1]);
    }
    wg_fence();
#pragma unroll
    for (int ks = 0; ks < 4; ks++) wg_n128_rs(d, a[ks], mkdesc(b2 + ks * 4096, 2048, 128, 0), ks);
    wg_commit(); wg_wait<0>();
#pragma unroll
    for (int q = 0; q < 4; q++) {
        uint32_t wv[4];
        lds128(wv, wf + tid * 64 + ((q ^ (tid >> 1)) & 3) * 16);
#pragma unroll
        for (int jj = 0; jj < 2; jj++) {
            const int j = 2 * q + jj;
            float yr[2], yi[2];
#pragma unroll
            for (int e = 0; e < 2; e++) {
                const float xr = d[j * 4 + e] + d[32 + j * 4 + 2 + e], xi = d[j * 4 + 2 + e] - d[32 + j * 4 + e];
                const float fr = bf_lo(wv[jj * 2 + e]) * wsc, fi = bf_hi(wv[jj * 2 + e]) * wsc;
                yr[e] = xr * fr - xi * fi; yi[e] = xr * fi + xi * fr;
            }
            a[q][jj * 2] = pack_h(yr[0], yr[1]); a[q][jj * 2 + 1] = pack_h(yi[0], yi[1]);
        }
    }
    wg_fence();
#pragma unroll
    for (int ks = 0; ks < 4; ks++) wg_n128_rs(d, a[ks], mkdesc(b2 + ks * 4096, 2048, 128, 0), ks);
    wg_commit(); wg_wait<0>();
#pragma unroll
    for (int j = 0; j < 8; j++) {
        float yr[2], yi[2];
#pragma unroll
        for (int e = 0; e < 2; e++) {
            const float vr = (d[j * 4 + e] - d[32 + j * 4 + 2 + e]) * 0.125f, vi = (d[j * 4 + 2 + e] + d[32 + j * 4 + e]) * 0.125f;
            const float cc = tc[j * 2 + e], ss = ts[j * 2 + e];
            yr[e] = vr * cc - vi * ss; yi[e] = vi * cc + vr * ss;
        }
        a[j >> 1][(j & 1) * 2] = pack_h(yr[0], yr[1]); a[j >> 1][(j & 1) * 2 + 1] = pack_h(yi[0], yi[1]);
    }
    __syncthreads();
    const int mm = lane >> 3, rr = lane & 7;
    const uint32_t rowo = (wl * 16 + (mm & 1) * 8 + rr) * 128;
#pragma unroll
    for (int q = 0; q < 4; q++) stsm4(z + rowo + (((2 * q + (mm >> 1)) ^ rr) << 4), a[q][0], a[q][1], a[q][2], a[q][3]);
    fence_async_smem();
    __syncthreads();
    wg_fence();
#pragma unroll
    for (int ks = 0; ks < 4; ks++) wg_n64_ss_tb<1>(d, mkdesc(a1 + ks * 256, 128, 1024, 0), mkdesc(z + ks * 2048, 1024, 1024, 1), ks);
    wg_commit(); wg_wait<0>();
#pragma unroll
    for (int q = 0; q < 4; q++)
        stsm4(wf + rowo + (((2 * q + (mm >> 1)) ^ rr) << 4), pack_h(d[q * 8] * r32, d[q * 8 + 1] * r32), pack_h(d[q * 8 + 2] * r32, d[q * 8 + 3] * r32),
              pack_h(d[q * 8 + 4] * r32, d[q * 8 + 5] * r32), pack_h(d[q * 8 + 6] * r32, d[q * 8 + 7] * r32));
    __syncwarp();
    if (!(realc && wl >= 2)) {
        const int kk = c == 320 ? 320 : (c & 1) * 160 + (c >> 1) + (wl >> 1) * 320;
#pragma unroll
        for (int i = 0; i < 4; i++) {
            const int r = wl * 16 + i * 4 + (lane >> 3), ch = lane & 7;
            uint32_t v[4];
            lds128(v, wf + r * 128 + ((ch ^ (r & 7)) << 4));
            ((uint4*)g_YT)[((size_t)(r & 31) * 640 + kk) * 8 + (ch ^ (kk & 7))] = make_uint4(v[0], v[1], v[2], v[3]);
        }
    }
    TL(first ? 7 : 21);
}

constexpr int O_XS = 0;
constexpr int O_MS = 81920;
constexpr int O_QKP = O_MS + 10752;
constexpr int O_VM = O_QKP + 4096;
constexpr int O_SC = O_VM + 4096;
constexpr int O_OS = O_SC + 1536;
constexpr int O_XCH = O_OS + 2048;
constexpr int O_SUM = O_XCH + 8192;
constexpr int O_MX = O_SUM + 256;
constexpr int O_STG = O_MS + 65536 - 8192;
static_assert(O_STG - 16384 >= O_MX + 1024, "shared-memory map");
constexpr int O_WO = O_STG + 16384;
constexpr int O_SCL = O_WO + 65536;
constexpr int O_BAR = O_SCL + 64;
constexpr int B_XF = O_BAR, B_S = O_BAR + 16, B_VX = O_BAR + 32, B_STG = O_BAR + 48, B_FREE = O_BAR + 72;
constexpr int T_FA = O_BAR + 96, T_EA = T_FA + 32, T_FB = T_EA + 32, T_EB = T_FB + 56, T_RED = T_EB + 32;
constexpr int O_WMX = O_BAR + 512, B_W = O_BAR + 64;
constexpr int O_LAST = (O_WMX + 192 + 1023) / 1024 * 1024;
constexpr int CH_SMEM = O_LAST + 8192;
static_assert(O_WO == 19 * 8192, "weight staging");
__device__ __forceinline__ uint32_t tail_b(int c) { return c % 7 < 4 ? O_XS + (c % 7) * 20480 : O_WO + (c % 7 - 4) * 20480; }
__device__ __forceinline__ int s_tx(int c) { return c == 2 ? 2 * 768 : 768 + 2048; }

#define NPERM 1
#define NWO0 1
#define NWO0B 4
#define NWO1 6
#define EN 25
#define VXN 100
#define AUNR 2
#define TDELAY 300
#define WDEPTH 6
#define RDELAY 570

#define STAMP(i)

#define NTA 23
#define NTB 26
template <int LO, int HI>
__device__ __forceinline__ void tok_issue(const uint32_t (&A0)[20][4], const uint32_t (&A1)[20][4], float (&b0)[16], float (&b1)[16], uint32_t xd,
                                          const uint32_t zero) {
    if (LO == 0) wg_fence();
    sfor<HI - LO>([&](auto I) {
        constexpr int i = LO + I;
        if constexpr (i < 20) wg_n32_x<i * 64, i>(b0, A0[i], xd); else wg_n32_x<(i - 20) * 64, i - 20>(b1, A1[i - 20], xd + zero);
        if constexpr (i == 19 || i == NTB - 1 || i == 39) wg_commit();
    });
}
__device__ __forceinline__ void tok_give(const float (&b0)[16], const uint32_t L16, const uint32_t xch0) {
    wg_wait<1>();
    sfor<2>([&](auto I) {
        constexpr int i = I;
        sts128_u<i * 512>(L16, xch0, pack_h(b0[8 * i], b0[8 * i + 1]), pack_h(b0[8 * i + 2], b0[8 * i + 3]), pack_h(b0[8 * i + 4], b0[8 * i + 5]),
                          pack_h(b0[8 * i + 6], b0[8 * i + 7]));
    });
}
__device__ __forceinline__ void tok_finish(float (&b1)[16], const uint32_t (&e)[2][4], const uint32_t L16, const uint32_t dst, const uint32_t idn) {
#pragma unroll
    for (int j = 0; j < 4; j++)
        asm volatile("mma.sync.aligned.m16n8k8.row.col.f32.f16.f16.f32 {%0,%1,%2,%3},{%4,%5},{%6},{%0,%1,%2,%3};"
                     : F4(b1, 4 * j) : "r"(e[j >> 1][(j & 1) * 2]), "r"(e[j >> 1][(j & 1) * 2 + 1]), "r"(idn));
    stsm4_u<0>(L16, dst, pack_bf(b1[0], b1[1]), pack_bf(b1[2], b1[3]), pack_bf(b1[4], b1[5]), pack_bf(b1[6], b1[7]));
    stsm4_u<512>(L16, dst, pack_bf(b1[8], b1[9]), pack_bf(b1[10], b1[11]), pack_bf(b1[12], b1[13]), pack_bf(b1[14], b1[15]));
}
__device__ __forceinline__ uint32_t uni(uint32_t v) { return __shfl_sync(~0u, v, 0); }
__device__ __forceinline__ uint32_t badd(uint32_t a, uint32_t b) { uint32_t r; asm("add.rn.bf16x2 %0,%1,%2;" : "=r"(r) : "r"(a), "r"(b)); return r; }
__device__ __forceinline__ uint32_t bmax(uint32_t a, uint32_t b) { uint32_t r; asm("max.bf16x2 %0,%1,%2;" : "=r"(r) : "r"(a), "r"(b)); return r; }
__device__ __forceinline__ uint32_t babsmax(uint32_t a, uint32_t b) { uint32_t r; asm("max.xorsign.abs.bf16x2 %0,%1,%2;" : "=r"(r) : "r"(a), "r"(b)); return r; }
__device__ __forceinline__ uint32_t habsmax(uint32_t a, uint32_t b) { uint32_t r; asm("max.xorsign.abs.f16x2 %0,%1,%2;" : "=r"(r) : "r"(a), "r"(b)); return r; }

template <int NPF>
__device__ __forceinline__ float mem_out(const uint32_t sb, const uint32_t L16, const uint32_t L8, uint32_t (&wo)[16][4], const uint32_t woa,
                                         char* dst, const bool odd) {
    bar_sync(2, 352);
    float a[4][4];
#pragma unroll
    for (int i = 0; i < 4; i++) a[i][0] = a[i][1] = a[i][2] = a[i][3] = 0.f;
    uint32_t ob[4][4], sm_[2], sc[2];
    sfor<8>([&](auto I) {
        constexpr int i = I;
        if constexpr (!(i & 1)) ldsm4t_u<O_OS + (i >> 1) * 512>(ob[i >> 1], L16, sb);
        if constexpr (i >= NPF) { ldsm4t(wo[i], woa + i * 1024); ldsm4t(wo[8 + i], (woa ^ 32) + i * 1024); }
    });
    lds64_u<O_SUM>(sm_, L8 & 24, sb); lds64(sc, sb + O_SCL);
#pragma unroll
    for (int i = 0; i < 8; i++) {
        mma_bf(a[i & 1], wo[i][0], wo[i][1], wo[i][2], wo[i][3], ob[i >> 1][(i & 1) * 2], ob[i >> 1][(i & 1) * 2 + 1]);
        mma_bf(a[2 + (i & 1)], wo[8 + i][0], wo[8 + i][1], wo[8 + i][2], wo[8 + i][3], ob[i >> 1][(i & 1) * 2], ob[i >> 1][(i & 1) * 2 + 1]);
    }
    const float f0 = rcp(__uint_as_float(sm_[0])) * __uint_as_float(sc[0]), f1 = rcp(__uint_as_float(sm_[1])) * __uint_as_float(sc[0]);
    red_h8(dst, pack_h((a[0][0] + a[1][0]) * f0, (a[0][1] + a[1][1]) * f1), pack_h((a[0][2] + a[1][2]) * f0, (a[0][3] + a[1][3]) * f1),
           pack_h((a[2][0] + a[3][0]) * f0, (a[2][1] + a[3][1]) * f1), pack_h(odd ? (a[2][3] + a[3][3]) * f1 : (a[2][2] + a[3][2]) * f0, 1.f));
    return __uint_as_float(sc[1]);
}

template <int NE, int UNR>
__device__ __forceinline__ void tok_attention(const uint32_t qk, const uint32_t dq, const uint32_t km, const uint32_t dk, const uint32_t vt, const uint32_t vm,
                                              const int e0, const int mi, const int lane, const int seg, const int h, const float iqk, const float iv) {
    const int g = lane >> 2, t = lane & 3;
    float s[6][4];
#pragma unroll
    for (int i = 0; i < 6; i++) s[i][0] = s[i][1] = s[i][2] = s[i][3] = 0.f;
#pragma unroll UNR
    for (int e = 0; e < 8; e++) {
        uint32_t q[4], k[4];
        ldsm4t(q, qk + (e >> 2) * dq + (e & 3) * 1024 + mi * 512);
        ldsm4t(k, km + (e >> 2) * dk + (e & 3) * 512);
        mma_bf(s[4], q[0], q[2], q[1], q[3], k[0], k[1]);
        mma_bf(s[5], q[0], q[2], q[1], q[3], k[2], k[3]);
        ldsm4t(k, qk + (e >> 2) * dq + 4096 + (e & 3) * 1024);
        mma_bf(s[0], q[0], q[2], q[1], q[3], k[0], k[1]);
        mma_bf(s[1], q[0], q[2], q[1], q[3], k[2], k[3]);
        if (mi) {
            ldsm4t(k, qk + (e >> 2) * dq + 4096 + (e & 3) * 1024 + 512);
            mma_bf(s[2], q[0], q[2], q[1], q[3], k[0], k[1]);
            mma_bf(s[3], q[0], q[2], q[1], q[3], k[2], k[3]);
        }
    }
#pragma unroll
    for (int q = 0; q < 4; q++) s[4][q] += s[5][q];
    const float sl = iqk * (0.08838834764831845f * 1.4426950408889634f);
    float mx[2] = {-3.0e38f, -3.0e38f};
#pragma unroll
    for (int i = 0; i < 5; i++)
#pragma unroll
        for (int q = 0; q < 4; q++) {
            const bool ok = i == 4 || (i * 8 + 2 * t + (q & 1)) <= (mi * 16 + g + (q >> 1) * 8);
            s[i][q] = ok ? s[i][q] * sl : -1.0e9f * 1.4426950408889634f;
            mx[q >> 1] = fmaxf(mx[q >> 1], s[i][q]);
        }
    float sum[2] = {0.f, 0.f};
#pragma unroll
    for (int r = 0; r < 2; r++) {
        mx[r] = fmaxf(mx[r], __shfl_xor_sync(~0u, mx[r], 1));
        mx[r] = fmaxf(mx[r], __shfl_xor_sync(~0u, mx[r], 2));
    }
#pragma unroll
    for (int i = 0; i < 5; i++)
#pragma unroll
        for (int q = 0; q < 4; q++) { s[i][q] = ex2(s[i][q] - mx[q >> 1]); sum[q >> 1] += s[i][q]; }
#pragma unroll
    for (int r = 0; r < 2; r++) {
        sum[r] += __shfl_xor_sync(~0u, sum[r], 1);
        sum[r] += __shfl_xor_sync(~0u, sum[r], 2);
        sum[r] = iv * rcp(sum[r]);
    }
    uint32_t pp[5][2];
#pragma unroll
    for (int i = 0; i < 5; i++) { pp[i][0] = pack_bf(s[i][0] * sum[0], s[i][1] * sum[0]); pp[i][1] = pack_bf(s[i][2] * sum[1], s[i][3] * sum[1]); }
    uint32_t* o = (uint32_t*)g_O + (((size_t)(seg >> 1) * 512 + h * 16) * 8 + (seg & 1) * 4 + mi * 2) * 32 + lane;
#pragma unroll(UNR == 8 ? NE : 1)
    for (int u = 0; u < NE; u++) {
        const int e = e0 + u;
        float o0[4] = {0.f, 0.f, 0.f, 0.f}, o1[4] = {0.f, 0.f, 0.f, 0.f};
        uint32_t v[4];
        lds64(v, vm + e * 256);
        mma_bf8(o0, pp[4][0], pp[4][1], v[0]);
        mma_bf8(o1, pp[4][0], pp[4][1], v[1]);
        ldsm4(v, vt + e * 1024);
        mma_bf(o0, pp[0][0], pp[0][1], pp[1][0], pp[1][1], v[0], v[2]);
        mma_bf(o1, pp[0][0], pp[0][1], pp[1][0], pp[1][1], v[1], v[3]);
        ldsm4(v, vt + e * 1024 + 512);
        mma_bf(o0, pp[2][0], pp[2][1], pp[3][0], pp[3][1], v[0], v[2]);
        mma_bf(o1, pp[2][0], pp[2][1], pp[3][0], pp[3][1], v[1], v[3]);
        o[(2 * e) * 256] = pack_bf(o0[0], o0[1]); o[(2 * e) * 256 + 32] = pack_bf(o0[2], o0[3]);
        o[(2 * e + 1) * 256] = pack_bf(o1[0], o1[1]); o[(2 * e + 1) * 256 + 32] = pack_bf(o1[2], o1[3]);
    }
}

__device__ __forceinline__
void attend_last(const uint32_t sb, const int layer) {
    const int tid = read_tid(), ln = tid & 31, w = tid >> 5;
    int h;
    asm volatile("mov.u32 %0,%%clusterid.x;" : "=r"(h));
    uint32_t inv[2];
    lds64(inv, sb + O_SCL + 16);
    mbar_wait(sb + B_S, (NSEG - 1) & 1);
    mbar_wait(sb + B_VX + 8, 0);
    if (layer == TLL) TL(54);
    if (w == 0 && ln < 2)
        asm volatile("mbarrier.arrive.relaxed.cluster.shared::cluster.b64 _,[%0];" ::"r"(mapa(sb + B_STG + 8, ln)) : "memory");
    tok_attention<2, AUNR>(sb + O_STG - 16384 + ln * 16, 16384, sb + O_LAST + ln * 16, 2048, sb + O_STG + 8192 - 16384 + ln * 16, sb + O_VM + 2048 + ln * 8,
                     (w >> 1) * 2, w & 1, ln, NSEG - 1, h, __uint_as_float(inv[0]), __uint_as_float(inv[1]));
    if (layer == TLL) TL(55);
    __syncwarp();
    if (ln == 0) red_release(g_flag + F_O + layer * 32 + 31);
    if (layer == TLL) TL(43);
}

template <int layer> __device__ __forceinline__ void chain_mma(const uint32_t sb, const int c, const int h, const uint32_t zero, const bf16* __restrict__ Wq,
                                          const bf16* __restrict__ Wk, const bf16* __restrict__ Wv, const bf16* __restrict__ Wo,
                                          const bf16* res, bf16* out) {
    int tid = read_tid(), lane = tid & 31;
    const int w = __shfl_sync(~0u, tid >> 5, 0), wg = w >> 2;
    [[maybe_unused]] const int cta = h * 3 + c;
    uint32_t A0[20][4], A1[20][4];
    const int t0 = (w & 3) + wg * 4, t1 = t0 ^ 4;
    float sl;
    {
        const int tl = tid & 127, r = tl >> 3, ch = tl & 7;
        const size_t so = (size_t)(wg * 320 + r) * 4096 + h * 128 + ch * 8;
        const bf16 *wa = (c == 2 ? Wv : Wq + c * 64) + so, *wb = (c == 2 ? Wv + 64 : Wk + c * 64) + so;
        const uint32_t ring = sb + wg * 4096;
        const uint32_t dst = ring + r * 128 + ((ch ^ r) & 7) * 16;
        const uint32_t src = ring + ((lane & 7) + (lane >> 4) * 8) * 128 + ((((w & 3) * 2 + ((lane >> 3) & 1)) ^ lane) & 7) * 16;
        const int q4 = lane & 3, gr = (c * 2 + ((w >> 1) & 1)) * 56 + (q4 == 3 ? 24 : (w & 1) * 32 + q4 * 8);
        const bf16* wo_ = Wo + (size_t)(h * 128 + (lane >> 2)) * 640 + wg * 320 + min(gr, 312);
        const uint32_t wdst = sb + O_WO + w * 8192 + (lane >> 2) * 64 + ((q4 ^ (lane >> 3)) & 3) * 16;
        auto issue = [&](int i) {
            if (i < 20) {
                const uint32_t d = dst + (i < 19 ? i * 8192 : O_LAST);
                cp_async16(d, wa + (size_t)i * 65536); cp_async16(d + 2048, wb + (size_t)i * 65536);
                if (i < 16) cp_async16(wdst + i * 512, wo_ + i * 5120, gr < 320 ? 16 : 0);
            }
            cp_commit();
        };
#pragma unroll 1
        for (int i = 0; i < WDEPTH; i++) issue(i);
        asm volatile("barrier.cluster.arrive.relaxed.aligned;" ::: "memory");
        float fa, fb;
        if (layer == 0) {
            uint32_t ma = 0, mb = 0;
#pragma unroll 1
            for (int i = 0; i < 20; i++) {
                issue(i + WDEPTH);
                cp_wait<WDEPTH>();
                const uint32_t d = dst + (i < 19 ? i * 8192 : O_LAST);
                uint32_t u[8];
                lds128(u, d); lds128(u + 4, d + 2048);
                ma = babsmax(babsmax(ma, babsmax(u[0], u[1])), babsmax(u[2], u[3])); mb = babsmax(babsmax(mb, babsmax(u[4], u[5])), babsmax(u[6], u[7]));
            }
            ma = __reduce_max_sync(~0u, max(ma & 0x7fffu, (ma >> 16) & 0x7fffu)); mb = __reduce_max_sync(~0u, max(mb & 0x7fffu, (mb >> 16) & 0x7fffu));
            asm volatile("barrier.cluster.wait.aligned;" ::: "memory");
            if (lane < 3)
                asm volatile("st.async.shared::cluster.mbarrier::complete_tx::bytes.v2.b32 [%0],{%1,%2},[%3];"
                             ::"r"(mapa(sb + O_WMX + (c * 8 + w) * 8, lane)), "r"(ma), "r"(mb), "r"(mapa(sb + B_W, lane)) : "memory");
            __syncwarp();
            {
                uint32_t off[4];
                float cs[4] = {0.f, 0.f, 0.f, 0.f};
#pragma unroll
                for (int q = 0; q < 4; q++) {
                    const int g_ = (c * 2 + ((w >> 1) & 1)) * 56 + (q == 3 ? 24 : (w & 1) * 32 + q * 8), col = wg * 320 + g_, nb = col / 80;
                    off[q] = g_ < 320 && !(q == 3 && (w & 1)) ? ((nb * 512 + h * 16) * 10 + (col - nb * 80) / 8) * 32 + lane : ~0u;
                }
                const uint32_t ta = sb + O_WO + w * 8192 + (lane & 7) * 64 + (((lane >> 3) ^ (lane >> 1)) & 3) * 16;
#pragma unroll 2
                for (int i = 0; i < 16; i++) {
                    uint32_t r[4];
                    ldsm4t(r, ta + i * 512);
#pragma unroll
                    for (int q = 0; q < 4; q++) {
                        if (off[q] != ~0u) ((uint32_t*)g_wot)[off[q] + i * 320] = r[q];
                        cs[q] += fabsf(bf_lo(r[q])) + fabsf(bf_hi(r[q]));
                    }
                }
                float cm = 0.f;
#pragma unroll
                for (int q = 0; q < 4; q++) {
                    cs[q] += __shfl_xor_sync(~0u, cs[q], 1); cs[q] += __shfl_xor_sync(~0u, cs[q], 2);
                    cm = fmaxf(cm, cs[q]);
                }
                const uint32_t n1 = __reduce_max_sync(~0u, __float_as_uint(cm));
                if (lane == 0) g_co[h * 32 + c * 8 + w] = __uint_as_float(n1);
            }
            mbar_wait(sb + B_W, 0);
            uint32_t v[2];
            lds64(v, sb + O_WMX + (lane < 24 ? lane : 0) * 8);
            const bool mine = (lane >> 3) < 3 && ((lane >> 4) == 1) == (c == 2);
            ma = __reduce_max_sync(~0u, mine ? v[0] : 0u); mb = __reduce_max_sync(~0u, mine ? v[1] : 0u);
            if (c == 2) ma = mb = max(ma, mb);
            fa = __uint_as_float(ma << 16); fb = __uint_as_float(mb << 16);
            if (tid == 0) {
                if (c != 1) g_wmx[h * 3 + c] = fa;
                if (c == 0) g_wmx[h * 3 + 1] = fb;
            }
        } else {
            fa = __ldcg(g_wmx + h * 3 + (c == 2 ? 2 : 0)); fb = __ldcg(g_wmx + h * 3 + (c == 2 ? 2 : 1));
            asm volatile("barrier.cluster.wait.aligned;" ::: "memory");
        }
        if (layer == TLL) TL(49);
        float ia, ib;
        const float sa = pow2_scale(fa, 6, &ia), sc_b = pow2_scale(fb, 6, &ib);
        sl = __uint_as_float(uni(__float_as_uint(ia * ib * (0.08838834764831845f * 1.4426950408889634f))));
        const uint32_t pa = pack_bf(sa, sa), pb = pack_bf(sc_b, sc_b);
        const int ahead = layer == 0 ? 20 : WDEPTH;
        auto convert = [&](int lo) {
#pragma unroll 1
            for (int i = lo; i < lo + 10; i++) {
                issue(i + ahead);
                cp_wait<WDEPTH>();
                const uint32_t d = dst + (i < 19 ? i * 8192 : O_LAST);
                uint32_t u[8];
                lds128(u, d); lds128(u + 4, d + 2048);
#pragma unroll
                for (int q = 0; q < 8; q++)
                    asm("{.reg .b32 m,l,u; mul.rn.bf16x2 m,%0,%1; shl.b32 l,m,16; and.b32 u,m,0xffff0000; cvt.rn.f16x2.f32 %0,u,l;}" : "+r"(u[q]) : "r"(q < 4 ? pa : pb));
                sts128(d, u[0], u[1], u[2], u[3]); sts128(d + 2048, u[4], u[5], u[6], u[7]);
            }
            bar_sync(6 + wg, 128);
        };
        const uint32_t s0 = src + wg * 2048, s1 = src + 2048 - wg * 2048;
        convert(0);
#pragma unroll
        for (int i = 0; i < 10; i++) { ldsm4t(A0[i], s0 + i * 8192); ldsm4t(A1[i], s1 + i * 8192); }
        if (layer == TLL) TL(50);
        convert(10);
#pragma unroll
        for (int i = 10; i < 20; i++) { ldsm4t(A0[i], s0 + (i < 19 ? i * 8192 : O_LAST)); ldsm4t(A1[i], s1 + (i < 19 ? i * 8192 : O_LAST)); }
        if (layer == TLL) TL(53);
        bar_arrive(9, 288);
        bar_sync(4, 288);
        asm volatile("barrier.cluster.arrive.relaxed.aligned;" ::: "memory");
    }
    const uint32_t idn = (lane >> 3) == (lane & 3) ? ((lane & 4) ? 0x3c000000u : 0x3c00u) : 0u;
    float invM = g_invM0;
    char* redp = red_base() + (size_t)layer * 32 * 32768 + w * 2048 + (lane >> 4) * 1024 + ((lane >> 3) & 1) * 256 + (lane & 7) * 16;
    const uint32_t ro2 = uni((w >> 1) * 4096 + 128), rown = uni(c == 2 ? ro2 : c * 16384);
    const uint32_t L16 = lane * 16, L8 = lane * 8, L4 = lane * 4;
    const uint32_t xch0 = uni(sb + O_XCH + t0 * 1024), xch1 = uni(sb + O_XCH + t1 * 1024);
    const uint32_t qo0 = uni(sb + O_QKP + (w & 3) * 1024 + (wg ? 768 : 0)), qp0 = uni(qo0 + (wg ? 128 : 256));
    const uint32_t qo1 = uni(sb + O_QKP + (w & 3) * 1024 + (wg ? 128 : 512)), qp1 = uni(qo1 + (wg ? 256 : 128));
    const uint32_t vo1 = uni(qo1 + (wg ? -128 : 256)), vp1 = uni(qp1 + (wg ? -128 : 256));
    const uint32_t msr = uni(sb + O_MS + wg * 5376);
    const uint32_t msw = uni(msr + ((w >> 1) & 1) * 896 + (w & 1) * 512), msh = uni(msr + ((w >> 1) & 1) * 896 + 384 + (w & 1) * 2);
    const uint32_t sco = uni(sb + O_SC + c * 768 + (w & 3) * 256);
    const uint32_t woa = sb + O_WO + w * 8192 + (lane >> 4) * 512 + (lane & 7) * 64 + (((lane >> 3) ^ (lane >> 1)) & 1) * 16 + ((lane >> 2) & 1) * 32;
    const uint32_t w512 = uni(sb + w * 512), w128 = uni(sb + w * 128);
    const uint32_t pd0 = uni(mapa(sb, c == 2 ? 0 : 2) - sb), pd1 = uni(mapa(sb, c == 1 ? 0 : 1) - sb);
    const bool scw = c < 2 && w >= 4 && w <= 6;
    uint32_t sn = uni(sb + O_STG + (c == 2 ? 8192 : 0) + t1 * 1024);
    uint32_t ka = uni(sb + (w == 6 ? O_QKP + 512 : O_STG + 4096 + (w & 1) * 512));
    uint32_t vs = uni(sb + O_VM + t1 * 256);
    uint32_t va = uni(sb + O_STG + 8192 + w * 2048), vr = uni(sb + O_VM + w * 512);
    const uint32_t sn2 = uni(2 * sn - 16384), ka2 = uni(2 * ka - (w == 6 ? 0 : 16384)), vs2 = uni(2 * vs + 2048), va2 = uni(2 * va - 16384),
                   vr2 = uni(2 * vr + 2048);
    uint32_t xd = uni((uint32_t)mkdesc(sb + O_XS + wg * 20480, 512, 128, 0));
    const uint32_t xd2 = uni(2 * xd + 2560);

    uint32_t wp[2 * NPERM + 1][4];
    sfor<NPERM>([&](auto I) { constexpr int i = I; ldsm4t(wp[2 * i], woa + i * 1024); ldsm4t(wp[2 * i + 1], (woa ^ 32) + i * 1024); });
    auto wo_fetch = [&](uint32_t (&wo)[16][4], auto I) {
        constexpr int i = I;
        if constexpr (i < NPERM) {
#pragma unroll
            for (int q = 0; q < 4; q++) { wo[i][q] = wp[2 * i][q]; wo[8 + i][q] = wp[2 * i + 1][q]; }
        } else { ldsm4t(wo[i], woa + i * 1024); ldsm4t(wo[8 + i], (woa ^ 32) + i * 1024); }
    };
    if (layer == TLL) TL(32);
    float b0[16], b1[16];
    mbar_wait(sb + B_XF, 0);
    if (layer == TLL) TL(33);
    tok_issue<0, NTB>(A0, A1, b0, b1, xd, zero);
    tok_give(b0, L16, xch0);
    tok_issue<NTB, 40>(A0, A1, b0, b1, xd, zero);
    bar_sync(4, 256);
    wg_wait<0>();
    {
        uint32_t e[2][4];
        lds128_u<0>(e[0], L16, xch1); lds128_u<512>(e[1], L16, xch1);
        tok_finish(b1, e, L16, sn, idn);
    }
    sn = sn2 - sn; xd = xd2 - xd;
    bar_sync(5, 288);
    asm volatile("barrier.cluster.wait.aligned;" ::: "memory");
    if (layer == TLL) TL(34);
    mbar_wait(sb + B_XF + 8, 0);
    if (layer == TLL) TL(35);
    tok_issue<0, NTA>(A0, A1, b0, b1, xd, zero);
    uint32_t tr = clock32() - RDELAY;

#pragma unroll 1
    for (int st = 0;; st++) {
        uint4 mv[3];
        asm volatile("{.reg .pred p; .reg .b32 t;\n"
                     "mov.b32 %0,0; mov.b32 %1,0; mov.b32 %2,0; mov.b32 %3,0; mov.b32 %4,0; mov.b32 %5,0; mov.b32 %6,0; mov.b32 %7,0;\n"
                     "mov.b32 %8,0; mov.b32 %9,0; mov.b32 %10,0; mov.b32 %11,0;\n"
                     "T_LOOP: mov.u32 t,%%clock; sub.u32 t,t,%14; setp.ge.u32 p,t,%15;\n"
                     "@p ld.relaxed.gpu.global.v4.u32 {%0,%1,%2,%3},[%12]; @p ld.relaxed.gpu.global.v4.u32 {%4,%5,%6,%7},[%12+16384];\n"
                     "@p ld.relaxed.gpu.global.v4.u32 {%8,%9,%10,%11},[%13];\n"
                     "@!p bra T_LOOP;}"
                     : "=r"(mv[0].x), "=r"(mv[0].y), "=r"(mv[0].z), "=r"(mv[0].w), "=r"(mv[1].x), "=r"(mv[1].y), "=r"(mv[1].z), "=r"(mv[1].w),
                       "=r"(mv[2].x), "=r"(mv[2].y), "=r"(mv[2].z), "=r"(mv[2].w)
                     : "l"(redp), "l"(redp + ro2), "r"(tr), "n"(RDELAY) : "memory");
        STAMP(10);
        tok_issue<NTA, NTB>(A0, A1, b0, b1, xd, zero);
        tok_give(b0, L16, xch0);
        tok_issue<NTB, 40>(A0, A1, b0, b1, xd, zero);
        xd = xd2 - xd;
        STAMP(9);
        if (zero >> 30) break;
        asm volatile("{.reg .pred p; .reg .b32 a,h,t,n; .reg .b16 l,u; .reg .b64 q;\n"
                     "add.u32 a,%12,%13; add.u32 h,%12,%14; mov.u32 n,0;\n"
                     "M_LOOP:\n .pragma \"nounroll\";\n"
                     "st.shared.b32 [a],%0; st.shared.b32 [a+128],%1; st.shared.b32 [a+256],%2; mov.b32 {l,u},%3; st.shared.b16 [h],l;\n"
                     "st.shared.b32 [a+1792],%4; st.shared.b32 [a+1920],%5; st.shared.b32 [a+2048],%6; mov.b32 {l,u},%7; st.shared.b16 [h+1792],l;\n"
                     "st.shared.b32 [a+3584],%8; st.shared.b32 [a+3712],%9; st.shared.b32 [a+3840],%10; mov.b32 {l,u},%11; st.shared.b16 [h+3584],l;\n"
                     "lop3.b32 t,%3,%7,0x50000000,0x7e; lop3.b32 t,t,%11,0x50000000,0xf6; setp.gt.u32 p,t,0xffff;\n"
                     "vote.sync.any.pred p,p,-1; add.u32 n,n,1; setp.lt.and.u32 p,n,%17,p; @!p bra M_DONE;\n"
                     "ld.relaxed.gpu.global.v4.u32 {%0,%1,%2,%3},[%15]; ld.relaxed.gpu.global.v4.u32 {%4,%5,%6,%7},[%15+16384];\n"
                     "cvt.u64.u32 q,%16; add.u64 q,q,%15; ld.relaxed.gpu.global.v4.u32 {%8,%9,%10,%11},[q];\n"
                     "bra M_LOOP;\n"
                     "M_DONE:}"
                     : "+r"(mv[0].x), "+r"(mv[0].y), "+r"(mv[0].z), "+r"(mv[0].w), "+r"(mv[1].x), "+r"(mv[1].y), "+r"(mv[1].z), "+r"(mv[1].w),
                       "+r"(mv[2].x), "+r"(mv[2].y), "+r"(mv[2].z), "+r"(mv[2].w)
                     : "r"(L4), "r"(msw), "r"(msh), "l"(redp), "r"(ro2), "n"(SPIN_LIM) : "memory");
        bar_sync(3, 256);
        STAMP(0);
        uint32_t e[2][4];
        float f1[4];
        {
            uint32_t b[10][4];
            float acc[4][4];
#pragma unroll
            for (int i = 0; i < 4; i++) acc[i][0] = acc[i][1] = acc[i][2] = acc[i][3] = 0.f;
            auto ld = [&](auto I) { constexpr int i = I; ldsm4t_u<i * 512>(b[i], L16, msr); };
            auto mm = [&](auto I) {
                constexpr int i = I;
                mma_f16(acc[0], A0[2 * i], b[i][0], b[i][1]); mma_f16(acc[2], A1[2 * i], b[i][0], b[i][1]);
                mma_f16(acc[1], A0[2 * i + 1], b[i][2], b[i][3]); mma_f16(acc[3], A1[2 * i + 1], b[i][2], b[i][3]);
            };
            ld(IC<0>()); ld(IC<1>()); ld(IC<2>()); ld(IC<3>());
            sts32_u<O_MX>(L4, w128,
                          habsmax(habsmax(habsmax(habsmax(mv[0].x, mv[0].y), habsmax(mv[0].z, mv[1].x)), habsmax(habsmax(mv[1].y, mv[1].z), mv[2].x)),
                                  habsmax(habsmax(mv[2].y, mv[2].z), habsmax(habsmax(mv[0].w, mv[1].w), mv[2].w) & 0xffffu)));
            wg_wait<0>();
            ld(IC<4>()); mm(IC<0>()); ld(IC<5>()); mm(IC<1>()); ld(IC<6>()); mm(IC<2>());
            ld(IC<7>()); mm(IC<3>()); ld(IC<8>()); mm(IC<4>()); ld(IC<9>()); mm(IC<5>());
            lds128_u<0>(e[0], L16, xch1); lds128_u<512>(e[1], L16, xch1);
            mm(IC<6>()); mm(IC<7>()); mm(IC<8>()); mm(IC<9>());
            const uint32_t u0 = pack_bf((acc[0][0] + acc[1][0]) * invM, (acc[0][1] + acc[1][1]) * invM);
            const uint32_t u1 = pack_bf((acc[0][2] + acc[1][2]) * invM, (acc[0][3] + acc[1][3]) * invM);
#pragma unroll
            for (int i = 0; i < 4; i++) f1[i] = (acc[2][i] + acc[3][i]) * invM;
            sts32_u<0>(L4, qo0, u0); sts32_u<0>(L4, qp0, u1); sts32_u<0>(L4, qo1, pack_bf(f1[0], f1[1])); sts32_u<0>(L4, qp1, pack_bf(f1[2], f1[3]));
        }
        STAMP(1);
        bar_sync(1, 320);
        if (__builtin_expect(scw, 1)) {
            float a[4][4];
#pragma unroll
            for (int i = 0; i < 4; i++) a[i][0] = a[i][1] = a[i][2] = a[i][3] = 0.f;
            uint32_t q[4][4], k[4][4];
            sfor<4>([&](auto I) {
                constexpr int i = I;
                ldsm4t_u<O_QKP + i * 1024>(q[i], L16, sb); ldsm4t_u<i * 1024>(k[i], L16, ka);
            });
#pragma unroll
            for (int i = 0; i < 4; i++) {
                mma_bf(a[i & 1], q[i][0], q[i][1], q[i][2], q[i][3], k[i][0], k[i][1]);
                mma_bf(a[2 + (i & 1)], q[i][0], q[i][1], q[i][2], q[i][3], k[i][2], k[i][3]);
            }
            const float mk = w == 6 ? 1.f : 0.f;
            const float x0 = (a[0][0] + a[0][2]) + (a[1][0] + a[1][2]), x1 = (a[0][1] + a[0][3]) + (a[1][1] + a[1][3]);
            const float y0 = (a[2][0] + a[2][2]) + (a[3][0] + a[3][2]), y1 = (a[2][1] + a[2][3]) + (a[3][1] + a[3][3]);
            st_share2(L8, sco, sb + B_S, pd0, pd1, pack_bf(fmaf(y0, mk, x0) * sl, fmaf(y1, mk, x1) * sl), pack_bf(y0 * sl, y1 * sl));
        }
        if (c == 2) {
            const uint32_t x = lds32_u<0>(L4, vo1), y = lds32_u<0>(L4, vp1);
            st_share2(L8, vs, sb + B_S, pd0, pd1, pack_bf(f1[0] + bf_lo(x), f1[1] + bf_hi(x)), pack_bf(f1[2] + bf_lo(y), f1[3] + bf_hi(y)));
        }
        STAMP(3);
        if (st == NSEG - 1) break;
        tok_finish(b1, e, L16, sn, idn);
        redp += (st & 1) ? 32768 - 512 : 512;
        if (wg == 0) {
            uint32_t wo[16][4], vx[2][2][4], vm[2][2];
            ldsm4_u<0>(vx[0][0], L16, va); ldsm4_u<512>(vx[0][1], L16, va); ldsm4_u<1024>(vx[1][0], L16, va); ldsm4_u<1536>(vx[1][1], L16, va);
            sfor<NWO0>([&](auto I) { wo_fetch(wo, I); });
            mbar_wait(sb + B_S, st & 1);
            STAMP(4);
            uint32_t s[5];
            {
                uint32_t p[2][5];
                sfor<2>([&](auto R) {
                    constexpr int r = R;
                    lds64_u<O_SC + r * 768>(p[r], L8, sb); lds64_u<O_SC + r * 768 + 256>(p[r] + 2, L8, sb); p[r][4] = lds32_u<O_SC + r * 768 + 512>(L8, sb);
                });
#pragma unroll
                for (int j = 0; j < 5; j++) s[j] = badd(p[0][j], p[1][j]);
            }
            lds64_u<0>(vm[0], L8, vr); lds64_u<256>(vm[1], L8, vr);
            uint32_t mm = bmax(bmax(bmax(s[0], s[1]), bmax(s[2], s[3])), s[4]);
            mm = bmax(bmax(mm, __shfl_xor_sync(~0u, mm, 1)), bmax(__shfl_xor_sync(~0u, mm, 2), __shfl_xor_sync(~0u, mm, 3)));
            const float m = fmaxf(bf_lo(mm), bf_hi(mm));
            float o0[4] = {0.f, 0.f, 0.f, 0.f}, o1[4] = {0.f, 0.f, 0.f, 0.f}, d[10];
#pragma unroll
            for (int j = 0; j < 5; j++) { d[2 * j] = bf_lo(s[j]) - m; d[2 * j + 1] = bf_hi(s[j]) - m; }
#pragma unroll
            for (int j = 0; j < 10; j++) d[(j + 8) % 10] = ex2(d[(j + 8) % 10]);
            float sum = ((d[8] + d[9]) + (d[0] + d[1])) + ((d[2] + d[3]) + (d[4] + d[5])) + (d[6] + d[7]);
            const uint32_t p4 = pack_bf(d[8], d[9]), p0 = pack_bf(d[0], d[1]), p1 = pack_bf(d[2], d[3]), p2 = pack_bf(d[4], d[5]), p3 = pack_bf(d[6], d[7]);
            mma_bf8(o0, vm[0][0], vm[0][1], p4);
            mma_bf8(o1, vm[1][0], vm[1][1], p4);
            mma_bf(o0, vx[0][0][0], vx[0][0][1], vx[0][0][2], vx[0][0][3], p0, p1);
            mma_bf(o1, vx[1][0][0], vx[1][0][1], vx[1][0][2], vx[1][0][3], p0, p1);
            mma_bf(o0, vx[0][1][0], vx[0][1][1], vx[0][1][2], vx[0][1][3], p2, p3);
            mma_bf(o1, vx[1][1][0], vx[1][1][1], vx[1][1][2], vx[1][1][3], p2, p3);
            sfor<NWO0B - NWO0>([&](auto I) { constexpr int i = I; wo_fetch(wo, IC<NWO0 + i>()); });
            sum += __shfl_xor_sync(~0u, sum, 1);
            sum += __shfl_xor_sync(~0u, sum, 2);
            sts32_u<O_OS>(L4, w512, pack_bf(o0[0], o0[1])); sts32_u<O_OS + 128>(L4, w512, pack_bf(o0[2], o0[3]));
            sts32_u<O_OS + 256>(L4, w512, pack_bf(o1[0], o1[1])); sts32_u<O_OS + 384>(L4, w512, pack_bf(o1[2], o1[3]));
            sts32_u<O_SUM>(lane & 28, sb, __float_as_uint(sum));
            STAMP(5);
            invM = mem_out<NWO0B>(sb, L16, L8, wo, woa, redp + rown, w & 1);
            tr = clock32();

        } else {
            uint32_t wo[16][4];
            sfor<NWO1>([&](auto I) { wo_fetch(wo, I); });
            invM = mem_out<NWO1>(sb, L16, L8, wo, woa, redp + rown, w & 1);
            tr = clock32();

        }
        STAMP(7);
        tok_issue<0, NTA>(A0, A1, b0, b1, xd, zero);
        sn = sn2 - sn; ka = ka2 - ka; vs = vs2 - vs; va = va2 - va; vr = vr2 - vr;
        STAMP(8);
    }
    if (layer == TLL) TL(40);
    if (c == 2) attend_last(sb, layer);
    bar_arrive(8, 320);
    tid = read_tid(); lane = tid & 31;
    float acc[40];
    const int nc = c == 2 ? 10 : 11;
    const int mb = 28 + (h >> 3), nj = c == 2 ? 1 : 2;
    uint32_t rv[2][2];
    const size_t go = ((size_t)(mb * 64 + (w & 3) * 16 + (lane >> 2)) * 640 + (h & 7) * 80 + (wg * 5 + c * 2) * 8 + (lane & 3) * 2) >> 1;
#pragma unroll
    for (int u = 0; u < 4; u++) rv[u >> 1][u & 1] = (u >> 1) < nj ? __ldcg((const uint32_t*)res + go + (u >> 1) * 4 + (u & 1) * 2560) : 0u;
#pragma unroll 1
    for (int k = 0; k < nc; k++) {
        mbar_wait(sb + T_FB + (k % 7) * 8, k >= 7);
        mbar_wait(sb + T_FA + (k & 3) * 8, (k >> 2) & 1);
        if (layer == TLL && k == 0) TL(41);
        const uint64_t da = mkdesc(sb + O_MS + (k & 3) * 16384 + wg * 8192, 1024, 128, 0), db = mkdesc(sb + tail_b(k) + wg * 10240, 1280, 128, 0);
        wg_fence();
#pragma unroll
        for (int q = 0; q < 4; q++) wg_n80_ss(acc, da + q * 128, db + q * 160, k | q);
        wg_commit();
        if (k > 0) {
            wg_wait<1>();
            if (lane == 0) { mbar_arrive(sb + T_EA + ((k - 1) & 3) * 8); if (k <= 4) mbar_arrive(sb + T_EB + (k - 1) * 8); }
        }
    }
    if (layer == TLL) TL(52);
    wg_wait<0>();
    asm volatile("barrier.cluster.arrive.relaxed.aligned; barrier.cluster.wait.aligned;" ::: "memory");
    const uint32_t ra = sb + O_XS + tid * 16, rb = sb + O_MS + tid * 16;
#pragma unroll
    for (int j = 0; j < 5; j++) {
        const float* q = acc + 4 * j;
        sts128(rb + j * 4096, __float_as_uint(wg ? q[0] : q[20]), __float_as_uint(wg ? q[1] : q[21]), __float_as_uint(wg ? q[2] : q[22]), __float_as_uint(wg ? q[3] : q[23]));
    }
    bar_sync(4, 256);
#pragma unroll
    for (int j = 0; j < 5; j++) {
        const float* q = acc + 4 * j;
        uint32_t p[4];
        lds128(p, sb + O_MS + (tid ^ 128) * 16 + j * 4096);
        asm volatile("st.async.shared::cluster.mbarrier::complete_tx::bytes.v4.f32 [%0],{%1,%2,%3,%4},[%5];" ::"r"(mapa(ra + c * 8192 + (j & 1) * 4096, j >> 1)),
                     "f"((wg ? q[20] : q[0]) + __uint_as_float(p[0])), "f"((wg ? q[21] : q[1]) + __uint_as_float(p[1])),
                     "f"((wg ? q[22] : q[2]) + __uint_as_float(p[2])), "f"((wg ? q[23] : q[3]) + __uint_as_float(p[3])), "r"(mapa(sb + T_RED, j >> 1)) : "memory");
    }
    mbar_wait(sb + T_RED, 0);
#pragma unroll 1
    for (int u = 0; u < nj; u++) {
        uint32_t p[3][4];
#pragma unroll
        for (int q = 0; q < 3; q++) lds128(p[q], ra + q * 8192 + u * 4096);
        float y[4];
#pragma unroll
        for (int i = 0; i < 4; i++) y[i] = __uint_as_float(p[0][i]) + __uint_as_float(p[1][i]) + __uint_as_float(p[2][i]);
        ((uint32_t*)out)[go + u * 4] = bfma(pack_bf(y[0], y[1]), 0x3f803f80u, u ? rv[1][0] : rv[0][0]);
        ((uint32_t*)out)[go + u * 4 + 2560] = bfma(pack_bf(y[2], y[3]), 0x3f803f80u, u ? rv[1][1] : rv[0][1]);
    }
    __syncwarp();
    if (layer == 0 && lane == 0) red_release(g_flag + F_R + mb);
    TL(layer == 0 ? 15 : 29);
    asm volatile("barrier.cluster.arrive.relaxed.aligned; barrier.cluster.wait.aligned;" ::: "memory");
}

__device__ __forceinline__ void tail_load_b(const uint32_t sb, const int h, const int c, const int k) {
    mbar_expect(sb + T_FB + (k % 7) * 8, 20480);
    bulk_g2s(sb + tail_b(k), (const char*)g_wot + (size_t)((h & 7) * GNC + c * 11 + k) * 20480, 20480, sb + T_FB + (k % 7) * 8);
}
template <int layer> __device__ __forceinline__ void chain_aux(const uint32_t sb, const int c, const int h, const int nact) {
    const int tid = read_tid(), w = __shfl_sync(~0u, tid >> 5, 0), lane = tid & 31;
    if (w == 8) {
        mbar_init(sb + O_BAR + lane * 8, lane == 2 ? (c == 2 ? 9 : 4) : (lane >= 16 && lane < 20) || (lane >= 27 && lane < 31) ? 8 : 1);
        asm volatile("fence.mbarrier_init.release.cluster;" ::: "memory");
        fence_async_smem();
        __syncwarp();
    }
    {
        uint4* z = (uint4*)red_base() + layer * 65536;
#pragma unroll 1
        for (int i = blockIdx.x * 128 + tid - 256; i < 65536; i += 96 * 128)
            if (i >= 2048 || (i & 32)) z[i] = make_uint4(0, 0, 0, 0);
    }
    if (w == 8 && lane == 0) {
        mbar_expect(sb + B_S, s_tx(c));
        mbar_expect(sb + B_W, 192);
        mbar_expect(sb + T_RED, (c == 2 ? 1 : 2) * 3 * 4096);
        if (layer == 1) prefetch_l2(red_base() + 32 * 32768 + blockIdx.x * 1024, 1024);
        if (layer == 0) wait_flag<400>(g_ready, NSETUP);
    }
    __syncwarp();
    cluster_sync_full();
    asm volatile("barrier.cluster.arrive.relaxed.aligned;" ::: "memory");
    pdl_wait();
    if (w == 11 && lane == 0) red_relaxed(g_flag + F_X + layer * 128 + 65);
    Flag* flag = g_flag + layer * NSEG * 32 + h;
    const Flag* xflag = g_flag + F_X + layer * 128;
    char* const it0 = g_item + (size_t)h * 32768;
    if (w == 8) {
#pragma unroll 1
        for (int n = 0; n < 3; n++) {
            wait_flag<100>(xflag + (n >> 1), 4);
            fence_async_glb();
            if (n == 0) { bar_sync(4, 288); fence_async_smem(); }
            if (lane == 0 && n < 2) {
                mbar_expect(sb + B_XF + n * 8, 40960);
                bulk_g2s(sb + O_XS + n * 40960, (const char*)g_xn + n * 40960, 40960, sb + B_XF + n * 8);
            }
            __syncwarp();
        }
#pragma unroll 1
        for (int n = 0; n < NSEG - 1; n++) {
            const int np = n & 1;
            if (n == 0) { wait_flag<100>(g_flag + F_W + layer * 128, 96); bar_sync(5, 288); } else bar_sync(2, 352);
            if (n == 1) TL(12 + layer * 14);
            if (n == 63) TL(13 + layer * 14);
            if (lane == 0) {
                const uint32_t vs = sb + O_STG + 8192 - np * 16384, vb = sb + B_VX + np * 8;
                if (c == 2) {
                    if (n > 0) __nanosleep(VXN);
                    fence_async_smem();
                    bulk_s2s(mapa(vs, 0), vs, 8192, mapa(vb, 0));
                    bulk_s2s(mapa(vs, 1), vs, 8192, mapa(vb, 1));
                } else mbar_expect(vb, 8192);
                if (n == 0) { mbar_expect(sb + B_XF, 40960); bulk_g2s(sb + O_XS, (const char*)g_xn + 2 * 40960, 40960, sb + B_XF); }
                if (n == h * 3 + c && !np && n + 6 < NSEG) prefetch_l2(red_base() + (size_t)(layer * 32 + (n >> 1) + 3) * 32768, 32768);
            }
            __syncwarp();
        }
        {
            bar_sync(2, 352);
            TL(13 + layer * 14);
            if (lane == 0) {
                if (c == 2) mbar_expect(sb + B_VX + 8, 2 * 8192 + 2 * 2048);
                else {
                    fence_async_smem();
                    bulk_s2s(mapa(sb + O_STG - (c == 0 ? 16384 : 0), 2), sb + O_STG - 16384, 8192, mapa(sb + B_VX + 8, 2));
                }
            }
            __syncwarp();
        }
    } else if (w == 11) {
        float cvo;
        {
            auto max8 = [&](const float* p) {
                const float4 u = ((const float4*)p)[0], v = ((const float4*)p)[1];
                return fmaxf(fmaxf(fmaxf(u.x, u.y), fmaxf(u.z, u.w)), fmaxf(fmaxf(v.x, v.y), fmaxf(v.z, v.w)));
            };
            wait_flag<300>(g_flag + F_W + layer * 128, 96);
            const float* pc = g_co + lane * 32;
            float a = 640.f * __ldcg(g_wmx + lane * 3 + 2), o = fmaxf(fmaxf(max8(pc), max8(pc + 8)), max8(pc + 16));
#pragma unroll 1
            for (int s = 16; s; s >>= 1) { a = fmaxf(a, __shfl_xor_sync(~0u, a, s)); o += __shfl_xor_sync(~0u, o, s); }
            cvo = a * o * 2.f;
        }
        float invM = g_invM0;
        float iq, ik, iv;
        weight_scale(h, 0, &iq); weight_scale(h, 1, &ik); weight_scale(h, 2, &iv);
        if (lane == 0) sts64(sb + O_SCL + 16, __float_as_uint(iq * ik), __float_as_uint(iv));
        const uint32_t L16 = sb + lane * 16 + O_MX;
#pragma unroll 1
        for (int st = 0; st < NSEG; st++) {
            bar_sync(1, 320);
            if (st == NSEG - 1) break;
            if (lane == 0) mbar_arrive(sb + B_STG + (st & 1) * 8);
            uint32_t u[2][4];
            lds128(u[0], L16); lds128(u[1], L16 + 512);
            uint32_t mx = habsmax(habsmax(habsmax(u[0][0], u[0][1]), habsmax(u[0][2], u[0][3])), habsmax(habsmax(u[1][0], u[1][1]), habsmax(u[1][2], u[1][3])));
            mx = __reduce_max_sync(~0u, max(mx & 0x7fffu, (mx >> 16) & 0x7fffu));
            const float bound = fmaxf(__half2float(__ushort_as_half((unsigned short)mx)) * invM, 25.5f) * cvo;
            const float sc = pow2_scale(bound, 15, &invM);
            sts64(sb + O_SCL, __float_as_uint(sc * iv), __float_as_uint(invM));
            bar_arrive(2, 352);
        }
    } else if (w == 10) {
        bar_sync(9, 288);
        if (lane == 0) red_release(g_flag + F_W + layer * 128);
        if (lane == 0) {
#pragma unroll 1
            for (int n = 0; n < NSEG - 1; n++) {
                mbar_sleep(sb + B_STG + (n & 1) * 8, (n >> 1) & 1);
                __nanosleep(EN);
                fence_async_smem();
                const uint32_t stg = sb + O_STG - (n & 1) * 16384;
                char* it = it0 + (size_t)(n % RING) * 32 * 32768;
                bulk_s2g(it + c * 8192, stg + (c == 2 ? 8192 : 0), 8192);
                bulk_commit();
                if (n + 1 >= RING && n + 1 < NSEG) wait_flag(flag - (RING - 1) * 32, 7);
                bulk_wait0();
                mbar_arrive(sb + B_FREE + (n & 1) * 8);
                fence_async_glb();
                red_relaxed(flag);
                flag += 32;
            }
        }
    } else {
        bool allx = false;
#pragma unroll 1
        for (int st = 0; st < NSEG - 1; st++) {
            const int par = st & 1;
            char* const it = it0 + (size_t)(st % RING) * 32 * 32768;
            if (lane == 0 && !allx && st + 3 < NSEG) {
                allx = ld_acquire(xflag + 64) >= nact;
                if (!allx) wait_flag(st + 4 < NSEG ? xflag + ((st + 3) >> 1) : xflag + 64, st + 4 < NSEG ? 4 : nact);
                fence_async_glb();
            }
            __syncwarp();
            if (c < 2) mbar_sleep(sb + B_VX + par * 8, (st >> 1) & 1);
            if (st < NSEG - 2) mbar_sleep(sb + B_XF + par * 8, ((st >> 1) + 1) & 1);
            bar_sync(1, 320);
            if (lane == 0 && st + 3 < NSEG) {
                mbar_expect(sb + B_XF + (par ^ 1) * 8, 40960);
                bulk_g2s_last(sb + O_XS + (par ^ 1) * 40960, (const char*)g_xn + (size_t)(st + 3) * 40960, 40960, sb + B_XF + (par ^ 1) * 8);
            } else if (lane == 0) {
                tail_load_b(sb, h, c, (par ^ 1) * 2); tail_load_b(sb, h, c, (par ^ 1) * 2 + 1);
            }
            __syncwarp();
            if (lane == 0 && c < 2) {
                fence_async_smem();
#pragma unroll 1
                for (int i = 0; i < 4; i++) bulk_s2g(it + 24576 + (c * 4 + i) * 512, sb + O_QKP + i * 1024 + 512, 512);
                bulk_commit();
                asm volatile("cp.async.bulk.wait_group.read 0;" ::: "memory");
            }
            __syncwarp();
            bar_arrive(2, 352);
            mbar_sleep(sb + B_S, par);
            __syncwarp();
            if (lane == 0) {
                mbar_expect(sb + B_S, s_tx(c));
                if (c == 2) { fence_async_smem(); bulk_s2g(it + 28672, sb + O_VM + par * 2048, 2048); bulk_commit(); }
            }
            __syncwarp();
            if (lane == 0) { bulk_wait0(); fence_async_glb(); red_relaxed(flag); }
            __syncwarp();
            mbar_sleep(sb + B_FREE + par * 8, (st >> 1) & 1);
            flag += 32;
        }
        {
            bar_sync(1, 320);
            if (lane == 0 && c < 2) {
                fence_async_smem();
#pragma unroll 1
                for (int i = 0; i < 4; i++)
                    bulk_s2s(mapa(sb + O_LAST + (c * 4 + i) * 512, 2), sb + O_QKP + i * 1024 + 512, 512, mapa(sb + B_VX + 8, 2));
            }
            __syncwarp();
            bar_arrive(8, 320);
        }
    }
    __syncwarp();
    const int nc = c == 2 ? 10 : 11;
    if (w == 10) {
        bar_sync(8, 320);
        if (lane == 0) {
            if (layer == 1 && blockIdx.x == 0) g_ready[0].v = 0;
            if (c < 2) mbar_sleep(sb + B_STG + 8, 1);
            fence_async_smem();
            __nanosleep(TDELAY);
            wait_flag(xflag + 64, nact);
            wait_flag<50>(g_flag + F_O + layer * 32 + 28 + (h >> 3), (h >> 3) == 3 ? 32 + 8 * 32 : 64);
            fence_async_glb();
#pragma unroll 1
            for (int k = 0; k < nc; k++) {
                if (k >= 4) mbar_sleep(sb + T_EA + (k & 3) * 8, ((k >> 2) - 1) & 1);
                mbar_expect(sb + T_FA + (k & 3) * 8, 16384);
                bulk_g2s_last(sb + O_MS + (k & 3) * 16384, (const char*)g_O + (size_t)((28 + (h >> 3)) * GNC + c * 11 + k) * 16384, 16384, sb + T_FA + (k & 3) * 8);
            }
        }
    } else if (w == 9 && lane == 0) {
        __nanosleep(TDELAY);
#pragma unroll 1
        for (int k = 4; k < nc; k++) {
            if (k >= 7) mbar_sleep(sb + T_EB + (k - 7) * 8, 0);
            tail_load_b(sb, h, c, k);
        }
    }
    __syncwarp();
    asm volatile("barrier.cluster.wait.aligned;" ::: "memory");
    asm volatile("barrier.cluster.arrive.relaxed.aligned; barrier.cluster.wait.aligned;" ::: "memory");
    asm volatile("barrier.cluster.arrive.relaxed.aligned; barrier.cluster.wait.aligned;" ::: "memory");
}

constexpr int RI_A = 0, RI_TAB = 81920, RI_STG = RI_TAB + 82 * 768;
constexpr int RI_RES = RI_STG + 25600, RI_ST = RI_RES + 2 * 64 * 336;
constexpr int HB_A = G_BAR + 64, HB_AFREE = HB_A + 32, HB_LN = HB_A + 40, HB_FULL = HB_A + 64, HB_DONE = HB_FULL + 48, HB_FREE = HB_DONE + 48;
constexpr int HP_SMEM = HB_FREE + 48;
static_assert(G_BAR >= RI_ST + 2048, "helper shared-memory map");
#define IDL 280
#define ITEM_NS 60
#define PFW_AT 28
#define PFW_NS 150
__device__ __forceinline__ void helper_aux(const uint32_t sb, const int j, const int nh, const int na, const int nbh, const int layer, const bf16* Wq,
                                           const bf16* Wk, const bf16* Wv, const bf16* Wo) {
    const int w = threadIdx.x >> 5, lane = threadIdx.x & 31, p = w - 8;
    if (lane == 0 && j < (nh & ~3)) {
        int n = 0;
        for (int a = j >> 2; a < 32; a += nh >> 2, n++) {
            if (n == 0) continue;
            mbar_wait(sb + HB_AFREE, (n - 1) & 1);
            mbar_expect(sb + HB_A + p * 8, 20480);
            bulk_g2s_last(sb + RI_A + p * 20480, (const char*)g_YT + (size_t)a * 81920 + p * 20480, 20480, sb + HB_A + p * 8);
            if (p == 0) { mbar_wait(sb + HB_LN, (n - 1) & 1); red_release(g_flag + F_X + layer * 128 + a - (nh >> 2)); }
        }
        if (p == 0) { mbar_wait(sb + HB_LN, (n - 1) & 1); red_release(g_flag + F_X + layer * 128 + (j >> 2) + (n - 1) * (nh >> 2)); }
    }
    __syncwarp();
    if (layer == 0 && w == 8 && lane == 0) wait_flag<400>(g_flag + F_W, 96);
    __syncwarp();
    bar_sync(3, 384);
    if (p == 3 && lane == 0 && j < (nh & ~3)) red_release(g_flag + F_X + layer * 128 + 64);
    fence_async_smem();
    Flag* oflag = g_flag + F_O + layer * 32;
    if (j < na) {
        int sl = p & 1, ph = 1;
        for (int idx = j + (p & 1) * na; idx < (NSEG - 1) * 32 && p >= 2 && lane == 0; idx += 2 * na) {
            mbar_wait(sb + HB_DONE + sl * 8, ph ^ 1);
            mbar_arrive(sb + HB_FREE + sl * 8);
            red_release(oflag + (idx >> 6));
            atomicAdd(&g_flag[layer * NSEG * 32 + idx].v, 1u);
            sl += 2;
            if (sl >= 6) { sl -= 6; ph ^= 1; }
        }
        for (int idx = j + p * na; idx < (NSEG - 1) * 32 && p < 2 && lane == 0; idx += 2 * na) {
            mbar_wait(sb + HB_FREE + sl * 8, ph);
            wait_flag<ITEM_NS>(g_flag + layer * NSEG * 32 + idx, 6);
            fence_async_glb();
            if (idx < (NSEG - 2) * 32) __nanosleep(IDL);
            mbar_expect(sb + HB_FULL + sl * 8, 30720);
            bulk_g2s(sb + sl * 30720, g_item + (size_t)(idx % (RING * 32)) * 32768, 30720, sb + HB_FULL + sl * 8);
            sl += 2;
            if (sl >= 6) { sl -= 6; ph ^= 1; }
        }
    } else if (lane == 0 && p == 3) {
        if (layer == 0) {
            wait_flag<1000>(oflag + PFW_AT, 64);
            const int np = nh - na;
#pragma unroll 1
            for (int i = j - na; i < 1280; i += np) {
                const bf16* W = i < 320 ? Wq : i < 640 ? Wk : i < 960 ? Wv : Wo;
                prefetch_l2((const char*)W + (size_t)(i % 320) * 16384, 16384);
                __nanosleep(PFW_NS);
            }
#pragma unroll 1
            for (int i = j - na; i < 205; i += np) {
                const char* p_ = i < 160 ? (const char*)g_Wf + i * 16384 : i < 165 ? (const char*)g_stat + (i - 144) * 16384
                               : i < 167 ? (const char*)g_ctab + (i - 165) * 8192 : (const char*)(g_flag + NFLAG) - (i - 166) * 16384;
                prefetch_l2(p_, 16384);
                __nanosleep(PFW_NS);
            }
            if (j - na < 16) prefetch_l2(g_rtab + (j - na) * (RF_A / 4), RF_A / 4);
#pragma unroll 1
            for (int i = j - na; i < 130; i += np) { prefetch_l2((const char*)g_xb + i * 16384, 16384); __nanosleep(PFW_NS); }
        }
    } else if (lane == 0) {
        if (p == 2) wait_flag<500>(g_flag + F_X + layer * 128 + 64, nh & ~3);
        int c0 = 0;
        for (int mb = (j - na) >> 3; mb < nbh; mb += (nh - na) >> 3, c0 += GNC) {
            if (p < 2) wait_flag<300>(oflag + 2 * mb + p, 64);
            fence_async_glb();
            oproj_load(sb, p, mb, (j - na) & 7, c0, nh - na < 24 ? 0 : mb == nbh - 1 ? GPACE2 : GPACE);
        }
    }
}
__device__ __forceinline__ void helper_mma(char* sm, const int jh, const int nh, const int na, const int nbh, const int layer, const bf16* res, bf16* x,
                                           bf16* out) {
    const uint32_t sb = smem_u32(sm);
    const int tid = threadIdx.x, w = tid >> 5, lane = tid & 31;
    const bool act = jh < (nh & ~3);
    const int j4 = jh & 3;
    const int fr = tid & 63, rg = w >> 1;
    auto chunk0 = [&](int u) { return u == 0 ? 5 * j4 : u == 1 ? 75 - 5 * j4 : u == 2 ? 40 + 5 * j4 : 35 - 5 * j4; };
    const int gr = tid / 20, gq_ = tid - gr * 20, go = gr * 80 + chunk0(gq_ / 5) + gq_ % 5;
    const uint32_t gs = sb + RI_RES + gr * 336 + gq_ * 16;
    auto residual = [&](int a, int n) {
#pragma unroll 1
        for (int r = 0; r < 64 - gr && tid < 240 && a < 32; r += 12) cp_async16(gs + (n & 1) * 21504 + r * 336, (const uint4*)res + (a * 64 + r) * 80 + go);
        cp_commit();
    };
    if (act) {
        if (tid < 240) {
            const int k0 = tid / 48, n = tid - k0 * 48;
            const float d = (float)(40 * j4 + n), amp = 2.f * 0.03952847075210474f;
#pragma unroll 4
            for (int u = 0; u < 16; u++)
                *(uint4*)(sm + RI_TAB + (tid + u * 240) * 16) = cos_row8(fmaf((float)((k0 + (u & 3) * 5) * 16 + ((u >> 2) & 1)), d, (float)((u & 8) * 20)), 2.f * d, amp);
            if (tid < 96) *(uint4*)(sm + RI_TAB + (3840 + tid) * 16) = make_uint4(k0 == 0 ? pack_h((n & 1) ? -amp : amp, 0.f) : 0u, 0, 0, 0);
        }
        fence_async_smem();
        residual(jh >> 2, 0);
    }
    bar_sync(1, 384);
    if (layer == TLL) TL(36);
    if (act) {
        const float4 wm = ((const float4*)g_wmax)[lane];
        const int wg = w >> 2;
        int n = 0;
#pragma unroll 1
        for (int a = jh >> 2; a < 32; a += nh >> 2, n++) {
            float acc[2][24];
            uint64_t da = mkdesc(sb + RI_A + wg * 40960, 1024, 1024, 1), db = mkdesc(sb + RI_TAB + wg * 30720, 768, 128, 0);
#pragma unroll
            for (int gq = 0; gq < 2; gq++) {
                mbar_wait(sb + HB_A + (wg * 2 + gq) * 8, n & 1);
                if (layer == TLL && n == TLN && gq == 0) TL(45);
                wg_fence();
#pragma unroll 5
                for (int k = 0; k < 10; k++) { wg_n48_ss_ta(acc[gq], da, db, k); da += 128; db += 96; }
                wg_commit();
            }
            if (wg == 0) {
                mbar_wait(sb + HB_A + 16, n & 1);
                wg_fence();
                wg_n48_ss_ta(acc[0], da, db + 20 * 96, 1);
                wg_commit();
            }
            float inv;
            pow2_scale(__uint_as_float(__reduce_max_sync(~0u, __float_as_uint(fmaxf(fmaxf(wm.x, wm.y), fmaxf(wm.z, wm.w))))), 0, &inv);
            const uint32_t ysc = pack_bf(inv, inv);
            wg_wait<0>();
            if (layer == TLL && n == TLN) TL(46);
            if (lane == 0) mbar_arrive(sb + HB_AFREE);
            const uint32_t ad = sb + RI_STG + ((w & 3) * 16 + (lane & 15)) * 400 + (lane >> 4) * 96 + wg * 192;
#pragma unroll
            for (int q = 0; q < 6; q++) {
                const float *e = acc[0] + q * 4, *o = acc[1] + q * 4;
                stsm4(ad + q * 16, pack_h(e[0] + o[0], e[1] + o[1]), pack_h(e[2] + o[2], e[3] + o[3]), pack_h(e[0] - o[0], e[1] - o[1]), pack_h(e[2] - o[2], e[3] - o[3]));
            }
            cp_wait<0>();
            bar_sync(4, 256);
            const uint32_t xa = sb + RI_RES + (n & 1) * 21504 + fr * 336 + rg * 80, sg = (rg & 1) ? 0xbc00bc00u : 0x3c003c00u;
            float sum = 0.f, sq = 0.f;
            uint32_t ya = sb + RI_STG + fr * 400 + (rg >> 1) * 96 + ((rg & 1) ? 64 : 0), carry;
            asm("fma.rn.f16x2 %0,%1,%2,%3;" : "=r"(carry) : "r"(lds32(ya + 208)), "r"(sg), "r"(lds32(ya + 16)));
#pragma unroll 1
            for (int ch = 0; ch < 5; ch++, ya += (rg & 1) ? -16 : 16) {
                uint32_t y[4], z[4], xr[4];
                lds128(y, ya); lds128(z, ya + 192); lds128(xr, xa + ch * 16);
#pragma unroll
                for (int q = 0; q < 4; q++) asm("fma.rn.f16x2 %0,%1,%2,%0;" : "+r"(y[q]) : "r"(z[q]), "r"(sg));
                if (rg & 1) {
                    const uint32_t y0 = y[0], y1 = y[1];
                    y[0] = __byte_perm(carry, y[3], 0x7610); y[1] = __byte_perm(y[3], y[2], 0x7610);
                    y[3] = __byte_perm(y1, y0, 0x7610); y[2] = __byte_perm(y[2], y1, 0x7610);
                    carry = y0;
                }
#pragma unroll
                for (int q = 0; q < 4; q++) {
                    const float2 yf = __half22float2(*(const __half2*)&y[q]);
                    xr[q] = bfma(pack_bf(yf.x, yf.y), ysc, xr[q]);
                    const float e = bf_lo(xr[q]), f = bf_hi(xr[q]);
                    sum += e + f; sq = fmaf(e, e, fmaf(f, f, sq));
                }
                sts128(xa + ch * 16, xr[0], xr[1], xr[2], xr[3]);
            }
            uint2* stat = g_stat + (size_t)(layer * 32 + a) * 1024 + rg * 64 + fr;
            asm volatile("st.relaxed.gpu.global.v2.u32 [%0],{%1,%2};" ::"l"(stat + j4 * 256), "r"(__float_as_uint(sum)), "r"(__float_as_uint(sq) | 0x80000000u) : "memory");
            if (layer == TLL && n == TLN) TL(47);
            uint32_t s0[3], s1[3];
            int lim = 0;
            do {
#pragma unroll
                for (int q = 0; q < 3; q++)
                    asm volatile("ld.relaxed.gpu.global.v2.u32 {%0,%1},[%2];" : "=r"(s0[q]), "=r"(s1[q]) : "l"(stat + ((j4 + 1 + q) & 3) * 256) : "memory");
            } while (__any_sync(~0u, (int)(s1[0] & s1[1] & s1[2]) >= 0) && ++lim < SPIN_LIM);
#pragma unroll
            for (int q = 0; q < 3; q++) { sum += __uint_as_float(s0[q]); sq -= __uint_as_float(s1[q]); }
            sts64(sb + RI_ST + tid * 8, __float_as_uint(sum), __float_as_uint(sq));
            bar_sync(4, 256);
            if (layer == TLL && n == TLN) TL(48);
#pragma unroll
            for (int q = 1; q < 4; q++) {
                uint32_t st2[2];
                lds64(st2, sb + RI_ST + ((tid + q * 64) & 255) * 8);
                sum += __uint_as_float(st2[0]); sq += __uint_as_float(st2[1]);
            }
            const float mean = sum * (1.f / 640.f), r = rsqrtf(fmaxf(fmaf(-mean, mean, sq * (1.f / 640.f)), 0.f) + 1e-5f), off = -mean * r;
            uint4* dst = (uint4*)g_xn + ((size_t)(2 * a + (w & 1)) * 80 + chunk0(rg)) * 32 + lane;
#pragma unroll
            for (int i = 0; i < 5; i++) {
                uint32_t u[4];
                lds128(u, xa + i * 16);
                dst[i * 32] = make_uint4(pack_h(fmaf(bf_lo(u[0]), r, off), fmaf(bf_hi(u[0]), r, off)), pack_h(fmaf(bf_lo(u[1]), r, off), fmaf(bf_hi(u[1]), r, off)),
                                         pack_h(fmaf(bf_lo(u[2]), r, off), fmaf(bf_hi(u[2]), r, off)), pack_h(fmaf(bf_lo(u[3]), r, off), fmaf(bf_hi(u[3]), r, off)));
            }
            __syncwarp();
            if (lane == 0) mbar_arrive(sb + HB_LN);
            if (layer == TLL) TL(37);
            if (layer == TLL && n == TLN) TL(44);
            residual(a + (nh >> 2), n + 1);
#pragma unroll 2
            for (int rr = 0; rr < 64 - gr && tid < 240; rr += 12) {
                uint32_t v[4];
                lds128(v, gs + (n & 1) * 21504 + rr * 336);
                ((uint4*)x)[(a * 64 + rr) * 80 + go] = make_uint4(v[0], v[1], v[2], v[3]);
            }
        }
    }
    bar_sync(3, 384);
    if (layer == TLL) TL(38);
    if (jh >= na) {
        int c0 = 0;
#pragma unroll 1
        for (int mb = (jh - na) >> 3; mb < nbh; mb += (nh - na) >> 3, c0 += GNC) oproj_mma(sb, mb, (jh - na) & 7, c0, x, out, layer);
        if (layer == TLL) TL(42);
        return;
    }
    const int p = w >> 1, mi = w & 1;
    int slot = p, ph = 0;
    for (int idx = jh + p * na; idx < (NSEG - 1) * 32; idx += 4 * na) {
        const uint32_t it = sb + slot * 30720 + lane * 16;
        float iq, ik, iv;
        weight_scale(idx & 31, 0, &iq); weight_scale(idx & 31, 1, &ik); weight_scale(idx & 31, 2, &iv);
        bar_sync(6 + p, 64);
        mbar_wait(sb + HB_DONE + slot * 8, ph ^ 1);
        mbar_wait(sb + HB_FULL + slot * 8, ph);
        tok_attention<8, 8>(it, 8192, it + 24576, 2048, it + 16384, it - lane * 8 + 28672, 0, mi, lane, idx >> 5, idx & 31, iq * ik, iv);
        __syncwarp();
        if (lane == 0) mbar_arrive(sb + HB_DONE + slot * 8);
        slot += 4;
        if (slot >= 6) { slot -= 6; ph ^= 1; }
    }
    if (layer == TLL) TL(39);
}

template <int layer> __global__ void __cluster_dims__(3, 1, 1) __launch_bounds__(384, 1)
k_chain(const int nact, const uint32_t zero, const bf16* __restrict__ Wq, const bf16* __restrict__ Wk, const bf16* __restrict__ Wv,
        const bf16* __restrict__ Wo, const bf16* res, bf16* out) {
    extern __shared__ __align__(1024) char sm[];
    const uint32_t sb = smem_u32(sm);
    const int b = blockIdx.x, h = b / 3, c = b - h * 3;
    pdl_go();
    if (threadIdx.x >= 256) {
        asm volatile("setmaxnreg.dec.sync.aligned.u32 24;");
        TL(11 + layer * 14);
        chain_aux<layer>(sb, c, h, nact);
    } else {
        asm volatile("setmaxnreg.inc.sync.aligned.u32 240;");
        chain_mma<layer>(sb, c, h, zero, Wq, Wk, Wv, Wo, res, out);
    }
}
__global__ void __launch_bounds__(384, 1) k_help(const bf16* res, bf16* x, bf16* out, const int layer, const int na, const int nbh, const int zero, const bf16* Wq,
                                                  const bf16* Wk, const bf16* Wv, const bf16* Wo) {
    extern __shared__ __align__(1024) char sm[];
    if (layer == TLL) TL(51);
    pdl_go();
    if (threadIdx.x >= 256) {
        const uint32_t sb = smem_u32(sm);
        const int p = (threadIdx.x >> 5) - 8, i = (threadIdx.x & 31) * 4 + p;
        if (i < 34) mbar_init(sb + G_BAR + i * 8, i < 4 ? 3 : i < 8 || i == 12 || i == 13 ? 8 : i >= 22 && i < 28 ? 2 : 1);
        fence_async_smem();
        wait_flag<100>(g_flag + F_X + layer * 128 + 65, 1);
        fence_async_glb();
        if (i == 8 + p && blockIdx.x < (gridDim.x & ~3)) {
            mbar_expect(sb + HB_A + p * 8, 20480);
            bulk_g2s(sb + RI_A + p * 20480, (const char*)g_YT + (size_t)(blockIdx.x >> 2) * 81920 + p * 20480, 20480, sb + HB_A + p * 8);
        }
        __syncwarp();
        bar_sync(2, 128);
        bar_arrive(1, 384);
    }
    if (threadIdx.x + zero >= 256) helper_aux(smem_u32(sm), blockIdx.x, gridDim.x, na, nbh, layer, Wq, Wk, Wv, Wo);
    else helper_mma(sm, blockIdx.x, gridDim.x, na, nbh, layer, res, x, out);
    __syncwarp();
    if (blockIdx.x == 0) pdl_wait();
}

#define COL_PAD 15872
template <class... P, class... A>
void launch_pdl(void (*k)(P...), int grid, int block, int smem, cudaStream_t st, A... args) {
    cudaLaunchConfig_t cfg = {};
    cfg.gridDim = dim3(grid); cfg.blockDim = dim3(block); cfg.dynamicSmemBytes = smem; cfg.stream = st;
    cudaLaunchAttribute at[1];
    at[0].id = cudaLaunchAttributeProgrammaticStreamSerialization; at[0].val.programmaticStreamSerializationAllowed = 1;
    cfg.attrs = at;
    cfg.numAttrs = 1;
    cudaLaunchKernelEx(&cfg, k, args...);
}

}

extern "C" void kernel_launch(void* const* d_in, const int* in_sizes, int n_in, void* d_out, int out_size) {
    const bf16* x = (const bf16*)d_in[0];
    const bf16* wr = (const bf16*)d_in[1];
    const bf16* wi = (const bf16*)d_in[2];
    const bf16* mem0 = (const bf16*)d_in[4];
    const bf16* Wq = (const bf16*)d_in[5];
    const bf16* Wk = (const bf16*)d_in[6];
    const bf16* Wv = (const bf16*)d_in[7];
    const bf16* Wo = (const bf16*)d_in[8];
    bf16* out = (bf16*)d_out;
    static int nhelp = 0;
    static bf16 *xa, *xb;
    static cudaStream_t s1;
    static cudaEvent_t ev_fork, ev_join;
    if (!nhelp) {
        cudaStreamCreateWithFlags(&s1, cudaStreamNonBlocking);
        cudaEventCreateWithFlags(&ev_fork, cudaEventDisableTiming);
        cudaEventCreateWithFlags(&ev_join, cudaEventDisableTiming);
        cudaFuncSetAttribute(k_setup, cudaFuncAttributeMaxDynamicSharedMemorySize, SU_SMEM);
        cudaFuncSetAttribute(k_rowf<0>, cudaFuncAttributeMaxDynamicSharedMemorySize, RF_SMEM);
        cudaFuncSetAttribute(k_rowf<1>, cudaFuncAttributeMaxDynamicSharedMemorySize, RF_SMEM);
        cudaFuncSetAttribute(k_col, cudaFuncAttributeMaxDynamicSharedMemorySize, COL_PAD);
        cudaFuncSetAttribute(k_chain<0>, cudaFuncAttributeMaxDynamicSharedMemorySize, CH_SMEM);
        cudaFuncSetAttribute(k_chain<1>, cudaFuncAttributeMaxDynamicSharedMemorySize, CH_SMEM);
        cudaFuncSetAttribute(k_setup, cudaFuncAttributePreferredSharedMemoryCarveout, 100);
        cudaFuncSetAttribute(k_rowf<0>, cudaFuncAttributePreferredSharedMemoryCarveout, 100);
        cudaFuncSetAttribute(k_rowf<1>, cudaFuncAttributePreferredSharedMemoryCarveout, 100);
        cudaFuncSetAttribute(k_col, cudaFuncAttributePreferredSharedMemoryCarveout, 100);
        cudaFuncSetAttribute(k_chain<0>, cudaFuncAttributePreferredSharedMemoryCarveout, 100);
        cudaFuncSetAttribute(k_chain<1>, cudaFuncAttributePreferredSharedMemoryCarveout, 100);
        cudaFuncSetAttribute(k_help, cudaFuncAttributeMaxDynamicSharedMemorySize, HP_SMEM);
        cudaFuncSetAttribute(k_help, cudaFuncAttributePreferredSharedMemoryCarveout, 100);
        int dev = 0, sms = 0;
        cudaGetDevice(&dev);
        cudaDeviceGetAttribute(&sms, cudaDevAttrMultiProcessorCount, dev);
        nhelp = sms - 96 < 12 ? 12 : sms - 96;
        cudaGetSymbolAddress((void**)&xa, g_xa);
        cudaGetSymbolAddress((void**)&xb, g_xb);
    }
    const int na = nhelp - (nhelp >= 36 ? 24 : nhelp >= 28 ? 16 : 8), nbh = 14;
    cudaStream_t s0 = cudaStreamPerThread;
    cudaEventRecord(ev_fork, s0);
    cudaStreamWaitEvent(s1, ev_fork, 0);
    k_rowf<1><<<(96 + nhelp) & ~1, 256, RF_SMEM, s0>>>(x);
    k_setup<<<NSETUP, 256, SU_SMEM, s1>>>(wr, wi, mem0);
    cudaEventRecord(ev_join, s1);
#define NLAYER 2
    for (int l = 0; l < NLAYER; l++) {
        const bf16* xin = l == 0 ? x : xb;
        if (l == 1) launch_pdl(k_rowf<0>, 128, 256, RF_SMEM, s0, xin);
        launch_pdl(k_col, 321, 128, l == 0 ? 0 : COL_PAD, s0, (int)(l == 0));
        launch_pdl(l == 0 ? k_chain<0> : k_chain<1>, 96, 384, CH_SMEM, s0, nhelp & ~3, 0u, Wq, Wk, Wv, Wo, (const bf16*)xa, l == 0 ? xb : out);
        launch_pdl(k_help, nhelp, 384, HP_SMEM, s0, xin, xa, l == 0 ? xb : out, l, na, nbh, 0, Wq, Wk, Wv, Wo);
    }
    cudaStreamWaitEvent(s0, ev_join, 0);
}
```

```cpp
#include <cuda_runtime.h>
#include <cuda_bf16.h>
#include <cuda_fp16.h>
#include <stdint.h>
#include <string.h>

namespace {

typedef __nv_bfloat16 bf16;
constexpr int S_ = 2048, D_ = 640, NSEG = 64;
constexpr int SPIN_LIM = 1 << 13;

__device__ float                  g_wmx[96];
__device__ __align__(1024) bf16   g_wot[4096 * 640];
__device__ __align__(16) float    g_co[1024];
__device__ __align__(256) uint2   g_stat[2 * 32 * 16 * 64];
__device__ float                  g_invM0;
__device__ __align__(16) float    g_wmax[128];
__device__ __align__(1024) char   g_redraw[65 * 32768];
constexpr int F_X = 2 * NSEG * 32, F_O = F_X + 2 * 128, NFLAG = F_O + 128, RING = 8;
constexpr int F_W = F_X + 66;
constexpr int F_R = F_O + 64;
constexpr int NSETUP = 131;
struct __align__(256) Flag { unsigned v; };
__device__ Flag                   g_flag[NFLAG];
__device__ Flag                   g_ready[1];
__device__ __align__(1024) char   g_item[RING * 32 * 32768];
__device__ __align__(1024) bf16   g_O[S_ * 4096];
__device__ __align__(1024) __half g_xn[S_ * D_];
__device__ __align__(1024) bf16   g_xa[S_ * D_];
__device__ __align__(1024) bf16   g_xb[S_ * D_];
__device__ __align__(1024) __half g_UT[D_ * S_];
__device__ __align__(1024) __half g_YT[D_ * S_];
__device__ __align__(1024) __half g_ctab[64 * 128 + 64 * 64];
__device__ __align__(1024) uint32_t g_Wf[321 * 2048];

#define TL(i)
#define TLN 0
#define TLL 1
#define CK(i)
__device__ __forceinline__ uint32_t smem_u32(const void* p) { return (uint32_t)__cvta_generic_to_shared(p); }
__device__ __forceinline__ uint32_t mapa(uint32_t a, uint32_t r) { uint32_t o; asm("mapa.shared::cluster.u32 %0,%1,%2;" : "=r"(o) : "r"(a), "r"(r)); return o; }
__device__ __forceinline__ void mbar_init(uint32_t a, int c) { asm volatile("mbarrier.init.shared::cta.b64 [%0],%1;" ::"r"(a), "r"(c) : "memory"); }
__device__ __forceinline__ void mbar_expect(uint32_t a, int bytes) { asm volatile("mbarrier.arrive.expect_tx.shared::cta.b64 _,[%0],%1;" ::"r"(a), "r"(bytes) : "memory"); }
__device__ __forceinline__ void mbar_arrive(uint32_t a) { asm volatile("mbarrier.arrive.shared::cta.b64 _,[%0];" ::"r"(a) : "memory"); }
__device__ __forceinline__ bool mbar_try(uint32_t a, uint32_t par) {
    uint32_t p;
    asm volatile("{.reg .pred q; mbarrier.try_wait.parity.shared::cta.b64 q,[%1],%2; selp.u32 %0,1,0,q;}" : "=r"(p) : "r"(a), "r"(par) : "memory");
    return p;
}
__device__ __forceinline__ void mbar_wait(uint32_t a, uint32_t par) {
    if (!mbar_try(a, par)) {
        int lim = 0;
        while (!mbar_try(a, par) && ++lim < SPIN_LIM) {}
    }
}
__device__ __forceinline__ void mbar_sleep(uint32_t a, uint32_t par) {
    asm volatile("{.reg .pred q; .reg .u32 n; mov.u32 n,0;\n"
                 "W_LOOP: mbarrier.try_wait.parity.shared::cta.b64 q,[%0],%1,%2; add.u32 n,n,1; setp.lt.and.u32 q,n,%3,!q; @q bra W_LOOP;}"
                 ::"r"(a), "r"(par), "n"(20000), "n"(SPIN_LIM) : "memory");
}
__device__ __forceinline__ void bar_arrive(int id, int n) { asm volatile("bar.arrive %0,%1;" ::"r"(id), "r"(n) : "memory"); }
__device__ __forceinline__ uint32_t clock32() { uint32_t c; asm volatile("mov.u32 %0,%%clock;" : "=r"(c)); return c; }
__device__ __forceinline__ uint32_t read_tid() { uint32_t v; asm volatile("mov.u32 %0,%%tid.x;" : "=r"(v)); return v; }
__device__ __forceinline__ void bar_sync(int id, int n) { asm volatile("bar.sync %0,%1;" ::"r"(id), "r"(n) : "memory"); }
__device__ __forceinline__ void fence_async_smem() { asm volatile("fence.proxy.async.shared::cta;" ::: "memory"); }
__device__ __forceinline__ void fence_async_glb() { asm volatile("fence.proxy.async.global;" ::: "memory"); }
__device__ __forceinline__ void cluster_sync_full() { asm volatile("barrier.cluster.arrive.aligned; barrier.cluster.wait.aligned;" ::: "memory"); }
__device__ __forceinline__ void bulk_g2s(uint32_t dst, const void* src, int bytes, uint32_t mb) {
    asm volatile("cp.async.bulk.shared::cluster.global.mbarrier::complete_tx::bytes [%0],[%1],%2,[%3];" ::"r"(dst), "l"(src), "r"(bytes), "r"(mb) : "memory");
}
__device__ __forceinline__ void bulk_g2s_last(uint32_t dst, const void* src, int bytes, uint32_t mb) {
    asm volatile("{.reg .b64 p; createpolicy.fractional.L2::evict_first.b64 p, 1.0;\n"
                 "cp.async.bulk.shared::cluster.global.mbarrier::complete_tx::bytes.L2::cache_hint [%0],[%1],%2,[%3],p;}"
                 ::"r"(dst), "l"(src), "r"(bytes), "r"(mb) : "memory");
}
__device__ __forceinline__ void bulk_s2s(uint32_t dst, uint32_t src, int bytes, uint32_t mb) {
    asm volatile("cp.async.bulk.shared::cluster.shared::cta.mbarrier::complete_tx::bytes [%0],[%1],%2,[%3];" ::"r"(dst), "r"(src), "r"(bytes), "r"(mb) : "memory");
}
__device__ __forceinline__ void bulk_s2g(void* dst, uint32_t src, int bytes) {
    asm volatile("cp.async.bulk.global.shared::cta.bulk_group [%0],[%1],%2;" ::"l"(dst), "r"(src), "r"(bytes) : "memory");
}
__device__ __forceinline__ void cp_async16(uint32_t dst, const void* src, uint32_t bytes = 16) {
    asm volatile("cp.async.cg.shared.global [%0],[%1],16,%2;" ::"r"(dst), "l"(src), "r"(bytes) : "memory");
}
__device__ __forceinline__ void cp_commit() { asm volatile("cp.async.commit_group;" ::: "memory"); }
template <int N> __device__ __forceinline__ void cp_wait() { asm volatile("cp.async.wait_group %0;" ::"n"(N) : "memory"); }
__device__ __forceinline__ void bulk_commit() { asm volatile("cp.async.bulk.commit_group;" ::: "memory"); }
__device__ __forceinline__ void bulk_wait0() { asm volatile("cp.async.bulk.wait_group 0;" ::: "memory"); }
__device__ __forceinline__ void ldsm4(uint32_t* r, uint32_t a) {
    asm volatile("ldmatrix.sync.aligned.m8n8.x4.shared.b16 {%0,%1,%2,%3},[%4];" : "=r"(r[0]), "=r"(r[1]), "=r"(r[2]), "=r"(r[3]) : "r"(a) : "memory");
}
__device__ __forceinline__ void ldsm4t(uint32_t* r, uint32_t a) {
    asm volatile("ldmatrix.sync.aligned.m8n8.x4.trans.shared.b16 {%0,%1,%2,%3},[%4];" : "=r"(r[0]), "=r"(r[1]), "=r"(r[2]), "=r"(r[3]) : "r"(a) : "memory");
}
__device__ __forceinline__ void stsm4(uint32_t a, uint32_t r0, uint32_t r1, uint32_t r2, uint32_t r3) {
    asm volatile("stmatrix.sync.aligned.m8n8.x4.shared.b16 [%0],{%1,%2,%3,%4};" ::"r"(a), "r"(r0), "r"(r1), "r"(r2), "r"(r3) : "memory");
}
__device__ __forceinline__ void stsm4t(uint32_t a, uint32_t r0, uint32_t r1, uint32_t r2, uint32_t r3) {
    asm volatile("stmatrix.sync.aligned.m8n8.x4.trans.shared.b16 [%0],{%1,%2,%3,%4};" ::"r"(a), "r"(r0), "r"(r1), "r"(r2), "r"(r3) : "memory");
}
__device__ __forceinline__ void lds128(uint32_t* r, uint32_t a) {
    asm volatile("ld.shared.v4.b32 {%0,%1,%2,%3},[%4];" : "=r"(r[0]), "=r"(r[1]), "=r"(r[2]), "=r"(r[3]) : "r"(a) : "memory");
}
__device__ __forceinline__ void lds64(uint32_t* r, uint32_t a) {
    asm volatile("ld.shared.v2.b32 {%0,%1},[%2];" : "=r"(r[0]), "=r"(r[1]) : "r"(a) : "memory");
}
__device__ __forceinline__ uint32_t lds32(uint32_t a) { uint32_t v; asm volatile("ld.shared.b32 %0,[%1];" : "=r"(v) : "r"(a) : "memory"); return v; }
__device__ __forceinline__ void sts128(uint32_t a, uint32_t r0, uint32_t r1, uint32_t r2, uint32_t r3) {
    asm volatile("st.shared.v4.b32 [%0],{%1,%2,%3,%4};" ::"r"(a), "r"(r0), "r"(r1), "r"(r2), "r"(r3) : "memory");
}
__device__ __forceinline__ void sts64(uint32_t a, uint32_t v0, uint32_t v1) { asm volatile("st.shared.v2.b32 [%0],{%1,%2};" ::"r"(a), "r"(v0), "r"(v1) : "memory"); }
[[maybe_unused]] __device__ __forceinline__ void sts32(uint32_t a, uint32_t v) { asm volatile("st.shared.b32 [%0],%1;" ::"r"(a), "r"(v) : "memory"); }
#define AU_(op) "{.reg .u32 t; add.u32 t,%4,%5; " op " {%0,%1,%2,%3},[t+%6];}"
template <int I> __device__ __forceinline__ void ldsm4_u(uint32_t* r, uint32_t a, uint32_t u) {
    asm volatile(AU_("ldmatrix.sync.aligned.m8n8.x4.shared.b16") : "=r"(r[0]), "=r"(r[1]), "=r"(r[2]), "=r"(r[3]) : "r"(a), "r"(u), "n"(I) : "memory");
}
template <int I> __device__ __forceinline__ void ldsm4t_u(uint32_t* r, uint32_t a, uint32_t u) {
    asm volatile(AU_("ldmatrix.sync.aligned.m8n8.x4.trans.shared.b16") : "=r"(r[0]), "=r"(r[1]), "=r"(r[2]), "=r"(r[3]) : "r"(a), "r"(u), "n"(I) : "memory");
}
template <int I> __device__ __forceinline__ void lds128_u(uint32_t* r, uint32_t a, uint32_t u) {
    asm volatile(AU_("ld.shared.v4.b32") : "=r"(r[0]), "=r"(r[1]), "=r"(r[2]), "=r"(r[3]) : "r"(a), "r"(u), "n"(I) : "memory");
}
template <int I> __device__ __forceinline__ void lds64_u(uint32_t* r, uint32_t a, uint32_t u) {
    asm volatile("{.reg .u32 t; add.u32 t,%2,%3; ld.shared.v2.b32 {%0,%1},[t+%4];}" : "=r"(r[0]), "=r"(r[1]) : "r"(a), "r"(u), "n"(I) : "memory");
}
template <int I> __device__ __forceinline__ uint32_t lds32_u(uint32_t a, uint32_t u) {
    uint32_t v;
    asm volatile("{.reg .u32 t; add.u32 t,%1,%2; ld.shared.b32 %0,[t+%3];}" : "=r"(v) : "r"(a), "r"(u), "n"(I) : "memory");
    return v;
}
template <int I> __device__ __forceinline__ void sts64_u(uint32_t a, uint32_t u, uint32_t v0, uint32_t v1) {
    asm volatile("{.reg .u32 t; add.u32 t,%0,%1; st.shared.v2.b32 [t+%2],{%3,%4};}" ::"r"(a), "r"(u), "n"(I), "r"(v0), "r"(v1) : "memory");
}
template <int I> __device__ __forceinline__ void sts32_u(uint32_t a, uint32_t u, uint32_t v) {
    asm volatile("{.reg .u32 t; add.u32 t,%0,%1; st.shared.b32 [t+%2],%3;}" ::"r"(a), "r"(u), "n"(I), "r"(v) : "memory");
}
template <int I> __device__ __forceinline__ void sts16_u(uint32_t a, uint32_t u, uint32_t v) {
    asm volatile("{.reg .u32 t; add.u32 t,%0,%1; st.shared.b16 [t+%2],%3;}" ::"r"(a), "r"(u), "n"(I), "h"((unsigned short)v) : "memory");
}
template <int I> __device__ __forceinline__ void sts128_u(uint32_t a, uint32_t u, uint32_t r0, uint32_t r1, uint32_t r2, uint32_t r3) {
    asm volatile("{.reg .u32 t; add.u32 t,%0,%1; st.shared.v4.b32 [t+%2],{%3,%4,%5,%6};}" ::"r"(a), "r"(u), "n"(I), "r"(r0), "r"(r1), "r"(r2), "r"(r3) : "memory");
}
template <int I> __device__ __forceinline__ void stsm4_u(uint32_t a, uint32_t u, uint32_t r0, uint32_t r1, uint32_t r2, uint32_t r3) {
    asm volatile("{.reg .u32 t; add.u32 t,%0,%1; stmatrix.sync.aligned.m8n8.x4.shared.b16 [t+%2],{%3,%4,%5,%6};}"
                 ::"r"(a), "r"(u), "n"(I), "r"(r0), "r"(r1), "r"(r2), "r"(r3) : "memory");
}
__device__ __forceinline__ void st_share2(uint32_t a, uint32_t u, uint32_t mb, uint32_t d0, uint32_t d1, uint32_t v0, uint32_t v1) {
    asm volatile("{.reg .pred p; .reg .u32 t,x,y; add.u32 t,%0,%1;\n"
                 "add.u32 x,t,%3; add.u32 y,%2,%3; st.async.shared::cluster.mbarrier::complete_tx::bytes.v2.b32 [x],{%5,%6},[y];\n"
                 "add.u32 x,t,%4; add.u32 y,%2,%4; st.async.shared::cluster.mbarrier::complete_tx::bytes.v2.b32 [x],{%5,%6},[y];\n"
                 "st.shared.v2.b32 [t],{%5,%6}; bar.warp.sync -1; setp.eq.u32 p,%0,0; @p mbarrier.arrive.shared::cta.b64 _,[%2];}"
                 ::"r"(a), "r"(u), "r"(mb), "r"(d0), "r"(d1), "r"(v0), "r"(v1) : "memory");
}
template <int V> struct IC { __host__ __device__ constexpr operator int() const { return V; } };
template <int N, class F> __device__ __forceinline__ void sfor(F f) {
    if constexpr (N > 0) { sfor<N - 1>(f); f(IC<N - 1>()); }
}
__device__ __forceinline__ void mma_f16(float* d, const uint32_t* a, uint32_t b0, uint32_t b1) {
    asm volatile("mma.sync.aligned.m16n8k16.row.col.f32.f16.f16.f32 {%0,%1,%2,%3},{%4,%5,%6,%7},{%8,%9},{%0,%1,%2,%3};"
                 : "+f"(d[0]), "+f"(d[1]), "+f"(d[2]), "+f"(d[3]) : "r"(a[0]), "r"(a[1]), "r"(a[2]), "r"(a[3]), "r"(b0), "r"(b1));
}
__device__ __forceinline__ void mma_bf(float* d, uint32_t a0, uint32_t a1, uint32_t a2, uint32_t a3, uint32_t b0, uint32_t b1) {
    asm volatile("mma.sync.aligned.m16n8k16.row.col.f32.bf16.bf16.f32 {%0,%1,%2,%3},{%4,%5,%6,%7},{%8,%9},{%0,%1,%2,%3};"
                 : "+f"(d[0]), "+f"(d[1]), "+f"(d[2]), "+f"(d[3]) : "r"(a0), "r"(a1), "r"(a2), "r"(a3), "r"(b0), "r"(b1));
}
__device__ __forceinline__ void mma_bf8(float* d, uint32_t a0, uint32_t a1, uint32_t b0) {
    asm volatile("mma.sync.aligned.m16n8k8.row.col.f32.bf16.bf16.f32 {%0,%1,%2,%3},{%4,%5},{%6},{%0,%1,%2,%3};"
                 : "+f"(d[0]), "+f"(d[1]), "+f"(d[2]), "+f"(d[3]) : "r"(a0), "r"(a1), "r"(b0));
}
__device__ __forceinline__ uint32_t pack_bf(float lo, float hi) { uint32_t r; asm("cvt.rn.bf16x2.f32 %0,%1,%2;" : "=r"(r) : "f"(hi), "f"(lo)); return r; }
__device__ __forceinline__ uint32_t pack_h(float lo, float hi) { uint32_t r; asm("cvt.rn.f16x2.f32 %0,%1,%2;" : "=r"(r) : "f"(hi), "f"(lo)); return r; }
__device__ __forceinline__ float bf_lo(uint32_t v) { return __uint_as_float(v << 16); }
__device__ __forceinline__ float bf_hi(uint32_t v) { return __uint_as_float(v & 0xffff0000u); }
__device__ __forceinline__ uint32_t bfma(uint32_t a, uint32_t b, uint32_t c) { uint32_t r; asm("fma.rn.bf16x2 %0,%1,%2,%3;" : "=r"(r) : "r"(a), "r"(b), "r"(c)); return r; }
__device__ __forceinline__ uint4 add_bf8(const uint4 x, const uint32_t* y, const uint32_t k = 0x3f803f80u) {
    return make_uint4(bfma(y[0], k, x.x), bfma(y[1], k, x.y), bfma(y[2], k, x.z), bfma(y[3], k, x.w));
}
__device__ __forceinline__ float ex2(float x) { float r; asm("ex2.approx.ftz.f32 %0,%1;" : "=f"(r) : "f"(x)); return r; }
__device__ __forceinline__ float rcp(float x) { float r; asm("rcp.approx.ftz.f32 %0,%1;" : "=f"(r) : "f"(x)); return r; }
__device__ __forceinline__ void wg_fence() { asm volatile("wgmma.fence.sync.aligned;" ::: "memory"); }
__device__ __forceinline__ void wg_commit() { asm volatile("wgmma.commit_group.sync.aligned;" ::: "memory"); }
template <int N> __device__ __forceinline__ void wg_wait() { asm volatile("wgmma.wait_group.sync.aligned %0;" ::"n"(N) : "memory"); }
__device__ __forceinline__ uint64_t mkdesc(uint32_t a, uint32_t lbo, uint32_t sbo, uint32_t sw) {
    return (uint64_t)((a & 0x3FFFF) >> 4) | ((uint64_t)(lbo >> 4) << 16) | ((uint64_t)(sbo >> 4) << 32) | ((uint64_t)sw << 62);
}
#define F4(d, i) "+f"(d[i]), "+f"(d[i + 1]), "+f"(d[i + 2]), "+f"(d[i + 3])
#define F8(d, i) F4(d, i), F4(d, i + 4)
#define F16(d, i) F8(d, i), F8(d, i + 8)
template <int OFF, int SC> __device__ __forceinline__ void wg_n32_x(float* d, const uint32_t* a, uint32_t lo) {
    asm volatile("{.reg .pred p; .reg .b32 l; .reg .b64 q; setp.ne.b32 p,%22,0; add.u32 l,%20,%21; mov.b64 q,{l,8};\n"
                 "wgmma.mma_async.sync.aligned.m64n32k16.f32.f16.f16 "
                 "{%0,%1,%2,%3,%4,%5,%6,%7,%8,%9,%10,%11,%12,%13,%14,%15},{%16,%17,%18,%19},q,p,1,1,0;}"
                 : F16(d, 0) : "r"(a[0]), "r"(a[1]), "r"(a[2]), "r"(a[3]), "r"(lo), "n"(OFF), "n"(SC));
}
__device__ __forceinline__ void wg_n128_rs(float* d, const uint32_t* a, uint64_t db, int sc) {
    asm volatile("{.reg .pred p; setp.ne.b32 p,%69,0; wgmma.mma_async.sync.aligned.m64n128k16.f32.f16.f16 "
                 "{%0,%1,%2,%3,%4,%5,%6,%7,%8,%9,%10,%11,%12,%13,%14,%15,%16,%17,%18,%19,%20,%21,%22,%23,%24,%25,%26,%27,%28,%29,%30,%31,"
                 "%32,%33,%34,%35,%36,%37,%38,%39,%40,%41,%42,%43,%44,%45,%46,%47,%48,%49,%50,%51,%52,%53,%54,%55,%56,%57,%58,%59,%60,%61,%62,%63},"
                 "{%64,%65,%66,%67},%68,p,1,1,0;}"
                 : F16(d, 0), F16(d, 16), F16(d, 32), F16(d, 48) : "r"(a[0]), "r"(a[1]), "r"(a[2]), "r"(a[3]), "l"(db), "r"(sc));
}
#define N80_REGS "{%0,%1,%2,%3,%4,%5,%6,%7,%8,%9,%10,%11,%12,%13,%14,%15,%16,%17,%18,%19,%20,%21,%22,%23,%24,%25,%26,%27,%28,%29,%30,%31,%32,%33,%34,%35,%36,%37,%38,%39}"
__device__ __forceinline__ void wg_n80_ss(float* d, uint64_t da, uint64_t db, int sc) {
    asm volatile("{.reg .pred p; setp.ne.b32 p,%42,0; wgmma.mma_async.sync.aligned.m64n80k16.f32.bf16.bf16 " N80_REGS ",%40,%41,p,1,1,0,0;}"
                 : F16(d, 0), F16(d, 16), F8(d, 32) : "l"(da), "l"(db), "r"(sc));
}
__device__ __forceinline__ void wg_n88_ss(float* d, uint64_t da, uint64_t db, int sc) {
    asm volatile("{.reg .pred p; setp.ne.b32 p,%46,0; wgmma.mma_async.sync.aligned.m64n88k16.f32.f16.f16 "
                 "{%0,%1,%2,%3,%4,%5,%6,%7,%8,%9,%10,%11,%12,%13,%14,%15,%16,%17,%18,%19,%20,%21,%22,%23,%24,%25,%26,%27,%28,%29,%30,%31,"
                 "%32,%33,%34,%35,%36,%37,%38,%39,%40,%41,%42,%43},%44,%45,p,1,1,0,0;}"
                 : F16(d, 0), F16(d, 16), F8(d, 32), F4(d, 40) : "l"(da), "l"(db), "r"(sc));
}
__device__ __forceinline__ void wg_n48_ss_ta(float* d, uint64_t da, uint64_t db, int sc) {
    asm volatile("{.reg .pred p; setp.ne.b32 p,%26,0; wgmma.mma_async.sync.aligned.m64n48k16.f32.f16.f16 "
                 "{%0,%1,%2,%3,%4,%5,%6,%7,%8,%9,%10,%11,%12,%13,%14,%15,%16,%17,%18,%19,%20,%21,%22,%23},%24,%25,p,1,1,1,0;}"
                 : F16(d, 0), F8(d, 16) : "l"(da), "l"(db), "r"(sc));
}
template <int TA> __device__ __forceinline__ void wg_n64_ss_tb(float* d, uint64_t da, uint64_t db, int sc) {
    asm volatile("{.reg .pred p; setp.ne.b32 p,%34,0; wgmma.mma_async.sync.aligned.m64n64k16.f32.f16.f16 "
                 "{%0,%1,%2,%3,%4,%5,%6,%7,%8,%9,%10,%11,%12,%13,%14,%15,%16,%17,%18,%19,%20,%21,%22,%23,%24,%25,%26,%27,%28,%29,%30,%31},"
                 "%32,%33,p,1,1,%35,1;}"
                 : F16(d, 0), F16(d, 16) : "l"(da), "l"(db), "r"(sc), "n"(TA));
}
__device__ __forceinline__ void pdl_wait() { asm volatile("griddepcontrol.wait;" ::: "memory"); }
__device__ __forceinline__ void pdl_go() { asm volatile("griddepcontrol.launch_dependents;" ::: "memory"); }
__device__ __forceinline__ float cos640(float p) {
    const float q = fmaf(p, 0.0015625f, 12582912.f) - 12582912.f;
    return __cosf(fmaf(q, -640.f, p) * 0.009817477042468103f);
}
__device__ __forceinline__ uint4 cos_row8(float p0, float step, float amp = 1.f) {
    float v[8];
    const float k = 2.f * cos640(step);
    v[0] = amp * cos640(p0); v[1] = amp * cos640(p0 + step);
#pragma unroll
    for (int i = 2; i < 8; i++) v[i] = fmaf(k, v[i - 1], -v[i - 2]);
    return make_uint4(pack_h(v[0], v[1]), pack_h(v[2], v[3]), pack_h(v[4], v[5]), pack_h(v[6], v[7]));
}
__device__ __forceinline__ float wfilter_max(int lane) {
    float m = fmaxf(fmaxf(g_wmax[lane], g_wmax[lane + 32]), fmaxf(g_wmax[lane + 64], g_wmax[lane + 96]));
    return __uint_as_float(__reduce_max_sync(~0u, __float_as_uint(m)));
}
__device__ __forceinline__ unsigned ld_acquire(const Flag* p) { unsigned v; asm volatile("ld.acquire.gpu.global.u32 %0,[%1];" : "=r"(v) : "l"(p) : "memory"); return v; }
#define POLL_NS 200
template <int NS = POLL_NS> __device__ __forceinline__ void wait_flag(const Flag* p, unsigned v) {
    if (ld_acquire(p) >= v) return;
    unsigned x;
    int lim = 0;
    do {
        __nanosleep(NS);
        asm volatile("ld.relaxed.gpu.global.u32 %0,[%1];" : "=r"(x) : "l"(p) : "memory");
    } while (x < v && ++lim < SPIN_LIM);
    ld_acquire(p);
}
__device__ __forceinline__ void prefetch_l2(const void* p, int bytes) { asm volatile("cp.async.bulk.prefetch.L2.global [%0],%1;" ::"l"(p), "r"(bytes) : "memory"); }
__device__ __forceinline__ void red_release(Flag* p) { asm volatile("red.release.gpu.global.add.u32 [%0],1;" ::"l"(p) : "memory"); }
__device__ __forceinline__ void red_relaxed(Flag* p) { asm volatile("red.relaxed.gpu.global.add.u32 [%0],1;" ::"l"(p) : "memory"); }
__device__ __forceinline__ void red_h8(void* p, uint32_t a, uint32_t b, uint32_t c, uint32_t d) {
    asm volatile("red.relaxed.gpu.global.add.noftz.v4.f16x2 [%0],{%1,%2,%3,%4};" ::"l"(p), "r"(a), "r"(b), "r"(c), "r"(d) : "memory");
}
__device__ __forceinline__ float pow2_scale(float bound, int top, float* inv) {
    int e = (int)((__float_as_uint(bound) >> 23) & 0xff) - 126;
    int k = top - e;
    k = max(-100, min(100, k));
    *inv = __uint_as_float((uint32_t)(127 - k) << 23);
    return __uint_as_float((uint32_t)(127 + k) << 23);
}
__device__ __forceinline__ char* red_base() { return (char*)(((uintptr_t)g_redraw + 32767) & ~(uintptr_t)32767); }

__device__ __forceinline__ void setup_a(char* sm, const int b, const bf16* __restrict__ wr, const bf16* __restrict__ wi) {
    const int tid = threadIdx.x, lane = tid & 31;
    const uint32_t sb = smem_u32(sm);
    auto row_byte = [&](int q) { return ((b >> 2) + 32 * ((q >> 1) * 8 + 2 * (b & 3) + (q & 1))) * 642; };
#pragma unroll 1
    for (int r = tid >> 5; r < 32; r += 8) {
        const char* src = (const char*)(r < 16 ? wr : wi) + (row_byte(r & 15) & ~15);
        cp_async16(sb + r * 672 + lane * 16, src + lane * 16);
        if (lane < 9) cp_async16(sb + r * 672 + 512 + lane * 16, src + 512 + lane * 16);
    }
    ((uint4*)g_stat)[b * 256 + tid] = make_uint4(0, 0, 0, 0);
    if (tid < 2 * (NFLAG / 128)) ((uint4*)(g_flag + b * (NFLAG / 128) + (tid >> 1)))[tid & 1] = make_uint4(0, 0, 0, 0);
    if (tid < 12) {
        const int i = b * 12 + tid;
        const int f = ((i >> 4) & 3) * 8 + (i & 7), im = (i >> 3) & 1, part = (i >> 8) & 1;
        ((uint4*)g_ctab)[i] = cos_row8((float)(i < 1024 ? (i >> 7) * 80 * (i & 63) + ((i & 64) ? 480 : 0) : ((i >> 6) & 3) * 160 * f + (im == part ? 0 : im ? 160 : 480)),
                                       (float)(i < 1024 ? 10 * (i & 63) : 20 * f));
    }
    asm volatile("cp.async.wait_all;" ::: "memory");
    __syncthreads();
    const int q0 = (tid & 3) * 4;
    const char* rp[4];
#pragma unroll
    for (int u = 0; u < 4; u++) rp[u] = sm + (q0 + u) * 672 + (row_byte(q0 + u) & 15);
    uint32_t mx = 0;
#pragma unroll 2
    for (int c = tid >> 2; c < 321; c += 64) {
        uint32_t v[4];
#pragma unroll
        for (int u = 0; u < 4; u++) {
            v[u] = ((const unsigned short*)rp[u])[c] | ((uint32_t)((const unsigned short*)(rp[u] + 16 * 672))[c] << 16);
            mx = __vmaxu2(mx, v[u] & 0x7fff7fffu);
        }
        ((uint4*)g_Wf)[(size_t)c * 512 + b * 4 + ((tid ^ (b >> 1)) & 3)] = make_uint4(v[0], v[1], v[2], v[3]);
    }
    mx = __reduce_max_sync(~0u, max(mx & 0xffffu, mx >> 16));
    __syncthreads();
    if (lane == 0) ((uint32_t*)sm)[tid >> 5] = mx;
    __syncthreads();
    if (tid < 32) {
        mx = __reduce_max_sync(~0u, ((uint32_t*)sm)[lane & 7]);
        if (tid == 0) g_wmax[b] = __uint_as_float(mx << 16);
    }
}
__device__ __forceinline__ void setup_b(const int b, const bf16* __restrict__ mem0) {
    const int tid = threadIdx.x;
    uint4* z = (uint4*)red_base();
    if (b < 3) {
        const int w = tid >> 5, lane = tid & 31, p = b * 2 + ((w >> 1) & 1), odd = w & 1;
        uint32_t mx = 0;
#pragma unroll 4
        for (int i = lane; i < 640; i += 32) {
            const uint4 u = ((const uint4*)mem0)[i];
            mx = __vmaxu2(__vmaxu2(mx, u.x & 0x7fff7fffu), __vmaxu2(__vmaxu2(u.y & 0x7fff7fffu, u.z & 0x7fff7fffu), u.w & 0x7fff7fffu));
        }
        float inv, v[7];
        const float sc = pow2_scale(__uint_as_float(__reduce_max_sync(~0u, max(mx & 0xffffu, mx >> 16)) << 16), 14, &inv);
        if (tid == 0) g_invM0 = inv;
#pragma unroll
        for (int j = 0; j < 7; j++) {
            const int r = p * 56 + (j < 6 ? odd * 32 + (j >> 1) * 8 : 24) + (lane >> 2), mr = 2 * (lane & 3) + (j < 6 ? (j & 1) : odd);
            v[j] = r < 320 ? __bfloat162float(mem0[mr * 640 + (w >> 2) * 320 + r]) * sc : 0.f;
        }
        const int off = w * 2048 + (lane >> 4) * 1024 + ((lane >> 3) & 1) * 256 + (lane & 7) * 16 + (b == 2 ? (w >> 1) * 4096 + 128 : b * 16384);
        const uint4 u = make_uint4(pack_h(v[0], v[1]), pack_h(v[2], v[3]), pack_h(v[4], v[5]), pack_h(v[6], 32.f));
        z[off >> 4] = u; z[65536 + (off >> 4)] = u;
    }
}

#define SU_PAD 40960
constexpr int SU_SMEM = SU_PAD;
__global__ void __launch_bounds__(256, 4) k_setup(const bf16* __restrict__ wr, const bf16* __restrict__ wi, const bf16* __restrict__ mem0) {
    extern __shared__ __align__(1024) char sm[];
    TL(0);
    if (blockIdx.x >= 128) setup_b(blockIdx.x - 128, mem0);
    else setup_a(sm, blockIdx.x, wr, wi);
    __syncthreads();
    if (threadIdx.x == 0) red_release(g_ready);
    TL(1);
}
__device__ __forceinline__ float weight_scale(int h, int ty, float* inv) { return pow2_scale(__ldcg(g_wmx + h * 3 + ty), 6, inv); }

#define STR_(x) #x
#define STR(x) STR_(x)
#define RF_U 1
constexpr int RF_A = 22 * 2816, RF_X = RF_A + 22 * 1024, RF_BAR = RF_X + 64 * 1344, RF_SMEM = RF_BAR + 80;
__device__ __align__(1024) char g_rtab[4 * RF_A];
template <int first> __global__ void __cluster_dims__(2, 1, 1) __launch_bounds__(256, 2) k_rowf(const bf16* x) {
    extern __shared__ __align__(1024) char sm[];
    TL(first ? 2 : 16);
    const int tid = threadIdx.x, w = tid >> 5, lane = tid & 31, g = lane >> 2, t = lane & 3;
    if (blockIdx.x >= 128) { __nanosleep(2500); return; }
    const int a = first ? blockIdx.x >> 2 : 31 - (blockIdx.x >> 2), gq = blockIdx.x & 3;
    if (!first) pdl_go();
    const uint32_t sb = smem_u32(sm), mb = sb + RF_BAR + w * 8;
    if (lane == 0) {
        mbar_init(mb, 1);
        asm volatile("fence.mbarrier_init.release.cluster;" ::: "memory");
        if (!first && w == 0) {
            mbar_init(sb + RF_BAR + 64, 1);
            fence_async_smem();
            mbar_expect(sb + RF_BAR + 64, RF_A);
            bulk_g2s(sb, g_rtab + gq * RF_A, RF_A, sb + RF_BAR + 64);
        }
    }
    if (lane == 0) mbar_expect(mb, 8 * 1280);
    __syncwarp();
    asm volatile("barrier.cluster.arrive.relaxed.aligned; barrier.cluster.wait.aligned;" ::: "memory");
    if (!first) {
        if (lane == 0) wait_flag<100>(g_flag + F_R + a, a < 28 ? 32 : 192);
        __syncwarp();
        fence_async_glb();
    }
    TL(first ? 3 : 17);
    if (lane < 4)
        asm volatile("cp.async.bulk.shared::cluster.global.mbarrier::complete_tx::bytes.multicast::cluster [%0],[%1],1280,[%2],%3;"
                     ::"r"(sb + RF_X + (w * 8 + (gq & 1) * 4 + lane) * 1344), "l"(x + (size_t)(a * 64 + w * 8 + (gq & 1) * 4 + lane) * 640), "r"(mb),
                     "h"((unsigned short)3) : "memory");
    __syncwarp();
    if (first) pdl_go();
    if (first) {
#pragma unroll 3
        for (int id = tid; id < 22 * 176; id += 256) {
            const int kg = id / 176, n = id - kg * 176;
            const float c = (float)(2 * n + (gq & 1));
            *(uint4*)(sm + id * 16) = cos_row8(fmaf((float)(kg * 8), c, (float)((gq & 2) * 80)), c, 0.03952847075210474f);
        }
    }
    mbar_wait(mb, 0);
    const uint32_t row = sb + RF_X + (w * 8 + g) * 1344;
    float st[4][4] = {};
#pragma unroll 1
    for (int i = 0; i < 20; i += 4) {
        uint32_t u[4][4];
#pragma unroll
        for (int q = 0; q < 4; q++) lds128(u[q], row + (4 * (i + q) + t) * 16);
#pragma unroll
        for (int q = 0; q < 4; q++) {
            mma_bf(st[(q & 1) * 2], u[q][0], 0x3f803f80u, u[q][1], 0x3f803f80u, u[q][0], u[q][1]);
            mma_bf(st[(q & 1) * 2 + 1], u[q][2], 0x3f803f80u, u[q][3], 0x3f803f80u, u[q][2], u[q][3]);
        }
    }
#pragma unroll
    for (int q = 0; q < 4; q++) { st[0][q] += st[2][q]; st[1][q] += st[3][q]; }
    const float sq = __shfl_sync(~0u, (g & 1) ? st[0][1] + st[1][1] : st[0][0] + st[1][0], g * 4 + (g >> 1));
    const float mean = __shfl_sync(~0u, (g & 1) ? st[0][3] + st[1][3] : st[0][2] + st[1][2], g * 4 + (g >> 1)) * (1.f / 640.f);
    const float r = rsqrtf(fmaxf(fmaf(-mean, mean, sq * (1.f / 640.f)), 0.f) + 1e-5f), off = gq == 0 ? -4.f * mean * r : 0.f;
    const float r1 = (gq == 1 || gq == 2) ? -r : r, r2 = (gq & 1) ? -r : r, r3 = gq >= 2 ? -r : r;
    const uint32_t aa = sb + RF_A + w * 128 + g * 16;
    auto el = [&](int d) { unsigned short v; asm volatile("ld.shared.u16 %0,[%1];" : "=h"(v) : "r"(row + d * 2)); return __uint_as_float((uint32_t)v << 16); };
_Pragma(STR(unroll RF_U))
    for (int i = 0; i < 5; i++) {
        const int ch = t + 4 * i;
        uint32_t u[4][4];
        lds128(u[0], row + ch * 16); lds128(u[1], row + (39 - ch) * 16); lds128(u[2], row + (40 + ch) * 16); lds128(u[3], row + (79 - ch) * 16);
        const float nb0 = el(320 - 8 * ch), nb1 = el(ch ? 640 - 8 * ch : 0);
        float o[8];
#pragma unroll
        for (int q = 0; q < 8; q++) {
            const int m = (8 - q) >> 1;
            const float e0 = (q & 1) ? bf_hi(u[0][q >> 1]) : bf_lo(u[0][q >> 1]), e2 = (q & 1) ? bf_hi(u[2][q >> 1]) : bf_lo(u[2][q >> 1]);
            const float e1 = q == 0 ? nb0 : (q & 1) ? bf_hi(u[1][m & 3]) : bf_lo(u[1][m & 3]), e3 = q == 0 ? nb1 : (q & 1) ? bf_hi(u[3][m & 3]) : bf_lo(u[3][m & 3]);
            o[q] = fmaf(e3, r3, fmaf(e2, r2, fmaf(e1, r1, fmaf(e0, r, off))));
        }
        if (ch == 0) o[0] *= 0.5f;
        sts128(aa + ch * 1024, pack_h(o[0], o[1]), pack_h(o[2], o[3]), pack_h(o[4], o[5]), pack_h(o[6], o[7]));
    }
    if (t < 2) sts128(aa + (20 + t) * 1024, t == 0 ? pack_h(fmaf(el(480), r2, fmaf(el(160), r, 0.5f * off)), 0.f) : 0u, 0u, 0u, 0u);
    fence_async_smem();
    __syncthreads();
    if (!first) mbar_wait(sb + RF_BAR + 64, 0);
    else if (a == 0 && tid == 0) { bulk_s2g(g_rtab + gq * RF_A, sb, RF_A); bulk_commit(); }
    const int wg = w >> 2;
    float acc[44];
    uint64_t da = mkdesc(sb + RF_A, 1024, 128, 0), db = mkdesc(sb + wg * 1408, 2816, 128, 0);
    wg_fence();
#pragma unroll 1
    for (int k = 0; k < 11; k++) { wg_n88_ss(acc, da, db, k); da += 128; db += 352; }
    wg_commit(); wg_wait<0>();
    const uint32_t stg = sb + RF_X + wg * 96 * 144;
#pragma unroll
    for (int j = 0; j < 12; j += 2) {
        const int m = lane >> 3, j1 = j < 10 ? j + 1 : j;
        stsm4t(stg + ((j + (m >> 1)) * 8 + (lane & 7)) * 144 + ((w & 3) * 16 + (m & 1) * 8) * 2, pack_h(acc[j * 4], acc[j * 4 + 1]),
               pack_h(acc[j * 4 + 2], acc[j * 4 + 3]), pack_h(acc[j1 * 4], acc[j1 * 4 + 1]), pack_h(acc[j1 * 4 + 2], acc[j1 * 4 + 3]));
    }
    bar_sync(1 + wg, 128);
#pragma unroll 3
    for (int rr = (tid & 127) >> 3; rr < 88; rr += 16) {
        const int ch = tid & 7, c = 2 * (wg * 88 + rr) + (gq & 1);
        if (c <= 320 - (gq >> 1) && (c | (gq ^ 2))) {
            uint32_t u[4];
            lds128(u, stg + rr * 144 + ch * 16);
            ((uint4*)g_UT)[((size_t)(c == 320 ? 1 : 2 * c + (gq >> 1)) * 32 + a) * 8 + (ch ^ (a & 7))] = make_uint4(u[0], u[1], u[2], u[3]);
        }
    }
    if (first && blockIdx.x < 4 && tid == 0) asm volatile("cp.async.bulk.wait_group.read 0;" ::: "memory");
    TL(first ? 4 : 18);
}

constexpr int GST = 4, GSTB = 32768 + 20480, GNC = 32;
constexpr int G_BAR = GST * GSTB + 3072;
#define GPACE 1100
#define GPACE2 650
__device__ __forceinline__ void oproj_load(const uint32_t sb, const int op, const int mb, const int nb, const int c0, const uint32_t pace) {
    const int by = op == 2 ? 20480 : 16384;
    const char* src = op == 2 ? (const char*)g_wot + (size_t)nb * GNC * 20480 : (const char*)g_O + (size_t)(2 * mb + op) * GNC * 16384;
    uint32_t t0 = clock32() - pace + op * (pace / 3);
#pragma unroll 1
    for (int c = c0; c < c0 + GNC; c++, src += by) {
        const int st = c % GST;
        if (c >= GST) mbar_wait(sb + G_BAR + (GST + st) * 8, ((c / GST) - 1) & 1);
        while (clock32() - t0 < pace) {}
        t0 = clock32();
        const int by_ = by;
        mbar_expect(sb + G_BAR + st * 8, by_);
        if (op == 2) bulk_g2s(sb + st * GSTB + 32768, src, by_, sb + G_BAR + st * 8);
        else bulk_g2s_last(sb + st * GSTB + op * 16384, src, by_, sb + G_BAR + st * 8);
    }
}
__device__ __forceinline__ void oproj_mma(const uint32_t sb, const int mb, const int nb, const int c0, const bf16* res, bf16* out, const int layer) {
    const int w = threadIdx.x >> 5, lane = threadIdx.x & 31, wg = w >> 2;
    float acc[40];
    uint4 rv[5];
#pragma unroll 1
    for (int c = c0; c < c0 + GNC; c++) {
        const int st = c % GST;
        mbar_wait(sb + G_BAR + st * 8, (c / GST) & 1);
        const uint32_t d = sb + st * GSTB;
        wg_fence();
#pragma unroll
        for (int k = 0; k < 8; k++)
            wg_n80_ss(acc, mkdesc(d + wg * 16384 + k * 2048, 1024, 128, 0), mkdesc(d + 32768 + k * 2560, 1280, 128, 0), (c - c0) | k);
        wg_commit();
        if (c > c0) {
            wg_wait<1>();
            if (lane == 0) mbar_arrive(sb + G_BAR + (GST + (c - 1) % GST) * 8);
        }
    }
#pragma unroll
    for (int i = 0; i < 5; i++) {
        const int id = i * 32 + lane, r = id / 10;
        rv[i] = __ldcg((const uint4*)res + (size_t)(mb * 128 + w * 16 + r) * 80 + nb * 10 + id - r * 10);
    }
    wg_wait<0>();
    bar_sync(5, 256);
    const uint32_t stg = sb + (GST - 1) * GSTB + w * 16 * 176;
#pragma unroll
    for (int j = 0; j < 5; j++)
        stsm4(stg + (lane & 15) * 176 + (2 * j + (lane >> 4)) * 16, pack_bf(acc[j * 8], acc[j * 8 + 1]), pack_bf(acc[j * 8 + 2], acc[j * 8 + 3]),
              pack_bf(acc[j * 8 + 4], acc[j * 8 + 5]), pack_bf(acc[j * 8 + 6], acc[j * 8 + 7]));
    __syncwarp();
#pragma unroll
    for (int i = 0; i < 5; i++) {
        const int id = i * 32 + lane, r = id / 10, ch = id - r * 10;
        uint32_t y[4];
        lds128(y, stg + r * 176 + ch * 16);
        ((uint4*)out)[(size_t)(mb * 128 + w * 16 + r) * 80 + nb * 10 + ch] = add_bf8(rv[i], y);
    }
    fence_async_smem();
    __syncwarp();
    if (lane == 0) {
        mbar_arrive(sb + G_BAR + (2 * GST - 1) * 8);
        if (layer == 0) red_release(g_flag + F_R + 2 * mb + wg);
    }
}

__global__ void __launch_bounds__(128, 4) k_col(const int first) {
    __shared__ __align__(1024) char sz[8192];
    __shared__ __align__(1024) char stab[24576];
    __shared__ __align__(1024) char swf[8192];
    __shared__ __align__(8) uint64_t bar[2];
    const int tid = threadIdx.x, wl = tid >> 5, lane = tid & 31, g = lane >> 2, t = lane & 3;
    const int c = blockIdx.x;
    TL(first ? 5 : 19);
    const bool realc = c == 0 || c == 320;
    const uint32_t z = smem_u32(sz), b2 = smem_u32(stab), a1 = b2 + 16384, wf = smem_u32(swf), mb = smem_u32(bar);
    if (tid == 0) { mbar_init(mb, 1); mbar_init(mb + 8, 1); fence_async_smem(); }
    if (realc) {
        for (int i = tid; i < 256; i += 128) sts128(z + 4096 + i * 16, 0, 0, 0, 0);
        fence_async_smem();
    }
    const int k1 = wl * 8 + g;
    float tc[16], ts[16];
#pragma unroll
    for (int j = 0; j < 16; j++) {
        const int p = ((j >> 1) * 8 + 2 * t + (j & 1)) * k1;
        __sincosf((float)(p - 1024) * 0.003067961575771282f, &ts[j], &tc[j]);
        ts[j] = -ts[j]; tc[j] = -tc[j];
    }
    if (first && tid == 32) { wait_flag<400>(g_ready, NSETUP); fence_async_glb(); }
    __syncthreads();
    if (tid == 32) {
        mbar_expect(mb + 8, 24576 + 8192);
        bulk_g2s(b2, g_ctab, 24576, mb + 8);
        bulk_g2s(wf, g_Wf + (size_t)c * 2048, 8192, mb + 8);
    }
    float inv;
    const float wsc = pow2_scale(wfilter_max(lane), 0, &inv) * (realc ? 0.0625f : 0.125f);
    pdl_wait();
    TL(first ? 6 : 20);
    if (tid == 0) {
        const int by = realc ? 4096 : 8192;
        mbar_expect(mb, by);
        bulk_g2s_last(z, (const char*)g_UT + (size_t)(c == 320 ? 1 : 2 * c) * 4096, by, mb);
    }
    pdl_go();
    mbar_wait(mb + 8, 0);
    mbar_wait(mb, 0);
    float d[64];
    uint32_t a[4][4];
    wg_fence();
#pragma unroll
    for (int ks = 0; ks < 4; ks++) wg_n64_ss_tb<0>(d, mkdesc(a1 + ks * 2048, 1024, 128, 0), mkdesc(z + ks * 2048, 1024, 1024, 1), ks);
    wg_commit(); wg_wait<0>();
    const float r32 = 0.17677669529663687f;
#pragma unroll
    for (int j = 0; j < 8; j++) {
        float yr[2], yi[2];
#pragma unroll
        for (int e = 0; e < 2; e++) {
            const float re = d[j * 4 + e] * r32, im = d[j * 4 + 2 + e] * r32, cc = tc[j * 2 + e], ss = ts[j * 2 + e];
            yr[e] = re * cc + im * ss; yi[e] = im * cc - re * ss;
        }
        a[j >> 1][(j & 1) * 2] = pack_h(yr[0], yr[1]); a[j >> 1][(j & 1) * 2 + 1] = pack_h(yi[0], yi[1]);
    }
    wg_fence();
#pragma unroll
    for (int ks = 0; ks < 4; ks++) wg_n128_rs(d, a[ks], mkdesc(b2 + ks * 4096, 2048, 128, 0), ks);
    wg_commit(); wg_wait<0>();
#pragma unroll
    for (int q = 0; q < 4; q++) {
        uint32_t wv[4];
        lds128(wv, wf + tid * 64 + ((q ^ (tid >> 1)) & 3) * 16);
#pragma unroll
        for (int jj = 0; jj < 2; jj++) {
            const int j = 2 * q + jj;
            float yr[2], yi[2];
#pragma unroll
            for (int e = 0; e < 2; e++) {
                const float xr = d[j * 4 + e] + d[32 + j * 4 + 2 + e], xi = d[j * 4 + 2 + e] - d[32 + j * 4 + e];
                const float fr = bf_lo(wv[jj * 2 + e]) * wsc, fi = bf_hi(wv[jj * 2 + e]) * wsc;
                yr[e] = xr * fr - xi * fi; yi[e] = xr * fi + xi * fr;
            }
            a[q][jj * 2] = pack_h(yr[0], yr[1]); a[q][jj * 2 + 1] = pack_h(yi[0], yi[1]);
        }
    }
    wg_fence();
#pragma unroll
    for (int ks = 0; ks < 4; ks++) wg_n128_rs(d, a[ks], mkdesc(b2 + ks * 4096, 2048, 128, 0), ks);
    wg_commit(); wg_wait<0>();
#pragma unroll
    for (int j = 0; j < 8; j++) {
        float yr[2], yi[2];
#pragma unroll
        for (int e = 0; e < 2; e++) {
            const float vr = (d[j * 4 + e] - d[32 + j * 4 + 2 + e]) * 0.125f, vi = (d[j * 4 + 2 + e] + d[32 + j * 4 + e]) * 0.125f;
            const float cc = tc[j * 2 + e], ss = ts[j * 2 + e];
            yr[e] = vr * cc - vi * ss; yi[e] = vi * cc + vr * ss;
        }
        a[j >> 1][(j & 1) * 2] = pack_h(yr[0], yr[1]); a[j >> 1][(j & 1) * 2 + 1] = pack_h(yi[0], yi[1]);
    }
    __syncthreads();
    const int mm = lane >> 3, rr = lane & 7;
    const uint32_t rowo = (wl * 16 + (mm & 1) * 8 + rr) * 128;
#pragma unroll
    for (int q = 0; q < 4; q++) stsm4(z + rowo + (((2 * q + (mm >> 1)) ^ rr) << 4), a[q][0], a[q][1], a[q][2], a[q][3]);
    fence_async_smem();
    __syncthreads();
    wg_fence();
#pragma unroll
    for (int ks = 0; ks < 4; ks++) wg_n64_ss_tb<1>(d, mkdesc(a1 + ks * 256, 128, 1024, 0), mkdesc(z + ks * 2048, 1024, 1024, 1), ks);
    wg_commit(); wg_wait<0>();
#pragma unroll
    for (int q = 0; q < 4; q++)
        stsm4(wf + rowo + (((2 * q + (mm >> 1)) ^ rr) << 4), pack_h(d[q * 8] * r32, d[q * 8 + 1] * r32), pack_h(d[q * 8 + 2] * r32, d[q * 8 + 3] * r32),
              pack_h(d[q * 8 + 4] * r32, d[q * 8 + 5] * r32), pack_h(d[q * 8 + 6] * r32, d[q * 8 + 7] * r32));
    __syncwarp();
    if (!(realc && wl >= 2)) {
        const int kk = c == 320 ? 320 : (c & 1) * 160 + (c >> 1) + (wl >> 1) * 320;
#pragma unroll
        for (int i = 0; i < 4; i++) {
            const int r = wl * 16 + i * 4 + (lane >> 3), ch = lane & 7;
            uint32_t v[4];
            lds128(v, wf + r * 128 + ((ch ^ (r & 7)) << 4));
            ((uint4*)g_YT)[((size_t)(r & 31) * 640 + kk) * 8 + (ch ^ (kk & 7))] = make_uint4(v[0], v[1], v[2], v[3]);
        }
    }
    TL(first ? 7 : 21);
}

constexpr int O_XS = 0;
constexpr int O_MS = 81920;
constexpr int O_QKP = O_MS + 10752;
constexpr int O_VM = O_QKP + 4096;
constexpr int O_SC = O_VM + 4096;
constexpr int O_OS = O_SC + 1536;
constexpr int O_XCH = O_OS + 2048;
constexpr int O_SUM = O_XCH + 8192;
constexpr int O_MX = O_SUM + 256;
constexpr int O_STG = O_MS + 65536 - 8192;
static_assert(O_STG - 16384 >= O_MX + 1024, "shared-memory map");
constexpr int O_WO = O_STG + 16384;
constexpr int O_SCL = O_WO + 65536;
constexpr int O_BAR = O_SCL + 64;
constexpr int B_XF = O_BAR, B_S = O_BAR + 16, B_VX = O_BAR + 32, B_STG = O_BAR + 48, B_FREE = O_BAR + 72;
constexpr int T_FA = O_BAR + 96, T_EA = T_FA + 32, T_FB = T_EA + 32, T_EB = T_FB + 56, T_RED = T_EB + 32;
constexpr int O_WMX = O_BAR + 512, B_W = O_BAR + 64;
constexpr int O_LAST = (O_WMX + 192 + 1023) / 1024 * 1024;
constexpr int CH_SMEM = O_LAST + 8192;
static_assert(O_WO == 19 * 8192, "weight staging");
__device__ __forceinline__ uint32_t tail_b(int c) { return c % 7 < 4 ? O_XS + (c % 7) * 20480 : O_WO + (c % 7 - 4) * 20480; }
__device__ __forceinline__ int s_tx(int c) { return c == 2 ? 2 * 768 : 768 + 2048; }

#define NPERM 1
#define NWO0 1
#define NWO0B 4
#define NWO1 6
#define EN 25
#define VXN 100
#define AUNR 2
#define TDELAY 300
#define WDEPTH 6
#define RDELAY 570

#define STAMP(i)

#define NTA 23
#define NTB 26
template <int LO, int HI>
__device__ __forceinline__ void tok_issue(const uint32_t (&A0)[20][4], const uint32_t (&A1)[20][4], float (&b0)[16], float (&b1)[16], uint32_t xd,
                                          const uint32_t zero) {
    if (LO == 0) wg_fence();
    sfor<HI - LO>([&](auto I) {
        constexpr int i = LO + I;
        if constexpr (i < 20) wg_n32_x<i * 64, i>(b0, A0[i], xd); else wg_n32_x<(i - 20) * 64, i - 20>(b1, A1[i - 20], xd + zero);
        if constexpr (i == 19 || i == NTB - 1 || i == 39) wg_commit();
    });
}
__device__ __forceinline__ void tok_give(const float (&b0)[16], const uint32_t L16, const uint32_t xch0) {
    wg_wait<1>();
    sfor<2>([&](auto I) {
        constexpr int i = I;
        sts128_u<i * 512>(L16, xch0, pack_h(b0[8 * i], b0[8 * i + 1]), pack_h(b0[8 * i + 2], b0[8 * i + 3]), pack_h(b0[8 * i + 4], b0[8 * i + 5]),
                          pack_h(b0[8 * i + 6], b0[8 * i + 7]));
    });
}
__device__ __forceinline__ void tok_finish(float (&b1)[16], const uint32_t (&e)[2][4], const uint32_t L16, const uint32_t dst, const uint32_t idn) {
#pragma unroll
    for (int j = 0; j < 4; j++)
        asm volatile("mma.sync.aligned.m16n8k8.row.col.f32.f16.f16.f32 {%0,%1,%2,%3},{%4,%5},{%6},{%0,%1,%2,%3};"
                     : F4(b1, 4 * j) : "r"(e[j >> 1][(j & 1) * 2]), "r"(e[j >> 1][(j & 1) * 2 + 1]), "r"(idn));
    stsm4_u<0>(L16, dst, pack_bf(b1[0], b1[1]), pack_bf(b1[2], b1[3]), pack_bf(b1[4], b1[5]), pack_bf(b1[6], b1[7]));
    stsm4_u<512>(L16, dst, pack_bf(b1[8], b1[9]), pack_bf(b1[10], b1[11]), pack_bf(b1[12], b1[13]), pack_bf(b1[14], b1[15]));
}
__device__ __forceinline__ uint32_t uni(uint32_t v) { return __shfl_sync(~0u, v, 0); }
__device__ __forceinline__ uint32_t badd(uint32_t a, uint32_t b) { uint32_t r; asm("add.rn.bf16x2 %0,%1,%2;" : "=r"(r) : "r"(a), "r"(b)); return r; }
__device__ __forceinline__ uint32_t bmax(uint32_t a, uint32_t b) { uint32_t r; asm("max.bf16x2 %0,%1,%2;" : "=r"(r) : "r"(a), "r"(b)); return r; }
__device__ __forceinline__ uint32_t babsmax(uint32_t a, uint32_t b) { uint32_t r; asm("max.xorsign.abs.bf16x2 %0,%1,%2;" : "=r"(r) : "r"(a), "r"(b)); return r; }
__device__ __forceinline__ uint32_t habsmax(uint32_t a, uint32_t b) { uint32_t r; asm("max.xorsign.abs.f16x2 %0,%1,%2;" : "=r"(r) : "r"(a), "r"(b)); return r; }

template <int NPF>
__device__ __forceinline__ float mem_out(const uint32_t sb, const uint32_t L16, const uint32_t L8, uint32_t (&wo)[16][4], const uint32_t woa,
                                         char* dst, const bool odd) {
    bar_sync(2, 352);
    float a[4][4];
#pragma unroll
    for (int i = 0; i < 4; i++) a[i][0] = a[i][1] = a[i][2] = a[i][3] = 0.f;
    uint32_t ob[4][4], sm_[2], sc[2];
    sfor<8>([&](auto I) {
        constexpr int i = I;
        if constexpr (!(i & 1)) ldsm4t_u<O_OS + (i >> 1) * 512>(ob[i >> 1], L16, sb);
        if constexpr (i >= NPF) { ldsm4t(wo[i], woa + i * 1024); ldsm4t(wo[8 + i], (woa ^ 32) + i * 1024); }
    });
    lds64_u<O_SUM>(sm_, L8 & 24, sb); lds64(sc, sb + O_SCL);
#pragma unroll
    for (int i = 0; i < 8; i++) {
        mma_bf(a[i & 1], wo[i][0], wo[i][1], wo[i][2], wo[i][3], ob[i >> 1][(i & 1) * 2], ob[i >> 1][(i & 1) * 2 + 1]);
        mma_bf(a[2 + (i & 1)], wo[8 + i][0], wo[8 + i][1], wo[8 + i][2], wo[8 + i][3], ob[i >> 1][(i & 1) * 2], ob[i >> 1][(i & 1) * 2 + 1]);
    }
    const float f0 = rcp(__uint_as_float(sm_[0])) * __uint_as_float(sc[0]), f1 = rcp(__uint_as_float(sm_[1])) * __uint_as_float(sc[0]);
    red_h8(dst, pack_h((a[0][0] + a[1][0]) * f0, (a[0][1] + a[1][1]) * f1), pack_h((a[0][2] + a[1][2]) * f0, (a[0][3] + a[1][3]) * f1),
           pack_h((a[2][0] + a[3][0]) * f0, (a[2][1] + a[3][1]) * f1), pack_h(odd ? (a[2][3] + a[3][3]) * f1 : (a[2][2] + a[3][2]) * f0, 1.f));
    return __uint_as_float(sc[1]);
}

template <int NE, int UNR>
__device__ __forceinline__ void tok_attention(const uint32_t qk, const uint32_t dq, const uint32_t km, const uint32_t dk, const uint32_t vt, const uint32_t vm,
                                              const int e0, const int mi, const int lane, const int seg, const int h, const float iqk, const float iv) {
    const int g = lane >> 2, t = lane & 3;
    float s[6][4];
#pragma unroll
    for (int i = 0; i < 6; i++) s[i][0] = s[i][1] = s[i][2] = s[i][3] = 0.f;
#pragma unroll UNR
    for (int e = 0; e < 8; e++) {
        uint32_t q[4], k[4];
        ldsm4t(q, qk + (e >> 2) * dq + (e & 3) * 1024 + mi * 512);
        ldsm4t(k, km + (e >> 2) * dk + (e & 3) * 512);
        mma_bf(s[4], q[0], q[2], q[1], q[3], k[0], k[1]);
        mma_bf(s[5], q[0], q[2], q[1], q[3], k[2], k[3]);
        ldsm4t(k, qk + (e >> 2) * dq + 4096 + (e & 3) * 1024);
        mma_bf(s[0], q[0], q[2], q[1], q[3], k[0], k[1]);
        mma_bf(s[1], q[0], q[2], q[1], q[3], k[2], k[3]);
        if (mi) {
            ldsm4t(k, qk + (e >> 2) * dq + 4096 + (e & 3) * 1024 + 512);
            mma_bf(s[2], q[0], q[2], q[1], q[3], k[0], k[1]);
            mma_bf(s[3], q[0], q[2], q[1], q[3], k[2], k[3]);
        }
    }
#pragma unroll
    for (int q = 0; q < 4; q++) s[4][q] += s[5][q];
    const float sl = iqk * (0.08838834764831845f * 1.4426950408889634f);
    float mx[2] = {-3.0e38f, -3.0e38f};
#pragma unroll
    for (int i = 0; i < 5; i++)
#pragma unroll
        for (int q = 0; q < 4; q++) {
            const bool ok = i == 4 || (i * 8 + 2 * t + (q & 1)) <= (mi * 16 + g + (q >> 1) * 8);
            s[i][q] = ok ? s[i][q] * sl : -1.0e9f * 1.4426950408889634f;
            mx[q >> 1] = fmaxf(mx[q >> 1], s[i][q]);
        }
    float sum[2] = {0.f, 0.f};
#pragma unroll
    for (int r = 0; r < 2; r++) {
        mx[r] = fmaxf(mx[r], __shfl_xor_sync(~0u, mx[r], 1));
        mx[r] = fmaxf(mx[r], __shfl_xor_sync(~0u, mx[r], 2));
    }
#pragma unroll
    for (int i = 0; i < 5; i++)
#pragma unroll
        for (int q = 0; q < 4; q++) { s[i][q] = ex2(s[i][q] - mx[q >> 1]); sum[q >> 1] += s[i][q]; }
#pragma unroll
    for (int r = 0; r < 2; r++) {
        sum[r] += __shfl_xor_sync(~0u, sum[r], 1);
        sum[r] += __shfl_xor_sync(~0u, sum[r], 2);
        sum[r] = iv * rcp(sum[r]);
    }
    uint32_t pp[5][2];
#pragma unroll
    for (int i = 0; i < 5; i++) { pp[i][0] = pack_bf(s[i][0] * sum[0], s[i][1] * sum[0]); pp[i][1] = pack_bf(s[i][2] * sum[1], s[i][3] * sum[1]); }
    uint32_t* o = (uint32_t*)g_O + (((size_t)(seg >> 1) * 512 + h * 16) * 8 + (seg & 1) * 4 + mi * 2) * 32 + lane;
#pragma unroll(UNR == 8 ? NE : 1)
    for (int u = 0; u < NE; u++) {
        const int e = e0 + u;
        float o0[4] = {0.f, 0.f, 0.f, 0.f}, o1[4] = {0.f, 0.f, 0.f, 0.f};
        uint32_t v[4];
        lds64(v, vm + e * 256);
        mma_bf8(o0, pp[4][0], pp[4][1], v[0]);
        mma_bf8(o1, pp[4][0], pp[4][1], v[1]);
        ldsm4(v, vt + e * 1024);
        mma_bf(o0, pp[0][0], pp[0][1], pp[1][0], pp[1][1], v[0], v[2]);
        mma_bf(o1, pp[0][0], pp[0][1], pp[1][0], pp[1][1], v[1], v[3]);
        ldsm4(v, vt + e * 1024 + 512);
        mma_bf(o0, pp[2][0], pp[2][1], pp[3][0], pp[3][1], v[0], v[2]);
        mma_bf(o1, pp[2][0], pp[2][1], pp[3][0], pp[3][1], v[1], v[3]);
        o[(2 * e) * 256] = pack_bf(o0[0], o0[1]); o[(2 * e) * 256 + 32] = pack_bf(o0[2], o0[3]);
        o[(2 * e + 1) * 256] = pack_bf(o1[0], o1[1]); o[(2 * e + 1) * 256 + 32] = pack_bf(o1[2], o1[3]);
    }
}

__device__ __forceinline__
void attend_last(const uint32_t sb, const int layer) {
    const int tid = read_tid(), ln = tid & 31, w = tid >> 5;
    int h;
    asm volatile("mov.u32 %0,%%clusterid.x;" : "=r"(h));
    uint32_t inv[2];
    lds64(inv, sb + O_SCL + 16);
    mbar_wait(sb + B_S, (NSEG - 1) & 1);
    mbar_wait(sb + B_VX + 8, 0);
    if (layer == TLL) TL(54);
    if (w == 0 && ln < 2)
        asm volatile("mbarrier.arrive.relaxed.cluster.shared::cluster.b64 _,[%0];" ::"r"(mapa(sb + B_STG + 8, ln)) : "memory");
    tok_attention<2, AUNR>(sb + O_STG - 16384 + ln * 16, 16384, sb + O_LAST + ln * 16, 2048, sb + O_STG + 8192 - 16384 + ln * 16, sb + O_VM + 2048 + ln * 8,
                     (w >> 1) * 2, w & 1, ln, NSEG - 1, h, __uint_as_float(inv[0]), __uint_as_float(inv[1]));
    if (layer == TLL) TL(55);
    __syncwarp();
    if (ln == 0) red_release(g_flag + F_O + layer * 32 + 31);
    if (layer == TLL) TL(43);
}

template <int layer> __device__ __forceinline__ void chain_mma(const uint32_t sb, const int c, const int h, const uint32_t zero, const bf16* __restrict__ Wq,
                                          const bf16* __restrict__ Wk, const bf16* __restrict__ Wv, const bf16* __restrict__ Wo,
                                          const bf16* res, bf16* out) {
    int tid = read_tid(), lane = tid & 31;
    const int w = __shfl_sync(~0u, tid >> 5, 0), wg = w >> 2;
    [[maybe_unused]] const int cta = h * 3 + c;
    uint32_t A0[20][4], A1[20][4];
    const int t0 = (w & 3) + wg * 4, t1 = t0 ^ 4;
    float sl;
    {
        const int tl = tid & 127, r = tl >> 3, ch = tl & 7;
        const size_t so = (size_t)(wg * 320 + r) * 4096 + h * 128 + ch * 8;
        const bf16 *wa = (c == 2 ? Wv : Wq + c * 64) + so, *wb = (c == 2 ? Wv + 64 : Wk + c * 64) + so;
        const uint32_t ring = sb + wg * 4096;
        const uint32_t dst = ring + r * 128 + ((ch ^ r) & 7) * 16;
        const uint32_t src = ring + ((lane & 7) + (lane >> 4) * 8) * 128 + ((((w & 3) * 2 + ((lane >> 3) & 1)) ^ lane) & 7) * 16;
        const int q4 = lane & 3, gr = (c * 2 + ((w >> 1) & 1)) * 56 + (q4 == 3 ? 24 : (w & 1) * 32 + q4 * 8);
        const bf16* wo_ = Wo + (size_t)(h * 128 + (lane >> 2)) * 640 + wg * 320 + min(gr, 312);
        const uint32_t wdst = sb + O_WO + w * 8192 + (lane >> 2) * 64 + ((q4 ^ (lane >> 3)) & 3) * 16;
        auto issue = [&](int i) {
            if (i < 20) {
                const uint32_t d = dst + (i < 19 ? i * 8192 : O_LAST);
                cp_async16(d, wa + (size_t)i * 65536); cp_async16(d + 2048, wb + (size_t)i * 65536);
                if (i < 16) cp_async16(wdst + i * 512, wo_ + i * 5120, gr < 320 ? 16 : 0);
            }
            cp_commit();
        };
#pragma unroll 1
        for (int i = 0; i < WDEPTH; i++) issue(i);
        asm volatile("barrier.cluster.arrive.relaxed.aligned;" ::: "memory");
        float fa, fb;
        if (layer == 0) {
            uint32_t ma = 0, mb = 0;
#pragma unroll 1
            for (int i = 0; i < 20; i++) {
                issue(i + WDEPTH);
                cp_wait<WDEPTH>();
                const uint32_t d = dst + (i < 19 ? i * 8192 : O_LAST);
                uint32_t u[8];
                lds128(u, d); lds128(u + 4, d + 2048);
                ma = babsmax(babsmax(ma, babsmax(u[0], u[1])), babsmax(u[2], u[3])); mb = babsmax(babsmax(mb, babsmax(u[4], u[5])), babsmax(u[6], u[7]));
            }
            ma = __reduce_max_sync(~0u, max(ma & 0x7fffu, (ma >> 16) & 0x7fffu)); mb = __reduce_max_sync(~0u, max(mb & 0x7fffu, (mb >> 16) & 0x7fffu));
            asm volatile("barrier.cluster.wait.aligned;" ::: "memory");
            if (lane < 3)
                asm volatile("st.async.shared::cluster.mbarrier::complete_tx::bytes.v2.b32 [%0],{%1,%2},[%3];"
                             ::"r"(mapa(sb + O_WMX + (c * 8 + w) * 8, lane)), "r"(ma), "r"(mb), "r"(mapa(sb + B_W, lane)) : "memory");
            __syncwarp();
            {
                uint32_t off[4];
                float cs[4] = {0.f, 0.f, 0.f, 0.f};
#pragma unroll
                for (int q = 0; q < 4; q++) {
                    const int g_ = (c * 2 + ((w >> 1) & 1)) * 56 + (q == 3 ? 24 : (w & 1) * 32 + q * 8), col = wg * 320 + g_, nb = col / 80;
                    off[q] = g_ < 320 && !(q == 3 && (w & 1)) ? ((nb * 512 + h * 16) * 10 + (col - nb * 80) / 8) * 32 + lane : ~0u;
                }
                const uint32_t ta = sb + O_WO + w * 8192 + (lane & 7) * 64 + (((lane >> 3) ^ (lane >> 1)) & 3) * 16;
#pragma unroll 2
                for (int i = 0; i < 16; i++) {
                    uint32_t r[4];
                    ldsm4t(r, ta + i * 512);
#pragma unroll
                    for (int q = 0; q < 4; q++) {
                        if (off[q] != ~0u) ((uint32_t*)g_wot)[off[q] + i * 320] = r[q];
                        cs[q] += fabsf(bf_lo(r[q])) + fabsf(bf_hi(r[q]));
                    }
                }
                float cm = 0.f;
#pragma unroll
                for (int q = 0; q < 4; q++) {
                    cs[q] += __shfl_xor_sync(~0u, cs[q], 1); cs[q] += __shfl_xor_sync(~0u, cs[q], 2);
                    cm = fmaxf(cm, cs[q]);
                }
                const uint32_t n1 = __reduce_max_sync(~0u, __float_as_uint(cm));
                if (lane == 0) g_co[h * 32 + c * 8 + w] = __uint_as_float(n1);
            }
            mbar_wait(sb + B_W, 0);
            uint32_t v[2];
            lds64(v, sb + O_WMX + (lane < 24 ? lane : 0) * 8);
            const bool mine = (lane >> 3) < 3 && ((lane >> 4) == 1) == (c == 2);
            ma = __reduce_max_sync(~0u, mine ? v[0] : 0u); mb = __reduce_max_sync(~0u, mine ? v[1] : 0u);
            if (c == 2) ma = mb = max(ma, mb);
            fa = __uint_as_float(ma << 16); fb = __uint_as_float(mb << 16);
            if (tid == 0) {
                if (c != 1) g_wmx[h * 3 + c] = fa;
                if (c == 0) g_wmx[h * 3 + 1] = fb;
            }
        } else {
            fa = __ldcg(g_wmx + h * 3 + (c == 2 ? 2 : 0)); fb = __ldcg(g_wmx + h * 3 + (c == 2 ? 2 : 1));
            asm volatile("barrier.cluster.wait.aligned;" ::: "memory");
        }
        if (layer == TLL) TL(49);
        float ia, ib;
        const float sa = pow2_scale(fa, 6, &ia), sc_b = pow2_scale(fb, 6, &ib);
        sl = __uint_as_float(uni(__float_as_uint(ia * ib * (0.08838834764831845f * 1.4426950408889634f))));
        const uint32_t pa = pack_bf(sa, sa), pb = pack_bf(sc_b, sc_b);
        const int ahead = layer == 0 ? 20 : WDEPTH;
        auto convert = [&](int lo) {
#pragma unroll 1
            for (int i = lo; i < lo + 10; i++) {
                issue(i + ahead);
                cp_wait<WDEPTH>();
                const uint32_t d = dst + (i < 19 ? i * 8192 : O_LAST);
                uint32_t u[8];
                lds128(u, d); lds128(u + 4, d + 2048);
#pragma unroll
                for (int q = 0; q < 8; q++)
                    asm("{.reg .b32 m,l,u; mul.rn.bf16x2 m,%0,%1; shl.b32 l,m,16; and.b32 u,m,0xffff0000; cvt.rn.f16x2.f32 %0,u,l;}" : "+r"(u[q]) : "r"(q < 4 ? pa : pb));
                sts128(d, u[0], u[1], u[2], u[3]); sts128(d + 2048, u[4], u[5], u[6], u[7]);
            }
            bar_sync(6 + wg, 128);
        };
        const uint32_t s0 = src + wg * 2048, s1 = src + 2048 - wg * 2048;
        convert(0);
#pragma unroll
        for (int i = 0; i < 10; i++) { ldsm4t(A0[i], s0 + i * 8192); ldsm4t(A1[i], s1 + i * 8192); }
        if (layer == TLL) TL(50);
        convert(10);
#pragma unroll
        for (int i = 10; i < 20; i++) { ldsm4t(A0[i], s0 + (i < 19 ? i * 8192 : O_LAST)); ldsm4t(A1[i], s1 + (i < 19 ? i * 8192 : O_LAST)); }
        if (layer == TLL) TL(53);
        bar_arrive(9, 288);
        bar_sync(4, 288);
        asm volatile("barrier.cluster.arrive.relaxed.aligned;" ::: "memory");
    }
    const uint32_t idn = (lane >> 3) == (lane & 3) ? ((lane & 4) ? 0x3c000000u : 0x3c00u) : 0u;
    float invM = g_invM0;
    char* redp = red_base() + (size_t)layer * 32 * 32768 + w * 2048 + (lane >> 4) * 1024 + ((lane >> 3) & 1) * 256 + (lane & 7) * 16;
    const uint32_t ro2 = uni((w >> 1) * 4096 + 128), rown = uni(c == 2 ? ro2 : c * 16384);
    const uint32_t L16 = lane * 16, L8 = lane * 8, L4 = lane * 4;
    const uint32_t xch0 = uni(sb + O_XCH + t0 * 1024), xch1 = uni(sb + O_XCH + t1 * 1024);
    const uint32_t qo0 = uni(sb + O_QKP + (w & 3) * 1024 + (wg ? 768 : 0)), qp0 = uni(qo0 + (wg ? 128 : 256));
    const uint32_t qo1 = uni(sb + O_QKP + (w & 3) * 1024 + (wg ? 128 : 512)), qp1 = uni(qo1 + (wg ? 256 : 128));
    const uint32_t vo1 = uni(qo1 + (wg ? -128 : 256)), vp1 = uni(qp1 + (wg ? -128 : 256));
    const uint32_t msr = uni(sb + O_MS + wg * 5376);
    const uint32_t msw = uni(msr + ((w >> 1) & 1) * 896 + (w & 1) * 512), msh = uni(msr + ((w >> 1) & 1) * 896 + 384 + (w & 1) * 2);
    const uint32_t sco = uni(sb + O_SC + c * 768 + (w & 3) * 256);
    const uint32_t woa = sb + O_WO + w * 8192 + (lane >> 4) * 512 + (lane & 7) * 64 + (((lane >> 3) ^ (lane >> 1)) & 1) * 16 + ((lane >> 2) & 1) * 32;
    const uint32_t w512 = uni(sb + w * 512), w128 = uni(sb + w * 128);
    const uint32_t pd0 = uni(mapa(sb, c == 2 ? 0 : 2) - sb), pd1 = uni(mapa(sb, c == 1 ? 0 : 1) - sb);
    const bool scw = c < 2 && w >= 4 && w <= 6;
    uint32_t sn = uni(sb + O_STG + (c == 2 ? 8192 : 0) + t1 * 1024);
    uint32_t ka = uni(sb + (w == 6 ? O_QKP + 512 : O_STG + 4096 + (w & 1) * 512));
    uint32_t vs = uni(sb + O_VM + t1 * 256);
    uint32_t va = uni(sb + O_STG + 8192 + w * 2048), vr = uni(sb + O_VM + w * 512);
    const uint32_t sn2 = uni(2 * sn - 16384), ka2 = uni(2 * ka - (w == 6 ? 0 : 16384)), vs2 = uni(2 * vs + 2048), va2 = uni(2 * va - 16384),
                   vr2 = uni(2 * vr + 2048);
    uint32_t xd = uni((uint32_t)mkdesc(sb + O_XS + wg * 20480, 512, 128, 0));
    const uint32_t xd2 = uni(2 * xd + 2560);

    uint32_t wp[2 * NPERM + 1][4];
    sfor<NPERM>([&](auto I) { constexpr int i = I; ldsm4t(wp[2 * i], woa + i * 1024); ldsm4t(wp[2 * i + 1], (woa ^ 32) + i * 1024); });
    auto wo_fetch = [&](uint32_t (&wo)[16][4], auto I) {
        constexpr int i = I;
        if constexpr (i < NPERM) {
#pragma unroll
            for (int q = 0; q < 4; q++) { wo[i][q] = wp[2 * i][q]; wo[8 + i][q] = wp[2 * i + 1][q]; }
        } else { ldsm4t(wo[i], woa + i * 1024); ldsm4t(wo[8 + i], (woa ^ 32) + i * 1024); }
    };
    if (layer == TLL) TL(32);
    float b0[16], b1[16];
    mbar_wait(sb + B_XF, 0);
    if (layer == TLL) TL(33);
    tok_issue<0, NTB>(A0, A1, b0, b1, xd, zero);
    tok_give(b0, L16, xch0);
    tok_issue<NTB, 40>(A0, A1, b0, b1, xd, zero);
    bar_sync(4, 256);
    wg_wait<0>();
    {
        uint32_t e[2][4];
        lds128_u<0>(e[0], L16, xch1); lds128_u<512>(e[1], L16, xch1);
        tok_finish(b1, e, L16, sn, idn);
    }
    sn = sn2 - sn; xd = xd2 - xd;
    bar_sync(5, 288);
    asm volatile("barrier.cluster.wait.aligned;" ::: "memory");
    if (layer == TLL) TL(34);
    mbar_wait(sb + B_XF + 8, 0);
    if (layer == TLL) TL(35);
    tok_issue<0, NTA>(A0, A1, b0, b1, xd, zero);
    uint32_t tr = clock32() - RDELAY;

#pragma unroll 1
    for (int st = 0;; st++) {
        uint4 mv[3];
        asm volatile("{.reg .pred p; .reg .b32 t;\n"
                     "mov.b32 %0,0; mov.b32 %1,0; mov.b32 %2,0; mov.b32 %3,0; mov.b32 %4,0; mov.b32 %5,0; mov.b32 %6,0; mov.b32 %7,0;\n"
                     "mov.b32 %8,0; mov.b32 %9,0; mov.b32 %10,0; mov.b32 %11,0;\n"
                     "T_LOOP: mov.u32 t,%%clock; sub.u32 t,t,%14; setp.ge.u32 p,t,%15;\n"
                     "@p ld.relaxed.gpu.global.v4.u32 {%0,%1,%2,%3},[%12]; @p ld.relaxed.gpu.global.v4.u32 {%4,%5,%6,%7},[%12+16384];\n"
                     "@p ld.relaxed.gpu.global.v4.u32 {%8,%9,%10,%11},[%13];\n"
                     "@!p bra T_LOOP;}"
                     : "=r"(mv[0].x), "=r"(mv[0].y), "=r"(mv[0].z), "=r"(mv[0].w), "=r"(mv[1].x), "=r"(mv[1].y), "=r"(mv[1].z), "=r"(mv[1].w),
                       "=r"(mv[2].x), "=r"(mv[2].y), "=r"(mv[2].z), "=r"(mv[2].w)
                     : "l"(redp), "l"(redp + ro2), "r"(tr), "n"(RDELAY) : "memory");
        STAMP(10);
        tok_issue<NTA, NTB>(A0, A1, b0, b1, xd, zero);
        tok_give(b0, L16, xch0);
        tok_issue<NTB, 40>(A0, A1, b0, b1, xd, zero);
        xd = xd2 - xd;
        STAMP(9);
        if (zero >> 30) break;
        asm volatile("{.reg .pred p; .reg .b32 a,h,t,n; .reg .b16 l,u; .reg .b64 q;\n"
                     "add.u32 a,%12,%13; add.u32 h,%12,%14; mov.u32 n,0;\n"
                     "M_LOOP:\n .pragma \"nounroll\";\n"
                     "st.shared.b32 [a],%0; st.shared.b32 [a+128],%1; st.shared.b32 [a+256],%2; mov.b32 {l,u},%3; st.shared.b16 [h],l;\n"
                     "st.shared.b32 [a+1792],%4; st.shared.b32 [a+1920],%5; st.shared.b32 [a+2048],%6; mov.b32 {l,u},%7; st.shared.b16 [h+1792],l;\n"
                     "st.shared.b32 [a+3584],%8; st.shared.b32 [a+3712],%9; st.shared.b32 [a+3840],%10; mov.b32 {l,u},%11; st.shared.b16 [h+3584],l;\n"
                     "lop3.b32 t,%3,%7,0x50000000,0x7e; lop3.b32 t,t,%11,0x50000000,0xf6; setp.gt.u32 p,t,0xffff;\n"
                     "vote.sync.any.pred p,p,-1; add.u32 n,n,1; setp.lt.and.u32 p,n,%17,p; @!p bra M_DONE;\n"
                     "ld.relaxed.gpu.global.v4.u32 {%0,%1,%2,%3},[%15]; ld.relaxed.gpu.global.v4.u32 {%4,%5,%6,%7},[%15+16384];\n"
                     "cvt.u64.u32 q,%16; add.u64 q,q,%15; ld.relaxed.gpu.global.v4.u32 {%8,%9,%10,%11},[q];\n"
                     "bra M_LOOP;\n"
                     "M_DONE:}"
                     : "+r"(mv[0].x), "+r"(mv[0].y), "+r"(mv[0].z), "+r"(mv[0].w), "+r"(mv[1].x), "+r"(mv[1].y), "+r"(mv[1].z), "+r"(mv[1].w),
                       "+r"(mv[2].x), "+r"(mv[2].y), "+r"(mv[2].z), "+r"(mv[2].w)
                     : "r"(L4), "r"(msw), "r"(msh), "l"(redp), "r"(ro2), "n"(SPIN_LIM) : "memory");
        bar_sync(3, 256);
        STAMP(0);
        uint32_t e[2][4];
        float f1[4];
        {
            uint32_t b[10][4];
            float acc[4][4];
#pragma unroll
            for (int i = 0; i < 4; i++) acc[i][0] = acc[i][1] = acc[i][2] = acc[i][3] = 0.f;
            auto ld = [&](auto I) { constexpr int i = I; ldsm4t_u<i * 512>(b[i], L16, msr); };
            auto mm = [&](auto I) {
                constexpr int i = I;
                mma_f16(acc[0], A0[2 * i], b[i][0], b[i][1]); mma_f16(acc[2], A1[2 * i], b[i][0], b[i][1]);
                mma_f16(acc[1], A0[2 * i + 1], b[i][2], b[i][3]); mma_f16(acc[3], A1[2 * i + 1], b[i][2], b[i][3]);
            };
            ld(IC<0>()); ld(IC<1>()); ld(IC<2>()); ld(IC<3>());
            sts32_u<O_MX>(L4, w128,
                          habsmax(habsmax(habsmax(habsmax(mv[0].x, mv[0].y), habsmax(mv[0].z, mv[1].x)), habsmax(habsmax(mv[1].y, mv[1].z), mv[2].x)),
                                  habsmax(habsmax(mv[2].y, mv[2].z), habsmax(habsmax(mv[0].w, mv[1].w), mv[2].w) & 0xffffu)));
            wg_wait<0>();
            ld(IC<4>()); mm(IC<0>()); ld(IC<5>()); mm(IC<1>()); ld(IC<6>()); mm(IC<2>());
            ld(IC<7>()); mm(IC<3>()); ld(IC<8>()); mm(IC<4>()); ld(IC<9>()); mm(IC<5>());
            lds128_u<0>(e[0], L16, xch1); lds128_u<512>(e[1], L16, xch1);
            mm(IC<6>()); mm(IC<7>()); mm(IC<8>()); mm(IC<9>());
            const uint32_t u0 = pack_bf((acc[0][0] + acc[1][0]) * invM, (acc[0][1] + acc[1][1]) * invM);
            const uint32_t u1 = pack_bf((acc[0][2] + acc[1][2]) * invM, (acc[0][3] + acc[1][3]) * invM);
#pragma unroll
            for (int i = 0; i < 4; i++) f1[i] = (acc[2][i] + acc[3][i]) * invM;
            sts32_u<0>(L4, qo0, u0); sts32_u<0>(L4, qp0, u1); sts32_u<0>(L4, qo1, pack_bf(f1[0], f1[1])); sts32_u<0>(L4, qp1, pack_bf(f1[2], f1[3]));
        }
        STAMP(1);
        bar_sync(1, 320);
        if (__builtin_expect(scw, 1)) {
            float a[4][4];
#pragma unroll
            for (int i = 0; i < 4; i++) a[i][0] = a[i][1] = a[i][2] = a[i][3] = 0.f;
            uint32_t q[4][4], k[4][4];
            sfor<4>([&](auto I) {
                constexpr int i = I;
                ldsm4t_u<O_QKP + i * 1024>(q[i], L16, sb); ldsm4t_u<i * 1024>(k[i], L16, ka);
            });
#pragma unroll
            for (int i = 0; i < 4; i++) {
                mma_bf(a[i & 1], q[i][0], q[i][1], q[i][2], q[i][3], k[i][0], k[i][1]);
                mma_bf(a[2 + (i & 1)], q[i][0], q[i][1], q[i][2], q[i][3], k[i][2], k[i][3]);
            }
            const float mk = w == 6 ? 1.f : 0.f;
            const float x0 = (a[0][0] + a[0][2]) + (a[1][0] + a[1][2]), x1 = (a[0][1] + a[0][3]) + (a[1][1] + a[1][3]);
            const float y0 = (a[2][0] + a[2][2]) + (a[3][0] + a[3][2]), y1 = (a[2][1] + a[2][3]) + (a[3][1] + a[3][3]);
            st_share2(L8, sco, sb + B_S, pd0, pd1, pack_bf(fmaf(y0, mk, x0) * sl, fmaf(y1, mk, x1) * sl), pack_bf(y0 * sl, y1 * sl));
        }
        if (c == 2) {
            const uint32_t x = lds32_u<0>(L4, vo1), y = lds32_u<0>(L4, vp1);
            st_share2(L8, vs, sb + B_S, pd0, pd1, pack_bf(f1[0] + bf_lo(x), f1[1] + bf_hi(x)), pack_bf(f1[2] + bf_lo(y), f1[3] + bf_hi(y)));
        }
        STAMP(3);
        if (st == NSEG - 1) break;
        tok_finish(b1, e, L16, sn, idn);
        redp += (st & 1) ? 32768 - 512 : 512;
        if (wg == 0) {
            uint32_t wo[16][4], vx[2][2][4], vm[2][2];
            ldsm4_u<0>(vx[0][0], L16, va); ldsm4_u<512>(vx[0][1], L16, va); ldsm4_u<1024>(vx[1][0], L16, va); ldsm4_u<1536>(vx[1][1], L16, va);
            sfor<NWO0>([&](auto I) { wo_fetch(wo, I); });
            mbar_wait(sb + B_S, st & 1);
            STAMP(4);
            uint32_t s[5];
            {
                uint32_t p[2][5];
                sfor<2>([&](auto R) {
                    constexpr int r = R;
                    lds64_u<O_SC + r * 768>(p[r], L8, sb); lds64_u<O_SC + r * 768 + 256>(p[r] + 2, L8, sb); p[r][4] = lds32_u<O_SC + r * 768 + 512>(L8, sb);
                });
#pragma unroll
                for (int j = 0; j < 5; j++) s[j] = badd(p[0][j], p[1][j]);
            }
            lds64_u<0>(vm[0], L8, vr); lds64_u<256>(vm[1], L8, vr);
            uint32_t mm = bmax(bmax(bmax(s[0], s[1]), bmax(s[2], s[3])), s[4]);
            mm = bmax(bmax(mm, __shfl_xor_sync(~0u, mm, 1)), bmax(__shfl_xor_sync(~0u, mm, 2), __shfl_xor_sync(~0u, mm, 3)));
            const float m = fmaxf(bf_lo(mm), bf_hi(mm));
            float o0[4] = {0.f, 0.f, 0.f, 0.f}, o1[4] = {0.f, 0.f, 0.f, 0.f}, d[10];
#pragma unroll
            for (int j = 0; j < 5; j++) { d[2 * j] = bf_lo(s[j]) - m; d[2 * j + 1] = bf_hi(s[j]) - m; }
#pragma unroll
            for (int j = 0; j < 10; j++) d[(j + 8) % 10] = ex2(d[(j + 8) % 10]);
            float sum = ((d[8] + d[9]) + (d[0] + d[1])) + ((d[2] + d[3]) + (d[4] + d[5])) + (d[6] + d[7]);
            const uint32_t p4 = pack_bf(d[8], d[9]), p0 = pack_bf(d[0], d[1]), p1 = pack_bf(d[2], d[3]), p2 = pack_bf(d[4], d[5]), p3 = pack_bf(d[6], d[7]);
            mma_bf8(o0, vm[0][0], vm[0][1], p4);
            mma_bf8(o1, vm[1][0], vm[1][1], p4);
            mma_bf(o0, vx[0][0][0], vx[0][0][1], vx[0][0][2], vx[0][0][3], p0, p1);
            mma_bf(o1, vx[1][0][0], vx[1][0][1], vx[1][0][2], vx[1][0][3], p0, p1);
            mma_bf(o0, vx[0][1][0], vx[0][1][1], vx[0][1][2], vx[0][1][3], p2, p3);
            mma_bf(o1, vx[1][1][0], vx[1][1][1], vx[1][1][2], vx[1][1][3], p2, p3);
            sfor<NWO0B - NWO0>([&](auto I) { constexpr int i = I; wo_fetch(wo, IC<NWO0 + i>()); });
            sum += __shfl_xor_sync(~0u, sum, 1);
            sum += __shfl_xor_sync(~0u, sum, 2);
            sts32_u<O_OS>(L4, w512, pack_bf(o0[0], o0[1])); sts32_u<O_OS + 128>(L4, w512, pack_bf(o0[2], o0[3]));
            sts32_u<O_OS + 256>(L4, w512, pack_bf(o1[0], o1[1])); sts32_u<O_OS + 384>(L4, w512, pack_bf(o1[2], o1[3]));
            sts32_u<O_SUM>(lane & 28, sb, __float_as_uint(sum));
            STAMP(5);
            invM = mem_out<NWO0B>(sb, L16, L8, wo, woa, redp + rown, w & 1);
            tr = clock32();

        } else {
            uint32_t wo[16][4];
            sfor<NWO1>([&](auto I) { wo_fetch(wo, I); });
            invM = mem_out<NWO1>(sb, L16, L8, wo, woa, redp + rown, w & 1);
            tr = clock32();

        }
        STAMP(7);
        tok_issue<0, NTA>(A0, A1, b0, b1, xd, zero);
        sn = sn2 - sn; ka = ka2 - ka; vs = vs2 - vs; va = va2 - va; vr = vr2 - vr;
        STAMP(8);
    }
    if (layer == TLL) TL(40);
    if (c == 2) attend_last(sb, layer);
    bar_arrive(8, 320);
    tid = read_tid(); lane = tid & 31;
    float acc[40];
    const int nc = c == 2 ? 10 : 11;
    const int mb = 28 + (h >> 3), nj = c == 2 ? 1 : 2;
    uint32_t rv[2][2];
    const size_t go = ((size_t)(mb * 64 + (w & 3) * 16 + (lane >> 2)) * 640 + (h & 7) * 80 + (wg * 5 + c * 2) * 8 + (lane & 3) * 2) >> 1;
#pragma unroll
    for (int u = 0; u < 4; u++) rv[u >> 1][u & 1] = (u >> 1) < nj ? __ldcg((const uint32_t*)res + go + (u >> 1) * 4 + (u & 1) * 2560) : 0u;
#pragma unroll 1
    for (int k = 0; k < nc; k++) {
        mbar_wait(sb + T_FB + (k % 7) * 8, k >= 7);
        mbar_wait(sb + T_FA + (k & 3) * 8, (k >> 2) & 1);
        if (layer == TLL && k == 0) TL(41);
        const uint64_t da = mkdesc(sb + O_MS + (k & 3) * 16384 + wg * 8192, 1024, 128, 0), db = mkdesc(sb + tail_b(k) + wg * 10240, 1280, 128, 0);
        wg_fence();
#pragma unroll
        for (int q = 0; q < 4; q++) wg_n80_ss(acc, da + q * 128, db + q * 160, k | q);
        wg_commit();
        if (k > 0) {
            wg_wait<1>();
            if (lane == 0) { mbar_arrive(sb + T_EA + ((k - 1) & 3) * 8); if (k <= 4) mbar_arrive(sb + T_EB + (k - 1) * 8); }
        }
    }
    if (layer == TLL) TL(52);
    wg_wait<0>();
    asm volatile("barrier.cluster.arrive.relaxed.aligned; barrier.cluster.wait.aligned;" ::: "memory");
    const uint32_t ra = sb + O_XS + tid * 16, rb = sb + O_MS + tid * 16;
#pragma unroll
    for (int j = 0; j < 5; j++) {
        const float* q = acc + 4 * j;
        sts128(rb + j * 4096, __float_as_uint(wg ? q[0] : q[20]), __float_as_uint(wg ? q[1] : q[21]), __float_as_uint(wg ? q[2] : q[22]), __float_as_uint(wg ? q[3] : q[23]));
    }
    bar_sync(4, 256);
    sfor<5>([&](auto J) {
        constexpr int j = J;
        const float* q = acc + 4 * j;
        uint32_t p[4];
        lds128(p, sb + O_MS + (tid ^ 128) * 16 + j * 4096);
        const uint32_t d = ra + c * 8192 + (j & 1) * 4096;
        asm volatile("{.reg .pred p; setp.eq.u32 p,%7,%8;\n"
                     "@!p st.async.shared::cluster.mbarrier::complete_tx::bytes.v4.f32 [%0],{%1,%2,%3,%4},[%5]; @p st.shared.v4.f32 [%6],{%1,%2,%3,%4};}"
                     ::"r"(mapa(d, j >> 1)), "f"((wg ? q[20] : q[0]) + __uint_as_float(p[0])), "f"((wg ? q[21] : q[1]) + __uint_as_float(p[1])),
                     "f"((wg ? q[22] : q[2]) + __uint_as_float(p[2])), "f"((wg ? q[23] : q[3]) + __uint_as_float(p[3])), "r"(mapa(sb + T_RED, j >> 1)),
                     "r"(d), "r"(c), "n"(j >> 1) : "memory");
    });
    mbar_wait(sb + T_RED, 0);
#pragma unroll 1
    for (int u = 0; u < nj; u++) {
        uint32_t p[3][4];
#pragma unroll
        for (int q = 0; q < 3; q++) lds128(p[q], ra + q * 8192 + u * 4096);
        float y[4];
#pragma unroll
        for (int i = 0; i < 4; i++) y[i] = __uint_as_float(p[0][i]) + __uint_as_float(p[1][i]) + __uint_as_float(p[2][i]);
        ((uint32_t*)out)[go + u * 4] = bfma(pack_bf(y[0], y[1]), 0x3f803f80u, u ? rv[1][0] : rv[0][0]);
        ((uint32_t*)out)[go + u * 4 + 2560] = bfma(pack_bf(y[2], y[3]), 0x3f803f80u, u ? rv[1][1] : rv[0][1]);
    }
    __syncwarp();
    if (layer == 0 && lane == 0) red_release(g_flag + F_R + mb);
    TL(layer == 0 ? 15 : 29);
    asm volatile("barrier.cluster.arrive.relaxed.aligned; barrier.cluster.wait.aligned;" ::: "memory");
}

__device__ __forceinline__ void tail_load_b(const uint32_t sb, const int h, const int c, const int k) {
    mbar_expect(sb + T_FB + (k % 7) * 8, 20480);
    bulk_g2s(sb + tail_b(k), (const char*)g_wot + (size_t)((h & 7) * GNC + c * 11 + k) * 20480, 20480, sb + T_FB + (k % 7) * 8);
}
template <int layer> __device__ __forceinline__ void chain_aux(const uint32_t sb, const int c, const int h, const int nact) {
    const int tid = read_tid(), w = __shfl_sync(~0u, tid >> 5, 0), lane = tid & 31;
    if (w == 8) {
        mbar_init(sb + O_BAR + lane * 8, lane == 2 ? (c == 2 ? 9 : 4) : (lane >= 16 && lane < 20) || (lane >= 27 && lane < 31) ? 8 : 1);
        asm volatile("fence.mbarrier_init.release.cluster;" ::: "memory");
        fence_async_smem();
        __syncwarp();
    }
    {
        uint4* z = (uint4*)red_base() + layer * 65536;
#pragma unroll 1
        for (int i = blockIdx.x * 128 + tid - 256; i < 65536; i += 96 * 128)
            if (i >= 2048 || (i & 32)) z[i] = make_uint4(0, 0, 0, 0);
    }
    if (w == 8 && lane == 0) {
        mbar_expect(sb + B_S, s_tx(c));
        mbar_expect(sb + B_W, 192);
        mbar_expect(sb + T_RED, (c == 2 ? 1 : 2) * 2 * 4096);
        if (layer == 1) prefetch_l2(red_base() + 32 * 32768 + blockIdx.x * 1024, 1024);
        if (layer == 0) wait_flag<400>(g_ready, NSETUP);
    }
    __syncwarp();
    cluster_sync_full();
    asm volatile("barrier.cluster.arrive.relaxed.aligned;" ::: "memory");
    pdl_wait();
    if (w == 11 && lane == 0) red_relaxed(g_flag + F_X + layer * 128 + 65);
    Flag* flag = g_flag + layer * NSEG * 32 + h;
    const Flag* xflag = g_flag + F_X + layer * 128;
    char* const it0 = g_item + (size_t)h * 32768;
    if (w == 8) {
#pragma unroll 1
        for (int n = 0; n < 3; n++) {
            wait_flag<100>(xflag + (n >> 1), 4);
            fence_async_glb();
            if (n == 0) { bar_sync(4, 288); fence_async_smem(); }
            if (lane == 0 && n < 2) {
                mbar_expect(sb + B_XF + n * 8, 40960);
                bulk_g2s(sb + O_XS + n * 40960, (const char*)g_xn + n * 40960, 40960, sb + B_XF + n * 8);
            }
            __syncwarp();
        }
#pragma unroll 1
        for (int n = 0; n < NSEG - 1; n++) {
            const int np = n & 1;
            if (n == 0) { wait_flag<100>(g_flag + F_W + layer * 128, 96); bar_sync(5, 288); } else bar_sync(2, 352);
            if (n == 1) TL(12 + layer * 14);
            if (n == 63) TL(13 + layer * 14);
            if (lane == 0) {
                const uint32_t vs = sb + O_STG + 8192 - np * 16384, vb = sb + B_VX + np * 8;
                if (c == 2) {
                    if (n > 0) __nanosleep(VXN);
                    fence_async_smem();
                    bulk_s2s(mapa(vs, 0), vs, 8192, mapa(vb, 0));
                    bulk_s2s(mapa(vs, 1), vs, 8192, mapa(vb, 1));
                } else mbar_expect(vb, 8192);
                if (n == 0) { mbar_expect(sb + B_XF, 40960); bulk_g2s(sb + O_XS, (const char*)g_xn + 2 * 40960, 40960, sb + B_XF); }
                if (n == h * 3 + c && !np && n + 6 < NSEG) prefetch_l2(red_base() + (size_t)(layer * 32 + (n >> 1) + 3) * 32768, 32768);
            }
            __syncwarp();
        }
        {
            bar_sync(2, 352);
            TL(13 + layer * 14);
            if (lane == 0) {
                if (c == 2) mbar_expect(sb + B_VX + 8, 2 * 8192 + 2 * 2048);
                else {
                    fence_async_smem();
                    bulk_s2s(mapa(sb + O_STG - (c == 0 ? 16384 : 0), 2), sb + O_STG - 16384, 8192, mapa(sb + B_VX + 8, 2));
                }
            }
            __syncwarp();
        }
    } else if (w == 11) {
        float cvo;
        {
            auto max8 = [&](const float* p) {
                const float4 u = ((const float4*)p)[0], v = ((const float4*)p)[1];
                return fmaxf(fmaxf(fmaxf(u.x, u.y), fmaxf(u.z, u.w)), fmaxf(fmaxf(v.x, v.y), fmaxf(v.z, v.w)));
            };
            wait_flag<300>(g_flag + F_W + layer * 128, 96);
            const float* pc = g_co + lane * 32;
            float a = 640.f * __ldcg(g_wmx + lane * 3 + 2), o = fmaxf(fmaxf(max8(pc), max8(pc + 8)), max8(pc + 16));
#pragma unroll 1
            for (int s = 16; s; s >>= 1) { a = fmaxf(a, __shfl_xor_sync(~0u, a, s)); o += __shfl_xor_sync(~0u, o, s); }
            cvo = a * o * 2.f;
        }
        float invM = g_invM0;
        float iq, ik, iv;
        weight_scale(h, 0, &iq); weight_scale(h, 1, &ik); weight_scale(h, 2, &iv);
        if (lane == 0) sts64(sb + O_SCL + 16, __float_as_uint(iq * ik), __float_as_uint(iv));
        const uint32_t L16 = sb + lane * 16 + O_MX;
#pragma unroll 1
        for (int st = 0; st < NSEG; st++) {
            bar_sync(1, 320);
            if (st == NSEG - 1) break;
            if (lane == 0) mbar_arrive(sb + B_STG + (st & 1) * 8);
            uint32_t u[2][4];
            lds128(u[0], L16); lds128(u[1], L16 + 512);
            uint32_t mx = habsmax(habsmax(habsmax(u[0][0], u[0][1]), habsmax(u[0][2], u[0][3])), habsmax(habsmax(u[1][0], u[1][1]), habsmax(u[1][2], u[1][3])));
            mx = __reduce_max_sync(~0u, max(mx & 0x7fffu, (mx >> 16) & 0x7fffu));
            const float bound = fmaxf(__half2float(__ushort_as_half((unsigned short)mx)) * invM, 25.5f) * cvo;
            const float sc = pow2_scale(bound, 15, &invM);
            sts64(sb + O_SCL, __float_as_uint(sc * iv), __float_as_uint(invM));
            bar_arrive(2, 352);
        }
    } else if (w == 10) {
        bar_sync(9, 288);
        if (lane == 0) red_release(g_flag + F_W + layer * 128);
        if (lane == 0) {
#pragma unroll 1
            for (int n = 0; n < NSEG - 1; n++) {
                mbar_sleep(sb + B_STG + (n & 1) * 8, (n >> 1) & 1);
                __nanosleep(EN);
                fence_async_smem();
                const uint32_t stg = sb + O_STG - (n & 1) * 16384;
                char* it = it0 + (size_t)(n % RING) * 32 * 32768;
                bulk_s2g(it + c * 8192, stg + (c == 2 ? 8192 : 0), 8192);
                bulk_commit();
                if (n + 1 >= RING && n + 1 < NSEG) wait_flag(flag - (RING - 1) * 32, 7);
                bulk_wait0();
                mbar_arrive(sb + B_FREE + (n & 1) * 8);
                fence_async_glb();
                red_relaxed(flag);
                flag += 32;
            }
        }
    } else {
        bool allx = false;
#pragma unroll 1
        for (int st = 0; st < NSEG - 1; st++) {
            const int par = st & 1;
            char* const it = it0 + (size_t)(st % RING) * 32 * 32768;
            if (lane == 0 && !allx && st + 3 < NSEG) {
                allx = ld_acquire(xflag + 64) >= nact;
                if (!allx) wait_flag(st + 4 < NSEG ? xflag + ((st + 3) >> 1) : xflag + 64, st + 4 < NSEG ? 4 : nact);
                fence_async_glb();
            }
            __syncwarp();
            if (c < 2) mbar_sleep(sb + B_VX + par * 8, (st >> 1) & 1);
            if (st < NSEG - 2) mbar_sleep(sb + B_XF + par * 8, ((st >> 1) + 1) & 1);
            bar_sync(1, 320);
            if (lane == 0 && st + 3 < NSEG) {
                mbar_expect(sb + B_XF + (par ^ 1) * 8, 40960);
                bulk_g2s_last(sb + O_XS + (par ^ 1) * 40960, (const char*)g_xn + (size_t)(st + 3) * 40960, 40960, sb + B_XF + (par ^ 1) * 8);
            } else if (lane == 0) {
                tail_load_b(sb, h, c, (par ^ 1) * 2); tail_load_b(sb, h, c, (par ^ 1) * 2 + 1);
            }
            __syncwarp();
            if (lane == 0 && c < 2) {
                fence_async_smem();
#pragma unroll 1
                for (int i = 0; i < 4; i++) bulk_s2g(it + 24576 + (c * 4 + i) * 512, sb + O_QKP + i * 1024 + 512, 512);
                bulk_commit();
                asm volatile("cp.async.bulk.wait_group.read 0;" ::: "memory");
            }
            __syncwarp();
            bar_arrive(2, 352);
            mbar_sleep(sb + B_S, par);
            __syncwarp();
            if (lane == 0) {
                mbar_expect(sb + B_S, s_tx(c));
                if (c == 2) { fence_async_smem(); bulk_s2g(it + 28672, sb + O_VM + par * 2048, 2048); bulk_commit(); }
            }
            __syncwarp();
            if (lane == 0) { bulk_wait0(); fence_async_glb(); red_relaxed(flag); }
            __syncwarp();
            mbar_sleep(sb + B_FREE + par * 8, (st >> 1) & 1);
            flag += 32;
        }
        {
            bar_sync(1, 320);
            if (lane == 0 && c < 2) {
                fence_async_smem();
#pragma unroll 1
                for (int i = 0; i < 4; i++)
                    bulk_s2s(mapa(sb + O_LAST + (c * 4 + i) * 512, 2), sb + O_QKP + i * 1024 + 512, 512, mapa(sb + B_VX + 8, 2));
            }
            __syncwarp();
            bar_arrive(8, 320);
        }
    }
    __syncwarp();
    const int nc = c == 2 ? 10 : 11;
    if (w == 10) {
        bar_sync(8, 320);
        if (lane == 0) {
            if (layer == 1 && blockIdx.x == 0) g_ready[0].v = 0;
            if (c < 2) mbar_sleep(sb + B_STG + 8, 1);
            fence_async_smem();
            __nanosleep(TDELAY);
            wait_flag(xflag + 64, nact);
            wait_flag<50>(g_flag + F_O + layer * 32 + 28 + (h >> 3), (h >> 3) == 3 ? 32 + 8 * 32 : 64);
            fence_async_glb();
#pragma unroll 1
            for (int k = 0; k < nc; k++) {
                if (k >= 4) mbar_sleep(sb + T_EA + (k & 3) * 8, ((k >> 2) - 1) & 1);
                mbar_expect(sb + T_FA + (k & 3) * 8, 16384);
                bulk_g2s_last(sb + O_MS + (k & 3) * 16384, (const char*)g_O + (size_t)((28 + (h >> 3)) * GNC + c * 11 + k) * 16384, 16384, sb + T_FA + (k & 3) * 8);
            }
        }
    } else if (w == 9 && lane == 0) {
        __nanosleep(TDELAY);
#pragma unroll 1
        for (int k = 4; k < nc; k++) {
            if (k >= 7) mbar_sleep(sb + T_EB + (k - 7) * 8, 0);
            tail_load_b(sb, h, c, k);
        }
    }
    __syncwarp();
    asm volatile("barrier.cluster.wait.aligned;" ::: "memory");
    asm volatile("barrier.cluster.arrive.relaxed.aligned; barrier.cluster.wait.aligned;" ::: "memory");
    asm volatile("barrier.cluster.arrive.relaxed.aligned; barrier.cluster.wait.aligned;" ::: "memory");
}

constexpr int RI_A = 0, RI_TAB = 81920, RI_STG = RI_TAB + 82 * 768;
constexpr int RI_RES = RI_STG + 25600, RI_ST = RI_RES + 2 * 64 * 336;
constexpr int HB_A = G_BAR + 64, HB_AFREE = HB_A + 32, HB_LN = HB_A + 40, HB_FULL = HB_A + 64, HB_DONE = HB_FULL + 48, HB_FREE = HB_DONE + 48;
constexpr int HP_SMEM = HB_FREE + 48;
static_assert(G_BAR >= RI_ST + 2048, "helper shared-memory map");
#define IDL 280
#define ITEM_NS 60
#define PFW_AT 28
#define PFW_NS 150
__device__ __forceinline__ void helper_aux(const uint32_t sb, const int j, const int nh, const int na, const int nbh, const int layer, const bf16* Wq,
                                           const bf16* Wk, const bf16* Wv, const bf16* Wo) {
    const int w = threadIdx.x >> 5, lane = threadIdx.x & 31, p = w - 8;
    if (lane == 0 && j < (nh & ~3)) {
        int n = 0;
        for (int a = j >> 2; a < 32; a += nh >> 2, n++) {
            if (n == 0) continue;
            mbar_wait(sb + HB_AFREE, (n - 1) & 1);
            mbar_expect(sb + HB_A + p * 8, 20480);
            bulk_g2s_last(sb + RI_A + p * 20480, (const char*)g_YT + (size_t)a * 81920 + p * 20480, 20480, sb + HB_A + p * 8);
            if (p == 0) { mbar_wait(sb + HB_LN, (n - 1) & 1); red_release(g_flag + F_X + layer * 128 + a - (nh >> 2)); }
        }
        if (p == 0) { mbar_wait(sb + HB_LN, (n - 1) & 1); red_release(g_flag + F_X + layer * 128 + (j >> 2) + (n - 1) * (nh >> 2)); }
    }
    __syncwarp();
    if (layer == 0 && w == 8 && lane == 0) wait_flag<400>(g_flag + F_W, 96);
    __syncwarp();
    bar_sync(3, 384);
    if (p == 3 && lane == 0 && j < (nh & ~3)) red_release(g_flag + F_X + layer * 128 + 64);
    fence_async_smem();
    Flag* oflag = g_flag + F_O + layer * 32;
    if (j < na) {
        int sl = p & 1, ph = 1;
        for (int idx = j + (p & 1) * na; idx < (NSEG - 1) * 32 && p >= 2 && lane == 0; idx += 2 * na) {
            mbar_wait(sb + HB_DONE + sl * 8, ph ^ 1);
            mbar_arrive(sb + HB_FREE + sl * 8);
            red_release(oflag + (idx >> 6));
            atomicAdd(&g_flag[layer * NSEG * 32 + idx].v, 1u);
            sl += 2;
            if (sl >= 6) { sl -= 6; ph ^= 1; }
        }
        for (int idx = j + p * na; idx < (NSEG - 1) * 32 && p < 2 && lane == 0; idx += 2 * na) {
            mbar_wait(sb + HB_FREE + sl * 8, ph);
            wait_flag<ITEM_NS>(g_flag + layer * NSEG * 32 + idx, 6);
            fence_async_glb();
            if (idx < (NSEG - 2) * 32) __nanosleep(IDL);
            mbar_expect(sb + HB_FULL + sl * 8, 30720);
            bulk_g2s(sb + sl * 30720, g_item + (size_t)(idx % (RING * 32)) * 32768, 30720, sb + HB_FULL + sl * 8);
            sl += 2;
            if (sl >= 6) { sl -= 6; ph ^= 1; }
        }
    } else if (lane == 0 && p == 3) {
        if (layer == 0) {
            wait_flag<1000>(oflag + PFW_AT, 64);
            const int np = nh - na;
#pragma unroll 1
            for (int i = j - na; i < 1280; i += np) {
                const bf16* W = i < 320 ? Wq : i < 640 ? Wk : i < 960 ? Wv : Wo;
                prefetch_l2((const char*)W + (size_t)(i % 320) * 16384, 16384);
                __nanosleep(PFW_NS);
            }
#pragma unroll 1
            for (int i = j - na; i < 205; i += np) {
                const char* p_ = i < 160 ? (const char*)g_Wf + i * 16384 : i < 165 ? (const char*)g_stat + (i - 144) * 16384
                               : i < 167 ? (const char*)g_ctab + (i - 165) * 8192 : (const char*)(g_flag + NFLAG) - (i - 166) * 16384;
                prefetch_l2(p_, 16384);
                __nanosleep(PFW_NS);
            }
            if (j - na < 16) prefetch_l2(g_rtab + (j - na) * (RF_A / 4), RF_A / 4);
#pragma unroll 1
            for (int i = j - na; i < 130; i += np) { prefetch_l2((const char*)g_xb + i * 16384, 16384); __nanosleep(PFW_NS); }
        }
    } else if (lane == 0) {
        if (p == 2) wait_flag<500>(g_flag + F_X + layer * 128 + 64, nh & ~3);
        int c0 = 0;
        for (int mb = (j - na) >> 3; mb < nbh; mb += (nh - na) >> 3, c0 += GNC) {
            if (p < 2) wait_flag<300>(oflag + 2 * mb + p, 64);
            fence_async_glb();
            oproj_load(sb, p, mb, (j - na) & 7, c0, nh - na < 24 ? 0 : mb == nbh - 1 ? GPACE2 : GPACE);
        }
    }
}
__device__ __forceinline__ void helper_mma(char* sm, const int jh, const int nh, const int na, const int nbh, const int layer, const bf16* res, bf16* x,
                                           bf16* out) {
    const uint32_t sb = smem_u32(sm);
    const int tid = threadIdx.x, w = tid >> 5, lane = tid & 31;
    const bool act = jh < (nh & ~3);
    const int j4 = jh & 3;
    const int fr = tid & 63, rg = w >> 1;
    auto chunk0 = [&](int u) { return u == 0 ? 5 * j4 : u == 1 ? 75 - 5 * j4 : u == 2 ? 40 + 5 * j4 : 35 - 5 * j4; };
    const int gr = tid / 20, gq_ = tid - gr * 20, go = gr * 80 + chunk0(gq_ / 5) + gq_ % 5;
    const uint32_t gs = sb + RI_RES + gr * 336 + gq_ * 16;
    auto residual = [&](int a, int n) {
#pragma unroll 1
        for (int r = 0; r < 64 - gr && tid < 240 && a < 32; r += 12) cp_async16(gs + (n & 1) * 21504 + r * 336, (const uint4*)res + (a * 64 + r) * 80 + go);
        cp_commit();
    };
    if (act) {
        if (tid < 240) {
            const int k0 = tid / 48, n = tid - k0 * 48;
            const float d = (float)(40 * j4 + n), amp = 2.f * 0.03952847075210474f;
#pragma unroll 4
            for (int u = 0; u < 16; u++)
                *(uint4*)(sm + RI_TAB + (tid + u * 240) * 16) = cos_row8(fmaf((float)((k0 + (u & 3) * 5) * 16 + ((u >> 2) & 1)), d, (float)((u & 8) * 20)), 2.f * d, amp);
            if (tid < 96) *(uint4*)(sm + RI_TAB + (3840 + tid) * 16) = make_uint4(k0 == 0 ? pack_h((n & 1) ? -amp : amp, 0.f) : 0u, 0, 0, 0);
        }
        fence_async_smem();
        residual(jh >> 2, 0);
    }
    bar_sync(1, 384);
    if (layer == TLL) TL(36);
    if (act) {
        const float4 wm = ((const float4*)g_wmax)[lane];
        const int wg = w >> 2;
        int n = 0;
#pragma unroll 1
        for (int a = jh >> 2; a < 32; a += nh >> 2, n++) {
            float acc[2][24];
            uint64_t da = mkdesc(sb + RI_A + wg * 40960, 1024, 1024, 1), db = mkdesc(sb + RI_TAB + wg * 30720, 768, 128, 0);
#pragma unroll
            for (int gq = 0; gq < 2; gq++) {
                mbar_wait(sb + HB_A + (wg * 2 + gq) * 8, n & 1);
                if (layer == TLL && n == TLN && gq == 0) TL(45);
                wg_fence();
#pragma unroll 5
                for (int k = 0; k < 10; k++) { wg_n48_ss_ta(acc[gq], da, db, k); da += 128; db += 96; }
                wg_commit();
            }
            if (wg == 0) {
                mbar_wait(sb + HB_A + 16, n & 1);
                wg_fence();
                wg_n48_ss_ta(acc[0], da, db + 20 * 96, 1);
                wg_commit();
            }
            float inv;
            pow2_scale(__uint_as_float(__reduce_max_sync(~0u, __float_as_uint(fmaxf(fmaxf(wm.x, wm.y), fmaxf(wm.z, wm.w))))), 0, &inv);
            const uint32_t ysc = pack_bf(inv, inv);
            wg_wait<0>();
            if (layer == TLL && n == TLN) TL(46);
            if (lane == 0) mbar_arrive(sb + HB_AFREE);
            const uint32_t ad = sb + RI_STG + ((w & 3) * 16 + (lane & 15)) * 400 + (lane >> 4) * 96 + wg * 192;
#pragma unroll
            for (int q = 0; q < 6; q++) {
                const float *e = acc[0] + q * 4, *o = acc[1] + q * 4;
                stsm4(ad + q * 16, pack_h(e[0] + o[0], e[1] + o[1]), pack_h(e[2] + o[2], e[3] + o[3]), pack_h(e[0] - o[0], e[1] - o[1]), pack_h(e[2] - o[2], e[3] - o[3]));
            }
            cp_wait<0>();
            bar_sync(4, 256);
            const uint32_t xa = sb + RI_RES + (n & 1) * 21504 + fr * 336 + rg * 80, sg = (rg & 1) ? 0xbc00bc00u : 0x3c003c00u;
            float sum = 0.f, sq = 0.f;
            uint32_t ya = sb + RI_STG + fr * 400 + (rg >> 1) * 96 + ((rg & 1) ? 64 : 0), carry;
            asm("fma.rn.f16x2 %0,%1,%2,%3;" : "=r"(carry) : "r"(lds32(ya + 208)), "r"(sg), "r"(lds32(ya + 16)));
#pragma unroll 1
            for (int ch = 0; ch < 5; ch++, ya += (rg & 1) ? -16 : 16) {
                uint32_t y[4], z[4], xr[4];
                lds128(y, ya); lds128(z, ya + 192); lds128(xr, xa + ch * 16);
#pragma unroll
                for (int q = 0; q < 4; q++) asm("fma.rn.f16x2 %0,%1,%2,%0;" : "+r"(y[q]) : "r"(z[q]), "r"(sg));
                if (rg & 1) {
                    const uint32_t y0 = y[0], y1 = y[1];
                    y[0] = __byte_perm(carry, y[3], 0x7610); y[1] = __byte_perm(y[3], y[2], 0x7610);
                    y[3] = __byte_perm(y1, y0, 0x7610); y[2] = __byte_perm(y[2], y1, 0x7610);
                    carry = y0;
                }
#pragma unroll
                for (int q = 0; q < 4; q++) {
                    const float2 yf = __half22float2(*(const __half2*)&y[q]);
                    xr[q] = bfma(pack_bf(yf.x, yf.y), ysc, xr[q]);
                    const float e = bf_lo(xr[q]), f = bf_hi(xr[q]);
                    sum += e + f; sq = fmaf(e, e, fmaf(f, f, sq));
                }
                sts128(xa + ch * 16, xr[0], xr[1], xr[2], xr[3]);
            }
            uint2* stat = g_stat + (size_t)(layer * 32 + a) * 1024 + rg * 64 + fr;
            asm volatile("st.relaxed.gpu.global.v2.u32 [%0],{%1,%2};" ::"l"(stat + j4 * 256), "r"(__float_as_uint(sum)), "r"(__float_as_uint(sq) | 0x80000000u) : "memory");
            if (layer == TLL && n == TLN) TL(47);
            uint32_t s0[3], s1[3];
            int lim = 0;
            do {
#pragma unroll
                for (int q = 0; q < 3; q++)
                    asm volatile("ld.relaxed.gpu.global.v2.u32 {%0,%1},[%2];" : "=r"(s0[q]), "=r"(s1[q]) : "l"(stat + ((j4 + 1 + q) & 3) * 256) : "memory");
            } while (__any_sync(~0u, (int)(s1[0] & s1[1] & s1[2]) >= 0) && ++lim < SPIN_LIM);
#pragma unroll
            for (int q = 0; q < 3; q++) { sum += __uint_as_float(s0[q]); sq -= __uint_as_float(s1[q]); }
            sts64(sb + RI_ST + tid * 8, __float_as_uint(sum), __float_as_uint(sq));
            bar_sync(4, 256);
            if (layer == TLL && n == TLN) TL(48);
#pragma unroll
            for (int q = 1; q < 4; q++) {
                uint32_t st2[2];
                lds64(st2, sb + RI_ST + ((tid + q * 64) & 255) * 8);
                sum += __uint_as_float(st2[0]); sq += __uint_as_float(st2[1]);
            }
            const float mean = sum * (1.f / 640.f), r = rsqrtf(fmaxf(fmaf(-mean, mean, sq * (1.f / 640.f)), 0.f) + 1e-5f), off = -mean * r;
            uint4* dst = (uint4*)g_xn + ((size_t)(2 * a + (w & 1)) * 80 + chunk0(rg)) * 32 + lane;
#pragma unroll
            for (int i = 0; i < 5; i++) {
                uint32_t u[4];
                lds128(u, xa + i * 16);
                dst[i * 32] = make_uint4(pack_h(fmaf(bf_lo(u[0]), r, off), fmaf(bf_hi(u[0]), r, off)), pack_h(fmaf(bf_lo(u[1]), r, off), fmaf(bf_hi(u[1]), r, off)),
                                         pack_h(fmaf(bf_lo(u[2]), r, off), fmaf(bf_hi(u[2]), r, off)), pack_h(fmaf(bf_lo(u[3]), r, off), fmaf(bf_hi(u[3]), r, off)));
            }
            __syncwarp();
            if (lane == 0) mbar_arrive(sb + HB_LN);
            if (layer == TLL) TL(37);
            if (layer == TLL && n == TLN) TL(44);
            residual(a + (nh >> 2), n + 1);
#pragma unroll 2
            for (int rr = 0; rr < 64 - gr && tid < 240; rr += 12) {
                uint32_t v[4];
                lds128(v, gs + (n & 1) * 21504 + rr * 336);
                ((uint4*)x)[(a * 64 + rr) * 80 + go] = make_uint4(v[0], v[1], v[2], v[3]);
            }
        }
    }
    bar_sync(3, 384);
    if (layer == TLL) TL(38);
    if (jh >= na) {
        int c0 = 0;
#pragma unroll 1
        for (int mb = (jh - na) >> 3; mb < nbh; mb += (nh - na) >> 3, c0 += GNC) oproj_mma(sb, mb, (jh - na) & 7, c0, x, out, layer);
        if (layer == TLL) TL(42);
        return;
    }
    const int p = w >> 1, mi = w & 1;
    int slot = p, ph = 0;
    for (int idx = jh + p * na; idx < (NSEG - 1) * 32; idx += 4 * na) {
        const uint32_t it = sb + slot * 30720 + lane * 16;
        float iq, ik, iv;
        weight_scale(idx & 31, 0, &iq); weight_scale(idx & 31, 1, &ik); weight_scale(idx & 31, 2, &iv);
        bar_sync(6 + p, 64);
        mbar_wait(sb + HB_DONE + slot * 8, ph ^ 1);
        mbar_wait(sb + HB_FULL + slot * 8, ph);
        tok_attention<8, 8>(it, 8192, it + 24576, 2048, it + 16384, it - lane * 8 + 28672, 0, mi, lane, idx >> 5, idx & 31, iq * ik, iv);
        __syncwarp();
        if (lane == 0) mbar_arrive(sb + HB_DONE + slot * 8);
        slot += 4;
        if (slot >= 6) { slot -= 6; ph ^= 1; }
    }
    if (layer == TLL) TL(39);
}

template <int layer> __global__ void __cluster_dims__(3, 1, 1) __launch_bounds__(384, 1)
k_chain(const int nact, const uint32_t zero, const bf16* __restrict__ Wq, const bf16* __restrict__ Wk, const bf16* __restrict__ Wv,
        const bf16* __restrict__ Wo, const bf16* res, bf16* out) {
    extern __shared__ __align__(1024) char sm[];
    const uint32_t sb = smem_u32(sm);
    const int b = blockIdx.x, h = b / 3, c = b - h * 3;
    pdl_go();
    if (threadIdx.x >= 256) {
        asm volatile("setmaxnreg.dec.sync.aligned.u32 24;");
        TL(11 + layer * 14);
        chain_aux<layer>(sb, c, h, nact);
    } else {
        asm volatile("setmaxnreg.inc.sync.aligned.u32 240;");
        chain_mma<layer>(sb, c, h, zero, Wq, Wk, Wv, Wo, res, out);
    }
}
__global__ void __launch_bounds__(384, 1) k_help(const bf16* res, bf16* x, bf16* out, const int layer, const int na, const int nbh, const int zero, const bf16* Wq,
                                                  const bf16* Wk, const bf16* Wv, const bf16* Wo) {
    extern __shared__ __align__(1024) char sm[];
    if (layer == TLL) TL(51);
    pdl_go();
    if (threadIdx.x >= 256) {
        const uint32_t sb = smem_u32(sm);
        const int p = (threadIdx.x >> 5) - 8, i = (threadIdx.x & 31) * 4 + p;
        if (i < 34) mbar_init(sb + G_BAR + i * 8, i < 4 ? 3 : i < 8 || i == 12 || i == 13 ? 8 : i >= 22 && i < 28 ? 2 : 1);
        fence_async_smem();
        wait_flag<100>(g_flag + F_X + layer * 128 + 65, 1);
        fence_async_glb();
        if (i == 8 + p && blockIdx.x < (gridDim.x & ~3)) {
            mbar_expect(sb + HB_A + p * 8, 20480);
            bulk_g2s(sb + RI_A + p * 20480, (const char*)g_YT + (size_t)(blockIdx.x >> 2) * 81920 + p * 20480, 20480, sb + HB_A + p * 8);
        }
        __syncwarp();
        bar_sync(2, 128);
        bar_arrive(1, 384);
    }
    if (threadIdx.x + zero >= 256) helper_aux(smem_u32(sm), blockIdx.x, gridDim.x, na, nbh, layer, Wq, Wk, Wv, Wo);
    else helper_mma(sm, blockIdx.x, gridDim.x, na, nbh, layer, res, x, out);
    __syncwarp();
    if (blockIdx.x == 0) pdl_wait();
}

#define COL_PAD 15872
template <class... P, class... A>
void launch_pdl(void (*k)(P...), int grid, int block, int smem, cudaStream_t st, A... args) {
    cudaLaunchConfig_t cfg = {};
    cfg.gridDim = dim3(grid); cfg.blockDim = dim3(block); cfg.dynamicSmemBytes = smem; cfg.stream = st;
    cudaLaunchAttribute at[1];
    at[0].id = cudaLaunchAttributeProgrammaticStreamSerialization; at[0].val.programmaticStreamSerializationAllowed = 1;
    cfg.attrs = at;
    cfg.numAttrs = 1;
    cudaLaunchKernelEx(&cfg, k, args...);
}

}

extern "C" void kernel_launch(void* const* d_in, const int* in_sizes, int n_in, void* d_out, int out_size) {
    const bf16* x = (const bf16*)d_in[0];
    const bf16* wr = (const bf16*)d_in[1];
    const bf16* wi = (const bf16*)d_in[2];
    const bf16* mem0 = (const bf16*)d_in[4];
    const bf16* Wq = (const bf16*)d_in[5];
    const bf16* Wk = (const bf16*)d_in[6];
    const bf16* Wv = (const bf16*)d_in[7];
    const bf16* Wo = (const bf16*)d_in[8];
    bf16* out = (bf16*)d_out;
    static int nhelp = 0;
    static bf16 *xa, *xb;
    static cudaStream_t s1;
    static cudaEvent_t ev_fork, ev_join;
    if (!nhelp) {
        cudaStreamCreateWithFlags(&s1, cudaStreamNonBlocking);
        cudaEventCreateWithFlags(&ev_fork, cudaEventDisableTiming);
        cudaEventCreateWithFlags(&ev_join, cudaEventDisableTiming);
        cudaFuncSetAttribute(k_setup, cudaFuncAttributeMaxDynamicSharedMemorySize, SU_SMEM);
        cudaFuncSetAttribute(k_rowf<0>, cudaFuncAttributeMaxDynamicSharedMemorySize, RF_SMEM);
        cudaFuncSetAttribute(k_rowf<1>, cudaFuncAttributeMaxDynamicSharedMemorySize, RF_SMEM);
        cudaFuncSetAttribute(k_col, cudaFuncAttributeMaxDynamicSharedMemorySize, COL_PAD);
        cudaFuncSetAttribute(k_chain<0>, cudaFuncAttributeMaxDynamicSharedMemorySize, CH_SMEM);
        cudaFuncSetAttribute(k_chain<1>, cudaFuncAttributeMaxDynamicSharedMemorySize, CH_SMEM);
        cudaFuncSetAttribute(k_setup, cudaFuncAttributePreferredSharedMemoryCarveout, 100);
        cudaFuncSetAttribute(k_rowf<0>, cudaFuncAttributePreferredSharedMemoryCarveout, 100);
        cudaFuncSetAttribute(k_rowf<1>, cudaFuncAttributePreferredSharedMemoryCarveout, 100);
        cudaFuncSetAttribute(k_col, cudaFuncAttributePreferredSharedMemoryCarveout, 100);
        cudaFuncSetAttribute(k_chain<0>, cudaFuncAttributePreferredSharedMemoryCarveout, 100);
        cudaFuncSetAttribute(k_chain<1>, cudaFuncAttributePreferredSharedMemoryCarveout, 100);
        cudaFuncSetAttribute(k_help, cudaFuncAttributeMaxDynamicSharedMemorySize, HP_SMEM);
        cudaFuncSetAttribute(k_help, cudaFuncAttributePreferredSharedMemoryCarveout, 100);
        int dev = 0, sms = 0;
        cudaGetDevice(&dev);
        cudaDeviceGetAttribute(&sms, cudaDevAttrMultiProcessorCount, dev);
        nhelp = sms - 96 < 12 ? 12 : sms - 96;
        cudaGetSymbolAddress((void**)&xa, g_xa);
        cudaGetSymbolAddress((void**)&xb, g_xb);
    }
    const int na = nhelp - (nhelp >= 36 ? 24 : nhelp >= 28 ? 16 : 8), nbh = 14;
    cudaStream_t s0 = cudaStreamPerThread;
    cudaEventRecord(ev_fork, s0);
    cudaStreamWaitEvent(s1, ev_fork, 0);
    k_rowf<1><<<(96 + nhelp) & ~1, 256, RF_SMEM, s0>>>(x);
    k_setup<<<NSETUP, 256, SU_SMEM, s1>>>(wr, wi, mem0);
    cudaEventRecord(ev_join, s1);
#define NLAYER 2
    for (int l = 0; l < NLAYER; l++) {
        const bf16* xin = l == 0 ? x : xb;
        if (l == 1) launch_pdl(k_rowf<0>, 128, 256, RF_SMEM, s0, xin);
        launch_pdl(k_col, 321, 128, l == 0 ? 0 : COL_PAD, s0, (int)(l == 0));
        launch_pdl(l == 0 ? k_chain<0> : k_chain<1>, 96, 384, CH_SMEM, s0, nhelp & ~3, 0u, Wq, Wk, Wv, Wo, (const bf16*)xa, l == 0 ? xb : out);
        launch_pdl(k_help, nhelp, 384, HP_SMEM, s0, xin, xa, l == 0 ? xb : out, l, na, nbh, 0, Wq, Wk, Wv, Wo);
    }
    cudaStreamWaitEvent(s0, ev_join, 0);
}
```

```cpp
#include <cuda_runtime.h>
#include <cuda_bf16.h>
#include <cuda_fp16.h>
#include <stdint.h>
#include <string.h>

namespace {

typedef __nv_bfloat16 bf16;
constexpr int S_ = 2048, D_ = 640, NSEG = 64;
constexpr int SPIN_LIM = 1 << 13;

__device__ float                  g_wmx[96];
__device__ __align__(1024) bf16   g_wot[4096 * 640];
__device__ __align__(16) float    g_co[1024];
__device__ __align__(256) uint2   g_stat[2 * 32 * 16 * 64];
__device__ float                  g_invM0;
__device__ __align__(16) float    g_wmax[128];
__device__ __align__(1024) char   g_redraw[65 * 32768];
constexpr int F_X = 2 * NSEG * 32, F_O = F_X + 2 * 128, NFLAG = F_O + 128, RING = 8;
constexpr int F_W = F_X + 66;
constexpr int F_R = F_O + 64;
constexpr int NSETUP = 131;
struct __align__(256) Flag { unsigned v; };
__device__ Flag                   g_flag[NFLAG];
__device__ Flag                   g_ready[1];
__device__ __align__(1024) char   g_item[RING * 32 * 32768];
__device__ __align__(1024) bf16   g_O[S_ * 4096];
__device__ __align__(1024) __half g_xn[S_ * D_];
__device__ __align__(1024) bf16   g_xa[S_ * D_];
__device__ __align__(1024) bf16   g_xb[S_ * D_];
__device__ __align__(1024) __half g_UT[D_ * S_];
__device__ __align__(1024) __half g_YT[D_ * S_];
__device__ __align__(1024) __half g_ctab[64 * 128 + 64 * 64];
__device__ __align__(1024) uint32_t g_Wf[321 * 2048];

#define TL(i)
#define TLN 0
#define TLL 1
#define CK(i)
__device__ __forceinline__ uint32_t smem_u32(const void* p) { return (uint32_t)__cvta_generic_to_shared(p); }
__device__ __forceinline__ uint32_t mapa(uint32_t a, uint32_t r) { uint32_t o; asm("mapa.shared::cluster.u32 %0,%1,%2;" : "=r"(o) : "r"(a), "r"(r)); return o; }
__device__ __forceinline__ void mbar_init(uint32_t a, int c) { asm volatile("mbarrier.init.shared::cta.b64 [%0],%1;" ::"r"(a), "r"(c) : "memory"); }
__device__ __forceinline__ void mbar_expect(uint32_t a, int bytes) { asm volatile("mbarrier.arrive.expect_tx.shared::cta.b64 _,[%0],%1;" ::"r"(a), "r"(bytes) : "memory"); }
__device__ __forceinline__ void mbar_arrive(uint32_t a) { asm volatile("mbarrier.arrive.shared::cta.b64 _,[%0];" ::"r"(a) : "memory"); }
__device__ __forceinline__ bool mbar_try(uint32_t a, uint32_t par) {
    uint32_t p;
    asm volatile("{.reg .pred q; mbarrier.try_wait.parity.shared::cta.b64 q,[%1],%2; selp.u32 %0,1,0,q;}" : "=r"(p) : "r"(a), "r"(par) : "memory");
    return p;
}
__device__ __forceinline__ void mbar_wait(uint32_t a, uint32_t par) {
    if (!mbar_try(a, par)) {
        int lim = 0;
        while (!mbar_try(a, par) && ++lim < SPIN_LIM) {}
    }
}
__device__ __forceinline__ void mbar_sleep(uint32_t a, uint32_t par) {
    asm volatile("{.reg .pred q; .reg .u32 n; mov.u32 n,0;\n"
                 "W_LOOP: mbarrier.try_wait.parity.shared::cta.b64 q,[%0],%1,%2; add.u32 n,n,1; setp.lt.and.u32 q,n,%3,!q; @q bra W_LOOP;}"
                 ::"r"(a), "r"(par), "n"(20000), "n"(SPIN_LIM) : "memory");
}
__device__ __forceinline__ void bar_arrive(int id, int n) { asm volatile("bar.arrive %0,%1;" ::"r"(id), "r"(n) : "memory"); }
__device__ __forceinline__ uint32_t clock32() { uint32_t c; asm volatile("mov.u32 %0,%%clock;" : "=r"(c)); return c; }
__device__ __forceinline__ uint32_t read_tid() { uint32_t v; asm volatile("mov.u32 %0,%%tid.x;" : "=r"(v)); return v; }
__device__ __forceinline__ void bar_sync(int id, int n) { asm volatile("bar.sync %0,%1;" ::"r"(id), "r"(n) : "memory"); }
__device__ __forceinline__ void fence_async_smem() { asm volatile("fence.proxy.async.shared::cta;" ::: "memory"); }
__device__ __forceinline__ void fence_async_glb() { asm volatile("fence.proxy.async.global;" ::: "memory"); }
__device__ __forceinline__ void cluster_sync_full() { asm volatile("barrier.cluster.arrive.aligned; barrier.cluster.wait.aligned;" ::: "memory"); }
__device__ __forceinline__ void bulk_g2s(uint32_t dst, const void* src, int bytes, uint32_t mb) {
    asm volatile("cp.async.bulk.shared::cluster.global.mbarrier::complete_tx::bytes [%0],[%1],%2,[%3];" ::"r"(dst), "l"(src), "r"(bytes), "r"(mb) : "memory");
}
__device__ __forceinline__ void bulk_g2s_last(uint32_t dst, const void* src, int bytes, uint32_t mb) {
    asm volatile("{.reg .b64 p; createpolicy.fractional.L2::evict_first.b64 p, 1.0;\n"
                 "cp.async.bulk.shared::cluster.global.mbarrier::complete_tx::bytes.L2::cache_hint [%0],[%1],%2,[%3],p;}"
                 ::"r"(dst), "l"(src), "r"(bytes), "r"(mb) : "memory");
}
__device__ __forceinline__ void bulk_s2s(uint32_t dst, uint32_t src, int bytes, uint32_t mb) {
    asm volatile("cp.async.bulk.shared::cluster.shared::cta.mbarrier::complete_tx::bytes [%0],[%1],%2,[%3];" ::"r"(dst), "r"(src), "r"(bytes), "r"(mb) : "memory");
}
__device__ __forceinline__ void bulk_s2g(void* dst, uint32_t src, int bytes) {
    asm volatile("cp.async.bulk.global.shared::cta.bulk_group [%0],[%1],%2;" ::"l"(dst), "r"(src), "r"(bytes) : "memory");
}
__device__ __forceinline__ void cp_async16(uint32_t dst, const void* src, uint32_t bytes = 16) {
    asm volatile("cp.async.cg.shared.global [%0],[%1],16,%2;" ::"r"(dst), "l"(src), "r"(bytes) : "memory");
}
__device__ __forceinline__ void cp_commit() { asm volatile("cp.async.commit_group;" ::: "memory"); }
template <int N> __device__ __forceinline__ void cp_wait() { asm volatile("cp.async.wait_group %0;" ::"n"(N) : "memory"); }
__device__ __forceinline__ void bulk_commit() { asm volatile("cp.async.bulk.commit_group;" ::: "memory"); }
__device__ __forceinline__ void bulk_wait0() { asm volatile("cp.async.bulk.wait_group 0;" ::: "memory"); }
__device__ __forceinline__ void ldsm4(uint32_t* r, uint32_t a) {
    asm volatile("ldmatrix.sync.aligned.m8n8.x4.shared.b16 {%0,%1,%2,%3},[%4];" : "=r"(r[0]), "=r"(r[1]), "=r"(r[2]), "=r"(r[3]) : "r"(a) : "memory");
}
__device__ __forceinline__ void ldsm4t(uint32_t* r, uint32_t a) {
    asm volatile("ldmatrix.sync.aligned.m8n8.x4.trans.shared.b16 {%0,%1,%2,%3},[%4];" : "=r"(r[0]), "=r"(r[1]), "=r"(r[2]), "=r"(r[3]) : "r"(a) : "memory");
}
__device__ __forceinline__ void stsm4(uint32_t a, uint32_t r0, uint32_t r1, uint32_t r2, uint32_t r3) {
    asm volatile("stmatrix.sync.aligned.m8n8.x4.shared.b16 [%0],{%1,%2,%3,%4};" ::"r"(a), "r"(r0), "r"(r1), "r"(r2), "r"(r3) : "memory");
}
__device__ __forceinline__ void stsm4t(uint32_t a, uint32_t r0, uint32_t r1, uint32_t r2, uint32_t r3) {
    asm volatile("stmatrix.sync.aligned.m8n8.x4.trans.shared.b16 [%0],{%1,%2,%3,%4};" ::"r"(a), "r"(r0), "r"(r1), "r"(r2), "r"(r3) : "memory");
}
__device__ __forceinline__ void lds128(uint32_t* r, uint32_t a) {
    asm volatile("ld.shared.v4.b32 {%0,%1,%2,%3},[%4];" : "=r"(r[0]), "=r"(r[1]), "=r"(r[2]), "=r"(r[3]) : "r"(a) : "memory");
}
__device__ __forceinline__ void lds64(uint32_t* r, uint32_t a) {
    asm volatile("ld.shared.v2.b32 {%0,%1},[%2];" : "=r"(r[0]), "=r"(r[1]) : "r"(a) : "memory");
}
__device__ __forceinline__ uint32_t lds32(uint32_t a) { uint32_t v; asm volatile("ld.shared.b32 %0,[%1];" : "=r"(v) : "r"(a) : "memory"); return v; }
__device__ __forceinline__ void sts128(uint32_t a, uint32_t r0, uint32_t r1, uint32_t r2, uint32_t r3) {
    asm volatile("st.shared.v4.b32 [%0],{%1,%2,%3,%4};" ::"r"(a), "r"(r0), "r"(r1), "r"(r2), "r"(r3) : "memory");
}
__device__ __forceinline__ void sts64(uint32_t a, uint32_t v0, uint32_t v1) { asm volatile("st.shared.v2.b32 [%0],{%1,%2};" ::"r"(a), "r"(v0), "r"(v1) : "memory"); }
[[maybe_unused]] __device__ __forceinline__ void sts32(uint32_t a, uint32_t v) { asm volatile("st.shared.b32 [%0],%1;" ::"r"(a), "r"(v) : "memory"); }
#define AU_(op) "{.reg .u32 t; add.u32 t,%4,%5; " op " {%0,%1,%2,%3},[t+%6];}"
template <int I> __device__ __forceinline__ void ldsm4_u(uint32_t* r, uint32_t a, uint32_t u) {
    asm volatile(AU_("ldmatrix.sync.aligned.m8n8.x4.shared.b16") : "=r"(r[0]), "=r"(r[1]), "=r"(r[2]), "=r"(r[3]) : "r"(a), "r"(u), "n"(I) : "memory");
}
template <int I> __device__ __forceinline__ void ldsm4t_u(uint32_t* r, uint32_t a, uint32_t u) {
    asm volatile(AU_("ldmatrix.sync.aligned.m8n8.x4.trans.shared.b16") : "=r"(r[0]), "=r"(r[1]), "=r"(r[2]), "=r"(r[3]) : "r"(a), "r"(u), "n"(I) : "memory");
}
template <int I> __device__ __forceinline__ void lds128_u(uint32_t* r, uint32_t a, uint32_t u) {
    asm volatile(AU_("ld.shared.v4.b32") : "=r"(r[0]), "=r"(r[1]), "=r"(r[2]), "=r"(r[3]) : "r"(a), "r"(u), "n"(I) : "memory");
}
template <int I> __device__ __forceinline__ void lds64_u(uint32_t* r, uint32_t a, uint32_t u) {
    asm volatile("{.reg .u32 t; add.u32 t,%2,%3; ld.shared.v2.b32 {%0,%1},[t+%4];}" : "=r"(r[0]), "=r"(r[1]) : "r"(a), "r"(u), "n"(I) : "memory");
}
template <int I> __device__ __forceinline__ uint32_t lds32_u(uint32_t a, uint32_t u) {
    uint32_t v;
    asm volatile("{.reg .u32 t; add.u32 t,%1,%2; ld.shared.b32 %0,[t+%3];}" : "=r"(v) : "r"(a), "r"(u), "n"(I) : "memory");
    return v;
}
template <int I> __device__ __forceinline__ void sts64_u(uint32_t a, uint32_t u, uint32_t v0, uint32_t v1) {
    asm volatile("{.reg .u32 t; add.u32 t,%0,%1; st.shared.v2.b32 [t+%2],{%3,%4};}" ::"r"(a), "r"(u), "n"(I), "r"(v0), "r"(v1) : "memory");
}
template <int I> __device__ __forceinline__ void sts32_u(uint32_t a, uint32_t u, uint32_t v) {
    asm volatile("{.reg .u32 t; add.u32 t,%0,%1; st.shared.b32 [t+%2],%3;}" ::"r"(a), "r"(u), "n"(I), "r"(v) : "memory");
}
template <int I> __device__ __forceinline__ void sts16_u(uint32_t a, uint32_t u, uint32_t v) {
    asm volatile("{.reg .u32 t; add.u32 t,%0,%1; st.shared.b16 [t+%2],%3;}" ::"r"(a), "r"(u), "n"(I), "h"((unsigned short)v) : "memory");
}
template <int I> __device__ __forceinline__ void sts128_u(uint32_t a, uint32_t u, uint32_t r0, uint32_t r1, uint32_t r2, uint32_t r3) {
    asm volatile("{.reg .u32 t; add.u32 t,%0,%1; st.shared.v4.b32 [t+%2],{%3,%4,%5,%6};}" ::"r"(a), "r"(u), "n"(I), "r"(r0), "r"(r1), "r"(r2), "r"(r3) : "memory");
}
template <int I> __device__ __forceinline__ void stsm4_u(uint32_t a, uint32_t u, uint32_t r0, uint32_t r1, uint32_t r2, uint32_t r3) {
    asm volatile("{.reg .u32 t; add.u32 t,%0,%1; stmatrix.sync.aligned.m8n8.x4.shared.b16 [t+%2],{%3,%4,%5,%6};}"
                 ::"r"(a), "r"(u), "n"(I), "r"(r0), "r"(r1), "r"(r2), "r"(r3) : "memory");
}
__device__ __forceinline__ void st_share2(uint32_t a, uint32_t u, uint32_t mb, uint32_t d0, uint32_t d1, uint32_t v0, uint32_t v1) {
    asm volatile("{.reg .pred p; .reg .u32 t,x,y; add.u32 t,%0,%1;\n"
                 "add.u32 x,t,%3; add.u32 y,%2,%3; st.async.shared::cluster.mbarrier::complete_tx::bytes.v2.b32 [x],{%5,%6},[y];\n"
                 "add.u32 x,t,%4; add.u32 y,%2,%4; st.async.shared::cluster.mbarrier::complete_tx::bytes.v2.b32 [x],{%5,%6},[y];\n"
                 "st.shared.v2.b32 [t],{%5,%6}; bar.warp.sync -1; setp.eq.u32 p,%0,0; @p mbarrier.arrive.shared::cta.b64 _,[%2];}"
                 ::"r"(a), "r"(u), "r"(mb), "r"(d0), "r"(d1), "r"(v0), "r"(v1) : "memory");
}
template <int V> struct IC { __host__ __device__ constexpr operator int() const { return V; } };
template <int N, class F> __device__ __forceinline__ void sfor(F f) {
    if constexpr (N > 0) { sfor<N - 1>(f); f(IC<N - 1>()); }
}
__device__ __forceinline__ void mma_f16(float* d, const uint32_t* a, uint32_t b0, uint32_t b1) {
    asm volatile("mma.sync.aligned.m16n8k16.row.col.f32.f16.f16.f32 {%0,%1,%2,%3},{%4,%5,%6,%7},{%8,%9},{%0,%1,%2,%3};"
                 : "+f"(d[0]), "+f"(d[1]), "+f"(d[2]), "+f"(d[3]) : "r"(a[0]), "r"(a[1]), "r"(a[2]), "r"(a[3]), "r"(b0), "r"(b1));
}
__device__ __forceinline__ void mma_bf(float* d, uint32_t a0, uint32_t a1, uint32_t a2, uint32_t a3, uint32_t b0, uint32_t b1) {
    asm volatile("mma.sync.aligned.m16n8k16.row.col.f32.bf16.bf16.f32 {%0,%1,%2,%3},{%4,%5,%6,%7},{%8,%9},{%0,%1,%2,%3};"
                 : "+f"(d[0]), "+f"(d[1]), "+f"(d[2]), "+f"(d[3]) : "r"(a0), "r"(a1), "r"(a2), "r"(a3), "r"(b0), "r"(b1));
}
__device__ __forceinline__ void mma_bf8(float* d, uint32_t a0, uint32_t a1, uint32_t b0) {
    asm volatile("mma.sync.aligned.m16n8k8.row.col.f32.bf16.bf16.f32 {%0,%1,%2,%3},{%4,%5},{%6},{%0,%1,%2,%3};"
                 : "+f"(d[0]), "+f"(d[1]), "+f"(d[2]), "+f"(d[3]) : "r"(a0), "r"(a1), "r"(b0));
}
__device__ __forceinline__ uint32_t pack_bf(float lo, float hi) { uint32_t r; asm("cvt.rn.bf16x2.f32 %0,%1,%2;" : "=r"(r) : "f"(hi), "f"(lo)); return r; }
__device__ __forceinline__ uint32_t pack_h(float lo, float hi) { uint32_t r; asm("cvt.rn.f16x2.f32 %0,%1,%2;" : "=r"(r) : "f"(hi), "f"(lo)); return r; }
__device__ __forceinline__ float bf_lo(uint32_t v) { return __uint_as_float(v << 16); }
__device__ __forceinline__ float bf_hi(uint32_t v) { return __uint_as_float(v & 0xffff0000u); }
__device__ __forceinline__ uint32_t bfma(uint32_t a, uint32_t b, uint32_t c) { uint32_t r; asm("fma.rn.bf16x2 %0,%1,%2,%3;" : "=r"(r) : "r"(a), "r"(b), "r"(c)); return r; }
__device__ __forceinline__ uint4 add_bf8(const uint4 x, const uint32_t* y, const uint32_t k = 0x3f803f80u) {
    return make_uint4(bfma(y[0], k, x.x), bfma(y[1], k, x.y), bfma(y[2], k, x.z), bfma(y[3], k, x.w));
}
__device__ __forceinline__ float ex2(float x) { float r; asm("ex2.approx.ftz.f32 %0,%1;" : "=f"(r) : "f"(x)); return r; }
__device__ __forceinline__ float rcp(float x) { float r; asm("rcp.approx.ftz.f32 %0,%1;" : "=f"(r) : "f"(x)); return r; }
__device__ __forceinline__ void wg_fence() { asm volatile("wgmma.fence.sync.aligned;" ::: "memory"); }
__device__ __forceinline__ void wg_commit() { asm volatile("wgmma.commit_group.sync.aligned;" ::: "memory"); }
template <int N> __device__ __forceinline__ void wg_wait() { asm volatile("wgmma.wait_group.sync.aligned %0;" ::"n"(N) : "memory"); }
__device__ __forceinline__ uint64_t mkdesc(uint32_t a, uint32_t lbo, uint32_t sbo, uint32_t sw) {
    return (uint64_t)((a & 0x3FFFF) >> 4) | ((uint64_t)(lbo >> 4) << 16) | ((uint64_t)(sbo >> 4) << 32) | ((uint64_t)sw << 62);
}
#define F4(d, i) "+f"(d[i]), "+f"(d[i + 1]), "+f"(d[i + 2]), "+f"(d[i + 3])
#define F8(d, i) F4(d, i), F4(d, i + 4)
#define F16(d, i) F8(d, i), F8(d, i + 8)
template <int OFF, int SC> __device__ __forceinline__ void wg_n32_x(float* d, const uint32_t* a, uint32_t lo) {
    asm volatile("{.reg .pred p; .reg .b32 l; .reg .b64 q; setp.ne.b32 p,%22,0; add.u32 l,%20,%21; mov.b64 q,{l,8};\n"
                 "wgmma.mma_async.sync.aligned.m64n32k16.f32.f16.f16 "
                 "{%0,%1,%2,%3,%4,%5,%6,%7,%8,%9,%10,%11,%12,%13,%14,%15},{%16,%17,%18,%19},q,p,1,1,0;}"
                 : F16(d, 0) : "r"(a[0]), "r"(a[1]), "r"(a[2]), "r"(a[3]), "r"(lo), "n"(OFF), "n"(SC));
}
__device__ __forceinline__ void wg_n128_rs(float* d, const uint32_t* a, uint64_t db, int sc) {
    asm volatile("{.reg .pred p; setp.ne.b32 p,%69,0; wgmma.mma_async.sync.aligned.m64n128k16.f32.f16.f16 "
                 "{%0,%1,%2,%3,%4,%5,%6,%7,%8,%9,%10,%11,%12,%13,%14,%15,%16,%17,%18,%19,%20,%21,%22,%23,%24,%25,%26,%27,%28,%29,%30,%31,"
                 "%32,%33,%34,%35,%36,%37,%38,%39,%40,%41,%42,%43,%44,%45,%46,%47,%48,%49,%50,%51,%52,%53,%54,%55,%56,%57,%58,%59,%60,%61,%62,%63},"
                 "{%64,%65,%66,%67},%68,p,1,1,0;}"
                 : F16(d, 0), F16(d, 16), F16(d, 32), F16(d, 48) : "r"(a[0]), "r"(a[1]), "r"(a[2]), "r"(a[3]), "l"(db), "r"(sc));
}
#define N80_REGS "{%0,%1,%2,%3,%4,%5,%6,%7,%8,%9,%10,%11,%12,%13,%14,%15,%16,%17,%18,%19,%20,%21,%22,%23,%24,%25,%26,%27,%28,%29,%30,%31,%32,%33,%34,%35,%36,%37,%38,%39}"
__device__ __forceinline__ void wg_n80_ss(float* d, uint64_t da, uint64_t db, int sc) {
    asm volatile("{.reg .pred p; setp.ne.b32 p,%42,0; wgmma.mma_async.sync.aligned.m64n80k16.f32.bf16.bf16 " N80_REGS ",%40,%41,p,1,1,0,0;}"
                 : F16(d, 0), F16(d, 16), F8(d, 32) : "l"(da), "l"(db), "r"(sc));
}
__device__ __forceinline__ void wg_n88_ss(float* d, uint64_t da, uint64_t db, int sc) {
    asm volatile("{.reg .pred p; setp.ne.b32 p,%46,0; wgmma.mma_async.sync.aligned.m64n88k16.f32.f16.f16 "
                 "{%0,%1,%2,%3,%4,%5,%6,%7,%8,%9,%10,%11,%12,%13,%14,%15,%16,%17,%18,%19,%20,%21,%22,%23,%24,%25,%26,%27,%28,%29,%30,%31,"
                 "%32,%33,%34,%35,%36,%37,%38,%39,%40,%41,%42,%43},%44,%45,p,1,1,0,0;}"
                 : F16(d, 0), F16(d, 16), F8(d, 32), F4(d, 40) : "l"(da), "l"(db), "r"(sc));
}
__device__ __forceinline__ void wg_n48_ss_ta(float* d, uint64_t da, uint64_t db, int sc) {
    asm volatile("{.reg .pred p; setp.ne.b32 p,%26,0; wgmma.mma_async.sync.aligned.m64n48k16.f32.f16.f16 "
                 "{%0,%1,%2,%3,%4,%5,%6,%7,%8,%9,%10,%11,%12,%13,%14,%15,%16,%17,%18,%19,%20,%21,%22,%23},%24,%25,p,1,1,1,0;}"
                 : F16(d, 0), F8(d, 16) : "l"(da), "l"(db), "r"(sc));
}
template <int TA> __device__ __forceinline__ void wg_n64_ss_tb(float* d, uint64_t da, uint64_t db, int sc) {
    asm volatile("{.reg .pred p; setp.ne.b32 p,%34,0; wgmma.mma_async.sync.aligned.m64n64k16.f32.f16.f16 "
                 "{%0,%1,%2,%3,%4,%5,%6,%7,%8,%9,%10,%11,%12,%13,%14,%15,%16,%17,%18,%19,%20,%21,%22,%23,%24,%25,%26,%27,%28,%29,%30,%31},"
                 "%32,%33,p,1,1,%35,1;}"
                 : F16(d, 0), F16(d, 16) : "l"(da), "l"(db), "r"(sc), "n"(TA));
}
__device__ __forceinline__ void pdl_wait() { asm volatile("griddepcontrol.wait;" ::: "memory"); }
__device__ __forceinline__ void pdl_go() { asm volatile("griddepcontrol.launch_dependents;" ::: "memory"); }
__device__ __forceinline__ float cos640(float p) {
    const float q = fmaf(p, 0.0015625f, 12582912.f) - 12582912.f;
    return __cosf(fmaf(q, -640.f, p) * 0.009817477042468103f);
}
__device__ __forceinline__ uint4 cos_row8(float p0, float step, float amp = 1.f) {
    float v[8];
    const float k = 2.f * cos640(step);
    v[0] = amp * cos640(p0); v[1] = amp * cos640(p0 + step);
#pragma unroll
    for (int i = 2; i < 8; i++) v[i] = fmaf(k, v[i - 1], -v[i - 2]);
    return make_uint4(pack_h(v[0], v[1]), pack_h(v[2], v[3]), pack_h(v[4], v[5]), pack_h(v[6], v[7]));
}
__device__ __forceinline__ float wfilter_max(int lane) {
    float m = fmaxf(fmaxf(g_wmax[lane], g_wmax[lane + 32]), fmaxf(g_wmax[lane + 64], g_wmax[lane + 96]));
    return __uint_as_float(__reduce_max_sync(~0u, __float_as_uint(m)));
}
__device__ __forceinline__ unsigned ld_acquire(const Flag* p) { unsigned v; asm volatile("ld.acquire.gpu.global.u32 %0,[%1];" : "=r"(v) : "l"(p) : "memory"); return v; }
#define POLL_NS 200
template <int NS = POLL_NS> __device__ __forceinline__ void wait_flag(const Flag* p, unsigned v) {
    if (ld_acquire(p) >= v) return;
    unsigned x;
    int lim = 0;
    do {
        __nanosleep(NS);
        asm volatile("ld.relaxed.gpu.global.u32 %0,[%1];" : "=r"(x) : "l"(p) : "memory");
    } while (x < v && ++lim < SPIN_LIM);
    ld_acquire(p);
}
__device__ __forceinline__ void prefetch_l2(const void* p, int bytes) { asm volatile("cp.async.bulk.prefetch.L2.global [%0],%1;" ::"l"(p), "r"(bytes) : "memory"); }
__device__ __forceinline__ void red_release(Flag* p) { asm volatile("red.release.gpu.global.add.u32 [%0],1;" ::"l"(p) : "memory"); }
__device__ __forceinline__ void red_relaxed(Flag* p) { asm volatile("red.relaxed.gpu.global.add.u32 [%0],1;" ::"l"(p) : "memory"); }
__device__ __forceinline__ void red_h8(void* p, uint32_t a, uint32_t b, uint32_t c, uint32_t d) {
    asm volatile("red.relaxed.gpu.global.add.noftz.v4.f16x2 [%0],{%1,%2,%3,%4};" ::"l"(p), "r"(a), "r"(b), "r"(c), "r"(d) : "memory");
}
__device__ __forceinline__ float pow2_scale(float bound, int top, float* inv) {
    int e = (int)((__float_as_uint(bound) >> 23) & 0xff) - 126;
    int k = top - e;
    k = max(-100, min(100, k));
    *inv = __uint_as_float((uint32_t)(127 - k) << 23);
    return __uint_as_float((uint32_t)(127 + k) << 23);
}
__device__ __forceinline__ char* red_base() { return (char*)(((uintptr_t)g_redraw + 32767) & ~(uintptr_t)32767); }

__device__ __forceinline__ void setup_a(char* sm, const int b, const bf16* __restrict__ wr, const bf16* __restrict__ wi) {
    const int tid = threadIdx.x, lane = tid & 31;
    const uint32_t sb = smem_u32(sm);
    auto row_byte = [&](int q) { return ((b >> 2) + 32 * ((q >> 1) * 8 + 2 * (b & 3) + (q & 1))) * 642; };
#pragma unroll 1
    for (int r = tid >> 5; r < 32; r += 8) {
        const char* src = (const char*)(r < 16 ? wr : wi) + (row_byte(r & 15) & ~15);
        cp_async16(sb + r * 672 + lane * 16, src + lane * 16);
        if (lane < 9) cp_async16(sb + r * 672 + 512 + lane * 16, src + 512 + lane * 16);
    }
    ((uint4*)g_stat)[b * 256 + tid] = make_uint4(0, 0, 0, 0);
    if (tid < 2 * (NFLAG / 128)) ((uint4*)(g_flag + b * (NFLAG / 128) + (tid >> 1)))[tid & 1] = make_uint4(0, 0, 0, 0);
    if (tid < 12) {
        const int i = b * 12 + tid;
        const int f = ((i >> 4) & 3) * 8 + (i & 7), im = (i >> 3) & 1, part = (i >> 8) & 1;
        ((uint4*)g_ctab)[i] = cos_row8((float)(i < 1024 ? (i >> 7) * 80 * (i & 63) + ((i & 64) ? 480 : 0) : ((i >> 6) & 3) * 160 * f + (im == part ? 0 : im ? 160 : 480)),
                                       (float)(i < 1024 ? 10 * (i & 63) : 20 * f), i < 1024 ? 0.125f : 0.17677669529663687f);
    }
    asm volatile("cp.async.wait_all;" ::: "memory");
    __syncthreads();
    const int q0 = (tid & 3) * 4;
    const char* rp[4];
#pragma unroll
    for (int u = 0; u < 4; u++) rp[u] = sm + (q0 + u) * 672 + (row_byte(q0 + u) & 15);
    uint32_t mx = 0;
#pragma unroll 2
    for (int c = tid >> 2; c < 321; c += 64) {
        uint32_t v[4];
#pragma unroll
        for (int u = 0; u < 4; u++) {
            v[u] = ((const unsigned short*)rp[u])[c] | ((uint32_t)((const unsigned short*)(rp[u] + 16 * 672))[c] << 16);
            mx = __vmaxu2(mx, v[u] & 0x7fff7fffu);
        }
        ((uint4*)g_Wf)[(size_t)c * 512 + b * 4 + ((tid ^ (b >> 1)) & 3)] = make_uint4(v[0], v[1], v[2], v[3]);
    }
    mx = __reduce_max_sync(~0u, max(mx & 0xffffu, mx >> 16));
    __syncthreads();
    if (lane == 0) ((uint32_t*)sm)[tid >> 5] = mx;
    __syncthreads();
    if (tid < 32) {
        mx = __reduce_max_sync(~0u, ((uint32_t*)sm)[lane & 7]);
        if (tid == 0) g_wmax[b] = __uint_as_float(mx << 16);
    }
}
__device__ __forceinline__ void setup_b(const int b, const bf16* __restrict__ mem0) {
    const int tid = threadIdx.x;
    uint4* z = (uint4*)red_base();
    if (b < 3) {
        const int w = tid >> 5, lane = tid & 31, p = b * 2 + ((w >> 1) & 1), odd = w & 1;
        uint32_t mx = 0;
#pragma unroll 4
        for (int i = lane; i < 640; i += 32) {
            const uint4 u = ((const uint4*)mem0)[i];
            mx = __vmaxu2(__vmaxu2(mx, u.x & 0x7fff7fffu), __vmaxu2(__vmaxu2(u.y & 0x7fff7fffu, u.z & 0x7fff7fffu), u.w & 0x7fff7fffu));
        }
        float inv, v[7];
        const float sc = pow2_scale(__uint_as_float(__reduce_max_sync(~0u, max(mx & 0xffffu, mx >> 16)) << 16), 14, &inv);
        if (tid == 0) g_invM0 = inv;
#pragma unroll
        for (int j = 0; j < 7; j++) {
            const int r = p * 56 + (j < 6 ? odd * 32 + (j >> 1) * 8 : 24) + (lane >> 2), mr = 2 * (lane & 3) + (j < 6 ? (j & 1) : odd);
            v[j] = r < 320 ? __bfloat162float(mem0[mr * 640 + (w >> 2) * 320 + r]) * sc : 0.f;
        }
        const int off = w * 2048 + (lane >> 4) * 1024 + ((lane >> 3) & 1) * 256 + (lane & 7) * 16 + (b == 2 ? (w >> 1) * 4096 + 128 : b * 16384);
        const uint4 u = make_uint4(pack_h(v[0], v[1]), pack_h(v[2], v[3]), pack_h(v[4], v[5]), pack_h(v[6], 32.f));
        z[off >> 4] = u; z[65536 + (off >> 4)] = u;
    }
}

#define SU_PAD 40960
constexpr int SU_SMEM = SU_PAD;
__global__ void __launch_bounds__(256, 4) k_setup(const bf16* __restrict__ wr, const bf16* __restrict__ wi, const bf16* __restrict__ mem0) {
    extern __shared__ __align__(1024) char sm[];
    TL(0);
    if (blockIdx.x >= 128) setup_b(blockIdx.x - 128, mem0);
    else setup_a(sm, blockIdx.x, wr, wi);
    __syncthreads();
    if (threadIdx.x == 0) red_release(g_ready);
    TL(1);
}
__device__ __forceinline__ float weight_scale(int h, int ty, float* inv) { return pow2_scale(__ldcg(g_wmx + h * 3 + ty), 6, inv); }

#define STR_(x) #x
#define STR(x) STR_(x)
#define RF_U 1
constexpr int RF_A = 22 * 2816, RF_X = RF_A + 22 * 1024, RF_BAR = RF_X + 64 * 1344, RF_SMEM = RF_BAR + 80;
__device__ __align__(1024) char g_rtab[4 * RF_A];
template <int first> __global__ void __cluster_dims__(2, 1, 1) __launch_bounds__(256, 2) k_rowf(const bf16* x) {
    extern __shared__ __align__(1024) char sm[];
    TL(first ? 2 : 16);
    const int tid = threadIdx.x, w = tid >> 5, lane = tid & 31, g = lane >> 2, t = lane & 3;
    if (blockIdx.x >= 128) { __nanosleep(2500); return; }
    const int a = first ? blockIdx.x >> 2 : 31 - (blockIdx.x >> 2), gq = blockIdx.x & 3;
    if (!first) pdl_go();
    const uint32_t sb = smem_u32(sm), mb = sb + RF_BAR + w * 8;
    if (lane == 0) {
        mbar_init(mb, 1);
        asm volatile("fence.mbarrier_init.release.cluster;" ::: "memory");
        if (!first && w == 0) {
            mbar_init(sb + RF_BAR + 64, 1);
            fence_async_smem();
            mbar_expect(sb + RF_BAR + 64, RF_A);
            bulk_g2s(sb, g_rtab + gq * RF_A, RF_A, sb + RF_BAR + 64);
        }
    }
    if (lane == 0) mbar_expect(mb, 8 * 1280);
    __syncwarp();
    asm volatile("barrier.cluster.arrive.relaxed.aligned; barrier.cluster.wait.aligned;" ::: "memory");
    if (!first) {
        if (lane == 0) wait_flag<100>(g_flag + F_R + a, a < 28 ? 32 : 192);
        __syncwarp();
        fence_async_glb();
    }
    TL(first ? 3 : 17);
    if (lane < 4)
        asm volatile("cp.async.bulk.shared::cluster.global.mbarrier::complete_tx::bytes.multicast::cluster [%0],[%1],1280,[%2],%3;"
                     ::"r"(sb + RF_X + (w * 8 + (gq & 1) * 4 + lane) * 1344), "l"(x + (size_t)(a * 64 + w * 8 + (gq & 1) * 4 + lane) * 640), "r"(mb),
                     "h"((unsigned short)3) : "memory");
    __syncwarp();
    if (first) pdl_go();
    if (first) {
#pragma unroll 3
        for (int id = tid; id < 22 * 176; id += 256) {
            const int kg = id / 176, n = id - kg * 176;
            const float c = (float)(2 * n + (gq & 1));
            *(uint4*)(sm + id * 16) = cos_row8(fmaf((float)(kg * 8), c, (float)((gq & 2) * 80)), c, 0.03952847075210474f);
        }
    }
    mbar_wait(mb, 0);
    const uint32_t row = sb + RF_X + (w * 8 + g) * 1344;
    float st[4][4] = {};
#pragma unroll 1
    for (int i = 0; i < 20; i += 4) {
        uint32_t u[4][4];
#pragma unroll
        for (int q = 0; q < 4; q++) lds128(u[q], row + (4 * (i + q) + t) * 16);
#pragma unroll
        for (int q = 0; q < 4; q++) {
            mma_bf(st[(q & 1) * 2], u[q][0], 0x3f803f80u, u[q][1], 0x3f803f80u, u[q][0], u[q][1]);
            mma_bf(st[(q & 1) * 2 + 1], u[q][2], 0x3f803f80u, u[q][3], 0x3f803f80u, u[q][2], u[q][3]);
        }
    }
#pragma unroll
    for (int q = 0; q < 4; q++) { st[0][q] += st[2][q]; st[1][q] += st[3][q]; }
    const float sq = __shfl_sync(~0u, (g & 1) ? st[0][1] + st[1][1] : st[0][0] + st[1][0], g * 4 + (g >> 1));
    const float mean = __shfl_sync(~0u, (g & 1) ? st[0][3] + st[1][3] : st[0][2] + st[1][2], g * 4 + (g >> 1)) * (1.f / 640.f);
    const float r = rsqrtf(fmaxf(fmaf(-mean, mean, sq * (1.f / 640.f)), 0.f) + 1e-5f), off = gq == 0 ? -4.f * mean * r : 0.f;
    const float r1 = (gq == 1 || gq == 2) ? -r : r, r2 = (gq & 1) ? -r : r, r3 = gq >= 2 ? -r : r;
    const uint32_t aa = sb + RF_A + w * 128 + g * 16;
    auto el = [&](int d) { unsigned short v; asm volatile("ld.shared.u16 %0,[%1];" : "=h"(v) : "r"(row + d * 2)); return __uint_as_float((uint32_t)v << 16); };
_Pragma(STR(unroll RF_U))
    for (int i = 0; i < 5; i++) {
        const int ch = t + 4 * i;
        uint32_t u[4][4];
        lds128(u[0], row + ch * 16); lds128(u[1], row + (39 - ch) * 16); lds128(u[2], row + (40 + ch) * 16); lds128(u[3], row + (79 - ch) * 16);
        const float nb0 = el(320 - 8 * ch), nb1 = el(ch ? 640 - 8 * ch : 0);
        float o[8];
#pragma unroll
        for (int q = 0; q < 8; q++) {
            const int m = (8 - q) >> 1;
            const float e0 = (q & 1) ? bf_hi(u[0][q >> 1]) : bf_lo(u[0][q >> 1]), e2 = (q & 1) ? bf_hi(u[2][q >> 1]) : bf_lo(u[2][q >> 1]);
            const float e1 = q == 0 ? nb0 : (q & 1) ? bf_hi(u[1][m & 3]) : bf_lo(u[1][m & 3]), e3 = q == 0 ? nb1 : (q & 1) ? bf_hi(u[3][m & 3]) : bf_lo(u[3][m & 3]);
            o[q] = fmaf(e3, r3, fmaf(e2, r2, fmaf(e1, r1, fmaf(e0, r, off))));
        }
        if (ch == 0) o[0] *= 0.5f;
        sts128(aa + ch * 1024, pack_h(o[0], o[1]), pack_h(o[2], o[3]), pack_h(o[4], o[5]), pack_h(o[6], o[7]));
    }
    if (t < 2) sts128(aa + (20 + t) * 1024, t == 0 ? pack_h(fmaf(el(480), r2, fmaf(el(160), r, 0.5f * off)), 0.f) : 0u, 0u, 0u, 0u);
    fence_async_smem();
    __syncthreads();
    if (!first) mbar_wait(sb + RF_BAR + 64, 0);
    else if (a == 0 && tid == 0) { bulk_s2g(g_rtab + gq * RF_A, sb, RF_A); bulk_commit(); }
    const int wg = w >> 2;
    float acc[44];
    uint64_t da = mkdesc(sb + RF_A, 1024, 128, 0), db = mkdesc(sb + wg * 1408, 2816, 128, 0);
    wg_fence();
#pragma unroll 1
    for (int k = 0; k < 11; k++) { wg_n88_ss(acc, da, db, k); da += 128; db += 352; }
    wg_commit(); wg_wait<0>();
    const uint32_t stg = sb + RF_X + wg * 96 * 144;
#pragma unroll
    for (int j = 0; j < 12; j += 2) {
        const int m = lane >> 3, j1 = j < 10 ? j + 1 : j;
        stsm4t(stg + ((j + (m >> 1)) * 8 + (lane & 7)) * 144 + ((w & 3) * 16 + (m & 1) * 8) * 2, pack_h(acc[j * 4], acc[j * 4 + 1]),
               pack_h(acc[j * 4 + 2], acc[j * 4 + 3]), pack_h(acc[j1 * 4], acc[j1 * 4 + 1]), pack_h(acc[j1 * 4 + 2], acc[j1 * 4 + 3]));
    }
    bar_sync(1 + wg, 128);
#pragma unroll 3
    for (int rr = (tid & 127) >> 3; rr < 88; rr += 16) {
        const int ch = tid & 7, c = 2 * (wg * 88 + rr) + (gq & 1);
        if (c <= 320 - (gq >> 1) && (c | (gq ^ 2))) {
            uint32_t u[4];
            lds128(u, stg + rr * 144 + ch * 16);
            ((uint4*)g_UT)[((size_t)(c == 320 ? 1 : 2 * c + (gq >> 1)) * 32 + a) * 8 + (ch ^ (a & 7))] = make_uint4(u[0], u[1], u[2], u[3]);
        }
    }
    if (first && blockIdx.x < 4 && tid == 0) asm volatile("cp.async.bulk.wait_group.read 0;" ::: "memory");
    TL(first ? 4 : 18);
}

constexpr int GST = 4, GSTB = 32768 + 20480, GNC = 32;
constexpr int G_BAR = GST * GSTB + 3072;
#define GPACE 1100
#define GPACE2 650
__device__ __forceinline__ void oproj_load(const uint32_t sb, const int op, const int mb, const int nb, const int c0, const uint32_t pace) {
    const int by = op == 2 ? 20480 : 16384;
    const char* src = op == 2 ? (const char*)g_wot + (size_t)nb * GNC * 20480 : (const char*)g_O + (size_t)(2 * mb + op) * GNC * 16384;
    uint32_t t0 = clock32() - pace + op * (pace / 3);
#pragma unroll 1
    for (int c = c0; c < c0 + GNC; c++, src += by) {
        const int st = c % GST;
        if (c >= GST) mbar_wait(sb + G_BAR + (GST + st) * 8, ((c / GST) - 1) & 1);
        while (clock32() - t0 < pace) {}
        t0 = clock32();
        const int by_ = by;
        mbar_expect(sb + G_BAR + st * 8, by_);
        if (op == 2) bulk_g2s(sb + st * GSTB + 32768, src, by_, sb + G_BAR + st * 8);
        else bulk_g2s_last(sb + st * GSTB + op * 16384, src, by_, sb + G_BAR + st * 8);
    }
}
__device__ __forceinline__ void oproj_mma(const uint32_t sb, const int mb, const int nb, const int c0, const bf16* res, bf16* out, const int layer) {
    const int w = threadIdx.x >> 5, lane = threadIdx.x & 31, wg = w >> 2;
    float acc[40];
    uint4 rv[5];
#pragma unroll 1
    for (int c = c0; c < c0 + GNC; c++) {
        const int st = c % GST;
        mbar_wait(sb + G_BAR + st * 8, (c / GST) & 1);
        const uint32_t d = sb + st * GSTB;
        wg_fence();
#pragma unroll
        for (int k = 0; k < 8; k++)
            wg_n80_ss(acc, mkdesc(d + wg * 16384 + k * 2048, 1024, 128, 0), mkdesc(d + 32768 + k * 2560, 1280, 128, 0), (c - c0) | k);
        wg_commit();
        if (c > c0) {
            wg_wait<1>();
            if (lane == 0) mbar_arrive(sb + G_BAR + (GST + (c - 1) % GST) * 8);
        }
    }
#pragma unroll
    for (int i = 0; i < 5; i++) {
        const int id = i * 32 + lane, r = id / 10;
        rv[i] = __ldcg((const uint4*)res + (size_t)(mb * 128 + w * 16 + r) * 80 + nb * 10 + id - r * 10);
    }
    wg_wait<0>();
    bar_sync(5, 256);
    const uint32_t stg = sb + (GST - 1) * GSTB + w * 16 * 176;
#pragma unroll
    for (int j = 0; j < 5; j++)
        stsm4(stg + (lane & 15) * 176 + (2 * j + (lane >> 4)) * 16, pack_bf(acc[j * 8], acc[j * 8 + 1]), pack_bf(acc[j * 8 + 2], acc[j * 8 + 3]),
              pack_bf(acc[j * 8 + 4], acc[j * 8 + 5]), pack_bf(acc[j * 8 + 6], acc[j * 8 + 7]));
    __syncwarp();
#pragma unroll
    for (int i = 0; i < 5; i++) {
        const int id = i * 32 + lane, r = id / 10, ch = id - r * 10;
        uint32_t y[4];
        lds128(y, stg + r * 176 + ch * 16);
        ((uint4*)out)[(size_t)(mb * 128 + w * 16 + r) * 80 + nb * 10 + ch] = add_bf8(rv[i], y);
    }
    fence_async_smem();
    __syncwarp();
    if (lane == 0) {
        mbar_arrive(sb + G_BAR + (2 * GST - 1) * 8);
        if (layer == 0) red_release(g_flag + F_R + 2 * mb + wg);
    }
}

__global__ void __launch_bounds__(128, 4) k_col(const int first) {
    __shared__ __align__(1024) char sz[8192];
    __shared__ __align__(1024) char stab[24576];
    __shared__ __align__(1024) char swf[8192];
    __shared__ __align__(8) uint64_t bar[2];
    const int tid = threadIdx.x, wl = tid >> 5, lane = tid & 31, g = lane >> 2, t = lane & 3;
    const int c = blockIdx.x;
    TL(first ? 5 : 19);
    const bool realc = c == 0 || c == 320;
    const uint32_t z = smem_u32(sz), b2 = smem_u32(stab), a1 = b2 + 16384, wf = smem_u32(swf), mb = smem_u32(bar);
    if (tid == 0) { mbar_init(mb, 1); mbar_init(mb + 8, 1); fence_async_smem(); }
    if (realc) {
        for (int i = tid; i < 256; i += 128) sts128(z + 4096 + i * 16, 0, 0, 0, 0);
        fence_async_smem();
    }
    const int k1 = wl * 8 + g;
    float tc[16], ts[16];
#pragma unroll
    for (int j = 0; j < 16; j++) {
        const int p = ((j >> 1) * 8 + 2 * t + (j & 1)) * k1;
        __sincosf((float)(p - 1024) * 0.003067961575771282f, &ts[j], &tc[j]);
        ts[j] = -ts[j]; tc[j] = -tc[j];
    }
    if (first && tid == 32) { wait_flag<400>(g_ready, NSETUP); fence_async_glb(); }
    __syncthreads();
    if (tid == 32) {
        mbar_expect(mb + 8, 24576 + 8192);
        bulk_g2s(b2, g_ctab, 24576, mb + 8);
        bulk_g2s(wf, g_Wf + (size_t)c * 2048, 8192, mb + 8);
    }
    float inv;
    const float wsc = pow2_scale(wfilter_max(lane), 0, &inv) * (realc ? 0.5f : 1.f);
    pdl_wait();
    TL(first ? 6 : 20);
    if (tid == 0) {
        const int by = realc ? 4096 : 8192;
        mbar_expect(mb, by);
        bulk_g2s_last(z, (const char*)g_UT + (size_t)(c == 320 ? 1 : 2 * c) * 4096, by, mb);
    }
    pdl_go();
    mbar_wait(mb + 8, 0);
    mbar_wait(mb, 0);
    float d[64];
    uint32_t a[4][4];
    wg_fence();
#pragma unroll
    for (int ks = 0; ks < 4; ks++) wg_n64_ss_tb<0>(d, mkdesc(a1 + ks * 2048, 1024, 128, 0), mkdesc(z + ks * 2048, 1024, 1024, 1), ks);
    wg_commit(); wg_wait<0>();
#pragma unroll
    for (int j = 0; j < 8; j++) {
        float yr[2], yi[2];
#pragma unroll
        for (int e = 0; e < 2; e++) {
            const float re = d[j * 4 + e], im = d[j * 4 + 2 + e], cc = tc[j * 2 + e], ss = ts[j * 2 + e];
            yr[e] = re * cc + im * ss; yi[e] = im * cc - re * ss;
        }
        a[j >> 1][(j & 1) * 2] = pack_h(yr[0], yr[1]); a[j >> 1][(j & 1) * 2 + 1] = pack_h(yi[0], yi[1]);
    }
    wg_fence();
#pragma unroll
    for (int ks = 0; ks < 4; ks++) wg_n128_rs(d, a[ks], mkdesc(b2 + ks * 4096, 2048, 128, 0), ks);
    wg_commit(); wg_wait<0>();
#pragma unroll
    for (int q = 0; q < 4; q++) {
        uint32_t wv[4];
        lds128(wv, wf + tid * 64 + ((q ^ (tid >> 1)) & 3) * 16);
#pragma unroll
        for (int jj = 0; jj < 2; jj++) {
            const int j = 2 * q + jj;
            float yr[2], yi[2];
#pragma unroll
            for (int e = 0; e < 2; e++) {
                const float xr = d[j * 4 + e] + d[32 + j * 4 + 2 + e], xi = d[j * 4 + 2 + e] - d[32 + j * 4 + e];
                const float fr = bf_lo(wv[jj * 2 + e]) * wsc, fi = bf_hi(wv[jj * 2 + e]) * wsc;
                yr[e] = xr * fr - xi * fi; yi[e] = xr * fi + xi * fr;
            }
            a[q][jj * 2] = pack_h(yr[0], yr[1]); a[q][jj * 2 + 1] = pack_h(yi[0], yi[1]);
        }
    }
    wg_fence();
#pragma unroll
    for (int ks = 0; ks < 4; ks++) wg_n128_rs(d, a[ks], mkdesc(b2 + ks * 4096, 2048, 128, 0), ks);
    wg_commit(); wg_wait<0>();
#pragma unroll
    for (int j = 0; j < 8; j++) {
        float yr[2], yi[2];
#pragma unroll
        for (int e = 0; e < 2; e++) {
            const float vr = d[j * 4 + e] - d[32 + j * 4 + 2 + e], vi = d[j * 4 + 2 + e] + d[32 + j * 4 + e];
            const float cc = tc[j * 2 + e], ss = ts[j * 2 + e];
            yr[e] = vr * cc - vi * ss; yi[e] = vi * cc + vr * ss;
        }
        a[j >> 1][(j & 1) * 2] = pack_h(yr[0], yr[1]); a[j >> 1][(j & 1) * 2 + 1] = pack_h(yi[0], yi[1]);
    }
    __syncthreads();
    const int mm = lane >> 3, rr = lane & 7;
    const uint32_t rowo = (wl * 16 + (mm & 1) * 8 + rr) * 128;
#pragma unroll
    for (int q = 0; q < 4; q++) stsm4(z + rowo + (((2 * q + (mm >> 1)) ^ rr) << 4), a[q][0], a[q][1], a[q][2], a[q][3]);
    fence_async_smem();
    __syncthreads();
    wg_fence();
#pragma unroll
    for (int ks = 0; ks < 4; ks++) wg_n64_ss_tb<1>(d, mkdesc(a1 + ks * 256, 128, 1024, 0), mkdesc(z + ks * 2048, 1024, 1024, 1), ks);
    wg_commit(); wg_wait<0>();
#pragma unroll
    for (int q = 0; q < 4; q++)
        stsm4(wf + rowo + (((2 * q + (mm >> 1)) ^ rr) << 4), pack_h(d[q * 8], d[q * 8 + 1]), pack_h(d[q * 8 + 2], d[q * 8 + 3]),
              pack_h(d[q * 8 + 4], d[q * 8 + 5]), pack_h(d[q * 8 + 6], d[q * 8 + 7]));
    __syncwarp();
    if (!(realc && wl >= 2)) {
        const int kk = c == 320 ? 320 : (c & 1) * 160 + (c >> 1) + (wl >> 1) * 320;
#pragma unroll
        for (int i = 0; i < 4; i++) {
            const int r = wl * 16 + i * 4 + (lane >> 3), ch = lane & 7;
            uint32_t v[4];
            lds128(v, wf + r * 128 + ((ch ^ (r & 7)) << 4));
            ((uint4*)g_YT)[((size_t)(r & 31) * 640 + kk) * 8 + (ch ^ (kk & 7))] = make_uint4(v[0], v[1], v[2], v[3]);
        }
    }
    TL(first ? 7 : 21);
}

constexpr int O_XS = 0;
constexpr int O_MS = 81920;
constexpr int O_QKP = O_MS + 10752;
constexpr int O_VM = O_QKP + 4096;
constexpr int O_SC = O_VM + 4096;
constexpr int O_OS = O_SC + 1536;
constexpr int O_XCH = O_OS + 2048;
constexpr int O_SUM = O_XCH + 8192;
constexpr int O_MX = O_SUM + 256;
constexpr int O_STG = O_MS + 65536 - 8192;
static_assert(O_STG - 16384 >= O_MX + 1024, "shared-memory map");
constexpr int O_WO = O_STG + 16384;
constexpr int O_SCL = O_WO + 65536;
constexpr int O_BAR = O_SCL + 64;
constexpr int B_XF = O_BAR, B_S = O_BAR + 16, B_VX = O_BAR + 32, B_STG = O_BAR + 48, B_FREE = O_BAR + 72;
constexpr int T_FA = O_BAR + 96, T_EA = T_FA + 32, T_FB = T_EA + 32, T_EB = T_FB + 56, T_RED = T_EB + 32;
constexpr int O_WMX = O_BAR + 512, B_W = O_BAR + 64;
constexpr int O_LAST = (O_WMX + 192 + 1023) / 1024 * 1024;
constexpr int CH_SMEM = O_LAST + 8192;
static_assert(O_WO == 19 * 8192, "weight staging");
__device__ __forceinline__ uint32_t tail_b(int c) { return c % 7 < 4 ? O_XS + (c % 7) * 20480 : O_WO + (c % 7 - 4) * 20480; }
__device__ __forceinline__ int s_tx(int c) { return c == 2 ? 2 * 768 : 768 + 2048; }

#define NPERM 1
#define NWO0 1
#define NWO0B 4
#define NWO1 6
#define EN 25
#define VXN 100
#define AUNR 2
#define TDELAY 300
#define WDEPTH 6
#define RDELAY 570

#define STAMP(i)

#define NTA 23
#define NTB 26
template <int LO, int HI>
__device__ __forceinline__ void tok_issue(const uint32_t (&A0)[20][4], const uint32_t (&A1)[20][4], float (&b0)[16], float (&b1)[16], uint32_t xd,
                                          const uint32_t zero) {
    if (LO == 0) wg_fence();
    sfor<HI - LO>([&](auto I) {
        constexpr int i = LO + I;
        if constexpr (i < 20) wg_n32_x<i * 64, i>(b0, A0[i], xd); else wg_n32_x<(i - 20) * 64, i - 20>(b1, A1[i - 20], xd + zero);
        if constexpr (i == 19 || i == NTB - 1 || i == 39) wg_commit();
    });
}
__device__ __forceinline__ void tok_give(const float (&b0)[16], const uint32_t L16, const uint32_t xch0) {
    wg_wait<1>();
    sfor<2>([&](auto I) {
        constexpr int i = I;
        sts128_u<i * 512>(L16, xch0, pack_h(b0[8 * i], b0[8 * i + 1]), pack_h(b0[8 * i + 2], b0[8 * i + 3]), pack_h(b0[8 * i + 4], b0[8 * i + 5]),
                          pack_h(b0[8 * i + 6], b0[8 * i + 7]));
    });
}
__device__ __forceinline__ void tok_finish(float (&b1)[16], const uint32_t (&e)[2][4], const uint32_t L16, const uint32_t dst, const uint32_t idn) {
#pragma unroll
    for (int j = 0; j < 4; j++)
        asm volatile("mma.sync.aligned.m16n8k8.row.col.f32.f16.f16.f32 {%0,%1,%2,%3},{%4,%5},{%6},{%0,%1,%2,%3};"
                     : F4(b1, 4 * j) : "r"(e[j >> 1][(j & 1) * 2]), "r"(e[j >> 1][(j & 1) * 2 + 1]), "r"(idn));
    stsm4_u<0>(L16, dst, pack_bf(b1[0], b1[1]), pack_bf(b1[2], b1[3]), pack_bf(b1[4], b1[5]), pack_bf(b1[6], b1[7]));
    stsm4_u<512>(L16, dst, pack_bf(b1[8], b1[9]), pack_bf(b1[10], b1[11]), pack_bf(b1[12], b1[13]), pack_bf(b1[14], b1[15]));
}
__device__ __forceinline__ uint32_t uni(uint32_t v) { return __shfl_sync(~0u, v, 0); }
__device__ __forceinline__ uint32_t badd(uint32_t a, uint32_t b) { uint32_t r; asm("add.rn.bf16x2 %0,%1,%2;" : "=r"(r) : "r"(a), "r"(b)); return r; }
__device__ __forceinline__ uint32_t bmax(uint32_t a, uint32_t b) { uint32_t r; asm("max.bf16x2 %0,%1,%2;" : "=r"(r) : "r"(a), "r"(b)); return r; }
__device__ __forceinline__ uint32_t babsmax(uint32_t a, uint32_t b) { uint32_t r; asm("max.xorsign.abs.bf16x2 %0,%1,%2;" : "=r"(r) : "r"(a), "r"(b)); return r; }
__device__ __forceinline__ uint32_t habsmax(uint32_t a, uint32_t b) { uint32_t r; asm("max.xorsign.abs.f16x2 %0,%1,%2;" : "=r"(r) : "r"(a), "r"(b)); return r; }

template <int NPF>
__device__ __forceinline__ float mem_out(const uint32_t sb, const uint32_t L16, const uint32_t L8, uint32_t (&wo)[16][4], const uint32_t woa,
                                         char* dst, const bool odd) {
    bar_sync(2, 352);
    float a[4][4];
#pragma unroll
    for (int i = 0; i < 4; i++) a[i][0] = a[i][1] = a[i][2] = a[i][3] = 0.f;
    uint32_t ob[4][4], sm_[2], sc[2];
    sfor<8>([&](auto I) {
        constexpr int i = I;
        if constexpr (!(i & 1)) ldsm4t_u<O_OS + (i >> 1) * 512>(ob[i >> 1], L16, sb);
        if constexpr (i >= NPF) { ldsm4t(wo[i], woa + i * 1024); ldsm4t(wo[8 + i], (woa ^ 32) + i * 1024); }
    });
    lds64_u<O_SUM>(sm_, L8 & 24, sb); lds64(sc, sb + O_SCL);
#pragma unroll
    for (int i = 0; i < 8; i++) {
        mma_bf(a[i & 1], wo[i][0], wo[i][1], wo[i][2], wo[i][3], ob[i >> 1][(i & 1) * 2], ob[i >> 1][(i & 1) * 2 + 1]);
        mma_bf(a[2 + (i & 1)], wo[8 + i][0], wo[8 + i][1], wo[8 + i][2], wo[8 + i][3], ob[i >> 1][(i & 1) * 2], ob[i >> 1][(i & 1) * 2 + 1]);
    }
    const float f0 = rcp(__uint_as_float(sm_[0])) * __uint_as_float(sc[0]), f1 = rcp(__uint_as_float(sm_[1])) * __uint_as_float(sc[0]);
    red_h8(dst, pack_h((a[0][0] + a[1][0]) * f0, (a[0][1] + a[1][1]) * f1), pack_h((a[0][2] + a[1][2]) * f0, (a[0][3] + a[1][3]) * f1),
           pack_h((a[2][0] + a[3][0]) * f0, (a[2][1] + a[3][1]) * f1), pack_h(odd ? (a[2][3] + a[3][3]) * f1 : (a[2][2] + a[3][2]) * f0, 1.f));
    return __uint_as_float(sc[1]);
}

template <int NE, int UNR>
__device__ __forceinline__ void tok_attention(const uint32_t qk, const uint32_t dq, const uint32_t km, const uint32_t dk, const uint32_t vt, const uint32_t vm,
                                              const int e0, const int mi, const int lane, const int seg, const int h, const float iqk, const float iv) {
    const int g = lane >> 2, t = lane & 3;
    float s[6][4];
#pragma unroll
    for (int i = 0; i < 6; i++) s[i][0] = s[i][1] = s[i][2] = s[i][3] = 0.f;
#pragma unroll UNR
    for (int e = 0; e < 8; e++) {
        uint32_t q[4], k[4];
        ldsm4t(q, qk + (e >> 2) * dq + (e & 3) * 1024 + mi * 512);
        ldsm4t(k, km + (e >> 2) * dk + (e & 3) * 512);
        mma_bf(s[4], q[0], q[2], q[1], q[3], k[0], k[1]);
        mma_bf(s[5], q[0], q[2], q[1], q[3], k[2], k[3]);
        ldsm4t(k, qk + (e >> 2) * dq + 4096 + (e & 3) * 1024);
        mma_bf(s[0], q[0], q[2], q[1], q[3], k[0], k[1]);
        mma_bf(s[1], q[0], q[2], q[1], q[3], k[2], k[3]);
        if (mi) {
            ldsm4t(k, qk + (e >> 2) * dq + 4096 + (e & 3) * 1024 + 512);
            mma_bf(s[2], q[0], q[2], q[1], q[3], k[0], k[1]);
            mma_bf(s[3], q[0], q[2], q[1], q[3], k[2], k[3]);
        }
    }
#pragma unroll
    for (int q = 0; q < 4; q++) s[4][q] += s[5][q];
    const float sl = iqk * (0.08838834764831845f * 1.4426950408889634f);
    float mx[2] = {-3.0e38f, -3.0e38f};
#pragma unroll
    for (int i = 0; i < 5; i++)
#pragma unroll
        for (int q = 0; q < 4; q++) {
            const bool ok = i == 4 || (i * 8 + 2 * t + (q & 1)) <= (mi * 16 + g + (q >> 1) * 8);
            s[i][q] = ok ? s[i][q] * sl : -1.0e9f * 1.4426950408889634f;
            mx[q >> 1] = fmaxf(mx[q >> 1], s[i][q]);
        }
    float sum[2] = {0.f, 0.f};
#pragma unroll
    for (int r = 0; r < 2; r++) {
        mx[r] = fmaxf(mx[r], __shfl_xor_sync(~0u, mx[r], 1));
        mx[r] = fmaxf(mx[r], __shfl_xor_sync(~0u, mx[r], 2));
    }
#pragma unroll
    for (int i = 0; i < 5; i++)
#pragma unroll
        for (int q = 0; q < 4; q++) { s[i][q] = ex2(s[i][q] - mx[q >> 1]); sum[q >> 1] += s[i][q]; }
#pragma unroll
    for (int r = 0; r < 2; r++) {
        sum[r] += __shfl_xor_sync(~0u, sum[r], 1);
        sum[r] += __shfl_xor_sync(~0u, sum[r], 2);
        sum[r] = iv * rcp(sum[r]);
    }
    uint32_t pp[5][2];
#pragma unroll
    for (int i = 0; i < 5; i++) { pp[i][0] = pack_bf(s[i][0] * sum[0], s[i][1] * sum[0]); pp[i][1] = pack_bf(s[i][2] * sum[1], s[i][3] * sum[1]); }
    uint32_t* o = (uint32_t*)g_O + (((size_t)(seg >> 1) * 512 + h * 16) * 8 + (seg & 1) * 4 + mi * 2) * 32 + lane;
#pragma unroll(UNR == 8 ? NE : 1)
    for (int u = 0; u < NE; u++) {
        const int e = e0 + u;
        float o0[4] = {0.f, 0.f, 0.f, 0.f}, o1[4] = {0.f, 0.f, 0.f, 0.f};
        uint32_t v[4];
        lds64(v, vm + e * 256);
        mma_bf8(o0, pp[4][0], pp[4][1], v[0]);
        mma_bf8(o1, pp[4][0], pp[4][1], v[1]);
        ldsm4(v, vt + e * 1024);
        mma_bf(o0, pp[0][0], pp[0][1], pp[1][0], pp[1][1], v[0], v[2]);
        mma_bf(o1, pp[0][0], pp[0][1], pp[1][0], pp[1][1], v[1], v[3]);
        ldsm4(v, vt + e * 1024 + 512);
        mma_bf(o0, pp[2][0], pp[2][1], pp[3][0], pp[3][1], v[0], v[2]);
        mma_bf(o1, pp[2][0], pp[2][1], pp[3][0], pp[3][1], v[1], v[3]);
        o[(2 * e) * 256] = pack_bf(o0[0], o0[1]); o[(2 * e) * 256 + 32] = pack_bf(o0[2], o0[3]);
        o[(2 * e + 1) * 256] = pack_bf(o1[0], o1[1]); o[(2 * e + 1) * 256 + 32] = pack_bf(o1[2], o1[3]);
    }
}

__device__ __forceinline__
void attend_last(const uint32_t sb, const int layer) {
    const int tid = read_tid(), ln = tid & 31, w = tid >> 5;
    int h;
    asm volatile("mov.u32 %0,%%clusterid.x;" : "=r"(h));
    uint32_t inv[2];
    lds64(inv, sb + O_SCL + 16);
    mbar_wait(sb + B_S, (NSEG - 1) & 1);
    mbar_wait(sb + B_VX + 8, 0);
    if (layer == TLL) TL(54);
    if (w == 0 && ln < 2)
        asm volatile("mbarrier.arrive.relaxed.cluster.shared::cluster.b64 _,[%0];" ::"r"(mapa(sb + B_STG + 8, ln)) : "memory");
    tok_attention<2, AUNR>(sb + O_STG - 16384 + ln * 16, 16384, sb + O_LAST + ln * 16, 2048, sb + O_STG + 8192 - 16384 + ln * 16, sb + O_VM + 2048 + ln * 8,
                     (w >> 1) * 2, w & 1, ln, NSEG - 1, h, __uint_as_float(inv[0]), __uint_as_float(inv[1]));
    if (layer == TLL) TL(55);
    __syncwarp();
    if (ln == 0) red_release(g_flag + F_O + layer * 32 + 31);
    if (layer == TLL) TL(43);
}

template <int layer> __device__ __forceinline__ void chain_mma(const uint32_t sb, const int c, const int h, const uint32_t zero, const bf16* __restrict__ Wq,
                                          const bf16* __restrict__ Wk, const bf16* __restrict__ Wv, const bf16* __restrict__ Wo,
                                          const bf16* res, bf16* out) {
    int tid = read_tid(), lane = tid & 31;
    const int w = __shfl_sync(~0u, tid >> 5, 0), wg = w >> 2;
    [[maybe_unused]] const int cta = h * 3 + c;
    uint32_t A0[20][4], A1[20][4];
    const int t0 = (w & 3) + wg * 4, t1 = t0 ^ 4;
    float sl;
    {
        const int tl = tid & 127, r = tl >> 3, ch = tl & 7;
        const size_t so = (size_t)(wg * 320 + r) * 4096 + h * 128 + ch * 8;
        const bf16 *wa = (c == 2 ? Wv : Wq + c * 64) + so, *wb = (c == 2 ? Wv + 64 : Wk + c * 64) + so;
        const uint32_t ring = sb + wg * 4096;
        const uint32_t dst = ring + r * 128 + ((ch ^ r) & 7) * 16;
        const uint32_t src = ring + ((lane & 7) + (lane >> 4) * 8) * 128 + ((((w & 3) * 2 + ((lane >> 3) & 1)) ^ lane) & 7) * 16;
        const int q4 = lane & 3, gr = (c * 2 + ((w >> 1) & 1)) * 56 + (q4 == 3 ? 24 : (w & 1) * 32 + q4 * 8);
        const bf16* wo_ = Wo + (size_t)(h * 128 + (lane >> 2)) * 640 + wg * 320 + min(gr, 312);
        const uint32_t wdst = sb + O_WO + w * 8192 + (lane >> 2) * 64 + ((q4 ^ (lane >> 3)) & 3) * 16;
        auto issue = [&](int i) {
            if (i < 20) {
                const uint32_t d = dst + (i < 19 ? i * 8192 : O_LAST);
                cp_async16(d, wa + (size_t)i * 65536); cp_async16(d + 2048, wb + (size_t)i * 65536);
                if (i < 16) cp_async16(wdst + i * 512, wo_ + i * 5120, gr < 320 ? 16 : 0);
            }
            cp_commit();
        };
#pragma unroll 1
        for (int i = 0; i < WDEPTH; i++) issue(i);
        asm volatile("barrier.cluster.arrive.relaxed.aligned;" ::: "memory");
        float fa, fb;
        if (layer == 0) {
            uint32_t ma = 0, mb = 0;
#pragma unroll 1
            for (int i = 0; i < 20; i++) {
                issue(i + WDEPTH);
                cp_wait<WDEPTH>();
                const uint32_t d = dst + (i < 19 ? i * 8192 : O_LAST);
                uint32_t u[8];
                lds128(u, d); lds128(u + 4, d + 2048);
                ma = babsmax(babsmax(ma, babsmax(u[0], u[1])), babsmax(u[2], u[3])); mb = babsmax(babsmax(mb, babsmax(u[4], u[5])), babsmax(u[6], u[7]));
            }
            ma = __reduce_max_sync(~0u, max(ma & 0x7fffu, (ma >> 16) & 0x7fffu)); mb = __reduce_max_sync(~0u, max(mb & 0x7fffu, (mb >> 16) & 0x7fffu));
            asm volatile("barrier.cluster.wait.aligned;" ::: "memory");
            if (lane < 3)
                asm volatile("st.async.shared::cluster.mbarrier::complete_tx::bytes.v2.b32 [%0],{%1,%2},[%3];"
                             ::"r"(mapa(sb + O_WMX + (c * 8 + w) * 8, lane)), "r"(ma), "r"(mb), "r"(mapa(sb + B_W, lane)) : "memory");
            __syncwarp();
            {
                uint32_t off[4];
                float cs[4] = {0.f, 0.f, 0.f, 0.f};
#pragma unroll
                for (int q = 0; q < 4; q++) {
                    const int g_ = (c * 2 + ((w >> 1) & 1)) * 56 + (q == 3 ? 24 : (w & 1) * 32 + q * 8), col = wg * 320 + g_, nb = col / 80;
                    off[q] = g_ < 320 && !(q == 3 && (w & 1)) ? ((nb * 512 + h * 16) * 10 + (col - nb * 80) / 8) * 32 + lane : ~0u;
                }
                const uint32_t ta = sb + O_WO + w * 8192 + (lane & 7) * 64 + (((lane >> 3) ^ (lane >> 1)) & 3) * 16;
#pragma unroll 2
                for (int i = 0; i < 16; i++) {
                    uint32_t r[4];
                    ldsm4t(r, ta + i * 512);
#pragma unroll
                    for (int q = 0; q < 4; q++) {
                        if (off[q] != ~0u) ((uint32_t*)g_wot)[off[q] + i * 320] = r[q];
                        cs[q] += fabsf(bf_lo(r[q])) + fabsf(bf_hi(r[q]));
                    }
                }
                float cm = 0.f;
#pragma unroll
                for (int q = 0; q < 4; q++) {
                    cs[q] += __shfl_xor_sync(~0u, cs[q], 1); cs[q] += __shfl_xor_sync(~0u, cs[q], 2);
                    cm = fmaxf(cm, cs[q]);
                }
                const uint32_t n1 = __reduce_max_sync(~0u, __float_as_uint(cm));
                if (lane == 0) g_co[h * 32 + c * 8 + w] = __uint_as_float(n1);
            }
            mbar_wait(sb + B_W, 0);
            uint32_t v[2];
            lds64(v, sb + O_WMX + (lane < 24 ? lane : 0) * 8);
            const bool mine = (lane >> 3) < 3 && ((lane >> 4) == 1) == (c == 2);
            ma = __reduce_max_sync(~0u, mine ? v[0] : 0u); mb = __reduce_max_sync(~0u, mine ? v[1] : 0u);
            if (c == 2) ma = mb = max(ma, mb);
            fa = __uint_as_float(ma << 16); fb = __uint_as_float(mb << 16);
            if (tid == 0) {
                if (c != 1) g_wmx[h * 3 + c] = fa;
                if (c == 0) g_wmx[h * 3 + 1] = fb;
            }
        } else {
            fa = __ldcg(g_wmx + h * 3 + (c == 2 ? 2 : 0)); fb = __ldcg(g_wmx + h * 3 + (c == 2 ? 2 : 1));
            asm volatile("barrier.cluster.wait.aligned;" ::: "memory");
        }
        if (layer == TLL) TL(49);
        float ia, ib;
        const float sa = pow2_scale(fa, 6, &ia), sc_b = pow2_scale(fb, 6, &ib);
        sl = __uint_as_float(uni(__float_as_uint(ia * ib * (0.08838834764831845f * 1.4426950408889634f))));
        const uint32_t pa = pack_bf(sa, sa), pb = pack_bf(sc_b, sc_b);
        const int ahead = layer == 0 ? 20 : WDEPTH;
        auto convert = [&](int lo) {
#pragma unroll 1
            for (int i = lo; i < lo + 10; i++) {
                issue(i + ahead);
                cp_wait<WDEPTH>();
                const uint32_t d = dst + (i < 19 ? i * 8192 : O_LAST);
                uint32_t u[8];
                lds128(u, d); lds128(u + 4, d + 2048);
#pragma unroll
                for (int q = 0; q < 8; q++)
                    asm("{.reg .b32 m,l,u; mul.rn.bf16x2 m,%0,%1; shl.b32 l,m,16; and.b32 u,m,0xffff0000; cvt.rn.f16x2.f32 %0,u,l;}" : "+r"(u[q]) : "r"(q < 4 ? pa : pb));
                sts128(d, u[0], u[1], u[2], u[3]); sts128(d + 2048, u[4], u[5], u[6], u[7]);
            }
            bar_sync(6 + wg, 128);
        };
        const uint32_t s0 = src + wg * 2048, s1 = src + 2048 - wg * 2048;
        convert(0);
#pragma unroll
        for (int i = 0; i < 10; i++) { ldsm4t(A0[i], s0 + i * 8192); ldsm4t(A1[i], s1 + i * 8192); }
        if (layer == TLL) TL(50);
        convert(10);
#pragma unroll
        for (int i = 10; i < 20; i++) { ldsm4t(A0[i], s0 + (i < 19 ? i * 8192 : O_LAST)); ldsm4t(A1[i], s1 + (i < 19 ? i * 8192 : O_LAST)); }
        if (layer == TLL) TL(53);
        bar_arrive(9, 288);
        bar_sync(4, 288);
        asm volatile("barrier.cluster.arrive.relaxed.aligned;" ::: "memory");
    }
    const uint32_t idn = (lane >> 3) == (lane & 3) ? ((lane & 4) ? 0x3c000000u : 0x3c00u) : 0u;
    float invM = g_invM0;
    char* redp = red_base() + (size_t)layer * 32 * 32768 + w * 2048 + (lane >> 4) * 1024 + ((lane >> 3) & 1) * 256 + (lane & 7) * 16;
    const uint32_t ro2 = uni((w >> 1) * 4096 + 128), rown = uni(c == 2 ? ro2 : c * 16384);
    const uint32_t L16 = lane * 16, L8 = lane * 8, L4 = lane * 4;
    const uint32_t xch0 = uni(sb + O_XCH + t0 * 1024), xch1 = uni(sb + O_XCH + t1 * 1024);
    const uint32_t qo0 = uni(sb + O_QKP + (w & 3) * 1024 + (wg ? 768 : 0)), qp0 = uni(qo0 + (wg ? 128 : 256));
    const uint32_t qo1 = uni(sb + O_QKP + (w & 3) * 1024 + (wg ? 128 : 512)), qp1 = uni(qo1 + (wg ? 256 : 128));
    const uint32_t vo1 = uni(qo1 + (wg ? -128 : 256)), vp1 = uni(qp1 + (wg ? -128 : 256));
    const uint32_t msr = uni(sb + O_MS + wg * 5376);
    const uint32_t msw = uni(msr + ((w >> 1) & 1) * 896 + (w & 1) * 512), msh = uni(msr + ((w >> 1) & 1) * 896 + 384 + (w & 1) * 2);
    const uint32_t sco = uni(sb + O_SC + c * 768 + (w & 3) * 256);
    const uint32_t woa = sb + O_WO + w * 8192 + (lane >> 4) * 512 + (lane & 7) * 64 + (((lane >> 3) ^ (lane >> 1)) & 1) * 16 + ((lane >> 2) & 1) * 32;
    const uint32_t w512 = uni(sb + w * 512), w128 = uni(sb + w * 128);
    const uint32_t pd0 = uni(mapa(sb, c == 2 ? 0 : 2) - sb), pd1 = uni(mapa(sb, c == 1 ? 0 : 1) - sb);
    const bool scw = c < 2 && w >= 4 && w <= 6;
    uint32_t sn = uni(sb + O_STG + (c == 2 ? 8192 : 0) + t1 * 1024);
    uint32_t ka = uni(sb + (w == 6 ? O_QKP + 512 : O_STG + 4096 + (w & 1) * 512));
    uint32_t vs = uni(sb + O_VM + t1 * 256);
    uint32_t va = uni(sb + O_STG + 8192 + w * 2048), vr = uni(sb + O_VM + w * 512);
    const uint32_t sn2 = uni(2 * sn - 16384), ka2 = uni(2 * ka - (w == 6 ? 0 : 16384)), vs2 = uni(2 * vs + 2048), va2 = uni(2 * va - 16384),
                   vr2 = uni(2 * vr + 2048);
    uint32_t xd = uni((uint32_t)mkdesc(sb + O_XS + wg * 20480, 512, 128, 0));
    const uint32_t xd2 = uni(2 * xd + 2560);

    uint32_t wp[2 * NPERM + 1][4];
    sfor<NPERM>([&](auto I) { constexpr int i = I; ldsm4t(wp[2 * i], woa + i * 1024); ldsm4t(wp[2 * i + 1], (woa ^ 32) + i * 1024); });
    auto wo_fetch = [&](uint32_t (&wo)[16][4], auto I) {
        constexpr int i = I;
        if constexpr (i < NPERM) {
#pragma unroll
            for (int q = 0; q < 4; q++) { wo[i][q] = wp[2 * i][q]; wo[8 + i][q] = wp[2 * i + 1][q]; }
        } else { ldsm4t(wo[i], woa + i * 1024); ldsm4t(wo[8 + i], (woa ^ 32) + i * 1024); }
    };
    if (layer == TLL) TL(32);
    float b0[16], b1[16];
    mbar_wait(sb + B_XF, 0);
    if (layer == TLL) TL(33);
    tok_issue<0, NTB>(A0, A1, b0, b1, xd, zero);
    tok_give(b0, L16, xch0);
    tok_issue<NTB, 40>(A0, A1, b0, b1, xd, zero);
    bar_sync(4, 256);
    wg_wait<0>();
    {
        uint32_t e[2][4];
        lds128_u<0>(e[0], L16, xch1); lds128_u<512>(e[1], L16, xch1);
        tok_finish(b1, e, L16, sn, idn);
    }
    sn = sn2 - sn; xd = xd2 - xd;
    bar_sync(5, 288);
    asm volatile("barrier.cluster.wait.aligned;" ::: "memory");
    if (layer == TLL) TL(34);
    mbar_wait(sb + B_XF + 8, 0);
    if (layer == TLL) TL(35);
    tok_issue<0, NTA>(A0, A1, b0, b1, xd, zero);
    uint32_t tr = clock32() - RDELAY;

#pragma unroll 1
    for (int st = 0;; st++) {
        uint4 mv[3];
        asm volatile("{.reg .pred p; .reg .b32 t;\n"
                     "mov.b32 %0,0; mov.b32 %1,0; mov.b32 %2,0; mov.b32 %3,0; mov.b32 %4,0; mov.b32 %5,0; mov.b32 %6,0; mov.b32 %7,0;\n"
                     "mov.b32 %8,0; mov.b32 %9,0; mov.b32 %10,0; mov.b32 %11,0;\n"
                     "T_LOOP: mov.u32 t,%%clock; sub.u32 t,t,%14; setp.ge.u32 p,t,%15;\n"
                     "@p ld.relaxed.gpu.global.v4.u32 {%0,%1,%2,%3},[%12]; @p ld.relaxed.gpu.global.v4.u32 {%4,%5,%6,%7},[%12+16384];\n"
                     "@p ld.relaxed.gpu.global.v4.u32 {%8,%9,%10,%11},[%13];\n"
                     "@!p bra T_LOOP;}"
                     : "=r"(mv[0].x), "=r"(mv[0].y), "=r"(mv[0].z), "=r"(mv[0].w), "=r"(mv[1].x), "=r"(mv[1].y), "=r"(mv[1].z), "=r"(mv[1].w),
                       "=r"(mv[2].x), "=r"(mv[2].y), "=r"(mv[2].z), "=r"(mv[2].w)
                     : "l"(redp), "l"(redp + ro2), "r"(tr), "n"(RDELAY) : "memory");
        STAMP(10);
        tok_issue<NTA, NTB>(A0, A1, b0, b1, xd, zero);
        tok_give(b0, L16, xch0);
        tok_issue<NTB, 40>(A0, A1, b0, b1, xd, zero);
        xd = xd2 - xd;
        STAMP(9);
        if (zero >> 30) break;
        asm volatile("{.reg .pred p; .reg .b32 a,h,t,n; .reg .b16 l,u; .reg .b64 q;\n"
                     "add.u32 a,%12,%13; add.u32 h,%12,%14; mov.u32 n,0;\n"
                     "M_LOOP:\n .pragma \"nounroll\";\n"
                     "st.shared.b32 [a],%0; st.shared.b32 [a+128],%1; st.shared.b32 [a+256],%2; mov.b32 {l,u},%3; st.shared.b16 [h],l;\n"
                     "st.shared.b32 [a+1792],%4; st.shared.b32 [a+1920],%5; st.shared.b32 [a+2048],%6; mov.b32 {l,u},%7; st.shared.b16 [h+1792],l;\n"
                     "st.shared.b32 [a+3584],%8; st.shared.b32 [a+3712],%9; st.shared.b32 [a+3840],%10; mov.b32 {l,u},%11; st.shared.b16 [h+3584],l;\n"
                     "lop3.b32 t,%3,%7,0x50000000,0x7e; lop3.b32 t,t,%11,0x50000000,0xf6; setp.gt.u32 p,t,0xffff;\n"
                     "vote.sync.any.pred p,p,-1; add.u32 n,n,1; setp.lt.and.u32 p,n,%17,p; @!p bra M_DONE;\n"
                     "ld.relaxed.gpu.global.v4.u32 {%0,%1,%2,%3},[%15]; ld.relaxed.gpu.global.v4.u32 {%4,%5,%6,%7},[%15+16384];\n"
                     "cvt.u64.u32 q,%16; add.u64 q,q,%15; ld.relaxed.gpu.global.v4.u32 {%8,%9,%10,%11},[q];\n"
                     "bra M_LOOP;\n"
                     "M_DONE:}"
                     : "+r"(mv[0].x), "+r"(mv[0].y), "+r"(mv[0].z), "+r"(mv[0].w), "+r"(mv[1].x), "+r"(mv[1].y), "+r"(mv[1].z), "+r"(mv[1].w),
                       "+r"(mv[2].x), "+r"(mv[2].y), "+r"(mv[2].z), "+r"(mv[2].w)
                     : "r"(L4), "r"(msw), "r"(msh), "l"(redp), "r"(ro2), "n"(SPIN_LIM) : "memory");
        bar_sync(3, 256);
        STAMP(0);
        uint32_t e[2][4];
        float f1[4];
        {
            uint32_t b[10][4];
            float acc[4][4];
#pragma unroll
            for (int i = 0; i < 4; i++) acc[i][0] = acc[i][1] = acc[i][2] = acc[i][3] = 0.f;
            auto ld = [&](auto I) { constexpr int i = I; ldsm4t_u<i * 512>(b[i], L16, msr); };
            auto mm = [&](auto I) {
                constexpr int i = I;
                mma_f16(acc[0], A0[2 * i], b[i][0], b[i][1]); mma_f16(acc[2], A1[2 * i], b[i][0], b[i][1]);
                mma_f16(acc[1], A0[2 * i + 1], b[i][2], b[i][3]); mma_f16(acc[3], A1[2 * i + 1], b[i][2], b[i][3]);
            };
            ld(IC<0>()); ld(IC<1>()); ld(IC<2>()); ld(IC<3>());
            sts32_u<O_MX>(L4, w128,
                          habsmax(habsmax(habsmax(habsmax(mv[0].x, mv[0].y), habsmax(mv[0].z, mv[1].x)), habsmax(habsmax(mv[1].y, mv[1].z), mv[2].x)),
                                  habsmax(habsmax(mv[2].y, mv[2].z), habsmax(habsmax(mv[0].w, mv[1].w), mv[2].w) & 0xffffu)));
            wg_wait<0>();
            ld(IC<4>()); mm(IC<0>()); ld(IC<5>()); mm(IC<1>()); ld(IC<6>()); mm(IC<2>());
            ld(IC<7>()); mm(IC<3>()); ld(IC<8>()); mm(IC<4>()); ld(IC<9>()); mm(IC<5>());
            lds128_u<0>(e[0], L16, xch1); lds128_u<512>(e[1], L16, xch1);
            mm(IC<6>()); mm(IC<7>()); mm(IC<8>()); mm(IC<9>());
            const uint32_t u0 = pack_bf((acc[0][0] + acc[1][0]) * invM, (acc[0][1] + acc[1][1]) * invM);
            const uint32_t u1 = pack_bf((acc[0][2] + acc[1][2]) * invM, (acc[0][3] + acc[1][3]) * invM);
#pragma unroll
            for (int i = 0; i < 4; i++) f1[i] = (acc[2][i] + acc[3][i]) * invM;
            sts32_u<0>(L4, qo0, u0); sts32_u<0>(L4, qp0, u1); sts32_u<0>(L4, qo1, pack_bf(f1[0], f1[1])); sts32_u<0>(L4, qp1, pack_bf(f1[2], f1[3]));
        }
        STAMP(1);
        bar_sync(1, 320);
        if (__builtin_expect(scw, 1)) {
            float a[4][4];
#pragma unroll
            for (int i = 0; i < 4; i++) a[i][0] = a[i][1] = a[i][2] = a[i][3] = 0.f;
            uint32_t q[4][4], k[4][4];
            sfor<4>([&](auto I) {
                constexpr int i = I;
                ldsm4t_u<O_QKP + i * 1024>(q[i], L16, sb); ldsm4t_u<i * 1024>(k[i], L16, ka);
            });
#pragma unroll
            for (int i = 0; i < 4; i++) {
                mma_bf(a[i & 1], q[i][0], q[i][1], q[i][2], q[i][3], k[i][0], k[i][1]);
                mma_bf(a[2 + (i & 1)], q[i][0], q[i][1], q[i][2], q[i][3], k[i][2], k[i][3]);
            }
            const float mk = w == 6 ? 1.f : 0.f;
            const float x0 = (a[0][0] + a[0][2]) + (a[1][0] + a[1][2]), x1 = (a[0][1] + a[0][3]) + (a[1][1] + a[1][3]);
            const float y0 = (a[2][0] + a[2][2]) + (a[3][0] + a[3][2]), y1 = (a[2][1] + a[2][3]) + (a[3][1] + a[3][3]);
            st_share2(L8, sco, sb + B_S, pd0, pd1, pack_bf(fmaf(y0, mk, x0) * sl, fmaf(y1, mk, x1) * sl), pack_bf(y0 * sl, y1 * sl));
        }
        if (c == 2) {
            const uint32_t x = lds32_u<0>(L4, vo1), y = lds32_u<0>(L4, vp1);
            st_share2(L8, vs, sb + B_S, pd0, pd1, pack_bf(f1[0] + bf_lo(x), f1[1] + bf_hi(x)), pack_bf(f1[2] + bf_lo(y), f1[3] + bf_hi(y)));
        }
        STAMP(3);
        if (st == NSEG - 1) break;
        tok_finish(b1, e, L16, sn, idn);
        redp += (st & 1) ? 32768 - 512 : 512;
        if (wg == 0) {
            uint32_t wo[16][4], vx[2][2][4], vm[2][2];
            ldsm4_u<0>(vx[0][0], L16, va); ldsm4_u<512>(vx[0][1], L16, va); ldsm4_u<1024>(vx[1][0], L16, va); ldsm4_u<1536>(vx[1][1], L16, va);
            sfor<NWO0>([&](auto I) { wo_fetch(wo, I); });
            mbar_wait(sb + B_S, st & 1);
            STAMP(4);
            uint32_t s[5];
            {
                uint32_t p[2][5];
                sfor<2>([&](auto R) {
                    constexpr int r = R;
                    lds64_u<O_SC + r * 768>(p[r], L8, sb); lds64_u<O_SC + r * 768 + 256>(p[r] + 2, L8, sb); p[r][4] = lds32_u<O_SC + r * 768 + 512>(L8, sb);
                });
#pragma unroll
                for (int j = 0; j < 5; j++) s[j] = badd(p[0][j], p[1][j]);
            }
            lds64_u<0>(vm[0], L8, vr); lds64_u<256>(vm[1], L8, vr);
            uint32_t mm = bmax(bmax(bmax(s[0], s[1]), bmax(s[2], s[3])), s[4]);
            mm = bmax(bmax(mm, __shfl_xor_sync(~0u, mm, 1)), bmax(__shfl_xor_sync(~0u, mm, 2), __shfl_xor_sync(~0u, mm, 3)));
            const float m = fmaxf(bf_lo(mm), bf_hi(mm));
            float o0[4] = {0.f, 0.f, 0.f, 0.f}, o1[4] = {0.f, 0.f, 0.f, 0.f}, d[10];
#pragma unroll
            for (int j = 0; j < 5; j++) { d[2 * j] = bf_lo(s[j]) - m; d[2 * j + 1] = bf_hi(s[j]) - m; }
#pragma unroll
            for (int j = 0; j < 10; j++) d[(j + 8) % 10] = ex2(d[(j + 8) % 10]);
            float sum = ((d[8] + d[9]) + (d[0] + d[1])) + ((d[2] + d[3]) + (d[4] + d[5])) + (d[6] + d[7]);
            const uint32_t p4 = pack_bf(d[8], d[9]), p0 = pack_bf(d[0], d[1]), p1 = pack_bf(d[2], d[3]), p2 = pack_bf(d[4], d[5]), p3 = pack_bf(d[6], d[7]);
            mma_bf8(o0, vm[0][0], vm[0][1], p4);
            mma_bf8(o1, vm[1][0], vm[1][1], p4);
            mma_bf(o0, vx[0][0][0], vx[0][0][1], vx[0][0][2], vx[0][0][3], p0, p1);
            mma_bf(o1, vx[1][0][0], vx[1][0][1], vx[1][0][2], vx[1][0][3], p0, p1);
            mma_bf(o0, vx[0][1][0], vx[0][1][1], vx[0][1][2], vx[0][1][3], p2, p3);
            mma_bf(o1, vx[1][1][0], vx[1][1][1], vx[1][1][2], vx[1][1][3], p2, p3);
            sfor<NWO0B - NWO0>([&](auto I) { constexpr int i = I; wo_fetch(wo, IC<NWO0 + i>()); });
            sum += __shfl_xor_sync(~0u, sum, 1);
            sum += __shfl_xor_sync(~0u, sum, 2);
            sts32_u<O_OS>(L4, w512, pack_bf(o0[0], o0[1])); sts32_u<O_OS + 128>(L4, w512, pack_bf(o0[2], o0[3]));
            sts32_u<O_OS + 256>(L4, w512, pack_bf(o1[0], o1[1])); sts32_u<O_OS + 384>(L4, w512, pack_bf(o1[2], o1[3]));
            sts32_u<O_SUM>(lane & 28, sb, __float_as_uint(sum));
            STAMP(5);
            invM = mem_out<NWO0B>(sb, L16, L8, wo, woa, redp + rown, w & 1);
            tr = clock32();

        } else {
            uint32_t wo[16][4];
            sfor<NWO1>([&](auto I) { wo_fetch(wo, I); });
            invM = mem_out<NWO1>(sb, L16, L8, wo, woa, redp + rown, w & 1);
            tr = clock32();

        }
        STAMP(7);
        tok_issue<0, NTA>(A0, A1, b0, b1, xd, zero);
        sn = sn2 - sn; ka = ka2 - ka; vs = vs2 - vs; va = va2 - va; vr = vr2 - vr;
        STAMP(8);
    }
    if (layer == TLL) TL(40);
    if (c == 2) attend_last(sb, layer);
    bar_arrive(8, 320);
    tid = read_tid(); lane = tid & 31;
    float acc[40];
    const int nc = c == 2 ? 10 : 11;
    const int mb = 28 + (h >> 3), nj = c == 2 ? 1 : 2;
    uint32_t rv[2][2];
    const size_t go = ((size_t)(mb * 64 + (w & 3) * 16 + (lane >> 2)) * 640 + (h & 7) * 80 + (wg * 5 + c * 2) * 8 + (lane & 3) * 2) >> 1;
#pragma unroll
    for (int u = 0; u < 4; u++) rv[u >> 1][u & 1] = (u >> 1) < nj ? __ldcg((const uint32_t*)res + go + (u >> 1) * 4 + (u & 1) * 2560) : 0u;
#pragma unroll 1
    for (int k = 0; k < nc; k++) {
        mbar_wait(sb + T_FB + (k % 7) * 8, k >= 7);
        mbar_wait(sb + T_FA + (k & 3) * 8, (k >> 2) & 1);
        if (layer == TLL && k == 0) TL(41);
        const uint64_t da = mkdesc(sb + O_MS + (k & 3) * 16384 + wg * 8192, 1024, 128, 0), db = mkdesc(sb + tail_b(k) + wg * 10240, 1280, 128, 0);
        wg_fence();
#pragma unroll
        for (int q = 0; q < 4; q++) wg_n80_ss(acc, da + q * 128, db + q * 160, k | q);
        wg_commit();
        if (k > 0) {
            wg_wait<1>();
            if (lane == 0) { mbar_arrive(sb + T_EA + ((k - 1) & 3) * 8); if (k <= 4) mbar_arrive(sb + T_EB + (k - 1) * 8); }
        }
    }
    if (layer == TLL) TL(52);
    wg_wait<0>();
    asm volatile("barrier.cluster.arrive.relaxed.aligned; barrier.cluster.wait.aligned;" ::: "memory");
    const uint32_t ra = sb + O_XS + tid * 16, rb = sb + O_MS + tid * 16;
#pragma unroll
    for (int j = 0; j < 5; j++) {
        const float* q = acc + 4 * j;
        sts128(rb + j * 4096, __float_as_uint(wg ? q[0] : q[20]), __float_as_uint(wg ? q[1] : q[21]), __float_as_uint(wg ? q[2] : q[22]), __float_as_uint(wg ? q[3] : q[23]));
    }
    bar_sync(4, 256);
    sfor<5>([&](auto J) {
        constexpr int j = J;
        const float* q = acc + 4 * j;
        uint32_t p[4];
        lds128(p, sb + O_MS + (tid ^ 128) * 16 + j * 4096);
        const uint32_t d = ra + c * 8192 + (j & 1) * 4096;
        asm volatile("{.reg .pred p; setp.eq.u32 p,%7,%8;\n"
                     "@!p st.async.shared::cluster.mbarrier::complete_tx::bytes.v4.f32 [%0],{%1,%2,%3,%4},[%5]; @p st.shared.v4.f32 [%6],{%1,%2,%3,%4};}"
                     ::"r"(mapa(d, j >> 1)), "f"((wg ? q[20] : q[0]) + __uint_as_float(p[0])), "f"((wg ? q[21] : q[1]) + __uint_as_float(p[1])),
                     "f"((wg ? q[22] : q[2]) + __uint_as_float(p[2])), "f"((wg ? q[23] : q[3]) + __uint_as_float(p[3])), "r"(mapa(sb + T_RED, j >> 1)),
                     "r"(d), "r"(c), "n"(j >> 1) : "memory");
    });
    mbar_wait(sb + T_RED, 0);
#pragma unroll 1
    for (int u = 0; u < nj; u++) {
        uint32_t p[3][4];
#pragma unroll
        for (int q = 0; q < 3; q++) lds128(p[q], ra + q * 8192 + u * 4096);
        float y[4];
#pragma unroll
        for (int i = 0; i < 4; i++) y[i] = __uint_as_float(p[0][i]) + __uint_as_float(p[1][i]) + __uint_as_float(p[2][i]);
        ((uint32_t*)out)[go + u * 4] = bfma(pack_bf(y[0], y[1]), 0x3f803f80u, u ? rv[1][0] : rv[0][0]);
        ((uint32_t*)out)[go + u * 4 + 2560] = bfma(pack_bf(y[2], y[3]), 0x3f803f80u, u ? rv[1][1] : rv[0][1]);
    }
    __syncwarp();
    if (layer == 0 && lane == 0) red_release(g_flag + F_R + mb);
    TL(layer == 0 ? 15 : 29);
    asm volatile("barrier.cluster.arrive.relaxed.aligned; barrier.cluster.wait.aligned;" ::: "memory");
}

__device__ __forceinline__ void tail_load_b(const uint32_t sb, const int h, const int c, const int k) {
    mbar_expect(sb + T_FB + (k % 7) * 8, 20480);
    bulk_g2s(sb + tail_b(k), (const char*)g_wot + (size_t)((h & 7) * GNC + c * 11 + k) * 20480, 20480, sb + T_FB + (k % 7) * 8);
}
template <int layer> __device__ __forceinline__ void chain_aux(const uint32_t sb, const int c, const int h, const int nact) {
    const int tid = read_tid(), w = __shfl_sync(~0u, tid >> 5, 0), lane = tid & 31;
    if (w == 8) {
        mbar_init(sb + O_BAR + lane * 8, lane == 2 ? (c == 2 ? 9 : 4) : (lane >= 16 && lane < 20) || (lane >= 27 && lane < 31) ? 8 : 1);
        asm volatile("fence.mbarrier_init.release.cluster;" ::: "memory");
        fence_async_smem();
        __syncwarp();
    }
    {
        uint4* z = (uint4*)red_base() + layer * 65536;
#pragma unroll 1
        for (int i = blockIdx.x * 128 + tid - 256; i < 65536; i += 96 * 128)
            if (i >= 2048 || (i & 32)) z[i] = make_uint4(0, 0, 0, 0);
    }
    if (w == 8 && lane == 0) {
        mbar_expect(sb + B_S, s_tx(c));
        mbar_expect(sb + B_W, 192);
        mbar_expect(sb + T_RED, (c == 2 ? 1 : 2) * 2 * 4096);
        if (layer == 1) prefetch_l2(red_base() + 32 * 32768 + blockIdx.x * 1024, 1024);
        if (layer == 0) wait_flag<400>(g_ready, NSETUP);
    }
    __syncwarp();
    cluster_sync_full();
    asm volatile("barrier.cluster.arrive.relaxed.aligned;" ::: "memory");
    pdl_wait();
    if (w == 11 && lane == 0) red_relaxed(g_flag + F_X + layer * 128 + 65);
    Flag* flag = g_flag + layer * NSEG * 32 + h;
    const Flag* xflag = g_flag + F_X + layer * 128;
    char* const it0 = g_item + (size_t)h * 32768;
    if (w == 8) {
#pragma unroll 1
        for (int n = 0; n < 3; n++) {
            wait_flag<100>(xflag + (n >> 1), 4);
            fence_async_glb();
            if (n == 0) { bar_sync(4, 288); fence_async_smem(); }
            if (lane == 0 && n < 2) {
                mbar_expect(sb + B_XF + n * 8, 40960);
                bulk_g2s(sb + O_XS + n * 40960, (const char*)g_xn + n * 40960, 40960, sb + B_XF + n * 8);
            }
            __syncwarp();
        }
#pragma unroll 1
        for (int n = 0; n < NSEG - 1; n++) {
            const int np = n & 1;
            if (n == 0) { wait_flag<100>(g_flag + F_W + layer * 128, 96); bar_sync(5, 288); } else bar_sync(2, 352);
            if (n == 1) TL(12 + layer * 14);
            if (n == 63) TL(13 + layer * 14);
            if (lane == 0) {
                const uint32_t vs = sb + O_STG + 8192 - np * 16384, vb = sb + B_VX + np * 8;
                if (c == 2) {
                    if (n > 0) __nanosleep(VXN);
                    fence_async_smem();
                    bulk_s2s(mapa(vs, 0), vs, 8192, mapa(vb, 0));
                    bulk_s2s(mapa(vs, 1), vs, 8192, mapa(vb, 1));
                } else mbar_expect(vb, 8192);
                if (n == 0) { mbar_expect(sb + B_XF, 40960); bulk_g2s(sb + O_XS, (const char*)g_xn + 2 * 40960, 40960, sb + B_XF); }
                if (n == h * 3 + c && !np && n + 6 < NSEG) prefetch_l2(red_base() + (size_t)(layer * 32 + (n >> 1) + 3) * 32768, 32768);
            }
            __syncwarp();
        }
        {
            bar_sync(2, 352);
            TL(13 + layer * 14);
            if (lane == 0) {
                if (c == 2) mbar_expect(sb + B_VX + 8, 2 * 8192 + 2 * 2048);
                else {
                    fence_async_smem();
                    bulk_s2s(mapa(sb + O_STG - (c == 0 ? 16384 : 0), 2), sb + O_STG - 16384, 8192, mapa(sb + B_VX + 8, 2));
                }
            }
            __syncwarp();
        }
    } else if (w == 11) {
        float cvo;
        {
            auto max8 = [&](const float* p) {
                const float4 u = ((const float4*)p)[0], v = ((const float4*)p)[1];
                return fmaxf(fmaxf(fmaxf(u.x, u.y), fmaxf(u.z, u.w)), fmaxf(fmaxf(v.x, v.y), fmaxf(v.z, v.w)));
            };
            wait_flag<300>(g_flag + F_W + layer * 128, 96);
            const float* pc = g_co + lane * 32;
            float a = 640.f * __ldcg(g_wmx + lane * 3 + 2), o = fmaxf(fmaxf(max8(pc), max8(pc + 8)), max8(pc + 16));
#pragma unroll 1
            for (int s = 16; s; s >>= 1) { a = fmaxf(a, __shfl_xor_sync(~0u, a, s)); o += __shfl_xor_sync(~0u, o, s); }
            cvo = a * o * 2.f;
        }
        float invM = g_invM0;
        float iq, ik, iv;
        weight_scale(h, 0, &iq); weight_scale(h, 1, &ik); weight_scale(h, 2, &iv);
        if (lane == 0) sts64(sb + O_SCL + 16, __float_as_uint(iq * ik), __float_as_uint(iv));
        const uint32_t L16 = sb + lane * 16 + O_MX;
#pragma unroll 1
        for (int st = 0; st < NSEG; st++) {
            bar_sync(1, 320);
            if (st == NSEG - 1) break;
            if (lane == 0) mbar_arrive(sb + B_STG + (st & 1) * 8);
            uint32_t u[2][4];
            lds128(u[0], L16); lds128(u[1], L16 + 512);
            uint32_t mx = habsmax(habsmax(habsmax(u[0][0], u[0][1]), habsmax(u[0][2], u[0][3])), habsmax(habsmax(u[1][0], u[1][1]), habsmax(u[1][2], u[1][3])));
            mx = __reduce_max_sync(~0u, max(mx & 0x7fffu, (mx >> 16) & 0x7fffu));
            const float bound = fmaxf(__half2float(__ushort_as_half((unsigned short)mx)) * invM, 25.5f) * cvo;
            const float sc = pow2_scale(bound, 15, &invM);
            sts64(sb + O_SCL, __float_as_uint(sc * iv), __float_as_uint(invM));
            bar_arrive(2, 352);
        }
    } else if (w == 10) {
        bar_sync(9, 288);
        if (lane == 0) red_release(g_flag + F_W + layer * 128);
        if (lane == 0) {
#pragma unroll 1
            for (int n = 0; n < NSEG - 1; n++) {
                mbar_sleep(sb + B_STG + (n & 1) * 8, (n >> 1) & 1);
                __nanosleep(EN);
                fence_async_smem();
                const uint32_t stg = sb + O_STG - (n & 1) * 16384;
                char* it = it0 + (size_t)(n % RING) * 32 * 32768;
                bulk_s2g(it + c * 8192, stg + (c == 2 ? 8192 : 0), 8192);
                bulk_commit();
                if (n + 1 >= RING && n + 1 < NSEG) wait_flag(flag - (RING - 1) * 32, 7);
                bulk_wait0();
                mbar_arrive(sb + B_FREE + (n & 1) * 8);
                fence_async_glb();
                red_relaxed(flag);
                flag += 32;
            }
        }
    } else {
        bool allx = false;
#pragma unroll 1
        for (int st = 0; st < NSEG - 1; st++) {
            const int par = st & 1;
            char* const it = it0 + (size_t)(st % RING) * 32 * 32768;
            if (lane == 0 && !allx && st + 3 < NSEG) {
                allx = ld_acquire(xflag + 64) >= nact;
                if (!allx) wait_flag(st + 4 < NSEG ? xflag + ((st + 3) >> 1) : xflag + 64, st + 4 < NSEG ? 4 : nact);
                fence_async_glb();
            }
            __syncwarp();
            if (c < 2) mbar_sleep(sb + B_VX + par * 8, (st >> 1) & 1);
            if (st < NSEG - 2) mbar_sleep(sb + B_XF + par * 8, ((st >> 1) + 1) & 1);
            bar_sync(1, 320);
            if (lane == 0 && st + 3 < NSEG) {
                mbar_expect(sb + B_XF + (par ^ 1) * 8, 40960);
                bulk_g2s_last(sb + O_XS + (par ^ 1) * 40960, (const char*)g_xn + (size_t)(st + 3) * 40960, 40960, sb + B_XF + (par ^ 1) * 8);
            } else if (lane == 0) {
                tail_load_b(sb, h, c, (par ^ 1) * 2); tail_load_b(sb, h, c, (par ^ 1) * 2 + 1);
            }
            __syncwarp();
            if (lane == 0 && c < 2) {
                fence_async_smem();
#pragma unroll 1
                for (int i = 0; i < 4; i++) bulk_s2g(it + 24576 + (c * 4 + i) * 512, sb + O_QKP + i * 1024 + 512, 512);
                bulk_commit();
                asm volatile("cp.async.bulk.wait_group.read 0;" ::: "memory");
            }
            __syncwarp();
            bar_arrive(2, 352);
            mbar_sleep(sb + B_S, par);
            __syncwarp();
            if (lane == 0) {
                mbar_expect(sb + B_S, s_tx(c));
                if (c == 2) { fence_async_smem(); bulk_s2g(it + 28672, sb + O_VM + par * 2048, 2048); bulk_commit(); }
            }
            __syncwarp();
            if (lane == 0) { bulk_wait0(); fence_async_glb(); red_relaxed(flag); }
            __syncwarp();
            mbar_sleep(sb + B_FREE + par * 8, (st >> 1) & 1);
            flag += 32;
        }
        {
            bar_sync(1, 320);
            if (lane == 0 && c < 2) {
                fence_async_smem();
#pragma unroll 1
                for (int i = 0; i < 4; i++)
                    bulk_s2s(mapa(sb + O_LAST + (c * 4 + i) * 512, 2), sb + O_QKP + i * 1024 + 512, 512, mapa(sb + B_VX + 8, 2));
            }
            __syncwarp();
            bar_arrive(8, 320);
        }
    }
    __syncwarp();
    const int nc = c == 2 ? 10 : 11;
    if (w == 10) {
        bar_sync(8, 320);
        if (lane == 0) {
            if (layer == 1 && blockIdx.x == 0) g_ready[0].v = 0;
            if (c < 2) mbar_sleep(sb + B_STG + 8, 1);
            fence_async_smem();
            __nanosleep(TDELAY);
            wait_flag(xflag + 64, nact);
            wait_flag<50>(g_flag + F_O + layer * 32 + 28 + (h >> 3), (h >> 3) == 3 ? 32 + 8 * 32 : 64);
            fence_async_glb();
#pragma unroll 1
            for (int k = 0; k < nc; k++) {
                if (k >= 4) mbar_sleep(sb + T_EA + (k & 3) * 8, ((k >> 2) - 1) & 1);
                mbar_expect(sb + T_FA + (k & 3) * 8, 16384);
                bulk_g2s_last(sb + O_MS + (k & 3) * 16384, (const char*)g_O + (size_t)((28 + (h >> 3)) * GNC + c * 11 + k) * 16384, 16384, sb + T_FA + (k & 3) * 8);
            }
        }
    } else if (w == 9 && lane == 0) {
        __nanosleep(TDELAY);
#pragma unroll 1
        for (int k = 4; k < nc; k++) {
            if (k >= 7) mbar_sleep(sb + T_EB + (k - 7) * 8, 0);
            tail_load_b(sb, h, c, k);
        }
    }
    __syncwarp();
    asm volatile("barrier.cluster.wait.aligned;" ::: "memory");
    asm volatile("barrier.cluster.arrive.relaxed.aligned; barrier.cluster.wait.aligned;" ::: "memory");
    asm volatile("barrier.cluster.arrive.relaxed.aligned; barrier.cluster.wait.aligned;" ::: "memory");
}

constexpr int RI_A = 0, RI_TAB = 81920, RI_STG = RI_TAB + 82 * 768;
constexpr int RI_RES = RI_STG + 25600, RI_ST = RI_RES + 2 * 64 * 336;
constexpr int HB_A = G_BAR + 64, HB_AFREE = HB_A + 32, HB_LN = HB_A + 40, HB_FULL = HB_A + 64, HB_DONE = HB_FULL + 48, HB_FREE = HB_DONE + 48;
constexpr int HP_SMEM = HB_FREE + 48;
static_assert(G_BAR >= RI_ST + 2048, "helper shared-memory map");
#define IDL 280
#define ITEM_NS 60
#define PFW_AT 28
#define PFW_NS 150
__device__ __forceinline__ void helper_aux(const uint32_t sb, const int j, const int nh, const int na, const int nbh, const int layer, const bf16* Wq,
                                           const bf16* Wk, const bf16* Wv, const bf16* Wo) {
    const int w = threadIdx.x >> 5, lane = threadIdx.x & 31, p = w - 8;
    if (lane == 0 && j < (nh & ~3)) {
        int n = 0;
        for (int a = j >> 2; a < 32; a += nh >> 2, n++) {
            if (n == 0) continue;
            mbar_wait(sb + HB_AFREE, (n - 1) & 1);
            mbar_expect(sb + HB_A + p * 8, 20480);
            bulk_g2s_last(sb + RI_A + p * 20480, (const char*)g_YT + (size_t)a * 81920 + p * 20480, 20480, sb + HB_A + p * 8);
            if (p == 0) { mbar_wait(sb + HB_LN, (n - 1) & 1); red_release(g_flag + F_X + layer * 128 + a - (nh >> 2)); }
        }
        if (p == 0) { mbar_wait(sb + HB_LN, (n - 1) & 1); red_release(g_flag + F_X + layer * 128 + (j >> 2) + (n - 1) * (nh >> 2)); }
    }
    __syncwarp();
    if (layer == 0 && w == 8 && lane == 0) wait_flag<400>(g_flag + F_W, 96);
    __syncwarp();
    bar_sync(3, 384);
    if (p == 3 && lane == 0 && j < (nh & ~3)) red_release(g_flag + F_X + layer * 128 + 64);
    fence_async_smem();
    Flag* oflag = g_flag + F_O + layer * 32;
    if (j < na) {
        int sl = p & 1, ph = 1;
        for (int idx = j + (p & 1) * na; idx < (NSEG - 1) * 32 && p >= 2 && lane == 0; idx += 2 * na) {
            mbar_wait(sb + HB_DONE + sl * 8, ph ^ 1);
            mbar_arrive(sb + HB_FREE + sl * 8);
            red_release(oflag + (idx >> 6));
            atomicAdd(&g_flag[layer * NSEG * 32 + idx].v, 1u);
            sl += 2;
            if (sl >= 6) { sl -= 6; ph ^= 1; }
        }
        for (int idx = j + p * na; idx < (NSEG - 1) * 32 && p < 2 && lane == 0; idx += 2 * na) {
            mbar_wait(sb + HB_FREE + sl * 8, ph);
            wait_flag<ITEM_NS>(g_flag + layer * NSEG * 32 + idx, 6);
            fence_async_glb();
            if (idx < (NSEG - 2) * 32) __nanosleep(IDL);
            mbar_expect(sb + HB_FULL + sl * 8, 30720);
            bulk_g2s(sb + sl * 30720, g_item + (size_t)(idx % (RING * 32)) * 32768, 30720, sb + HB_FULL + sl * 8);
            sl += 2;
            if (sl >= 6) { sl -= 6; ph ^= 1; }
        }
    } else if (lane == 0 && p == 3) {
        if (layer == 0) {
            wait_flag<1000>(oflag + PFW_AT, 64);
            const int np = nh - na;
#pragma unroll 1
            for (int i = j - na; i < 1280; i += np) {
                const bf16* W = i < 320 ? Wq : i < 640 ? Wk : i < 960 ? Wv : Wo;
                prefetch_l2((const char*)W + (size_t)(i % 320) * 16384, 16384);
                __nanosleep(PFW_NS);
            }
#pragma unroll 1
            for (int i = j - na; i < 205; i += np) {
                const char* p_ = i < 160 ? (const char*)g_Wf + i * 16384 : i < 165 ? (const char*)g_stat + (i - 144) * 16384
                               : i < 167 ? (const char*)g_ctab + (i - 165) * 8192 : (const char*)(g_flag + NFLAG) - (i - 166) * 16384;
                prefetch_l2(p_, 16384);
                __nanosleep(PFW_NS);
            }
            if (j - na < 16) prefetch_l2(g_rtab + (j - na) * (RF_A / 4), RF_A / 4);
#pragma unroll 1
            for (int i = j - na; i < 130; i += np) { prefetch_l2((const char*)g_xb + i * 16384, 16384); __nanosleep(PFW_NS); }
        }
    } else if (lane == 0) {
        if (p == 2) wait_flag<500>(g_flag + F_X + layer * 128 + 64, nh & ~3);
        int c0 = 0;
        for (int mb = (j - na) >> 3; mb < nbh; mb += (nh - na) >> 3, c0 += GNC) {
            if (p < 2) wait_flag<300>(oflag + 2 * mb + p, 64);
            fence_async_glb();
            oproj_load(sb, p, mb, (j - na) & 7, c0, nh - na < 24 ? 0 : mb == nbh - 1 ? GPACE2 : GPACE);
        }
    }
}
__device__ __forceinline__ void helper_mma(char* sm, const int jh, const int nh, const int na, const int nbh, const int layer, const bf16* res, bf16* x,
                                           bf16* out) {
    const uint32_t sb = smem_u32(sm);
    const int tid = threadIdx.x, w = tid >> 5, lane = tid & 31;
    const bool act = jh < (nh & ~3);
    const int j4 = jh & 3;
    const int fr = tid & 63, rg = w >> 1;
    auto chunk0 = [&](int u) { return u == 0 ? 5 * j4 : u == 1 ? 75 - 5 * j4 : u == 2 ? 40 + 5 * j4 : 35 - 5 * j4; };
    const int gr = tid / 20, gq_ = tid - gr * 20, go = gr * 80 + chunk0(gq_ / 5) + gq_ % 5;
    const uint32_t gs = sb + RI_RES + gr * 336 + gq_ * 16;
    auto residual = [&](int a, int n) {
#pragma unroll 1
        for (int r = 0; r < 64 - gr && tid < 240 && a < 32; r += 12) cp_async16(gs + (n & 1) * 21504 + r * 336, (const uint4*)res + (a * 64 + r) * 80 + go);
        cp_commit();
    };
    if (act) {
        if (tid < 240) {
            const int k0 = tid / 48, n = tid - k0 * 48;
            const float d = (float)(40 * j4 + n), amp = 2.f * 0.03952847075210474f;
#pragma unroll 4
            for (int u = 0; u < 16; u++)
                *(uint4*)(sm + RI_TAB + (tid + u * 240) * 16) = cos_row8(fmaf((float)((k0 + (u & 3) * 5) * 16 + ((u >> 2) & 1)), d, (float)((u & 8) * 20)), 2.f * d, amp);
            if (tid < 96) *(uint4*)(sm + RI_TAB + (3840 + tid) * 16) = make_uint4(k0 == 0 ? pack_h((n & 1) ? -amp : amp, 0.f) : 0u, 0, 0, 0);
        }
        fence_async_smem();
        residual(jh >> 2, 0);
    }
    bar_sync(1, 384);
    if (layer == TLL) TL(36);
    if (act) {
        const float4 wm = ((const float4*)g_wmax)[lane];
        const int wg = w >> 2;
        int n = 0;
#pragma unroll 1
        for (int a = jh >> 2; a < 32; a += nh >> 2, n++) {
            float acc[2][24];
            uint64_t da = mkdesc(sb + RI_A + wg * 40960, 1024, 1024, 1), db = mkdesc(sb + RI_TAB + wg * 30720, 768, 128, 0);
#pragma unroll
            for (int gq = 0; gq < 2; gq++) {
                mbar_wait(sb + HB_A + (wg * 2 + gq) * 8, n & 1);
                if (layer == TLL && n == TLN && gq == 0) TL(45);
                wg_fence();
#pragma unroll 5
                for (int k = 0; k < 10; k++) { wg_n48_ss_ta(acc[gq], da, db, k); da += 128; db += 96; }
                wg_commit();
            }
            if (wg == 0) {
                mbar_wait(sb + HB_A + 16, n & 1);
                wg_fence();
                wg_n48_ss_ta(acc[0], da, db + 20 * 96, 1);
                wg_commit();
            }
            float inv;
            pow2_scale(__uint_as_float(__reduce_max_sync(~0u, __float_as_uint(fmaxf(fmaxf(wm.x, wm.y), fmaxf(wm.z, wm.w))))), 0, &inv);
            const uint32_t ysc = pack_bf(inv, inv);
            wg_wait<0>();
            if (layer == TLL && n == TLN) TL(46);
            if (lane == 0) mbar_arrive(sb + HB_AFREE);
            const uint32_t ad = sb + RI_STG + ((w & 3) * 16 + (lane & 15)) * 400 + (lane >> 4) * 96 + wg * 192;
#pragma unroll
            for (int q = 0; q < 6; q++) {
                const float *e = acc[0] + q * 4, *o = acc[1] + q * 4;
                stsm4(ad + q * 16, pack_h(e[0] + o[0], e[1] + o[1]), pack_h(e[2] + o[2], e[3] + o[3]), pack_h(e[0] - o[0], e[1] - o[1]), pack_h(e[2] - o[2], e[3] - o[3]));
            }
            cp_wait<0>();
            bar_sync(4, 256);
            const uint32_t xa = sb + RI_RES + (n & 1) * 21504 + fr * 336 + rg * 80, sg = (rg & 1) ? 0xbc00bc00u : 0x3c003c00u;
            float sum = 0.f, sq = 0.f;
            uint32_t ya = sb + RI_STG + fr * 400 + (rg >> 1) * 96 + ((rg & 1) ? 64 : 0), carry;
            asm("fma.rn.f16x2 %0,%1,%2,%3;" : "=r"(carry) : "r"(lds32(ya + 208)), "r"(sg), "r"(lds32(ya + 16)));
#pragma unroll 1
            for (int ch = 0; ch < 5; ch++, ya += (rg & 1) ? -16 : 16) {
                uint32_t y[4], z[4], xr[4];
                lds128(y, ya); lds128(z, ya + 192); lds128(xr, xa + ch * 16);
#pragma unroll
                for (int q = 0; q < 4; q++) asm("fma.rn.f16x2 %0,%1,%2,%0;" : "+r"(y[q]) : "r"(z[q]), "r"(sg));
                if (rg & 1) {
                    const uint32_t y0 = y[0], y1 = y[1];
                    y[0] = __byte_perm(carry, y[3], 0x7610); y[1] = __byte_perm(y[3], y[2], 0x7610);
                    y[3] = __byte_perm(y1, y0, 0x7610); y[2] = __byte_perm(y[2], y1, 0x7610);
                    carry = y0;
                }
#pragma unroll
                for (int q = 0; q < 4; q++) {
                    const float2 yf = __half22float2(*(const __half2*)&y[q]);
                    xr[q] = bfma(pack_bf(yf.x, yf.y), ysc, xr[q]);
                    const float e = bf_lo(xr[q]), f = bf_hi(xr[q]);
                    sum += e + f; sq = fmaf(e, e, fmaf(f, f, sq));
                }
                sts128(xa + ch * 16, xr[0], xr[1], xr[2], xr[3]);
            }
            uint2* stat = g_stat + (size_t)(layer * 32 + a) * 1024 + rg * 64 + fr;
            asm volatile("st.relaxed.gpu.global.v2.u32 [%0],{%1,%2};" ::"l"(stat + j4 * 256), "r"(__float_as_uint(sum)), "r"(__float_as_uint(sq) | 0x80000000u) : "memory");
            if (layer == TLL && n == TLN) TL(47);
            uint32_t s0[3], s1[3];
            int lim = 0;
            do {
#pragma unroll
                for (int q = 0; q < 3; q++)
                    asm volatile("ld.relaxed.gpu.global.v2.u32 {%0,%1},[%2];" : "=r"(s0[q]), "=r"(s1[q]) : "l"(stat + ((j4 + 1 + q) & 3) * 256) : "memory");
            } while (__any_sync(~0u, (int)(s1[0] & s1[1] & s1[2]) >= 0) && ++lim < SPIN_LIM);
#pragma unroll
            for (int q = 0; q < 3; q++) { sum += __uint_as_float(s0[q]); sq -= __uint_as_float(s1[q]); }
            sts64(sb + RI_ST + tid * 8, __float_as_uint(sum), __float_as_uint(sq));
            bar_sync(4, 256);
            if (layer == TLL && n == TLN) TL(48);
#pragma unroll
            for (int q = 1; q < 4; q++) {
                uint32_t st2[2];
                lds64(st2, sb + RI_ST + ((tid + q * 64) & 255) * 8);
                sum += __uint_as_float(st2[0]); sq += __uint_as_float(st2[1]);
            }
            const float mean = sum * (1.f / 640.f), r = rsqrtf(fmaxf(fmaf(-mean, mean, sq * (1.f / 640.f)), 0.f) + 1e-5f), off = -mean * r;
            uint4* dst = (uint4*)g_xn + ((size_t)(2 * a + (w & 1)) * 80 + chunk0(rg)) * 32 + lane;
#pragma unroll
            for (int i = 0; i < 5; i++) {
                uint32_t u[4];
                lds128(u, xa + i * 16);
                dst[i * 32] = make_uint4(pack_h(fmaf(bf_lo(u[0]), r, off), fmaf(bf_hi(u[0]), r, off)), pack_h(fmaf(bf_lo(u[1]), r, off), fmaf(bf_hi(u[1]), r, off)),
                                         pack_h(fmaf(bf_lo(u[2]), r, off), fmaf(bf_hi(u[2]), r, off)), pack_h(fmaf(bf_lo(u[3]), r, off), fmaf(bf_hi(u[3]), r, off)));
            }
            __syncwarp();
            if (lane == 0) mbar_arrive(sb + HB_LN);
            if (layer == TLL) TL(37);
            if (layer == TLL && n == TLN) TL(44);
            residual(a + (nh >> 2), n + 1);
#pragma unroll 2
            for (int rr = 0; rr < 64 - gr && tid < 240; rr += 12) {
                uint32_t v[4];
                lds128(v, gs + (n & 1) * 21504 + rr * 336);
                ((uint4*)x)[(a * 64 + rr) * 80 + go] = make_uint4(v[0], v[1], v[2], v[3]);
            }
        }
    }
    bar_sync(3, 384);
    if (layer == TLL) TL(38);
    if (jh >= na) {
        int c0 = 0;
#pragma unroll 1
        for (int mb = (jh - na) >> 3; mb < nbh; mb += (nh - na) >> 3, c0 += GNC) oproj_mma(sb, mb, (jh - na) & 7, c0, x, out, layer);
        if (layer == TLL) TL(42);
        return;
    }
    const int p = w >> 1, mi = w & 1;
    int slot = p, ph = 0;
    for (int idx = jh + p * na; idx < (NSEG - 1) * 32; idx += 4 * na) {
        const uint32_t it = sb + slot * 30720 + lane * 16;
        float iq, ik, iv;
        weight_scale(idx & 31, 0, &iq); weight_scale(idx & 31, 1, &ik); weight_scale(idx & 31, 2, &iv);
        bar_sync(6 + p, 64);
        mbar_wait(sb + HB_DONE + slot * 8, ph ^ 1);
        mbar_wait(sb + HB_FULL + slot * 8, ph);
        tok_attention<8, 8>(it, 8192, it + 24576, 2048, it + 16384, it - lane * 8 + 28672, 0, mi, lane, idx >> 5, idx & 31, iq * ik, iv);
        __syncwarp();
        if (lane == 0) mbar_arrive(sb + HB_DONE + slot * 8);
        slot += 4;
        if (slot >= 6) { slot -= 6; ph ^= 1; }
    }
    if (layer == TLL) TL(39);
}

template <int layer> __global__ void __cluster_dims__(3, 1, 1) __launch_bounds__(384, 1)
k_chain(const int nact, const uint32_t zero, const bf16* __restrict__ Wq, const bf16* __restrict__ Wk, const bf16* __restrict__ Wv,
        const bf16* __restrict__ Wo, const bf16* res, bf16* out) {
    extern __shared__ __align__(1024) char sm[];
    const uint32_t sb = smem_u32(sm);
    const int b = blockIdx.x, h = b / 3, c = b - h * 3;
    pdl_go();
    if (threadIdx.x >= 256) {
        asm volatile("setmaxnreg.dec.sync.aligned.u32 24;");
        TL(11 + layer * 14);
        chain_aux<layer>(sb, c, h, nact);
    } else {
        asm volatile("setmaxnreg.inc.sync.aligned.u32 240;");
        chain_mma<layer>(sb, c, h, zero, Wq, Wk, Wv, Wo, res, out);
    }
}
__global__ void __launch_bounds__(384, 1) k_help(const bf16* res, bf16* x, bf16* out, const int layer, const int na, const int nbh, const int zero, const bf16* Wq,
                                                  const bf16* Wk, const bf16* Wv, const bf16* Wo) {
    extern __shared__ __align__(1024) char sm[];
    if (layer == TLL) TL(51);
    pdl_go();
    if (threadIdx.x >= 256) {
        const uint32_t sb = smem_u32(sm);
        const int p = (threadIdx.x >> 5) - 8, i = (threadIdx.x & 31) * 4 + p;
        if (i < 34) mbar_init(sb + G_BAR + i * 8, i < 4 ? 3 : i < 8 || i == 12 || i == 13 ? 8 : i >= 22 && i < 28 ? 2 : 1);
        fence_async_smem();
        wait_flag<100>(g_flag + F_X + layer * 128 + 65, 1);
        fence_async_glb();
        if (i == 8 + p && blockIdx.x < (gridDim.x & ~3)) {
            mbar_expect(sb + HB_A + p * 8, 20480);
            bulk_g2s(sb + RI_A + p * 20480, (const char*)g_YT + (size_t)(blockIdx.x >> 2) * 81920 + p * 20480, 20480, sb + HB_A + p * 8);
        }
        __syncwarp();
        bar_sync(2, 128);
        bar_arrive(1, 384);
    }
    if (threadIdx.x + zero >= 256) helper_aux(smem_u32(sm), blockIdx.x, gridDim.x, na, nbh, layer, Wq, Wk, Wv, Wo);
    else helper_mma(sm, blockIdx.x, gridDim.x, na, nbh, layer, res, x, out);
    __syncwarp();
    if (blockIdx.x == 0) pdl_wait();
}

#define COL_PAD 15872
template <class... P, class... A>
void launch_pdl(void (*k)(P...), int grid, int block, int smem, cudaStream_t st, A... args) {
    cudaLaunchConfig_t cfg = {};
    cfg.gridDim = dim3(grid); cfg.blockDim = dim3(block); cfg.dynamicSmemBytes = smem; cfg.stream = st;
    cudaLaunchAttribute at[1];
    at[0].id = cudaLaunchAttributeProgrammaticStreamSerialization; at[0].val.programmaticStreamSerializationAllowed = 1;
    cfg.attrs = at;
    cfg.numAttrs = 1;
    cudaLaunchKernelEx(&cfg, k, args...);
}

}

extern "C" void kernel_launch(void* const* d_in, const int* in_sizes, int n_in, void* d_out, int out_size) {
    const bf16* x = (const bf16*)d_in[0];
    const bf16* wr = (const bf16*)d_in[1];
    const bf16* wi = (const bf16*)d_in[2];
    const bf16* mem0 = (const bf16*)d_in[4];
    const bf16* Wq = (const bf16*)d_in[5];
    const bf16* Wk = (const bf16*)d_in[6];
    const bf16* Wv = (const bf16*)d_in[7];
    const bf16* Wo = (const bf16*)d_in[8];
    bf16* out = (bf16*)d_out;
    static int nhelp = 0;
    static bf16 *xa, *xb;
    static cudaStream_t s1;
    static cudaEvent_t ev_fork, ev_join;
    if (!nhelp) {
        cudaStreamCreateWithFlags(&s1, cudaStreamNonBlocking);
        cudaEventCreateWithFlags(&ev_fork, cudaEventDisableTiming);
        cudaEventCreateWithFlags(&ev_join, cudaEventDisableTiming);
        cudaFuncSetAttribute(k_setup, cudaFuncAttributeMaxDynamicSharedMemorySize, SU_SMEM);
        cudaFuncSetAttribute(k_rowf<0>, cudaFuncAttributeMaxDynamicSharedMemorySize, RF_SMEM);
        cudaFuncSetAttribute(k_rowf<1>, cudaFuncAttributeMaxDynamicSharedMemorySize, RF_SMEM);
        cudaFuncSetAttribute(k_col, cudaFuncAttributeMaxDynamicSharedMemorySize, COL_PAD);
        cudaFuncSetAttribute(k_chain<0>, cudaFuncAttributeMaxDynamicSharedMemorySize, CH_SMEM);
        cudaFuncSetAttribute(k_chain<1>, cudaFuncAttributeMaxDynamicSharedMemorySize, CH_SMEM);
        cudaFuncSetAttribute(k_setup, cudaFuncAttributePreferredSharedMemoryCarveout, 100);
        cudaFuncSetAttribute(k_rowf<0>, cudaFuncAttributePreferredSharedMemoryCarveout, 100);
        cudaFuncSetAttribute(k_rowf<1>, cudaFuncAttributePreferredSharedMemoryCarveout, 100);
        cudaFuncSetAttribute(k_col, cudaFuncAttributePreferredSharedMemoryCarveout, 100);
        cudaFuncSetAttribute(k_chain<0>, cudaFuncAttributePreferredSharedMemoryCarveout, 100);
        cudaFuncSetAttribute(k_chain<1>, cudaFuncAttributePreferredSharedMemoryCarveout, 100);
        cudaFuncSetAttribute(k_help, cudaFuncAttributeMaxDynamicSharedMemorySize, HP_SMEM);
        cudaFuncSetAttribute(k_help, cudaFuncAttributePreferredSharedMemoryCarveout, 100);
        int dev = 0, sms = 0;
        cudaGetDevice(&dev);
        cudaDeviceGetAttribute(&sms, cudaDevAttrMultiProcessorCount, dev);
        nhelp = sms - 96 < 12 ? 12 : sms - 96;
        cudaGetSymbolAddress((void**)&xa, g_xa);
        cudaGetSymbolAddress((void**)&xb, g_xb);
    }
    const int na = nhelp - (nhelp >= 36 ? 24 : nhelp >= 28 ? 16 : 8), nbh = 14;
    cudaStream_t s0 = cudaStreamPerThread;
    cudaEventRecord(ev_fork, s0);
    cudaStreamWaitEvent(s1, ev_fork, 0);
    k_rowf<1><<<(96 + nhelp) & ~1, 256, RF_SMEM, s0>>>(x);
    k_setup<<<NSETUP, 256, SU_SMEM, s1>>>(wr, wi, mem0);
    cudaEventRecord(ev_join, s1);
#define NLAYER 2
    for (int l = 0; l < NLAYER; l++) {
        const bf16* xin = l == 0 ? x : xb;
        if (l == 1) launch_pdl(k_rowf<0>, 128, 256, RF_SMEM, s0, xin);
        launch_pdl(k_col, 321, 128, l == 0 ? 0 : COL_PAD, s0, (int)(l == 0));
        launch_pdl(l == 0 ? k_chain<0> : k_chain<1>, 96, 384, CH_SMEM, s0, nhelp & ~3, 0u, Wq, Wk, Wv, Wo, (const bf16*)xa, l == 0 ? xb : out);
        launch_pdl(k_help, nhelp, 384, HP_SMEM, s0, xin, xa, l == 0 ? xb : out, l, na, nbh, 0, Wq, Wk, Wv, Wo);
    }
    cudaStreamWaitEvent(s0, ev_join, 0);
}
```

```cpp
#include <cuda_runtime.h>
#include <cuda_bf16.h>
#include <cuda_fp16.h>
#include <stdint.h>
#include <string.h>

namespace {

typedef __nv_bfloat16 bf16;
constexpr int S_ = 2048, D_ = 640, NSEG = 64;
constexpr int SPIN_LIM = 1 << 13;

__device__ float                  g_wmx[96];
__device__ __align__(1024) bf16   g_wot[4096 * 640];
__device__ __align__(16) float    g_co[1024];
__device__ __align__(256) uint2   g_stat[2 * 32 * 16 * 64];
__device__ float                  g_invM0;
__device__ __align__(16) float    g_wmax[128];
__device__ __align__(1024) char   g_redraw[65 * 32768];
constexpr int F_X = 2 * NSEG * 32, F_O = F_X + 2 * 128, NFLAG = F_O + 128, RING = 8;
constexpr int F_W = F_X + 66;
constexpr int F_R = F_O + 64;
constexpr int NSETUP = 131;
struct __align__(256) Flag { unsigned v; };
__device__ Flag                   g_flag[NFLAG];
__device__ Flag                   g_ready[1];
__device__ __align__(1024) char   g_item[RING * 32 * 32768];
__device__ __align__(1024) bf16   g_O[S_ * 4096];
__device__ __align__(1024) __half g_xn[S_ * D_];
__device__ __align__(1024) bf16   g_xa[S_ * D_];
__device__ __align__(1024) bf16   g_xb[S_ * D_];
__device__ __align__(1024) __half g_UT[D_ * S_];
__device__ __align__(1024) __half g_YT[D_ * S_];
__device__ __align__(1024) __half g_ctab[64 * 128 + 64 * 64];
__device__ __align__(1024) uint32_t g_Wf[321 * 2048];

#define TL(i)
#define TLN 0
#define TLL 1
#define CK(i)
__device__ __forceinline__ uint32_t smem_u32(const void* p) { return (uint32_t)__cvta_generic_to_shared(p); }
__device__ __forceinline__ uint32_t mapa(uint32_t a, uint32_t r) { uint32_t o; asm("mapa.shared::cluster.u32 %0,%1,%2;" : "=r"(o) : "r"(a), "r"(r)); return o; }
__device__ __forceinline__ void mbar_init(uint32_t a, int c) { asm volatile("mbarrier.init.shared::cta.b64 [%0],%1;" ::"r"(a), "r"(c) : "memory"); }
__device__ __forceinline__ void mbar_expect(uint32_t a, int bytes) { asm volatile("mbarrier.arrive.expect_tx.shared::cta.b64 _,[%0],%1;" ::"r"(a), "r"(bytes) : "memory"); }
__device__ __forceinline__ void mbar_arrive(uint32_t a) { asm volatile("mbarrier.arrive.shared::cta.b64 _,[%0];" ::"r"(a) : "memory"); }
__device__ __forceinline__ bool mbar_try(uint32_t a, uint32_t par) {
    uint32_t p;
    asm volatile("{.reg .pred q; mbarrier.try_wait.parity.shared::cta.b64 q,[%1],%2; selp.u32 %0,1,0,q;}" : "=r"(p) : "r"(a), "r"(par) : "memory");
    return p;
}
__device__ __forceinline__ void mbar_wait(uint32_t a, uint32_t par) {
    if (!mbar_try(a, par)) {
        int lim = 0;
        while (!mbar_try(a, par) && ++lim < SPIN_LIM) {}
    }
}
__device__ __forceinline__ void mbar_sleep(uint32_t a, uint32_t par) {
    asm volatile("{.reg .pred q; .reg .u32 n; mov.u32 n,0;\n"
                 "W_LOOP: mbarrier.try_wait.parity.shared::cta.b64 q,[%0],%1,%2; add.u32 n,n,1; setp.lt.and.u32 q,n,%3,!q; @q bra W_LOOP;}"
                 ::"r"(a), "r"(par), "n"(20000), "n"(SPIN_LIM) : "memory");
}
__device__ __forceinline__ void bar_arrive(int id, int n) { asm volatile("bar.arrive %0,%1;" ::"r"(id), "r"(n) : "memory"); }
__device__ __forceinline__ uint32_t clock32() { uint32_t c; asm volatile("mov.u32 %0,%%clock;" : "=r"(c)); return c; }
__device__ __forceinline__ uint32_t read_tid() { uint32_t v; asm volatile("mov.u32 %0,%%tid.x;" : "=r"(v)); return v; }
__device__ __forceinline__ void bar_sync(int id, int n) { asm volatile("bar.sync %0,%1;" ::"r"(id), "r"(n) : "memory"); }
__device__ __forceinline__ void fence_async_smem() { asm volatile("fence.proxy.async.shared::cta;" ::: "memory"); }
__device__ __forceinline__ void fence_async_glb() { asm volatile("fence.proxy.async.global;" ::: "memory"); }
__device__ __forceinline__ void cluster_sync_full() { asm volatile("barrier.cluster.arrive.aligned; barrier.cluster.wait.aligned;" ::: "memory"); }
__device__ __forceinline__ void bulk_g2s(uint32_t dst, const void* src, int bytes, uint32_t mb) {
    asm volatile("cp.async.bulk.shared::cluster.global.mbarrier::complete_tx::bytes [%0],[%1],%2,[%3];" ::"r"(dst), "l"(src), "r"(bytes), "r"(mb) : "memory");
}
__device__ __forceinline__ void bulk_g2s_last(uint32_t dst, const void* src, int bytes, uint32_t mb) {
    asm volatile("{.reg .b64 p; createpolicy.fractional.L2::evict_first.b64 p, 1.0;\n"
                 "cp.async.bulk.shared::cluster.global.mbarrier::complete_tx::bytes.L2::cache_hint [%0],[%1],%2,[%3],p;}"
                 ::"r"(dst), "l"(src), "r"(bytes), "r"(mb) : "memory");
}
__device__ __forceinline__ void bulk_s2s(uint32_t dst, uint32_t src, int bytes, uint32_t mb) {
    asm volatile("cp.async.bulk.shared::cluster.shared::cta.mbarrier::complete_tx::bytes [%0],[%1],%2,[%3];" ::"r"(dst), "r"(src), "r"(bytes), "r"(mb) : "memory");
}
__device__ __forceinline__ void bulk_s2g(void* dst, uint32_t src, int bytes) {
    asm volatile("cp.async.bulk.global.shared::cta.bulk_group [%0],[%1],%2;" ::"l"(dst), "r"(src), "r"(bytes) : "memory");
}
__device__ __forceinline__ void cp_async16(uint32_t dst, const void* src, uint32_t bytes = 16) {
    asm volatile("cp.async.cg.shared.global [%0],[%1],16,%2;" ::"r"(dst), "l"(src), "r"(bytes) : "memory");
}
__device__ __forceinline__ void cp_commit() { asm volatile("cp.async.commit_group;" ::: "memory"); }
template <int N> __device__ __forceinline__ void cp_wait() { asm volatile("cp.async.wait_group %0;" ::"n"(N) : "memory"); }
__device__ __forceinline__ void bulk_commit() { asm volatile("cp.async.bulk.commit_group;" ::: "memory"); }
__device__ __forceinline__ void bulk_wait0() { asm volatile("cp.async.bulk.wait_group 0;" ::: "memory"); }
__device__ __forceinline__ void ldsm4(uint32_t* r, uint32_t a) {
    asm volatile("ldmatrix.sync.aligned.m8n8.x4.shared.b16 {%0,%1,%2,%3},[%4];" : "=r"(r[0]), "=r"(r[1]), "=r"(r[2]), "=r"(r[3]) : "r"(a) : "memory");
}
__device__ __forceinline__ void ldsm4t(uint32_t* r, uint32_t a) {
    asm volatile("ldmatrix.sync.aligned.m8n8.x4.trans.shared.b16 {%0,%1,%2,%3},[%4];" : "=r"(r[0]), "=r"(r[1]), "=r"(r[2]), "=r"(r[3]) : "r"(a) : "memory");
}
__device__ __forceinline__ void stsm4(uint32_t a, uint32_t r0, uint32_t r1, uint32_t r2, uint32_t r3) {
    asm volatile("stmatrix.sync.aligned.m8n8.x4.shared.b16 [%0],{%1,%2,%3,%4};" ::"r"(a), "r"(r0), "r"(r1), "r"(r2), "r"(r3) : "memory");
}
__device__ __forceinline__ void stsm4t(uint32_t a, uint32_t r0, uint32_t r1, uint32_t r2, uint32_t r3) {
    asm volatile("stmatrix.sync.aligned.m8n8.x4.trans.shared.b16 [%0],{%1,%2,%3,%4};" ::"r"(a), "r"(r0), "r"(r1), "r"(r2), "r"(r3) : "memory");
}
__device__ __forceinline__ void lds128(uint32_t* r, uint32_t a) {
    asm volatile("ld.shared.v4.b32 {%0,%1,%2,%3},[%4];" : "=r"(r[0]), "=r"(r[1]), "=r"(r[2]), "=r"(r[3]) : "r"(a) : "memory");
}
__device__ __forceinline__ void lds64(uint32_t* r, uint32_t a) {
    asm volatile("ld.shared.v2.b32 {%0,%1},[%2];" : "=r"(r[0]), "=r"(r[1]) : "r"(a) : "memory");
}
__device__ __forceinline__ uint32_t lds32(uint32_t a) { uint32_t v; asm volatile("ld.shared.b32 %0,[%1];" : "=r"(v) : "r"(a) : "memory"); return v; }
__device__ __forceinline__ void sts128(uint32_t a, uint32_t r0, uint32_t r1, uint32_t r2, uint32_t r3) {
    asm volatile("st.shared.v4.b32 [%0],{%1,%2,%3,%4};" ::"r"(a), "r"(r0), "r"(r1), "r"(r2), "r"(r3) : "memory");
}
__device__ __forceinline__ void sts64(uint32_t a, uint32_t v0, uint32_t v1) { asm volatile("st.shared.v2.b32 [%0],{%1,%2};" ::"r"(a), "r"(v0), "r"(v1) : "memory"); }
[[maybe_unused]] __device__ __forceinline__ void sts32(uint32_t a, uint32_t v) { asm volatile("st.shared.b32 [%0],%1;" ::"r"(a), "r"(v) : "memory"); }
#define AU_(op) "{.reg .u32 t; add.u32 t,%4,%5; " op " {%0,%1,%2,%3},[t+%6];}"
template <int I> __device__ __forceinline__ void ldsm4_u(uint32_t* r, uint32_t a, uint32_t u) {
    asm volatile(AU_("ldmatrix.sync.aligned.m8n8.x4.shared.b16") : "=r"(r[0]), "=r"(r[1]), "=r"(r[2]), "=r"(r[3]) : "r"(a), "r"(u), "n"(I) : "memory");
}
template <int I> __device__ __forceinline__ void ldsm4t_u(uint32_t* r, uint32_t a, uint32_t u) {
    asm volatile(AU_("ldmatrix.sync.aligned.m8n8.x4.trans.shared.b16") : "=r"(r[0]), "=r"(r[1]), "=r"(r[2]), "=r"(r[3]) : "r"(a), "r"(u), "n"(I) : "memory");
}
template <int I> __device__ __forceinline__ void lds128_u(uint32_t* r, uint32_t a, uint32_t u) {
    asm volatile(AU_("ld.shared.v4.b32") : "=r"(r[0]), "=r"(r[1]), "=r"(r[2]), "=r"(r[3]) : "r"(a), "r"(u), "n"(I) : "memory");
}
template <int I> __device__ __forceinline__ void lds64_u(uint32_t* r, uint32_t a, uint32_t u) {
    asm volatile("{.reg .u32 t; add.u32 t,%2,%3; ld.shared.v2.b32 {%0,%1},[t+%4];}" : "=r"(r[0]), "=r"(r[1]) : "r"(a), "r"(u), "n"(I) : "memory");
}
template <int I> __device__ __forceinline__ uint32_t lds32_u(uint32_t a, uint32_t u) {
    uint32_t v;
    asm volatile("{.reg .u32 t; add.u32 t,%1,%2; ld.shared.b32 %0,[t+%3];}" : "=r"(v) : "r"(a), "r"(u), "n"(I) : "memory");
    return v;
}
template <int I> __device__ __forceinline__ void sts64_u(uint32_t a, uint32_t u, uint32_t v0, uint32_t v1) {
    asm volatile("{.reg .u32 t; add.u32 t,%0,%1; st.shared.v2.b32 [t+%2],{%3,%4};}" ::"r"(a), "r"(u), "n"(I), "r"(v0), "r"(v1) : "memory");
}
template <int I> __device__ __forceinline__ void sts32_u(uint32_t a, uint32_t u, uint32_t v) {
    asm volatile("{.reg .u32 t; add.u32 t,%0,%1; st.shared.b32 [t+%2],%3;}" ::"r"(a), "r"(u), "n"(I), "r"(v) : "memory");
}
template <int I> __device__ __forceinline__ void sts16_u(uint32_t a, uint32_t u, uint32_t v) {
    asm volatile("{.reg .u32 t; add.u32 t,%0,%1; st.shared.b16 [t+%2],%3;}" ::"r"(a), "r"(u), "n"(I), "h"((unsigned short)v) : "memory");
}
template <int I> __device__ __forceinline__ void sts128_u(uint32_t a, uint32_t u, uint32_t r0, uint32_t r1, uint32_t r2, uint32_t r3) {
    asm volatile("{.reg .u32 t; add.u32 t,%0,%1; st.shared.v4.b32 [t+%2],{%3,%4,%5,%6};}" ::"r"(a), "r"(u), "n"(I), "r"(r0), "r"(r1), "r"(r2), "r"(r3) : "memory");
}
template <int I> __device__ __forceinline__ void stsm4_u(uint32_t a, uint32_t u, uint32_t r0, uint32_t r1, uint32_t r2, uint32_t r3) {
    asm volatile("{.reg .u32 t; add.u32 t,%0,%1; stmatrix.sync.aligned.m8n8.x4.shared.b16 [t+%2],{%3,%4,%5,%6};}"
                 ::"r"(a), "r"(u), "n"(I), "r"(r0), "r"(r1), "r"(r2), "r"(r3) : "memory");
}
__device__ __forceinline__ void st_share2(uint32_t a, uint32_t u, uint32_t mb, uint32_t d0, uint32_t d1, uint32_t v0, uint32_t v1) {
    asm volatile("{.reg .pred p; .reg .u32 t,x,y; add.u32 t,%0,%1;\n"
                 "add.u32 x,t,%3; add.u32 y,%2,%3; st.async.shared::cluster.mbarrier::complete_tx::bytes.v2.b32 [x],{%5,%6},[y];\n"
                 "add.u32 x,t,%4; add.u32 y,%2,%4; st.async.shared::cluster.mbarrier::complete_tx::bytes.v2.b32 [x],{%5,%6},[y];\n"
                 "st.shared.v2.b32 [t],{%5,%6}; bar.warp.sync -1; setp.eq.u32 p,%0,0; @p mbarrier.arrive.shared::cta.b64 _,[%2];}"
                 ::"r"(a), "r"(u), "r"(mb), "r"(d0), "r"(d1), "r"(v0), "r"(v1) : "memory");
}
template <int V> struct IC { __host__ __device__ constexpr operator int() const { return V; } };
template <int N, class F> __device__ __forceinline__ void sfor(F f) {
    if constexpr (N > 0) { sfor<N - 1>(f); f(IC<N - 1>()); }
}
__device__ __forceinline__ void mma_f16(float* d, const uint32_t* a, uint32_t b0, uint32_t b1) {
    asm volatile("mma.sync.aligned.m16n8k16.row.col.f32.f16.f16.f32 {%0,%1,%2,%3},{%4,%5,%6,%7},{%8,%9},{%0,%1,%2,%3};"
                 : "+f"(d[0]), "+f"(d[1]), "+f"(d[2]), "+f"(d[3]) : "r"(a[0]), "r"(a[1]), "r"(a[2]), "r"(a[3]), "r"(b0), "r"(b1));
}
__device__ __forceinline__ void mma_bf(float* d, uint32_t a0, uint32_t a1, uint32_t a2, uint32_t a3, uint32_t b0, uint32_t b1) {
    asm volatile("mma.sync.aligned.m16n8k16.row.col.f32.bf16.bf16.f32 {%0,%1,%2,%3},{%4,%5,%6,%7},{%8,%9},{%0,%1,%2,%3};"
                 : "+f"(d[0]), "+f"(d[1]), "+f"(d[2]), "+f"(d[3]) : "r"(a0), "r"(a1), "r"(a2), "r"(a3), "r"(b0), "r"(b1));
}
__device__ __forceinline__ void mma_bf8(float* d, uint32_t a0, uint32_t a1, uint32_t b0) {
    asm volatile("mma.sync.aligned.m16n8k8.row.col.f32.bf16.bf16.f32 {%0,%1,%2,%3},{%4,%5},{%6},{%0,%1,%2,%3};"
                 : "+f"(d[0]), "+f"(d[1]), "+f"(d[2]), "+f"(d[3]) : "r"(a0), "r"(a1), "r"(b0));
}
__device__ __forceinline__ uint32_t pack_bf(float lo, float hi) { uint32_t r; asm("cvt.rn.bf16x2.f32 %0,%1,%2;" : "=r"(r) : "f"(hi), "f"(lo)); return r; }
__device__ __forceinline__ uint32_t pack_h(float lo, float hi) { uint32_t r; asm("cvt.rn.f16x2.f32 %0,%1,%2;" : "=r"(r) : "f"(hi), "f"(lo)); return r; }
__device__ __forceinline__ float bf_lo(uint32_t v) { return __uint_as_float(v << 16); }
__device__ __forceinline__ float bf_hi(uint32_t v) { return __uint_as_float(v & 0xffff0000u); }
__device__ __forceinline__ uint32_t bfma(uint32_t a, uint32_t b, uint32_t c) { uint32_t r; asm("fma.rn.bf16x2 %0,%1,%2,%3;" : "=r"(r) : "r"(a), "r"(b), "r"(c)); return r; }
__device__ __forceinline__ uint4 add_bf8(const uint4 x, const uint32_t* y, const uint32_t k = 0x3f803f80u) {
    return make_uint4(bfma(y[0], k, x.x), bfma(y[1], k, x.y), bfma(y[2], k, x.z), bfma(y[3], k, x.w));
}
__device__ __forceinline__ float ex2(float x) { float r; asm("ex2.approx.ftz.f32 %0,%1;" : "=f"(r) : "f"(x)); return r; }
__device__ __forceinline__ float rcp(float x) { float r; asm("rcp.approx.ftz.f32 %0,%1;" : "=f"(r) : "f"(x)); return r; }
__device__ __forceinline__ void wg_fence() { asm volatile("wgmma.fence.sync.aligned;" ::: "memory"); }
__device__ __forceinline__ void wg_commit() { asm volatile("wgmma.commit_group.sync.aligned;" ::: "memory"); }
template <int N> __device__ __forceinline__ void wg_wait() { asm volatile("wgmma.wait_group.sync.aligned %0;" ::"n"(N) : "memory"); }
__device__ __forceinline__ uint64_t mkdesc(uint32_t a, uint32_t lbo, uint32_t sbo, uint32_t sw) {
    return (uint64_t)((a & 0x3FFFF) >> 4) | ((uint64_t)(lbo >> 4) << 16) | ((uint64_t)(sbo >> 4) << 32) | ((uint64_t)sw << 62);
}
#define F4(d, i) "+f"(d[i]), "+f"(d[i + 1]), "+f"(d[i + 2]), "+f"(d[i + 3])
#define F8(d, i) F4(d, i), F4(d, i + 4)
#define F16(d, i) F8(d, i), F8(d, i + 8)
template <int OFF, int SC> __device__ __forceinline__ void wg_n32_x(float* d, const uint32_t* a, uint32_t lo) {
    asm volatile("{.reg .pred p; .reg .b32 l; .reg .b64 q; setp.ne.b32 p,%22,0; add.u32 l,%20,%21; mov.b64 q,{l,8};\n"
                 "wgmma.mma_async.sync.aligned.m64n32k16.f32.f16.f16 "
                 "{%0,%1,%2,%3,%4,%5,%6,%7,%8,%9,%10,%11,%12,%13,%14,%15},{%16,%17,%18,%19},q,p,1,1,0;}"
                 : F16(d, 0) : "r"(a[0]), "r"(a[1]), "r"(a[2]), "r"(a[3]), "r"(lo), "n"(OFF), "n"(SC));
}
__device__ __forceinline__ void wg_n128_rs(float* d, const uint32_t* a, uint64_t db, int sc) {
    asm volatile("{.reg .pred p; setp.ne.b32 p,%69,0; wgmma.mma_async.sync.aligned.m64n128k16.f32.f16.f16 "
                 "{%0,%1,%2,%3,%4,%5,%6,%7,%8,%9,%10,%11,%12,%13,%14,%15,%16,%17,%18,%19,%20,%21,%22,%23,%24,%25,%26,%27,%28,%29,%30,%31,"
                 "%32,%33,%34,%35,%36,%37,%38,%39,%40,%41,%42,%43,%44,%45,%46,%47,%48,%49,%50,%51,%52,%53,%54,%55,%56,%57,%58,%59,%60,%61,%62,%63},"
                 "{%64,%65,%66,%67},%68,p,1,1,0;}"
                 : F16(d, 0), F16(d, 16), F16(d, 32), F16(d, 48) : "r"(a[0]), "r"(a[1]), "r"(a[2]), "r"(a[3]), "l"(db), "r"(sc));
}
#define N80_REGS "{%0,%1,%2,%3,%4,%5,%6,%7,%8,%9,%10,%11,%12,%13,%14,%15,%16,%17,%18,%19,%20,%21,%22,%23,%24,%25,%26,%27,%28,%29,%30,%31,%32,%33,%34,%35,%36,%37,%38,%39}"
__device__ __forceinline__ void wg_n80_ss(float* d, uint64_t da, uint64_t db, int sc) {
    asm volatile("{.reg .pred p; setp.ne.b32 p,%42,0; wgmma.mma_async.sync.aligned.m64n80k16.f32.bf16.bf16 " N80_REGS ",%40,%41,p,1,1,0,0;}"
                 : F16(d, 0), F16(d, 16), F8(d, 32) : "l"(da), "l"(db), "r"(sc));
}
__device__ __forceinline__ void wg_n88_ss(float* d, uint64_t da, uint64_t db, int sc) {
    asm volatile("{.reg .pred p; setp.ne.b32 p,%46,0; wgmma.mma_async.sync.aligned.m64n88k16.f32.f16.f16 "
                 "{%0,%1,%2,%3,%4,%5,%6,%7,%8,%9,%10,%11,%12,%13,%14,%15,%16,%17,%18,%19,%20,%21,%22,%23,%24,%25,%26,%27,%28,%29,%30,%31,"
                 "%32,%33,%34,%35,%36,%37,%38,%39,%40,%41,%42,%43},%44,%45,p,1,1,0,0;}"
                 : F16(d, 0), F16(d, 16), F8(d, 32), F4(d, 40) : "l"(da), "l"(db), "r"(sc));
}
__device__ __forceinline__ void wg_n48_ss_ta(float* d, uint64_t da, uint64_t db, int sc) {
    asm volatile("{.reg .pred p; setp.ne.b32 p,%26,0; wgmma.mma_async.sync.aligned.m64n48k16.f32.f16.f16 "
                 "{%0,%1,%2,%3,%4,%5,%6,%7,%8,%9,%10,%11,%12,%13,%14,%15,%16,%17,%18,%19,%20,%21,%22,%23},%24,%25,p,1,1,1,0;}"
                 : F16(d, 0), F8(d, 16) : "l"(da), "l"(db), "r"(sc));
}
template <int TA> __device__ __forceinline__ void wg_n64_ss_tb(float* d, uint64_t da, uint64_t db, int sc) {
    asm volatile("{.reg .pred p; setp.ne.b32 p,%34,0; wgmma.mma_async.sync.aligned.m64n64k16.f32.f16.f16 "
                 "{%0,%1,%2,%3,%4,%5,%6,%7,%8,%9,%10,%11,%12,%13,%14,%15,%16,%17,%18,%19,%20,%21,%22,%23,%24,%25,%26,%27,%28,%29,%30,%31},"
                 "%32,%33,p,1,1,%35,1;}"
                 : F16(d, 0), F16(d, 16) : "l"(da), "l"(db), "r"(sc), "n"(TA));
}
__device__ __forceinline__ void pdl_wait() { asm volatile("griddepcontrol.wait;" ::: "memory"); }
__device__ __forceinline__ void pdl_go() { asm volatile("griddepcontrol.launch_dependents;" ::: "memory"); }
__device__ __forceinline__ float cos640(float p) {
    const float q = fmaf(p, 0.0015625f, 12582912.f) - 12582912.f;
    return __cosf(fmaf(q, -640.f, p) * 0.009817477042468103f);
}
__device__ __forceinline__ uint4 cos_row8(float p0, float step, float amp = 1.f) {
    float v[8];
    const float k = 2.f * cos640(step);
    v[0] = amp * cos640(p0); v[1] = amp * cos640(p0 + step);
#pragma unroll
    for (int i = 2; i < 8; i++) v[i] = fmaf(k, v[i - 1], -v[i - 2]);
    return make_uint4(pack_h(v[0], v[1]), pack_h(v[2], v[3]), pack_h(v[4], v[5]), pack_h(v[6], v[7]));
}
__device__ __forceinline__ float wfilter_max(int lane) {
    float m = fmaxf(fmaxf(g_wmax[lane], g_wmax[lane + 32]), fmaxf(g_wmax[lane + 64], g_wmax[lane + 96]));
    return __uint_as_float(__reduce_max_sync(~0u, __float_as_uint(m)));
}
__device__ __forceinline__ unsigned ld_acquire(const Flag* p) { unsigned v; asm volatile("ld.acquire.gpu.global.u32 %0,[%1];" : "=r"(v) : "l"(p) : "memory"); return v; }
#define POLL_NS 200
template <int NS = POLL_NS> __device__ __forceinline__ void wait_flag(const Flag* p, unsigned v) {
    if (ld_acquire(p) >= v) return;
    unsigned x;
    int lim = 0;
    do {
        __nanosleep(NS);
        asm volatile("ld.relaxed.gpu.global.u32 %0,[%1];" : "=r"(x) : "l"(p) : "memory");
    } while (x < v && ++lim < SPIN_LIM);
    ld_acquire(p);
}
__device__ __forceinline__ void prefetch_l2(const void* p, int bytes) { asm volatile("cp.async.bulk.prefetch.L2.global [%0],%1;" ::"l"(p), "r"(bytes) : "memory"); }
__device__ __forceinline__ void red_release(Flag* p) { asm volatile("red.release.gpu.global.add.u32 [%0],1;" ::"l"(p) : "memory"); }
__device__ __forceinline__ void red_relaxed(Flag* p) { asm volatile("red.relaxed.gpu.global.add.u32 [%0],1;" ::"l"(p) : "memory"); }
__device__ __forceinline__ void red_h8(void* p, uint32_t a, uint32_t b, uint32_t c, uint32_t d) {
    asm volatile("red.relaxed.gpu.global.add.noftz.v4.f16x2 [%0],{%1,%2,%3,%4};" ::"l"(p), "r"(a), "r"(b), "r"(c), "r"(d) : "memory");
}
__device__ __forceinline__ float pow2_scale(float bound, int top, float* inv) {
    int e = (int)((__float_as_uint(bound) >> 23) & 0xff) - 126;
    int k = top - e;
    k = max(-100, min(100, k));
    *inv = __uint_as_float((uint32_t)(127 - k) << 23);
    return __uint_as_float((uint32_t)(127 + k) << 23);
}
__device__ __forceinline__ char* red_base() { return (char*)(((uintptr_t)g_redraw + 32767) & ~(uintptr_t)32767); }

__device__ __forceinline__ void setup_a(char* sm, const int b, const bf16* __restrict__ wr, const bf16* __restrict__ wi) {
    const int tid = threadIdx.x, lane = tid & 31;
    const uint32_t sb = smem_u32(sm);
    auto row_byte = [&](int q) { return ((b >> 2) + 32 * ((q >> 1) * 8 + 2 * (b & 3) + (q & 1))) * 642; };
#pragma unroll 1
    for (int r = tid >> 5; r < 32; r += 8) {
        const char* src = (const char*)(r < 16 ? wr : wi) + (row_byte(r & 15) & ~15);
        cp_async16(sb + r * 672 + lane * 16, src + lane * 16);
        if (lane < 9) cp_async16(sb + r * 672 + 512 + lane * 16, src + 512 + lane * 16);
    }
    ((uint4*)g_stat)[b * 256 + tid] = make_uint4(0, 0, 0, 0);
    if (tid < 2 * (NFLAG / 128)) ((uint4*)(g_flag + b * (NFLAG / 128) + (tid >> 1)))[tid & 1] = make_uint4(0, 0, 0, 0);
    if (tid < 12) {
        const int i = b * 12 + tid;
        const int f = ((i >> 4) & 3) * 8 + (i & 7), im = (i >> 3) & 1, part = (i >> 8) & 1;
        ((uint4*)g_ctab)[i] = cos_row8((float)(i < 1024 ? (i >> 7) * 80 * (i & 63) + ((i & 64) ? 480 : 0) : ((i >> 6) & 3) * 160 * f + (im == part ? 0 : im ? 160 : 480)),
                                       (float)(i < 1024 ? 10 * (i & 63) : 20 * f), i < 1024 ? 0.125f : 0.17677669529663687f);
    }
    asm volatile("cp.async.wait_all;" ::: "memory");
    __syncthreads();
    const int q0 = (tid & 3) * 4;
    const char* rp[4];
#pragma unroll
    for (int u = 0; u < 4; u++) rp[u] = sm + (q0 + u) * 672 + (row_byte(q0 + u) & 15);
    uint32_t mx = 0;
#pragma unroll 2
    for (int c = tid >> 2; c < 321; c += 64) {
        uint32_t v[4];
#pragma unroll
        for (int u = 0; u < 4; u++) {
            v[u] = ((const unsigned short*)rp[u])[c] | ((uint32_t)((const unsigned short*)(rp[u] + 16 * 672))[c] << 16);
            mx = __vmaxu2(mx, v[u] & 0x7fff7fffu);
        }
        ((uint4*)g_Wf)[(size_t)c * 512 + b * 4 + ((tid ^ (b >> 1)) & 3)] = make_uint4(v[0], v[1], v[2], v[3]);
    }
    mx = __reduce_max_sync(~0u, max(mx & 0xffffu, mx >> 16));
    __syncthreads();
    if (lane == 0) ((uint32_t*)sm)[tid >> 5] = mx;
    __syncthreads();
    if (tid < 32) {
        mx = __reduce_max_sync(~0u, ((uint32_t*)sm)[lane & 7]);
        if (tid == 0) g_wmax[b] = __uint_as_float(mx << 16);
    }
}
__device__ __forceinline__ void setup_b(const int b, const bf16* __restrict__ mem0) {
    const int tid = threadIdx.x;
    uint4* z = (uint4*)red_base();
    if (b < 3) {
        const int w = tid >> 5, lane = tid & 31, p = b * 2 + ((w >> 1) & 1), odd = w & 1;
        uint32_t mx = 0;
#pragma unroll 4
        for (int i = lane; i < 640; i += 32) {
            const uint4 u = ((const uint4*)mem0)[i];
            mx = __vmaxu2(__vmaxu2(mx, u.x & 0x7fff7fffu), __vmaxu2(__vmaxu2(u.y & 0x7fff7fffu, u.z & 0x7fff7fffu), u.w & 0x7fff7fffu));
        }
        float inv, v[7];
        const float sc = pow2_scale(__uint_as_float(__reduce_max_sync(~0u, max(mx & 0xffffu, mx >> 16)) << 16), 14, &inv);
        if (tid == 0) g_invM0 = inv;
#pragma unroll
        for (int j = 0; j < 7; j++) {
            const int r = p * 56 + (j < 6 ? odd * 32 + (j >> 1) * 8 : 24) + (lane >> 2), mr = 2 * (lane & 3) + (j < 6 ? (j & 1) : odd);
            v[j] = r < 320 ? __bfloat162float(mem0[mr * 640 + (w >> 2) * 320 + r]) * sc : 0.f;
        }
        const int off = w * 2048 + (lane >> 4) * 1024 + ((lane >> 3) & 1) * 256 + (lane & 7) * 16 + (b == 2 ? (w >> 1) * 4096 + 128 : b * 16384);
        const uint4 u = make_uint4(pack_h(v[0], v[1]), pack_h(v[2], v[3]), pack_h(v[4], v[5]), pack_h(v[6], 32.f));
        z[off >> 4] = u; z[65536 + (off >> 4)] = u;
    }
}

#define SU_PAD 40960
constexpr int SU_SMEM = SU_PAD;
__global__ void __launch_bounds__(256, 4) k_setup(const bf16* __restrict__ wr, const bf16* __restrict__ wi, const bf16* __restrict__ mem0) {
    extern __shared__ __align__(1024) char sm[];
    TL(0);
    if (blockIdx.x >= 128) setup_b(blockIdx.x - 128, mem0);
    else setup_a(sm, blockIdx.x, wr, wi);
    __syncthreads();
    if (threadIdx.x == 0) red_release(g_ready);
    TL(1);
}
__device__ __forceinline__ float weight_scale(int h, int ty, float* inv) { return pow2_scale(__ldcg(g_wmx + h * 3 + ty), 6, inv); }

#define STR_(x) #x
#define STR(x) STR_(x)
#define RF_U 1
constexpr int RF_A = 22 * 2816, RF_X = RF_A + 22 * 1024, RF_BAR = RF_X + 64 * 1344, RF_SMEM = RF_BAR + 80;
__device__ __align__(1024) char g_rtab[4 * RF_A];
template <int first> __global__ void __cluster_dims__(2, 1, 1) __launch_bounds__(256, 2) k_rowf(const bf16* x) {
    extern __shared__ __align__(1024) char sm[];
    TL(first ? 2 : 16);
    const int tid = threadIdx.x, w = tid >> 5, lane = tid & 31, g = lane >> 2, t = lane & 3;
    if (blockIdx.x >= 128) { __nanosleep(2500); return; }
    const int a = first ? blockIdx.x >> 2 : 31 - (blockIdx.x >> 2), gq = blockIdx.x & 3;
    if (!first) pdl_go();
    const uint32_t sb = smem_u32(sm), mb = sb + RF_BAR + w * 8;
    if (lane == 0) {
        mbar_init(mb, 1);
        asm volatile("fence.mbarrier_init.release.cluster;" ::: "memory");
        if (!first && w == 0) {
            mbar_init(sb + RF_BAR + 64, 1);
            fence_async_smem();
            mbar_expect(sb + RF_BAR + 64, RF_A);
            bulk_g2s(sb, g_rtab + gq * RF_A, RF_A, sb + RF_BAR + 64);
        }
    }
    if (lane == 0) mbar_expect(mb, 8 * 1280);
    __syncwarp();
    asm volatile("barrier.cluster.arrive.relaxed.aligned; barrier.cluster.wait.aligned;" ::: "memory");
    if (!first) {
        if (lane == 0) wait_flag<100>(g_flag + F_R + a, a < 28 ? 32 : 192);
        __syncwarp();
        fence_async_glb();
    }
    TL(first ? 3 : 17);
    if (lane < 4)
        asm volatile("cp.async.bulk.shared::cluster.global.mbarrier::complete_tx::bytes.multicast::cluster [%0],[%1],1280,[%2],%3;"
                     ::"r"(sb + RF_X + (w * 8 + (gq & 1) * 4 + lane) * 1344), "l"(x + (size_t)(a * 64 + w * 8 + (gq & 1) * 4 + lane) * 640), "r"(mb),
                     "h"((unsigned short)3) : "memory");
    __syncwarp();
    if (first) pdl_go();
    if (first) {
#pragma unroll 3
        for (int id = tid; id < 22 * 176; id += 256) {
            const int kg = id / 176, n = id - kg * 176;
            const float c = (float)(2 * n + (gq & 1));
            *(uint4*)(sm + id * 16) = cos_row8(fmaf((float)(kg * 8), c, (float)((gq & 2) * 80)), c, 0.03952847075210474f);
        }
    }
    mbar_wait(mb, 0);
    const uint32_t row = sb + RF_X + (w * 8 + g) * 1344;
    float st[4][4] = {};
#pragma unroll 1
    for (int i = 0; i < 20; i += 4) {
        uint32_t u[4][4];
#pragma unroll
        for (int q = 0; q < 4; q++) lds128(u[q], row + (4 * (i + q) + t) * 16);
#pragma unroll
        for (int q = 0; q < 4; q++) {
            mma_bf(st[(q & 1) * 2], u[q][0], 0x3f803f80u, u[q][1], 0x3f803f80u, u[q][0], u[q][1]);
            mma_bf(st[(q & 1) * 2 + 1], u[q][2], 0x3f803f80u, u[q][3], 0x3f803f80u, u[q][2], u[q][3]);
        }
    }
#pragma unroll
    for (int q = 0; q < 4; q++) { st[0][q] += st[2][q]; st[1][q] += st[3][q]; }
    const float sq = __shfl_sync(~0u, (g & 1) ? st[0][1] + st[1][1] : st[0][0] + st[1][0], g * 4 + (g >> 1));
    const float mean = __shfl_sync(~0u, (g & 1) ? st[0][3] + st[1][3] : st[0][2] + st[1][2], g * 4 + (g >> 1)) * (1.f / 640.f);
    const float r = rsqrtf(fmaxf(fmaf(-mean, mean, sq * (1.f / 640.f)), 0.f) + 1e-5f), off = gq == 0 ? -4.f * mean * r : 0.f;
    const float r1 = (gq == 1 || gq == 2) ? -r : r, r2 = (gq & 1) ? -r : r, r3 = gq >= 2 ? -r : r;
    const uint32_t aa = sb + RF_A + w * 128 + g * 16;
    auto el = [&](int d) { unsigned short v; asm volatile("ld.shared.u16 %0,[%1];" : "=h"(v) : "r"(row + d * 2)); return __uint_as_float((uint32_t)v << 16); };
_Pragma(STR(unroll RF_U))
    for (int i = 0; i < 5; i++) {
        const int ch = t + 4 * i;
        uint32_t u[4][4];
        lds128(u[0], row + ch * 16); lds128(u[1], row + (39 - ch) * 16); lds128(u[2], row + (40 + ch) * 16); lds128(u[3], row + (79 - ch) * 16);
        const float nb0 = el(320 - 8 * ch), nb1 = el(ch ? 640 - 8 * ch : 0);
        float o[8];
#pragma unroll
        for (int q = 0; q < 8; q++) {
            const int m = (8 - q) >> 1;
            const float e0 = (q & 1) ? bf_hi(u[0][q >> 1]) : bf_lo(u[0][q >> 1]), e2 = (q & 1) ? bf_hi(u[2][q >> 1]) : bf_lo(u[2][q >> 1]);
            const float e1 = q == 0 ? nb0 : (q & 1) ? bf_hi(u[1][m & 3]) : bf_lo(u[1][m & 3]), e3 = q == 0 ? nb1 : (q & 1) ? bf_hi(u[3][m & 3]) : bf_lo(u[3][m & 3]);
            o[q] = fmaf(e3, r3, fmaf(e2, r2, fmaf(e1, r1, fmaf(e0, r, off))));
        }
        if (ch == 0) o[0] *= 0.5f;
        sts128(aa + ch * 1024, pack_h(o[0], o[1]), pack_h(o[2], o[3]), pack_h(o[4], o[5]), pack_h(o[6], o[7]));
    }
    if (t < 2) sts128(aa + (20 + t) * 1024, t == 0 ? pack_h(fmaf(el(480), r2, fmaf(el(160), r, 0.5f * off)), 0.f) : 0u, 0u, 0u, 0u);
    fence_async_smem();
    __syncthreads();
    if (!first) mbar_wait(sb + RF_BAR + 64, 0);
    else if (a == 0 && tid == 0) { bulk_s2g(g_rtab + gq * RF_A, sb, RF_A); bulk_commit(); }
    const int wg = w >> 2;
    float acc[44];
    uint64_t da = mkdesc(sb + RF_A, 1024, 128, 0), db = mkdesc(sb + wg * 1408, 2816, 128, 0);
    wg_fence();
#pragma unroll 1
    for (int k = 0; k < 11; k++) { wg_n88_ss(acc, da, db, k); da += 128; db += 352; }
    wg_commit(); wg_wait<0>();
    const uint32_t stg = sb + RF_X + wg * 96 * 144;
#pragma unroll
    for (int j = 0; j < 12; j += 2) {
        const int m = lane >> 3, j1 = j < 10 ? j + 1 : j;
        stsm4t(stg + ((j + (m >> 1)) * 8 + (lane & 7)) * 144 + ((w & 3) * 16 + (m & 1) * 8) * 2, pack_h(acc[j * 4], acc[j * 4 + 1]),
               pack_h(acc[j * 4 + 2], acc[j * 4 + 3]), pack_h(acc[j1 * 4], acc[j1 * 4 + 1]), pack_h(acc[j1 * 4 + 2], acc[j1 * 4 + 3]));
    }
    bar_sync(1 + wg, 128);
#pragma unroll 3
    for (int rr = (tid & 127) >> 3; rr < 88; rr += 16) {
        const int ch = tid & 7, c = 2 * (wg * 88 + rr) + (gq & 1);
        if (c <= 320 - (gq >> 1) && (c | (gq ^ 2))) {
            uint32_t u[4];
            lds128(u, stg + rr * 144 + ch * 16);
            ((uint4*)g_UT)[((size_t)(c == 320 ? 1 : 2 * c + (gq >> 1)) * 32 + a) * 8 + (ch ^ (a & 7))] = make_uint4(u[0], u[1], u[2], u[3]);
        }
    }
    if (first && blockIdx.x < 4 && tid == 0) asm volatile("cp.async.bulk.wait_group.read 0;" ::: "memory");
    TL(first ? 4 : 18);
}

constexpr int GST = 4, GSTB = 32768 + 20480, GNC = 32;
constexpr int G_BAR = GST * GSTB + 3072;
#define GPACE 1100
#define GPACE2 650
__device__ __forceinline__ void oproj_load(const uint32_t sb, const int op, const int mb, const int nb, const int c0, const uint32_t pace) {
    const int by = op == 2 ? 20480 : 16384;
    const char* src = op == 2 ? (const char*)g_wot + (size_t)nb * GNC * 20480 : (const char*)g_O + (size_t)(2 * mb + op) * GNC * 16384;
    uint32_t t0 = clock32() - pace + op * (pace / 3);
#pragma unroll 1
    for (int c = c0; c < c0 + GNC; c++, src += by) {
        const int st = c % GST;
        if (c >= GST) mbar_wait(sb + G_BAR + (GST + st) * 8, ((c / GST) - 1) & 1);
        while (clock32() - t0 < pace) {}
        t0 = clock32();
        const int by_ = by;
        mbar_expect(sb + G_BAR + st * 8, by_);
        if (op == 2) bulk_g2s(sb + st * GSTB + 32768, src, by_, sb + G_BAR + st * 8);
        else bulk_g2s_last(sb + st * GSTB + op * 16384, src, by_, sb + G_BAR + st * 8);
    }
}
__device__ __forceinline__ void oproj_mma(const uint32_t sb, const int mb, const int nb, const int c0, const bf16* res, bf16* out, const int layer) {
    const int w = threadIdx.x >> 5, lane = threadIdx.x & 31, wg = w >> 2;
    float acc[40];
    uint4 rv[5];
#pragma unroll 1
    for (int c = c0; c < c0 + GNC; c++) {
        const int st = c % GST;
        mbar_wait(sb + G_BAR + st * 8, (c / GST) & 1);
        const uint32_t d = sb + st * GSTB;
        wg_fence();
#pragma unroll
        for (int k = 0; k < 8; k++)
            wg_n80_ss(acc, mkdesc(d + wg * 16384 + k * 2048, 1024, 128, 0), mkdesc(d + 32768 + k * 2560, 1280, 128, 0), (c - c0) | k);
        wg_commit();
        if (c > c0) {
            wg_wait<1>();
            if (lane == 0) mbar_arrive(sb + G_BAR + (GST + (c - 1) % GST) * 8);
        }
    }
#pragma unroll
    for (int i = 0; i < 5; i++) {
        const int id = i * 32 + lane, r = id / 10;
        rv[i] = __ldcg((const uint4*)res + (size_t)(mb * 128 + w * 16 + r) * 80 + nb * 10 + id - r * 10);
    }
    wg_wait<0>();
    bar_sync(5, 256);
    const uint32_t stg = sb + (GST - 1) * GSTB + w * 16 * 176;
#pragma unroll
    for (int j = 0; j < 5; j++)
        stsm4(stg + (lane & 15) * 176 + (2 * j + (lane >> 4)) * 16, pack_bf(acc[j * 8], acc[j * 8 + 1]), pack_bf(acc[j * 8 + 2], acc[j * 8 + 3]),
              pack_bf(acc[j * 8 + 4], acc[j * 8 + 5]), pack_bf(acc[j * 8 + 6], acc[j * 8 + 7]));
    __syncwarp();
#pragma unroll
    for (int i = 0; i < 5; i++) {
        const int id = i * 32 + lane, r = id / 10, ch = id - r * 10;
        uint32_t y[4];
        lds128(y, stg + r * 176 + ch * 16);
        ((uint4*)out)[(size_t)(mb * 128 + w * 16 + r) * 80 + nb * 10 + ch] = add_bf8(rv[i], y);
    }
    fence_async_smem();
    __syncwarp();
    if (lane == 0) {
        mbar_arrive(sb + G_BAR + (2 * GST - 1) * 8);
        if (layer == 0) red_release(g_flag + F_R + 2 * mb + wg);
    }
}

__global__ void __launch_bounds__(128, 4) k_col(const int first) {
    __shared__ __align__(1024) char sz[8192];
    __shared__ __align__(1024) char stab[24576];
    __shared__ __align__(1024) char swf[8192];
    __shared__ __align__(8) uint64_t bar[2];
    const int tid = threadIdx.x, wl = tid >> 5, lane = tid & 31, g = lane >> 2, t = lane & 3;
    const int c = blockIdx.x;
    TL(first ? 5 : 19);
    const bool realc = c == 0 || c == 320;
    const uint32_t z = smem_u32(sz), b2 = smem_u32(stab), a1 = b2 + 16384, wf = smem_u32(swf), mb = smem_u32(bar);
    if (tid == 0) { mbar_init(mb, 1); mbar_init(mb + 8, 1); fence_async_smem(); }
    if (realc) {
        for (int i = tid; i < 256; i += 128) sts128(z + 4096 + i * 16, 0, 0, 0, 0);
        fence_async_smem();
    }
    const int k1 = wl * 8 + g;
    float tc[16], ts[16];
#pragma unroll
    for (int j = 0; j < 16; j++) {
        const int p = ((j >> 1) * 8 + 2 * t + (j & 1)) * k1;
        __sincosf((float)(p - 1024) * 0.003067961575771282f, &ts[j], &tc[j]);
        ts[j] = -ts[j]; tc[j] = -tc[j];
    }
    if (first && tid == 32) { wait_flag<400>(g_ready, NSETUP); fence_async_glb(); }
    __syncthreads();
    if (tid == 32) {
        mbar_expect(mb + 8, 24576 + 8192);
        bulk_g2s(b2, g_ctab, 24576, mb + 8);
        bulk_g2s(wf, g_Wf + (size_t)c * 2048, 8192, mb + 8);
    }
    float inv;
    const float wsc = pow2_scale(wfilter_max(lane), 0, &inv) * (realc ? 0.5f : 1.f);
    pdl_wait();
    TL(first ? 6 : 20);
    if (tid == 0) {
        const int by = realc ? 4096 : 8192;
        mbar_expect(mb, by);
        bulk_g2s_last(z, (const char*)g_UT + (size_t)(c == 320 ? 1 : 2 * c) * 4096, by, mb);
    }
    pdl_go();
    mbar_wait(mb + 8, 0);
    mbar_wait(mb, 0);
    float d[64];
    uint32_t a[4][4];
    wg_fence();
#pragma unroll
    for (int ks = 0; ks < 4; ks++) wg_n64_ss_tb<0>(d, mkdesc(a1 + ks * 2048, 1024, 128, 0), mkdesc(z + ks * 2048, 1024, 1024, 1), ks);
    wg_commit(); wg_wait<0>();
#pragma unroll
    for (int j = 0; j < 8; j++) {
        float yr[2], yi[2];
#pragma unroll
        for (int e = 0; e < 2; e++) {
            const float re = d[j * 4 + e], im = d[j * 4 + 2 + e], cc = tc[j * 2 + e], ss = ts[j * 2 + e];
            yr[e] = re * cc + im * ss; yi[e] = im * cc - re * ss;
        }
        a[j >> 1][(j & 1) * 2] = pack_h(yr[0], yr[1]); a[j >> 1][(j & 1) * 2 + 1] = pack_h(yi[0], yi[1]);
    }
    wg_fence();
#pragma unroll
    for (int ks = 0; ks < 4; ks++) wg_n128_rs(d, a[ks], mkdesc(b2 + ks * 4096, 2048, 128, 0), ks);
    wg_commit(); wg_wait<0>();
#pragma unroll
    for (int q = 0; q < 4; q++) {
        uint32_t wv[4];
        lds128(wv, wf + tid * 64 + ((q ^ (tid >> 1)) & 3) * 16);
#pragma unroll
        for (int jj = 0; jj < 2; jj++) {
            const int j = 2 * q + jj;
            float yr[2], yi[2];
#pragma unroll
            for (int e = 0; e < 2; e++) {
                const float xr = d[j * 4 + e] + d[32 + j * 4 + 2 + e], xi = d[j * 4 + 2 + e] - d[32 + j * 4 + e];
                const float fr = bf_lo(wv[jj * 2 + e]) * wsc, fi = bf_hi(wv[jj * 2 + e]) * wsc;
                yr[e] = xr * fr - xi * fi; yi[e] = xr * fi + xi * fr;
            }
            a[q][jj * 2] = pack_h(yr[0], yr[1]); a[q][jj * 2 + 1] = pack_h(yi[0], yi[1]);
        }
    }
    wg_fence();
#pragma unroll
    for (int ks = 0; ks < 4; ks++) wg_n128_rs(d, a[ks], mkdesc(b2 + ks * 4096, 2048, 128, 0), ks);
    wg_commit(); wg_wait<0>();
#pragma unroll
    for (int j = 0; j < 8; j++) {
        float yr[2], yi[2];
#pragma unroll
        for (int e = 0; e < 2; e++) {
            const float vr = d[j * 4 + e] - d[32 + j * 4 + 2 + e], vi = d[j * 4 + 2 + e] + d[32 + j * 4 + e];
            const float cc = tc[j * 2 + e], ss = ts[j * 2 + e];
            yr[e] = vr * cc - vi * ss; yi[e] = vi * cc + vr * ss;
        }
        a[j >> 1][(j & 1) * 2] = pack_h(yr[0], yr[1]); a[j >> 1][(j & 1) * 2 + 1] = pack_h(yi[0], yi[1]);
    }
    __syncthreads();
    const int mm = lane >> 3, rr = lane & 7;
    const uint32_t rowo = (wl * 16 + (mm & 1) * 8 + rr) * 128;
#pragma unroll
    for (int q = 0; q < 4; q++) stsm4(z + rowo + (((2 * q + (mm >> 1)) ^ rr) << 4), a[q][0], a[q][1], a[q][2], a[q][3]);
    fence_async_smem();
    __syncthreads();
    wg_fence();
#pragma unroll
    for (int ks = 0; ks < 4; ks++) wg_n64_ss_tb<1>(d, mkdesc(a1 + ks * 256, 128, 1024, 0), mkdesc(z + ks * 2048, 1024, 1024, 1), ks);
    wg_commit(); wg_wait<0>();
#pragma unroll
    for (int q = 0; q < 4; q++)
        stsm4(wf + rowo + (((2 * q + (mm >> 1)) ^ rr) << 4), pack_h(d[q * 8], d[q * 8 + 1]), pack_h(d[q * 8 + 2], d[q * 8 + 3]),
              pack_h(d[q * 8 + 4], d[q * 8 + 5]), pack_h(d[q * 8 + 6], d[q * 8 + 7]));
    __syncwarp();
    if (!(realc && wl >= 2)) {
        const int kk = c == 320 ? 320 : (c & 1) * 160 + (c >> 1) + (wl >> 1) * 320;
#pragma unroll
        for (int i = 0; i < 4; i++) {
            const int r = wl * 16 + i * 4 + (lane >> 3), ch = lane & 7;
            uint32_t v[4];
            lds128(v, wf + r * 128 + ((ch ^ (r & 7)) << 4));
            ((uint4*)g_YT)[((size_t)(r & 31) * 640 + kk) * 8 + (ch ^ (kk & 7))] = make_uint4(v[0], v[1], v[2], v[3]);
        }
    }
    TL(first ? 7 : 21);
}

constexpr int O_XS = 0;
constexpr int O_MS = 81920;
constexpr int O_QKP = O_MS + 10752;
constexpr int O_VM = O_QKP + 4096;
constexpr int O_SC = O_VM + 4096;
constexpr int O_OS = O_SC + 1536;
constexpr int O_XCH = O_OS + 2048;
constexpr int O_SUM = O_XCH + 8192;
constexpr int O_MX = O_SUM + 256;
constexpr int O_STG = O_MS + 65536 - 8192;
static_assert(O_STG - 16384 >= O_MX + 1024, "shared-memory map");
constexpr int O_WO = O_STG + 16384;
constexpr int O_SCL = O_WO + 65536;
constexpr int O_BAR = O_SCL + 64;
constexpr int B_XF = O_BAR, B_S = O_BAR + 16, B_GO = O_BAR + 24, B_VH = O_BAR + 88, B_VX = O_BAR + 32, B_STG = O_BAR + 48, B_FREE = O_BAR + 72;
constexpr int T_FA = O_BAR + 96, T_EA = T_FA + 32, T_FB = T_EA + 32, T_EB = T_FB + 56, T_RED = T_EB + 32;
constexpr int O_WMX = O_BAR + 512, B_W = O_BAR + 64;
constexpr int O_LAST = (O_WMX + 192 + 1023) / 1024 * 1024;
constexpr int CH_SMEM = O_LAST + 8192;
static_assert(O_WO == 19 * 8192, "weight staging");
__device__ __forceinline__ uint32_t tail_b(int c) { return c % 7 < 4 ? O_XS + (c % 7) * 20480 : O_WO + (c % 7 - 4) * 20480; }
__device__ __forceinline__ int s_tx(int c) { return c == 2 ? 2 * 768 : 768 + 2048; }

#define NPERM 1
#define NWO0 1
#define NWO0B 6
#define NWO1 6
#define EN 25
#define AUNR 2
#define TDELAY 300
#define WDEPTH 6
#define RDELAY 560

#define STAMP(i)

#define NTA 20
#define NTB 26
template <int LO, int HI>
__device__ __forceinline__ void tok_issue(const uint32_t (&A0)[20][4], const uint32_t (&A1)[20][4], float (&b0)[16], float (&b1)[16], uint32_t xd,
                                          const uint32_t zero) {
    if (LO == 0) wg_fence();
    sfor<HI - LO>([&](auto I) {
        constexpr int i = LO + I;
        if constexpr (i < 20) wg_n32_x<i * 64, i>(b0, A0[i], xd); else wg_n32_x<(i - 20) * 64, i - 20>(b1, A1[i - 20], xd + zero);
        if constexpr (i == 19 || i == NTB - 1 || i == 39) wg_commit();
    });
}
__device__ __forceinline__ void tok_give(const float (&b0)[16], const uint32_t L16, const uint32_t xch0) {
    wg_wait<1>();
    sfor<2>([&](auto I) {
        constexpr int i = I;
        sts128_u<i * 512>(L16, xch0, pack_h(b0[8 * i], b0[8 * i + 1]), pack_h(b0[8 * i + 2], b0[8 * i + 3]), pack_h(b0[8 * i + 4], b0[8 * i + 5]),
                          pack_h(b0[8 * i + 6], b0[8 * i + 7]));
    });
}
__device__ __forceinline__ void tok_finish(float (&b1)[16], const uint32_t (&e)[2][4], const uint32_t L16, const uint32_t dst, const uint32_t idn) {
#pragma unroll
    for (int j = 0; j < 4; j++)
        asm volatile("mma.sync.aligned.m16n8k8.row.col.f32.f16.f16.f32 {%0,%1,%2,%3},{%4,%5},{%6},{%0,%1,%2,%3};"
                     : F4(b1, 4 * j) : "r"(e[j >> 1][(j & 1) * 2]), "r"(e[j >> 1][(j & 1) * 2 + 1]), "r"(idn));
    stsm4_u<0>(L16, dst, pack_bf(b1[0], b1[1]), pack_bf(b1[2], b1[3]), pack_bf(b1[4], b1[5]), pack_bf(b1[6], b1[7]));
    stsm4_u<512>(L16, dst, pack_bf(b1[8], b1[9]), pack_bf(b1[10], b1[11]), pack_bf(b1[12], b1[13]), pack_bf(b1[14], b1[15]));
}
__device__ __forceinline__ uint32_t uni(uint32_t v) { return __shfl_sync(~0u, v, 0); }
__device__ __forceinline__ uint32_t badd(uint32_t a, uint32_t b) { uint32_t r; asm("add.rn.bf16x2 %0,%1,%2;" : "=r"(r) : "r"(a), "r"(b)); return r; }
__device__ __forceinline__ uint32_t bmax(uint32_t a, uint32_t b) { uint32_t r; asm("max.bf16x2 %0,%1,%2;" : "=r"(r) : "r"(a), "r"(b)); return r; }
__device__ __forceinline__ uint32_t babsmax(uint32_t a, uint32_t b) { uint32_t r; asm("max.xorsign.abs.bf16x2 %0,%1,%2;" : "=r"(r) : "r"(a), "r"(b)); return r; }
__device__ __forceinline__ uint32_t habsmax(uint32_t a, uint32_t b) { uint32_t r; asm("max.xorsign.abs.f16x2 %0,%1,%2;" : "=r"(r) : "r"(a), "r"(b)); return r; }

template <int NPF>
__device__ __forceinline__ float mem_out(const uint32_t sb, const uint32_t L16, const uint32_t L8, uint32_t (&wo)[16][4], const uint32_t woa,
                                         char* dst, const bool odd) {
    bar_sync(2, 352);
    float a[4][4];
#pragma unroll
    for (int i = 0; i < 4; i++) a[i][0] = a[i][1] = a[i][2] = a[i][3] = 0.f;
    uint32_t ob[4][4], sm_[2], sc[2];
    sfor<8>([&](auto I) {
        constexpr int i = I;
        if constexpr (!(i & 1)) ldsm4t_u<O_OS + (i >> 1) * 512>(ob[i >> 1], L16, sb);
        if constexpr (i >= NPF) { ldsm4t(wo[i], woa + i * 1024); ldsm4t(wo[8 + i], (woa ^ 32) + i * 1024); }
    });
    lds64_u<O_SUM>(sm_, L8 & 24, sb); lds64(sc, sb + O_SCL);
#pragma unroll
    for (int i = 0; i < 8; i++) {
        mma_bf(a[i & 1], wo[i][0], wo[i][1], wo[i][2], wo[i][3], ob[i >> 1][(i & 1) * 2], ob[i >> 1][(i & 1) * 2 + 1]);
        mma_bf(a[2 + (i & 1)], wo[8 + i][0], wo[8 + i][1], wo[8 + i][2], wo[8 + i][3], ob[i >> 1][(i & 1) * 2], ob[i >> 1][(i & 1) * 2 + 1]);
    }
    const float f0 = rcp(__uint_as_float(sm_[0])) * __uint_as_float(sc[0]), f1 = rcp(__uint_as_float(sm_[1])) * __uint_as_float(sc[0]);
    red_h8(dst, pack_h((a[0][0] + a[1][0]) * f0, (a[0][1] + a[1][1]) * f1), pack_h((a[0][2] + a[1][2]) * f0, (a[0][3] + a[1][3]) * f1),
           pack_h((a[2][0] + a[3][0]) * f0, (a[2][1] + a[3][1]) * f1), pack_h(odd ? (a[2][3] + a[3][3]) * f1 : (a[2][2] + a[3][2]) * f0, 1.f));
    return __uint_as_float(sc[1]);
}

template <int NE, int UNR>
__device__ __forceinline__ void tok_attention(const uint32_t qk, const uint32_t dq, const uint32_t km, const uint32_t dk, const uint32_t vt, const uint32_t vm,
                                              const int e0, const int mi, const int lane, const int seg, const int h, const float iqk, const float iv) {
    const int g = lane >> 2, t = lane & 3;
    float s[6][4];
#pragma unroll
    for (int i = 0; i < 6; i++) s[i][0] = s[i][1] = s[i][2] = s[i][3] = 0.f;
#pragma unroll UNR
    for (int e = 0; e < 8; e++) {
        uint32_t q[4], k[4];
        ldsm4t(q, qk + (e >> 2) * dq + (e & 3) * 1024 + mi * 512);
        ldsm4t(k, km + (e >> 2) * dk + (e & 3) * 512);
        mma_bf(s[4], q[0], q[2], q[1], q[3], k[0], k[1]);
        mma_bf(s[5], q[0], q[2], q[1], q[3], k[2], k[3]);
        ldsm4t(k, qk + (e >> 2) * dq + 4096 + (e & 3) * 1024);
        mma_bf(s[0], q[0], q[2], q[1], q[3], k[0], k[1]);
        mma_bf(s[1], q[0], q[2], q[1], q[3], k[2], k[3]);
        if (mi) {
            ldsm4t(k, qk + (e >> 2) * dq + 4096 + (e & 3) * 1024 + 512);
            mma_bf(s[2], q[0], q[2], q[1], q[3], k[0], k[1]);
            mma_bf(s[3], q[0], q[2], q[1], q[3], k[2], k[3]);
        }
    }
#pragma unroll
    for (int q = 0; q < 4; q++) s[4][q] += s[5][q];
    const float sl = iqk * (0.08838834764831845f * 1.4426950408889634f);
    float mx[2] = {-3.0e38f, -3.0e38f};
#pragma unroll
    for (int i = 0; i < 5; i++)
#pragma unroll
        for (int q = 0; q < 4; q++) {
            const bool ok = i == 4 || (i * 8 + 2 * t + (q & 1)) <= (mi * 16 + g + (q >> 1) * 8);
            s[i][q] = ok ? s[i][q] * sl : -1.0e9f * 1.4426950408889634f;
            mx[q >> 1] = fmaxf(mx[q >> 1], s[i][q]);
        }
    float sum[2] = {0.f, 0.f};
#pragma unroll
    for (int r = 0; r < 2; r++) {
        mx[r] = fmaxf(mx[r], __shfl_xor_sync(~0u, mx[r], 1));
        mx[r] = fmaxf(mx[r], __shfl_xor_sync(~0u, mx[r], 2));
    }
#pragma unroll
    for (int i = 0; i < 5; i++)
#pragma unroll
        for (int q = 0; q < 4; q++) { s[i][q] = ex2(s[i][q] - mx[q >> 1]); sum[q >> 1] += s[i][q]; }
#pragma unroll
    for (int r = 0; r < 2; r++) {
        sum[r] += __shfl_xor_sync(~0u, sum[r], 1);
        sum[r] += __shfl_xor_sync(~0u, sum[r], 2);
        sum[r] = iv * rcp(sum[r]);
    }
    uint32_t pp[5][2];
#pragma unroll
    for (int i = 0; i < 5; i++) { pp[i][0] = pack_bf(s[i][0] * sum[0], s[i][1] * sum[0]); pp[i][1] = pack_bf(s[i][2] * sum[1], s[i][3] * sum[1]); }
    uint32_t* o = (uint32_t*)g_O + (((size_t)(seg >> 1) * 512 + h * 16) * 8 + (seg & 1) * 4 + mi * 2) * 32 + lane;
#pragma unroll(UNR == 8 ? NE : 1)
    for (int u = 0; u < NE; u++) {
        const int e = e0 + u;
        float o0[4] = {0.f, 0.f, 0.f, 0.f}, o1[4] = {0.f, 0.f, 0.f, 0.f};
        uint32_t v[4];
        lds64(v, vm + e * 256);
        mma_bf8(o0, pp[4][0], pp[4][1], v[0]);
        mma_bf8(o1, pp[4][0], pp[4][1], v[1]);
        ldsm4(v, vt + e * 1024);
        mma_bf(o0, pp[0][0], pp[0][1], pp[1][0], pp[1][1], v[0], v[2]);
        mma_bf(o1, pp[0][0], pp[0][1], pp[1][0], pp[1][1], v[1], v[3]);
        ldsm4(v, vt + e * 1024 + 512);
        mma_bf(o0, pp[2][0], pp[2][1], pp[3][0], pp[3][1], v[0], v[2]);
        mma_bf(o1, pp[2][0], pp[2][1], pp[3][0], pp[3][1], v[1], v[3]);
        o[(2 * e) * 256] = pack_bf(o0[0], o0[1]); o[(2 * e) * 256 + 32] = pack_bf(o0[2], o0[3]);
        o[(2 * e + 1) * 256] = pack_bf(o1[0], o1[1]); o[(2 * e + 1) * 256 + 32] = pack_bf(o1[2], o1[3]);
    }
}

__device__ __forceinline__
void attend_last(const uint32_t sb, const int layer) {
    const int tid = read_tid(), ln = tid & 31, w = tid >> 5;
    int h;
    asm volatile("mov.u32 %0,%%clusterid.x;" : "=r"(h));
    uint32_t inv[2];
    lds64(inv, sb + O_SCL + 16);
    mbar_wait(sb + B_S, (NSEG - 1) & 1);
    mbar_wait(sb + B_VX + 8, 0);
    if (layer == TLL) TL(54);
    if (w == 0 && ln < 2)
        asm volatile("mbarrier.arrive.relaxed.cluster.shared::cluster.b64 _,[%0];" ::"r"(mapa(sb + B_STG + 8, ln)) : "memory");
    tok_attention<2, AUNR>(sb + O_STG - 16384 + ln * 16, 16384, sb + O_LAST + ln * 16, 2048, sb + O_STG + 8192 - 16384 + ln * 16, sb + O_VM + 2048 + ln * 8,
                     (w >> 1) * 2, w & 1, ln, NSEG - 1, h, __uint_as_float(inv[0]), __uint_as_float(inv[1]));
    if (layer == TLL) TL(55);
    __syncwarp();
    if (ln == 0) red_release(g_flag + F_O + layer * 32 + 31);
    if (layer == TLL) TL(43);
}

template <int layer> __device__ __forceinline__ void chain_mma(const uint32_t sb, const int c, const int h, const uint32_t zero, const bf16* __restrict__ Wq,
                                          const bf16* __restrict__ Wk, const bf16* __restrict__ Wv, const bf16* __restrict__ Wo,
                                          const bf16* res, bf16* out) {
    int tid = read_tid(), lane = tid & 31;
    const int w = __shfl_sync(~0u, tid >> 5, 0), wg = w >> 2;
    [[maybe_unused]] const int cta = h * 3 + c;
    uint32_t A0[20][4], A1[20][4];
    const int t0 = (w & 3) + wg * 4, t1 = t0 ^ 4;
    float sl;
    {
        const int tl = tid & 127, r = tl >> 3, ch = tl & 7;
        const size_t so = (size_t)(wg * 320 + r) * 4096 + h * 128 + ch * 8;
        const bf16 *wa = (c == 2 ? Wv : Wq + c * 64) + so, *wb = (c == 2 ? Wv + 64 : Wk + c * 64) + so;
        const uint32_t ring = sb + wg * 4096;
        const uint32_t dst = ring + r * 128 + ((ch ^ r) & 7) * 16;
        const uint32_t src = ring + ((lane & 7) + (lane >> 4) * 8) * 128 + ((((w & 3) * 2 + ((lane >> 3) & 1)) ^ lane) & 7) * 16;
        const int q4 = lane & 3, gr = (c * 2 + ((w >> 1) & 1)) * 56 + (q4 == 3 ? 24 : (w & 1) * 32 + q4 * 8);
        const bf16* wo_ = Wo + (size_t)(h * 128 + (lane >> 2)) * 640 + wg * 320 + min(gr, 312);
        const uint32_t wdst = sb + O_WO + w * 8192 + (lane >> 2) * 64 + ((q4 ^ (lane >> 3)) & 3) * 16;
        auto issue = [&](int i) {
            if (i < 20) {
                const uint32_t d = dst + (i < 19 ? i * 8192 : O_LAST);
                cp_async16(d, wa + (size_t)i * 65536); cp_async16(d + 2048, wb + (size_t)i * 65536);
                if (i < 16) cp_async16(wdst + i * 512, wo_ + i * 5120, gr < 320 ? 16 : 0);
            }
            cp_commit();
        };
#pragma unroll 1
        for (int i = 0; i < WDEPTH; i++) issue(i);
        asm volatile("barrier.cluster.arrive.relaxed.aligned;" ::: "memory");
        float fa, fb;
        if (layer == 0) {
            uint32_t ma = 0, mb = 0;
#pragma unroll 1
            for (int i = 0; i < 20; i++) {
                issue(i + WDEPTH);
                cp_wait<WDEPTH>();
                const uint32_t d = dst + (i < 19 ? i * 8192 : O_LAST);
                uint32_t u[8];
                lds128(u, d); lds128(u + 4, d + 2048);
                ma = babsmax(babsmax(ma, babsmax(u[0], u[1])), babsmax(u[2], u[3])); mb = babsmax(babsmax(mb, babsmax(u[4], u[5])), babsmax(u[6], u[7]));
            }
            ma = __reduce_max_sync(~0u, max(ma & 0x7fffu, (ma >> 16) & 0x7fffu)); mb = __reduce_max_sync(~0u, max(mb & 0x7fffu, (mb >> 16) & 0x7fffu));
            asm volatile("barrier.cluster.wait.aligned;" ::: "memory");
            if (lane < 3)
                asm volatile("st.async.shared::cluster.mbarrier::complete_tx::bytes.v2.b32 [%0],{%1,%2},[%3];"
                             ::"r"(mapa(sb + O_WMX + (c * 8 + w) * 8, lane)), "r"(ma), "r"(mb), "r"(mapa(sb + B_W, lane)) : "memory");
            __syncwarp();
            {
                uint32_t off[4];
                float cs[4] = {0.f, 0.f, 0.f, 0.f};
#pragma unroll
                for (int q = 0; q < 4; q++) {
                    const int g_ = (c * 2 + ((w >> 1) & 1)) * 56 + (q == 3 ? 24 : (w & 1) * 32 + q * 8), col = wg * 320 + g_, nb = col / 80;
                    off[q] = g_ < 320 && !(q == 3 && (w & 1)) ? ((nb * 512 + h * 16) * 10 + (col - nb * 80) / 8) * 32 + lane : ~0u;
                }
                const uint32_t ta = sb + O_WO + w * 8192 + (lane & 7) * 64 + (((lane >> 3) ^ (lane >> 1)) & 3) * 16;
#pragma unroll 2
                for (int i = 0; i < 16; i++) {
                    uint32_t r[4];
                    ldsm4t(r, ta + i * 512);
#pragma unroll
                    for (int q = 0; q < 4; q++) {
                        if (off[q] != ~0u) ((uint32_t*)g_wot)[off[q] + i * 320] = r[q];
                        cs[q] += fabsf(bf_lo(r[q])) + fabsf(bf_hi(r[q]));
                    }
                }
                float cm = 0.f;
#pragma unroll
                for (int q = 0; q < 4; q++) {
                    cs[q] += __shfl_xor_sync(~0u, cs[q], 1); cs[q] += __shfl_xor_sync(~0u, cs[q], 2);
                    cm = fmaxf(cm, cs[q]);
                }
                const uint32_t n1 = __reduce_max_sync(~0u, __float_as_uint(cm));
                if (lane == 0) g_co[h * 32 + c * 8 + w] = __uint_as_float(n1);
            }
            mbar_wait(sb + B_W, 0);
            uint32_t v[2];
            lds64(v, sb + O_WMX + (lane < 24 ? lane : 0) * 8);
            const bool mine = (lane >> 3) < 3 && ((lane >> 4) == 1) == (c == 2);
            ma = __reduce_max_sync(~0u, mine ? v[0] : 0u); mb = __reduce_max_sync(~0u, mine ? v[1] : 0u);
            if (c == 2) ma = mb = max(ma, mb);
            fa = __uint_as_float(ma << 16); fb = __uint_as_float(mb << 16);
            if (tid == 0) {
                if (c != 1) g_wmx[h * 3 + c] = fa;
                if (c == 0) g_wmx[h * 3 + 1] = fb;
            }
        } else {
            fa = __ldcg(g_wmx + h * 3 + (c == 2 ? 2 : 0)); fb = __ldcg(g_wmx + h * 3 + (c == 2 ? 2 : 1));
            asm volatile("barrier.cluster.wait.aligned;" ::: "memory");
        }
        if (layer == TLL) TL(49);
        float ia, ib;
        const float sa = pow2_scale(fa, 6, &ia), sc_b = pow2_scale(fb, 6, &ib);
        sl = __uint_as_float(uni(__float_as_uint(ia * ib * (0.08838834764831845f * 1.4426950408889634f))));
        const uint32_t pa = pack_bf(sa, sa), pb = pack_bf(sc_b, sc_b);
        const int ahead = layer == 0 ? 20 : WDEPTH;
        auto convert = [&](int lo) {
#pragma unroll 1
            for (int i = lo; i < lo + 10; i++) {
                issue(i + ahead);
                cp_wait<WDEPTH>();
                const uint32_t d = dst + (i < 19 ? i * 8192 : O_LAST);
                uint32_t u[8];
                lds128(u, d); lds128(u + 4, d + 2048);
#pragma unroll
                for (int q = 0; q < 8; q++)
                    asm("{.reg .b32 m,l,u; mul.rn.bf16x2 m,%0,%1; shl.b32 l,m,16; and.b32 u,m,0xffff0000; cvt.rn.f16x2.f32 %0,u,l;}" : "+r"(u[q]) : "r"(q < 4 ? pa : pb));
                sts128(d, u[0], u[1], u[2], u[3]); sts128(d + 2048, u[4], u[5], u[6], u[7]);
            }
            bar_sync(6 + wg, 128);
        };
        const uint32_t s0 = src + wg * 2048, s1 = src + 2048 - wg * 2048;
        convert(0);
#pragma unroll
        for (int i = 0; i < 10; i++) { ldsm4t(A0[i], s0 + i * 8192); ldsm4t(A1[i], s1 + i * 8192); }
        if (layer == TLL) TL(50);
        convert(10);
#pragma unroll
        for (int i = 10; i < 20; i++) { ldsm4t(A0[i], s0 + (i < 19 ? i * 8192 : O_LAST)); ldsm4t(A1[i], s1 + (i < 19 ? i * 8192 : O_LAST)); }
        if (layer == TLL) TL(53);
        bar_arrive(9, 288);
        bar_sync(4, 288);
        asm volatile("barrier.cluster.arrive.relaxed.aligned;" ::: "memory");
    }
    const uint32_t idn = (lane >> 3) == (lane & 3) ? ((lane & 4) ? 0x3c000000u : 0x3c00u) : 0u;
    float invM = g_invM0;
    char* redp = red_base() + (size_t)layer * 32 * 32768 + w * 2048 + (lane >> 4) * 1024 + ((lane >> 3) & 1) * 256 + (lane & 7) * 16;
    const uint32_t ro2 = uni((w >> 1) * 4096 + 128), rown = uni(c == 2 ? ro2 : c * 16384);
    const uint32_t L16 = lane * 16, L8 = lane * 8, L4 = lane * 4;
    const uint32_t xch0 = uni(sb + O_XCH + t0 * 1024), xch1 = uni(sb + O_XCH + t1 * 1024);
    const uint32_t qo0 = uni(sb + O_QKP + (w & 3) * 1024 + (wg ? 768 : 0)), qp0 = uni(qo0 + (wg ? 128 : 256));
    const uint32_t qo1 = uni(sb + O_QKP + (w & 3) * 1024 + (wg ? 128 : 512)), qp1 = uni(qo1 + (wg ? 256 : 128));
    const uint32_t vo1 = uni(qo1 + (wg ? -128 : 256)), vp1 = uni(qp1 + (wg ? -128 : 256));
    const uint32_t msr = uni(sb + O_MS + wg * 5376);
    const uint32_t msw = uni(msr + ((w >> 1) & 1) * 896 + (w & 1) * 512), msh = uni(msr + ((w >> 1) & 1) * 896 + 384 + (w & 1) * 2);
    const uint32_t sco = uni(sb + O_SC + c * 768 + (w & 3) * 256);
    const uint32_t woa = sb + O_WO + w * 8192 + (lane >> 4) * 512 + (lane & 7) * 64 + (((lane >> 3) ^ (lane >> 1)) & 1) * 16 + ((lane >> 2) & 1) * 32;
    const uint32_t w512 = uni(sb + w * 512), w128 = uni(sb + w * 128);
    const uint32_t pd0 = uni(mapa(sb, c == 2 ? 0 : 2) - sb), pd1 = uni(mapa(sb, c == 1 ? 0 : 1) - sb);
    const bool scw = c < 2 && w >= 4 && w <= 6;
    uint32_t sn = uni(sb + O_STG + (c == 2 ? 8192 : 0) + t1 * 1024);
    uint32_t ka = uni(sb + (w == 6 ? O_QKP + 512 : O_STG + 4096 + (w & 1) * 512));
    uint32_t vs = uni(sb + O_VM + t1 * 256);
    uint32_t va = uni(sb + O_STG + 8192 + w * 2048), vr = uni(sb + O_VM + w * 512);
    const uint32_t sn2 = uni(2 * sn - 16384), ka2 = uni(2 * ka - (w == 6 ? 0 : 16384)), vs2 = uni(2 * vs + 2048), va2 = uni(2 * va - 16384),
                   vr2 = uni(2 * vr + 2048);
    uint32_t xd = uni((uint32_t)mkdesc(sb + O_XS + wg * 20480, 512, 128, 0));
    const uint32_t xd2 = uni(2 * xd + 2560);

    uint32_t wp[2 * NPERM + 1][4];
    sfor<NPERM>([&](auto I) { constexpr int i = I; ldsm4t(wp[2 * i], woa + i * 1024); ldsm4t(wp[2 * i + 1], (woa ^ 32) + i * 1024); });
    auto wo_fetch = [&](uint32_t (&wo)[16][4], auto I) {
        constexpr int i = I;
        if constexpr (i < NPERM) {
#pragma unroll
            for (int q = 0; q < 4; q++) { wo[i][q] = wp[2 * i][q]; wo[8 + i][q] = wp[2 * i + 1][q]; }
        } else { ldsm4t(wo[i], woa + i * 1024); ldsm4t(wo[8 + i], (woa ^ 32) + i * 1024); }
    };
    if (layer == TLL) TL(32);
    float b0[16], b1[16];
    mbar_wait(sb + B_XF, 0);
    if (layer == TLL) TL(33);
    tok_issue<0, NTB>(A0, A1, b0, b1, xd, zero);
    tok_give(b0, L16, xch0);
    tok_issue<NTB, 40>(A0, A1, b0, b1, xd, zero);
    bar_sync(4, 256);
    wg_wait<0>();
    {
        uint32_t e[2][4];
        lds128_u<0>(e[0], L16, xch1); lds128_u<512>(e[1], L16, xch1);
        tok_finish(b1, e, L16, sn, idn);
    }
    sn = sn2 - sn; xd = xd2 - xd;
    bar_sync(5, 288);
    asm volatile("barrier.cluster.wait.aligned;" ::: "memory");
    if (layer == TLL) TL(34);
    mbar_wait(sb + B_XF + 8, 0);
    if (layer == TLL) TL(35);
    tok_issue<0, NTA>(A0, A1, b0, b1, xd, zero);
    uint32_t tr = clock32() - RDELAY;

#pragma unroll 1
    for (int st = 0;; st++) {
        uint4 mv[3];
        asm volatile("{.reg .pred p; .reg .b32 t;\n"
                     "mov.b32 %0,0; mov.b32 %1,0; mov.b32 %2,0; mov.b32 %3,0; mov.b32 %4,0; mov.b32 %5,0; mov.b32 %6,0; mov.b32 %7,0;\n"
                     "mov.b32 %8,0; mov.b32 %9,0; mov.b32 %10,0; mov.b32 %11,0;\n"
                     "T_LOOP: mov.u32 t,%%clock; sub.u32 t,t,%14; setp.ge.u32 p,t,%15;\n"
                     "@p ld.relaxed.gpu.global.v4.u32 {%0,%1,%2,%3},[%12]; @p ld.relaxed.gpu.global.v4.u32 {%4,%5,%6,%7},[%12+16384];\n"
                     "@p ld.relaxed.gpu.global.v4.u32 {%8,%9,%10,%11},[%13];\n"
                     "@!p bra T_LOOP;}"
                     : "=r"(mv[0].x), "=r"(mv[0].y), "=r"(mv[0].z), "=r"(mv[0].w), "=r"(mv[1].x), "=r"(mv[1].y), "=r"(mv[1].z), "=r"(mv[1].w),
                       "=r"(mv[2].x), "=r"(mv[2].y), "=r"(mv[2].z), "=r"(mv[2].w)
                     : "l"(redp), "l"(redp + ro2), "r"(tr), "n"(RDELAY) : "memory");
        STAMP(10);
        tok_issue<NTA, NTB>(A0, A1, b0, b1, xd, zero);
        tok_give(b0, L16, xch0);
        tok_issue<NTB, 40>(A0, A1, b0, b1, xd, zero);
        xd = xd2 - xd;
        STAMP(9);
        if (zero >> 30) break;
        asm volatile("{.reg .pred p; .reg .b32 a,h,t,n; .reg .b16 l,u; .reg .b64 q;\n"
                     "add.u32 a,%12,%13; add.u32 h,%12,%14; mov.u32 n,0;\n"
                     "M_LOOP:\n .pragma \"nounroll\";\n"
                     "st.shared.b32 [a],%0; st.shared.b32 [a+128],%1; st.shared.b32 [a+256],%2; mov.b32 {l,u},%3; st.shared.b16 [h],l;\n"
                     "st.shared.b32 [a+1792],%4; st.shared.b32 [a+1920],%5; st.shared.b32 [a+2048],%6; mov.b32 {l,u},%7; st.shared.b16 [h+1792],l;\n"
                     "st.shared.b32 [a+3584],%8; st.shared.b32 [a+3712],%9; st.shared.b32 [a+3840],%10; mov.b32 {l,u},%11; st.shared.b16 [h+3584],l;\n"
                     "lop3.b32 t,%3,%7,0x50000000,0x7e; lop3.b32 t,t,%11,0x50000000,0xf6; setp.gt.u32 p,t,0xffff;\n"
                     "vote.sync.any.pred p,p,-1; add.u32 n,n,1; setp.lt.and.u32 p,n,%17,p; @!p bra M_DONE;\n"
                     "ld.relaxed.gpu.global.v4.u32 {%0,%1,%2,%3},[%15]; ld.relaxed.gpu.global.v4.u32 {%4,%5,%6,%7},[%15+16384];\n"
                     "cvt.u64.u32 q,%16; add.u64 q,q,%15; ld.relaxed.gpu.global.v4.u32 {%8,%9,%10,%11},[q];\n"
                     "bra M_LOOP;\n"
                     "M_DONE:}"
                     : "+r"(mv[0].x), "+r"(mv[0].y), "+r"(mv[0].z), "+r"(mv[0].w), "+r"(mv[1].x), "+r"(mv[1].y), "+r"(mv[1].z), "+r"(mv[1].w),
                       "+r"(mv[2].x), "+r"(mv[2].y), "+r"(mv[2].z), "+r"(mv[2].w)
                     : "r"(L4), "r"(msw), "r"(msh), "l"(redp), "r"(ro2), "n"(SPIN_LIM) : "memory");
        bar_sync(3, 256);
        STAMP(0);
        uint32_t e[2][4];
        float f1[4];
        {
            uint32_t b[10][4];
            float acc[4][4];
#pragma unroll
            for (int i = 0; i < 4; i++) acc[i][0] = acc[i][1] = acc[i][2] = acc[i][3] = 0.f;
            auto ld = [&](auto I) { constexpr int i = I; ldsm4t_u<i * 512>(b[i], L16, msr); };
            auto mm = [&](auto I) {
                constexpr int i = I;
                mma_f16(acc[0], A0[2 * i], b[i][0], b[i][1]); mma_f16(acc[2], A1[2 * i], b[i][0], b[i][1]);
                mma_f16(acc[1], A0[2 * i + 1], b[i][2], b[i][3]); mma_f16(acc[3], A1[2 * i + 1], b[i][2], b[i][3]);
            };
            ld(IC<0>()); ld(IC<1>()); ld(IC<2>()); ld(IC<3>());
            sts32_u<O_MX>(L4, w128,
                          habsmax(habsmax(habsmax(habsmax(mv[0].x, mv[0].y), habsmax(mv[0].z, mv[1].x)), habsmax(habsmax(mv[1].y, mv[1].z), mv[2].x)),
                                  habsmax(habsmax(mv[2].y, mv[2].z), habsmax(habsmax(mv[0].w, mv[1].w), mv[2].w) & 0xffffu)));
            wg_wait<0>();
            ld(IC<4>()); mm(IC<0>()); ld(IC<5>()); mm(IC<1>()); ld(IC<6>()); mm(IC<2>());
            ld(IC<7>()); mm(IC<3>()); ld(IC<8>()); mm(IC<4>()); ld(IC<9>()); mm(IC<5>());
            lds128_u<0>(e[0], L16, xch1); lds128_u<512>(e[1], L16, xch1);
            mm(IC<6>()); mm(IC<7>()); mm(IC<8>()); mm(IC<9>());
            const uint32_t u0 = pack_bf((acc[0][0] + acc[1][0]) * invM, (acc[0][1] + acc[1][1]) * invM);
            const uint32_t u1 = pack_bf((acc[0][2] + acc[1][2]) * invM, (acc[0][3] + acc[1][3]) * invM);
#pragma unroll
            for (int i = 0; i < 4; i++) f1[i] = (acc[2][i] + acc[3][i]) * invM;
            sts32_u<0>(L4, qo0, u0); sts32_u<0>(L4, qp0, u1); sts32_u<0>(L4, qo1, pack_bf(f1[0], f1[1])); sts32_u<0>(L4, qp1, pack_bf(f1[2], f1[3]));
        }
        STAMP(1);
        bar_sync(1, 320);
        if (__builtin_expect(scw, 1)) {
            float a[4][4];
#pragma unroll
            for (int i = 0; i < 4; i++) a[i][0] = a[i][1] = a[i][2] = a[i][3] = 0.f;
            uint32_t q[4][4], k[4][4];
            sfor<4>([&](auto I) {
                constexpr int i = I;
                ldsm4t_u<O_QKP + i * 1024>(q[i], L16, sb); ldsm4t_u<i * 1024>(k[i], L16, ka);
            });
#pragma unroll
            for (int i = 0; i < 4; i++) {
                mma_bf(a[i & 1], q[i][0], q[i][1], q[i][2], q[i][3], k[i][0], k[i][1]);
                mma_bf(a[2 + (i & 1)], q[i][0], q[i][1], q[i][2], q[i][3], k[i][2], k[i][3]);
            }
            const float mk = w == 6 ? 1.f : 0.f;
            const float x0 = (a[0][0] + a[0][2]) + (a[1][0] + a[1][2]), x1 = (a[0][1] + a[0][3]) + (a[1][1] + a[1][3]);
            const float y0 = (a[2][0] + a[2][2]) + (a[3][0] + a[3][2]), y1 = (a[2][1] + a[2][3]) + (a[3][1] + a[3][3]);
            st_share2(L8, sco, sb + B_S, pd0, pd1, pack_bf(fmaf(y0, mk, x0) * sl, fmaf(y1, mk, x1) * sl), pack_bf(y0 * sl, y1 * sl));
        }
        if (c == 2) {
            const uint32_t x = lds32_u<0>(L4, vo1), y = lds32_u<0>(L4, vp1);
            st_share2(L8, vs, sb + B_S, pd0, pd1, pack_bf(f1[0] + bf_lo(x), f1[1] + bf_hi(x)), pack_bf(f1[2] + bf_lo(y), f1[3] + bf_hi(y)));
        }
        STAMP(3);
        if (st == NSEG - 1) break;
        tok_finish(b1, e, L16, sn, idn);
        asm volatile("{.reg .pred p; setp.eq.u32 p,%1,0; @p mbarrier.arrive.shared::cta.b64 _,[%0];}" ::"r"(sb + B_GO), "r"(L4 + (c != 2)) : "memory");
        redp += (st & 1) ? 32768 - 512 : 512;
        if (wg == 0) {
            uint32_t wo[16][4], vx[2][2][4], vm[2][2];
            ldsm4_u<0>(vx[0][0], L16, va); ldsm4_u<512>(vx[0][1], L16, va); ldsm4_u<1024>(vx[1][0], L16, va); ldsm4_u<1536>(vx[1][1], L16, va);
            sfor<NWO0>([&](auto I) { wo_fetch(wo, I); });
            mbar_wait(sb + B_S, st & 1);
            STAMP(4);
            uint32_t s[5];
            {
                uint32_t p[2][5];
                sfor<2>([&](auto R) {
                    constexpr int r = R;
                    lds64_u<O_SC + r * 768>(p[r], L8, sb); lds64_u<O_SC + r * 768 + 256>(p[r] + 2, L8, sb); p[r][4] = lds32_u<O_SC + r * 768 + 512>(L8, sb);
                });
#pragma unroll
                for (int j = 0; j < 5; j++) s[j] = badd(p[0][j], p[1][j]);
            }
            lds64_u<0>(vm[0], L8, vr); lds64_u<256>(vm[1], L8, vr);
            uint32_t mm = bmax(bmax(bmax(s[0], s[1]), bmax(s[2], s[3])), s[4]);
            mm = bmax(bmax(mm, __shfl_xor_sync(~0u, mm, 1)), bmax(__shfl_xor_sync(~0u, mm, 2), __shfl_xor_sync(~0u, mm, 3)));
            const float m = fmaxf(bf_lo(mm), bf_hi(mm));
            float o0[4] = {0.f, 0.f, 0.f, 0.f}, o1[4] = {0.f, 0.f, 0.f, 0.f}, d[10];
#pragma unroll
            for (int j = 0; j < 5; j++) { d[2 * j] = bf_lo(s[j]) - m; d[2 * j + 1] = bf_hi(s[j]) - m; }
#pragma unroll
            for (int j = 0; j < 10; j++) d[(j + 8) % 10] = ex2(d[(j + 8) % 10]);
            float sum = ((d[8] + d[9]) + (d[0] + d[1])) + ((d[2] + d[3]) + (d[4] + d[5])) + (d[6] + d[7]);
            const uint32_t p4 = pack_bf(d[8], d[9]), p0 = pack_bf(d[0], d[1]), p1 = pack_bf(d[2], d[3]), p2 = pack_bf(d[4], d[5]), p3 = pack_bf(d[6], d[7]);
            mma_bf8(o0, vm[0][0], vm[0][1], p4);
            mma_bf8(o1, vm[1][0], vm[1][1], p4);
            mma_bf(o0, vx[0][0][0], vx[0][0][1], vx[0][0][2], vx[0][0][3], p0, p1);
            mma_bf(o1, vx[1][0][0], vx[1][0][1], vx[1][0][2], vx[1][0][3], p0, p1);
            mma_bf(o0, vx[0][1][0], vx[0][1][1], vx[0][1][2], vx[0][1][3], p2, p3);
            mma_bf(o1, vx[1][1][0], vx[1][1][1], vx[1][1][2], vx[1][1][3], p2, p3);
            sfor<NWO0B - NWO0>([&](auto I) { constexpr int i = I; wo_fetch(wo, IC<NWO0 + i>()); });
            sum += __shfl_xor_sync(~0u, sum, 1);
            sum += __shfl_xor_sync(~0u, sum, 2);
            sts32_u<O_OS>(L4, w512, pack_bf(o0[0], o0[1])); sts32_u<O_OS + 128>(L4, w512, pack_bf(o0[2], o0[3]));
            sts32_u<O_OS + 256>(L4, w512, pack_bf(o1[0], o1[1])); sts32_u<O_OS + 384>(L4, w512, pack_bf(o1[2], o1[3]));
            sts32_u<O_SUM>(lane & 28, sb, __float_as_uint(sum));
            STAMP(5);
            invM = mem_out<NWO0B>(sb, L16, L8, wo, woa, redp + rown, w & 1);
            tr = clock32();

        } else {
            uint32_t wo[16][4];
            sfor<NWO1>([&](auto I) { wo_fetch(wo, I); });
            invM = mem_out<NWO1>(sb, L16, L8, wo, woa, redp + rown, w & 1);
            tr = clock32();

        }
        STAMP(7);
        tok_issue<0, NTA>(A0, A1, b0, b1, xd, zero);
        sn = sn2 - sn; ka = ka2 - ka; vs = vs2 - vs; va = va2 - va; vr = vr2 - vr;
        STAMP(8);
    }
    if (layer == TLL) TL(40);
    if (c == 2) attend_last(sb, layer);
    bar_arrive(8, 320);
    tid = read_tid(); lane = tid & 31;
    float acc[40];
    const int nc = c == 2 ? 10 : 11;
    const int mb = 28 + (h >> 3), nj = c == 2 ? 1 : 2;
    uint32_t rv[2][2];
    const size_t go = ((size_t)(mb * 64 + (w & 3) * 16 + (lane >> 2)) * 640 + (h & 7) * 80 + (wg * 5 + c * 2) * 8 + (lane & 3) * 2) >> 1;
#pragma unroll
    for (int u = 0; u < 4; u++) rv[u >> 1][u & 1] = (u >> 1) < nj ? __ldcg((const uint32_t*)res + go + (u >> 1) * 4 + (u & 1) * 2560) : 0u;
#pragma unroll 1
    for (int k = 0; k < nc; k++) {
        mbar_wait(sb + T_FB + (k % 7) * 8, k >= 7);
        mbar_wait(sb + T_FA + (k & 3) * 8, (k >> 2) & 1);
        if (layer == TLL && k == 0) TL(41);
        const uint64_t da = mkdesc(sb + O_MS + (k & 3) * 16384 + wg * 8192, 1024, 128, 0), db = mkdesc(sb + tail_b(k) + wg * 10240, 1280, 128, 0);
        wg_fence();
#pragma unroll
        for (int q = 0; q < 4; q++) wg_n80_ss(acc, da + q * 128, db + q * 160, k | q);
        wg_commit();
        if (k > 0) {
            wg_wait<1>();
            if (lane == 0) { mbar_arrive(sb + T_EA + ((k - 1) & 3) * 8); if (k <= 4) mbar_arrive(sb + T_EB + (k - 1) * 8); }
        }
    }
    if (layer == TLL) TL(52);
    wg_wait<0>();
    asm volatile("barrier.cluster.arrive.relaxed.aligned; barrier.cluster.wait.aligned;" ::: "memory");
    const uint32_t ra = sb + O_XS + tid * 16, rb = sb + O_MS + tid * 16;
#pragma unroll
    for (int j = 0; j < 5; j++) {
        const float* q = acc + 4 * j;
        sts128(rb + j * 4096, __float_as_uint(wg ? q[0] : q[20]), __float_as_uint(wg ? q[1] : q[21]), __float_as_uint(wg ? q[2] : q[22]), __float_as_uint(wg ? q[3] : q[23]));
    }
    bar_sync(4, 256);
    sfor<5>([&](auto J) {
        constexpr int j = J;
        const float* q = acc + 4 * j;
        uint32_t p[4];
        lds128(p, sb + O_MS + (tid ^ 128) * 16 + j * 4096);
        const uint32_t d = ra + c * 8192 + (j & 1) * 4096;
        asm volatile("{.reg .pred p; setp.eq.u32 p,%7,%8;\n"
                     "@!p st.async.shared::cluster.mbarrier::complete_tx::bytes.v4.f32 [%0],{%1,%2,%3,%4},[%5]; @p st.shared.v4.f32 [%6],{%1,%2,%3,%4};}"
                     ::"r"(mapa(d, j >> 1)), "f"((wg ? q[20] : q[0]) + __uint_as_float(p[0])), "f"((wg ? q[21] : q[1]) + __uint_as_float(p[1])),
                     "f"((wg ? q[22] : q[2]) + __uint_as_float(p[2])), "f"((wg ? q[23] : q[3]) + __uint_as_float(p[3])), "r"(mapa(sb + T_RED, j >> 1)),
                     "r"(d), "r"(c), "n"(j >> 1) : "memory");
    });
    mbar_wait(sb + T_RED, 0);
#pragma unroll 1
    for (int u = 0; u < nj; u++) {
        uint32_t p[3][4];
#pragma unroll
        for (int q = 0; q < 3; q++) lds128(p[q], ra + q * 8192 + u * 4096);
        float y[4];
#pragma unroll
        for (int i = 0; i < 4; i++) y[i] = __uint_as_float(p[0][i]) + __uint_as_float(p[1][i]) + __uint_as_float(p[2][i]);
        ((uint32_t*)out)[go + u * 4] = bfma(pack_bf(y[0], y[1]), 0x3f803f80u, u ? rv[1][0] : rv[0][0]);
        ((uint32_t*)out)[go + u * 4 + 2560] = bfma(pack_bf(y[2], y[3]), 0x3f803f80u, u ? rv[1][1] : rv[0][1]);
    }
    __syncwarp();
    if (layer == 0 && lane == 0) red_release(g_flag + F_R + mb);
    TL(layer == 0 ? 15 : 29);
    asm volatile("barrier.cluster.arrive.relaxed.aligned; barrier.cluster.wait.aligned;" ::: "memory");
}

__device__ __forceinline__ void tail_load_b(const uint32_t sb, const int h, const int c, const int k) {
    mbar_expect(sb + T_FB + (k % 7) * 8, 20480);
    bulk_g2s(sb + tail_b(k), (const char*)g_wot + (size_t)((h & 7) * GNC + c * 11 + k) * 20480, 20480, sb + T_FB + (k % 7) * 8);
}
template <int layer> __device__ __forceinline__ void chain_aux(const uint32_t sb, const int c, const int h, const int nact) {
    const int tid = read_tid(), w = __shfl_sync(~0u, tid >> 5, 0), lane = tid & 31;
    if (w == 8) {
        mbar_init(sb + O_BAR + lane * 8, lane == 2 ? (c == 2 ? 9 : 4) : lane == 3 || (lane >= 16 && lane < 20) || (lane >= 27 && lane < 31) ? 8 : 1);
        asm volatile("fence.mbarrier_init.release.cluster;" ::: "memory");
        fence_async_smem();
        __syncwarp();
    }
    {
        uint4* z = (uint4*)red_base() + layer * 65536;
#pragma unroll 1
        for (int i = blockIdx.x * 128 + tid - 256; i < 65536; i += 96 * 128)
            if (i >= 2048 || (i & 32)) z[i] = make_uint4(0, 0, 0, 0);
    }
    if (w == 8 && lane == 0) {
        mbar_expect(sb + B_S, s_tx(c));
        mbar_expect(sb + B_W, 192);
        mbar_expect(sb + T_RED, (c == 2 ? 1 : 2) * 2 * 4096);
        if (layer == 1) prefetch_l2(red_base() + 32 * 32768 + blockIdx.x * 1024, 1024);
        if (layer == 0) wait_flag<400>(g_ready, NSETUP);
    }
    __syncwarp();
    cluster_sync_full();
    asm volatile("barrier.cluster.arrive.relaxed.aligned;" ::: "memory");
    pdl_wait();
    if (w == 11 && lane == 0) red_relaxed(g_flag + F_X + layer * 128 + 65);
    Flag* flag = g_flag + layer * NSEG * 32 + h;
    const Flag* xflag = g_flag + F_X + layer * 128;
    char* const it0 = g_item + (size_t)h * 32768;
    if (w == 8) {
#pragma unroll 1
        for (int n = 0; n < 3; n++) {
            wait_flag<100>(xflag + (n >> 1), 4);
            fence_async_glb();
            if (n == 0) { bar_sync(4, 288); fence_async_smem(); }
            if (lane == 0 && n < 2) {
                mbar_expect(sb + B_XF + n * 8, 40960);
                bulk_g2s(sb + O_XS + n * 40960, (const char*)g_xn + n * 40960, 40960, sb + B_XF + n * 8);
            }
            __syncwarp();
        }
#pragma unroll 1
        for (int n = 0; n < NSEG - 1; n++) {
            const int np = n & 1;
            char* const vit = it0 + (size_t)(n % RING) * 32 * 32768 + 16384;
            if (c == 2 && n > 0) {
                if (lane == 0) {
                    if (n >= RING) wait_flag(flag + (n - RING) * 32, 7);
                    mbar_sleep(sb + B_GO, (n - 1) & 1);
                    fence_async_smem();
                    bulk_s2g(vit, sb + O_STG + 8192 - np * 16384, 8192);
                    bulk_commit();
                }
                __syncwarp();
            }
            if (n == 0) { wait_flag<100>(g_flag + F_W + layer * 128, 96); bar_sync(5, 288); } else bar_sync(2, 352);
            if (n == 1) TL(12 + layer * 14);
            if (n == 63) TL(13 + layer * 14);
            if (lane == 0) {
                const uint32_t vs = sb + O_STG + 8192 - np * 16384, vb = sb + B_VX + np * 8;
                if (n == 0) { mbar_expect(sb + B_XF, 40960); bulk_g2s(sb + O_XS, (const char*)g_xn + 2 * 40960, 40960, sb + B_XF); }
                if (c == 2) {
                    if (n == 0) { fence_async_smem(); bulk_s2g(vit, vs, 8192); bulk_commit(); }
                    bulk_wait0();
                    fence_async_glb();
                    asm volatile("mbarrier.arrive.relaxed.cluster.shared::cluster.b64 _,[%0];" ::"r"(mapa(sb + B_VH, 0)) : "memory");
                    asm volatile("mbarrier.arrive.relaxed.cluster.shared::cluster.b64 _,[%0];" ::"r"(mapa(sb + B_VH, 1)) : "memory");
                    red_relaxed(flag + n * 32);
                } else {
                    mbar_sleep(sb + B_VH, np);
                    fence_async_glb();
                    mbar_expect(vb, 8192);
                    bulk_g2s(vs, vit, 8192, vb);
                }
                if (n == h * 3 + c && !np && n + 6 < NSEG) prefetch_l2(red_base() + (size_t)(layer * 32 + (n >> 1) + 3) * 32768, 32768);
            }
            __syncwarp();
        }
        {
            bar_sync(2, 352);
            TL(13 + layer * 14);
            if (lane == 0) {
                if (c == 2) mbar_expect(sb + B_VX + 8, 2 * 8192 + 2 * 2048);
                else {
                    fence_async_smem();
                    bulk_s2s(mapa(sb + O_STG - (c == 0 ? 16384 : 0), 2), sb + O_STG - 16384, 8192, mapa(sb + B_VX + 8, 2));
                }
            }
            __syncwarp();
        }
    } else if (w == 11) {
        float cvo;
        {
            auto max8 = [&](const float* p) {
                const float4 u = ((const float4*)p)[0], v = ((const float4*)p)[1];
                return fmaxf(fmaxf(fmaxf(u.x, u.y), fmaxf(u.z, u.w)), fmaxf(fmaxf(v.x, v.y), fmaxf(v.z, v.w)));
            };
            wait_flag<300>(g_flag + F_W + layer * 128, 96);
            const float* pc = g_co + lane * 32;
            float a = 640.f * __ldcg(g_wmx + lane * 3 + 2), o = fmaxf(fmaxf(max8(pc), max8(pc + 8)), max8(pc + 16));
#pragma unroll 1
            for (int s = 16; s; s >>= 1) { a = fmaxf(a, __shfl_xor_sync(~0u, a, s)); o += __shfl_xor_sync(~0u, o, s); }
            cvo = a * o * 2.f;
        }
        float invM = g_invM0;
        float iq, ik, iv;
        weight_scale(h, 0, &iq); weight_scale(h, 1, &ik); weight_scale(h, 2, &iv);
        if (lane == 0) sts64(sb + O_SCL + 16, __float_as_uint(iq * ik), __float_as_uint(iv));
        const uint32_t L16 = sb + lane * 16 + O_MX;
#pragma unroll 1
        for (int st = 0; st < NSEG; st++) {
            bar_sync(1, 320);
            if (st == NSEG - 1) break;
            if (lane == 0) mbar_arrive(sb + B_STG + (st & 1) * 8);
            uint32_t u[2][4];
            lds128(u[0], L16); lds128(u[1], L16 + 512);
            uint32_t mx = habsmax(habsmax(habsmax(u[0][0], u[0][1]), habsmax(u[0][2], u[0][3])), habsmax(habsmax(u[1][0], u[1][1]), habsmax(u[1][2], u[1][3])));
            mx = __reduce_max_sync(~0u, max(mx & 0x7fffu, (mx >> 16) & 0x7fffu));
            const float bound = fmaxf(__half2float(__ushort_as_half((unsigned short)mx)) * invM, 25.5f) * cvo;
            const float sc = pow2_scale(bound, 15, &invM);
            sts64(sb + O_SCL, __float_as_uint(sc * iv), __float_as_uint(invM));
            bar_arrive(2, 352);
        }
    } else if (w == 10) {
        bar_sync(9, 288);
        if (lane == 0) red_release(g_flag + F_W + layer * 128);
        if (lane == 0) {
#pragma unroll 1
            for (int n = 0; n < NSEG - 1; n++) {
                mbar_sleep(sb + B_STG + (n & 1) * 8, (n >> 1) & 1);
                __nanosleep(EN);
                fence_async_smem();
                const uint32_t stg = sb + O_STG - (n & 1) * 16384;
                char* it = it0 + (size_t)(n % RING) * 32 * 32768;
                if (c < 2) bulk_s2g(it + c * 8192, stg, 8192);
                bulk_commit();
                if (n + 1 >= RING && n + 1 < NSEG) wait_flag(flag - (RING - 1) * 32, 7);
                bulk_wait0();
                mbar_arrive(sb + B_FREE + (n & 1) * 8);
                fence_async_glb();
                if (c < 2) red_relaxed(flag);
                flag += 32;
            }
        }
    } else {
        bool allx = false;
#pragma unroll 1
        for (int st = 0; st < NSEG - 1; st++) {
            const int par = st & 1;
            char* const it = it0 + (size_t)(st % RING) * 32 * 32768;
            if (lane == 0 && !allx && st + 3 < NSEG) {
                allx = ld_acquire(xflag + 64) >= nact;
                if (!allx) wait_flag(st + 4 < NSEG ? xflag + ((st + 3) >> 1) : xflag + 64, st + 4 < NSEG ? 4 : nact);
                fence_async_glb();
            }
            __syncwarp();
            if (c < 2) mbar_sleep(sb + B_VX + par * 8, (st >> 1) & 1);
            if (st < NSEG - 2) mbar_sleep(sb + B_XF + par * 8, ((st >> 1) + 1) & 1);
            bar_sync(1, 320);
            if (lane == 0 && st + 3 < NSEG) {
                mbar_expect(sb + B_XF + (par ^ 1) * 8, 40960);
                bulk_g2s_last(sb + O_XS + (par ^ 1) * 40960, (const char*)g_xn + (size_t)(st + 3) * 40960, 40960, sb + B_XF + (par ^ 1) * 8);
            } else if (lane == 0) {
                tail_load_b(sb, h, c, (par ^ 1) * 2); tail_load_b(sb, h, c, (par ^ 1) * 2 + 1);
            }
            __syncwarp();
            if (lane == 0 && c < 2) {
                fence_async_smem();
#pragma unroll 1
                for (int i = 0; i < 4; i++) bulk_s2g(it + 24576 + (c * 4 + i) * 512, sb + O_QKP + i * 1024 + 512, 512);
                bulk_commit();
                asm volatile("cp.async.bulk.wait_group.read 0;" ::: "memory");
            }
            __syncwarp();
            bar_arrive(2, 352);
            mbar_sleep(sb + B_S, par);
            __syncwarp();
            if (lane == 0) {
                mbar_expect(sb + B_S, s_tx(c));
                if (c == 2) { fence_async_smem(); bulk_s2g(it + 28672, sb + O_VM + par * 2048, 2048); bulk_commit(); }
            }
            __syncwarp();
            if (lane == 0) { bulk_wait0(); fence_async_glb(); red_relaxed(flag); }
            __syncwarp();
            mbar_sleep(sb + B_FREE + par * 8, (st >> 1) & 1);
            flag += 32;
        }
        {
            bar_sync(1, 320);
            if (lane == 0 && c < 2) {
                fence_async_smem();
#pragma unroll 1
                for (int i = 0; i < 4; i++)
                    bulk_s2s(mapa(sb + O_LAST + (c * 4 + i) * 512, 2), sb + O_QKP + i * 1024 + 512, 512, mapa(sb + B_VX + 8, 2));
            }
            __syncwarp();
            bar_arrive(8, 320);
        }
    }
    __syncwarp();
    const int nc = c == 2 ? 10 : 11;
    if (w == 10) {
        bar_sync(8, 320);
        if (lane == 0) {
            if (layer == 1 && blockIdx.x == 0) g_ready[0].v = 0;
            if (c < 2) mbar_sleep(sb + B_STG + 8, 1);
            fence_async_smem();
            __nanosleep(TDELAY);
            wait_flag(xflag + 64, nact);
            wait_flag<50>(g_flag + F_O + layer * 32 + 28 + (h >> 3), (h >> 3) == 3 ? 32 + 8 * 32 : 64);
            fence_async_glb();
#pragma unroll 1
            for (int k = 0; k < nc; k++) {
                if (k >= 4) mbar_sleep(sb + T_EA + (k & 3) * 8, ((k >> 2) - 1) & 1);
                mbar_expect(sb + T_FA + (k & 3) * 8, 16384);
                bulk_g2s_last(sb + O_MS + (k & 3) * 16384, (const char*)g_O + (size_t)((28 + (h >> 3)) * GNC + c * 11 + k) * 16384, 16384, sb + T_FA + (k & 3) * 8);
            }
        }
    } else if (w == 9 && lane == 0) {
        __nanosleep(TDELAY);
#pragma unroll 1
        for (int k = 4; k < nc; k++) {
            if (k >= 7) mbar_sleep(sb + T_EB + (k - 7) * 8, 0);
            tail_load_b(sb, h, c, k);
        }
    }
    __syncwarp();
    asm volatile("barrier.cluster.wait.aligned;" ::: "memory");
    asm volatile("barrier.cluster.arrive.relaxed.aligned; barrier.cluster.wait.aligned;" ::: "memory");
    asm volatile("barrier.cluster.arrive.relaxed.aligned; barrier.cluster.wait.aligned;" ::: "memory");
}

constexpr int RI_A = 0, RI_TAB = 81920, RI_STG = RI_TAB + 82 * 768;
constexpr int RI_RES = RI_STG + 25600, RI_ST = RI_RES + 2 * 64 * 336;
constexpr int HB_A = G_BAR + 64, HB_AFREE = HB_A + 32, HB_LN = HB_A + 40, HB_FULL = HB_A + 64, HB_DONE = HB_FULL + 48, HB_FREE = HB_DONE + 48;
constexpr int HP_SMEM = HB_FREE + 48;
static_assert(G_BAR >= RI_ST + 2048, "helper shared-memory map");
#define IDL 280
#define ITEM_NS 60
#define PFW_AT 28
#define PFW_NS 150
__device__ __forceinline__ void helper_aux(const uint32_t sb, const int j, const int nh, const int na, const int nbh, const int layer, const bf16* Wq,
                                           const bf16* Wk, const bf16* Wv, const bf16* Wo) {
    const int w = threadIdx.x >> 5, lane = threadIdx.x & 31, p = w - 8;
    if (lane == 0 && j < (nh & ~3)) {
        int n = 0;
        for (int a = j >> 2; a < 32; a += nh >> 2, n++) {
            if (n == 0) continue;
            mbar_wait(sb + HB_AFREE, (n - 1) & 1);
            mbar_expect(sb + HB_A + p * 8, 20480);
            bulk_g2s_last(sb + RI_A + p * 20480, (const char*)g_YT + (size_t)a * 81920 + p * 20480, 20480, sb + HB_A + p * 8);
            if (p == 0) { mbar_wait(sb + HB_LN, (n - 1) & 1); red_release(g_flag + F_X + layer * 128 + a - (nh >> 2)); }
        }
        if (p == 0) { mbar_wait(sb + HB_LN, (n - 1) & 1); red_release(g_flag + F_X + layer * 128 + (j >> 2) + (n - 1) * (nh >> 2)); }
    }
    __syncwarp();
    if (layer == 0 && w == 8 && lane == 0) wait_flag<400>(g_flag + F_W, 96);
    __syncwarp();
    bar_sync(3, 384);
    if (p == 3 && lane == 0 && j < (nh & ~3)) red_release(g_flag + F_X + layer * 128 + 64);
    fence_async_smem();
    Flag* oflag = g_flag + F_O + layer * 32;
    if (j < na) {
        int sl = p & 1, ph = 1;
        for (int idx = j + (p & 1) * na; idx < (NSEG - 1) * 32 && p >= 2 && lane == 0; idx += 2 * na) {
            mbar_wait(sb + HB_DONE + sl * 8, ph ^ 1);
            mbar_arrive(sb + HB_FREE + sl * 8);
            red_release(oflag + (idx >> 6));
            atomicAdd(&g_flag[layer * NSEG * 32 + idx].v, 1u);
            sl += 2;
            if (sl >= 6) { sl -= 6; ph ^= 1; }
        }
        for (int idx = j + p * na; idx < (NSEG - 1) * 32 && p < 2 && lane == 0; idx += 2 * na) {
            mbar_wait(sb + HB_FREE + sl * 8, ph);
            wait_flag<ITEM_NS>(g_flag + layer * NSEG * 32 + idx, 6);
            fence_async_glb();
            if (idx < (NSEG - 2) * 32) __nanosleep(IDL);
            mbar_expect(sb + HB_FULL + sl * 8, 30720);
            bulk_g2s(sb + sl * 30720, g_item + (size_t)(idx % (RING * 32)) * 32768, 30720, sb + HB_FULL + sl * 8);
            sl += 2;
            if (sl >= 6) { sl -= 6; ph ^= 1; }
        }
    } else if (lane == 0 && p == 3) {
        if (layer == 0) {
            wait_flag<1000>(oflag + PFW_AT, 64);
            const int np = nh - na;
#pragma unroll 1
            for (int i = j - na; i < 1280; i += np) {
                const bf16* W = i < 320 ? Wq : i < 640 ? Wk : i < 960 ? Wv : Wo;
                prefetch_l2((const char*)W + (size_t)(i % 320) * 16384, 16384);
                __nanosleep(PFW_NS);
            }
#pragma unroll 1
            for (int i = j - na; i < 205; i += np) {
                const char* p_ = i < 160 ? (const char*)g_Wf + i * 16384 : i < 165 ? (const char*)g_stat + (i - 144) * 16384
                               : i < 167 ? (const char*)g_ctab + (i - 165) * 8192 : (const char*)(g_flag + NFLAG) - (i - 166) * 16384;
                prefetch_l2(p_, 16384);
                __nanosleep(PFW_NS);
            }
            if (j - na < 16) prefetch_l2(g_rtab + (j - na) * (RF_A / 4), RF_A / 4);
#pragma unroll 1
            for (int i = j - na; i < 130; i += np) { prefetch_l2((const char*)g_xb + i * 16384, 16384); __nanosleep(PFW_NS); }
        }
    } else if (lane == 0) {
        if (p == 2) wait_flag<500>(g_flag + F_X + layer * 128 + 64, nh & ~3);
        int c0 = 0;
        for (int mb = (j - na) >> 3; mb < nbh; mb += (nh - na) >> 3, c0 += GNC) {
            if (p < 2) wait_flag<300>(oflag + 2 * mb + p, 64);
            fence_async_glb();
            oproj_load(sb, p, mb, (j - na) & 7, c0, nh - na < 24 ? 0 : mb == nbh - 1 ? GPACE2 : GPACE);
        }
    }
}
__device__ __forceinline__ void helper_mma(char* sm, const int jh, const int nh, const int na, const int nbh, const int layer, const bf16* res, bf16* x,
                                           bf16* out) {
    const uint32_t sb = smem_u32(sm);
    const int tid = threadIdx.x, w = tid >> 5, lane = tid & 31;
    const bool act = jh < (nh & ~3);
    const int j4 = jh & 3;
    const int fr = tid & 63, rg = w >> 1;
    auto chunk0 = [&](int u) { return u == 0 ? 5 * j4 : u == 1 ? 75 - 5 * j4 : u == 2 ? 40 + 5 * j4 : 35 - 5 * j4; };
    const int gr = tid / 20, gq_ = tid - gr * 20, go = gr * 80 + chunk0(gq_ / 5) + gq_ % 5;
    const uint32_t gs = sb + RI_RES + gr * 336 + gq_ * 16;
    auto residual = [&](int a, int n) {
#pragma unroll 1
        for (int r = 0; r < 64 - gr && tid < 240 && a < 32; r += 12) cp_async16(gs + (n & 1) * 21504 + r * 336, (const uint4*)res + (a * 64 + r) * 80 + go);
        cp_commit();
    };
    if (act) {
        if (tid < 240) {
            const int k0 = tid / 48, n = tid - k0 * 48;
            const float d = (float)(40 * j4 + n), amp = 2.f * 0.03952847075210474f;
#pragma unroll 4
            for (int u = 0; u < 16; u++)
                *(uint4*)(sm + RI_TAB + (tid + u * 240) * 16) = cos_row8(fmaf((float)((k0 + (u & 3) * 5) * 16 + ((u >> 2) & 1)), d, (float)((u & 8) * 20)), 2.f * d, amp);
            if (tid < 96) *(uint4*)(sm + RI_TAB + (3840 + tid) * 16) = make_uint4(k0 == 0 ? pack_h((n & 1) ? -amp : amp, 0.f) : 0u, 0, 0, 0);
        }
        fence_async_smem();
        residual(jh >> 2, 0);
    }
    bar_sync(1, 384);
    if (layer == TLL) TL(36);
    if (act) {
        const float4 wm = ((const float4*)g_wmax)[lane];
        const int wg = w >> 2;
        int n = 0;
#pragma unroll 1
        for (int a = jh >> 2; a < 32; a += nh >> 2, n++) {
            float acc[2][24];
            uint64_t da = mkdesc(sb + RI_A + wg * 40960, 1024, 1024, 1), db = mkdesc(sb + RI_TAB + wg * 30720, 768, 128, 0);
#pragma unroll
            for (int gq = 0; gq < 2; gq++) {
                mbar_wait(sb + HB_A + (wg * 2 + gq) * 8, n & 1);
                if (layer == TLL && n == TLN && gq == 0) TL(45);
                wg_fence();
#pragma unroll 5
                for (int k = 0; k < 10; k++) { wg_n48_ss_ta(acc[gq], da, db, k); da += 128; db += 96; }
                wg_commit();
            }
            if (wg == 0) {
                mbar_wait(sb + HB_A + 16, n & 1);
                wg_fence();
                wg_n48_ss_ta(acc[0], da, db + 20 * 96, 1);
                wg_commit();
            }
            float inv;
            pow2_scale(__uint_as_float(__reduce_max_sync(~0u, __float_as_uint(fmaxf(fmaxf(wm.x, wm.y), fmaxf(wm.z, wm.w))))), 0, &inv);
            const uint32_t ysc = pack_bf(inv, inv);
            wg_wait<0>();
            if (layer == TLL && n == TLN) TL(46);
            if (lane == 0) mbar_arrive(sb + HB_AFREE);
            const uint32_t ad = sb + RI_STG + ((w & 3) * 16 + (lane & 15)) * 400 + (lane >> 4) * 96 + wg * 192;
#pragma unroll
            for (int q = 0; q < 6; q++) {
                const float *e = acc[0] + q * 4, *o = acc[1] + q * 4;
                stsm4(ad + q * 16, pack_h(e[0] + o[0], e[1] + o[1]), pack_h(e[2] + o[2], e[3] + o[3]), pack_h(e[0] - o[0], e[1] - o[1]), pack_h(e[2] - o[2], e[3] - o[3]));
            }
            cp_wait<0>();
            bar_sync(4, 256);
            const uint32_t xa = sb + RI_RES + (n & 1) * 21504 + fr * 336 + rg * 80, sg = (rg & 1) ? 0xbc00bc00u : 0x3c003c00u;
            float sum = 0.f, sq = 0.f;
            uint32_t ya = sb + RI_STG + fr * 400 + (rg >> 1) * 96 + ((rg & 1) ? 64 : 0), carry;
            asm("fma.rn.f16x2 %0,%1,%2,%3;" : "=r"(carry) : "r"(lds32(ya + 208)), "r"(sg), "r"(lds32(ya + 16)));
#pragma unroll 1
            for (int ch = 0; ch < 5; ch++, ya += (rg & 1) ? -16 : 16) {
                uint32_t y[4], z[4], xr[4];
                lds128(y, ya); lds128(z, ya + 192); lds128(xr, xa + ch * 16);
#pragma unroll
                for (int q = 0; q < 4; q++) asm("fma.rn.f16x2 %0,%1,%2,%0;" : "+r"(y[q]) : "r"(z[q]), "r"(sg));
                if (rg & 1) {
                    const uint32_t y0 = y[0], y1 = y[1];
                    y[0] = __byte_perm(carry, y[3], 0x7610); y[1] = __byte_perm(y[3], y[2], 0x7610);
                    y[3] = __byte_perm(y1, y0, 0x7610); y[2] = __byte_perm(y[2], y1, 0x7610);
                    carry = y0;
                }
#pragma unroll
                for (int q = 0; q < 4; q++) {
                    const float2 yf = __half22float2(*(const __half2*)&y[q]);
                    xr[q] = bfma(pack_bf(yf.x, yf.y), ysc, xr[q]);
                    const float e = bf_lo(xr[q]), f = bf_hi(xr[q]);
                    sum += e + f; sq = fmaf(e, e, fmaf(f, f, sq));
                }
                sts128(xa + ch * 16, xr[0], xr[1], xr[2], xr[3]);
            }
            uint2* stat = g_stat + (size_t)(layer * 32 + a) * 1024 + rg * 64 + fr;
            asm volatile("st.relaxed.gpu.global.v2.u32 [%0],{%1,%2};" ::"l"(stat + j4 * 256), "r"(__float_as_uint(sum)), "r"(__float_as_uint(sq) | 0x80000000u) : "memory");
            if (layer == TLL && n == TLN) TL(47);
            uint32_t s0[3], s1[3];
            int lim = 0;
            do {
#pragma unroll
                for (int q = 0; q < 3; q++)
                    asm volatile("ld.relaxed.gpu.global.v2.u32 {%0,%1},[%2];" : "=r"(s0[q]), "=r"(s1[q]) : "l"(stat + ((j4 + 1 + q) & 3) * 256) : "memory");
            } while (__any_sync(~0u, (int)(s1[0] & s1[1] & s1[2]) >= 0) && ++lim < SPIN_LIM);
#pragma unroll
            for (int q = 0; q < 3; q++) { sum += __uint_as_float(s0[q]); sq -= __uint_as_float(s1[q]); }
            sts64(sb + RI_ST + tid * 8, __float_as_uint(sum), __float_as_uint(sq));
            bar_sync(4, 256);
            if (layer == TLL && n == TLN) TL(48);
#pragma unroll
            for (int q = 1; q < 4; q++) {
                uint32_t st2[2];
                lds64(st2, sb + RI_ST + ((tid + q * 64) & 255) * 8);
                sum += __uint_as_float(st2[0]); sq += __uint_as_float(st2[1]);
            }
            const float mean = sum * (1.f / 640.f), r = rsqrtf(fmaxf(fmaf(-mean, mean, sq * (1.f / 640.f)), 0.f) + 1e-5f), off = -mean * r;
            uint4* dst = (uint4*)g_xn + ((size_t)(2 * a + (w & 1)) * 80 + chunk0(rg)) * 32 + lane;
#pragma unroll
            for (int i = 0; i < 5; i++) {
                uint32_t u[4];
                lds128(u, xa + i * 16);
                dst[i * 32] = make_uint4(pack_h(fmaf(bf_lo(u[0]), r, off), fmaf(bf_hi(u[0]), r, off)), pack_h(fmaf(bf_lo(u[1]), r, off), fmaf(bf_hi(u[1]), r, off)),
                                         pack_h(fmaf(bf_lo(u[2]), r, off), fmaf(bf_hi(u[2]), r, off)), pack_h(fmaf(bf_lo(u[3]), r, off), fmaf(bf_hi(u[3]), r, off)));
            }
            __syncwarp();
            if (lane == 0) mbar_arrive(sb + HB_LN);
            if (layer == TLL) TL(37);
            if (layer == TLL && n == TLN) TL(44);
            residual(a + (nh >> 2), n + 1);
#pragma unroll 2
            for (int rr = 0; rr < 64 - gr && tid < 240; rr += 12) {
                uint32_t v[4];
                lds128(v, gs + (n & 1) * 21504 + rr * 336);
                ((uint4*)x)[(a * 64 + rr) * 80 + go] = make_uint4(v[0], v[1], v[2], v[3]);
            }
        }
    }
    bar_sync(3, 384);
    if (layer == TLL) TL(38);
    if (jh >= na) {
        int c0 = 0;
#pragma unroll 1
        for (int mb = (jh - na) >> 3; mb < nbh; mb += (nh - na) >> 3, c0 += GNC) oproj_mma(sb, mb, (jh - na) & 7, c0, x, out, layer);
        if (layer == TLL) TL(42);
        return;
    }
    const int p = w >> 1, mi = w & 1;
    int slot = p, ph = 0;
    for (int idx = jh + p * na; idx < (NSEG - 1) * 32; idx += 4 * na) {
        const uint32_t it = sb + slot * 30720 + lane * 16;
        float iq, ik, iv;
        weight_scale(idx & 31, 0, &iq); weight_scale(idx & 31, 1, &ik); weight_scale(idx & 31, 2, &iv);
        bar_sync(6 + p, 64);
        mbar_wait(sb + HB_DONE + slot * 8, ph ^ 1);
        mbar_wait(sb + HB_FULL + slot * 8, ph);
        tok_attention<8, 8>(it, 8192, it + 24576, 2048, it + 16384, it - lane * 8 + 28672, 0, mi, lane, idx >> 5, idx & 31, iq * ik, iv);
        __syncwarp();
        if (lane == 0) mbar_arrive(sb + HB_DONE + slot * 8);
        slot += 4;
        if (slot >= 6) { slot -= 6; ph ^= 1; }
    }
    if (layer == TLL) TL(39);
}

template <int layer> __global__ void __cluster_dims__(3, 1, 1) __launch_bounds__(384, 1)
k_chain(const int nact, const uint32_t zero, const bf16* __restrict__ Wq, const bf16* __restrict__ Wk, const bf16* __restrict__ Wv,
        const bf16* __restrict__ Wo, const bf16* res, bf16* out) {
    extern __shared__ __align__(1024) char sm[];
    const uint32_t sb = smem_u32(sm);
    const int b = blockIdx.x, h = b / 3, c = b - h * 3;
    pdl_go();
    if (threadIdx.x >= 256) {
        asm volatile("setmaxnreg.dec.sync.aligned.u32 24;");
        TL(11 + layer * 14);
        chain_aux<layer>(sb, c, h, nact);
    } else {
        asm volatile("setmaxnreg.inc.sync.aligned.u32 240;");
        chain_mma<layer>(sb, c, h, zero, Wq, Wk, Wv, Wo, res, out);
    }
}
__global__ void __launch_bounds__(384, 1) k_help(const bf16* res, bf16* x, bf16* out, const int layer, const int na, const int nbh, const int zero, const bf16* Wq,
                                                  const bf16* Wk, const bf16* Wv, const bf16* Wo) {
    extern __shared__ __align__(1024) char sm[];
    if (layer == TLL) TL(51);
    pdl_go();
    if (threadIdx.x >= 256) {
        const uint32_t sb = smem_u32(sm);
        const int p = (threadIdx.x >> 5) - 8, i = (threadIdx.x & 31) * 4 + p;
        if (i < 34) mbar_init(sb + G_BAR + i * 8, i < 4 ? 3 : i < 8 || i == 12 || i == 13 ? 8 : i >= 22 && i < 28 ? 2 : 1);
        fence_async_smem();
        wait_flag<100>(g_flag + F_X + layer * 128 + 65, 1);
        fence_async_glb();
        if (i == 8 + p && blockIdx.x < (gridDim.x & ~3)) {
            mbar_expect(sb + HB_A + p * 8, 20480);
            bulk_g2s(sb + RI_A + p * 20480, (const char*)g_YT + (size_t)(blockIdx.x >> 2) * 81920 + p * 20480, 20480, sb + HB_A + p * 8);
        }
        __syncwarp();
        bar_sync(2, 128);
        bar_arrive(1, 384);
    }
    if (threadIdx.x + zero >= 256) helper_aux(smem_u32(sm), blockIdx.x, gridDim.x, na, nbh, layer, Wq, Wk, Wv, Wo);
    else helper_mma(sm, blockIdx.x, gridDim.x, na, nbh, layer, res, x, out);
    __syncwarp();
    if (blockIdx.x == 0) pdl_wait();
}

#define COL_PAD 15872
template <class... P, class... A>
void launch_pdl(void (*k)(P...), int grid, int block, int smem, cudaStream_t st, A... args) {
    cudaLaunchConfig_t cfg = {};
    cfg.gridDim = dim3(grid); cfg.blockDim = dim3(block); cfg.dynamicSmemBytes = smem; cfg.stream = st;
    cudaLaunchAttribute at[1];
    at[0].id = cudaLaunchAttributeProgrammaticStreamSerialization; at[0].val.programmaticStreamSerializationAllowed = 1;
    cfg.attrs = at;
    cfg.numAttrs = 1;
    cudaLaunchKernelEx(&cfg, k, args...);
}

}

extern "C" void kernel_launch(void* const* d_in, const int* in_sizes, int n_in, void* d_out, int out_size) {
    const bf16* x = (const bf16*)d_in[0];
    const bf16* wr = (const bf16*)d_in[1];
    const bf16* wi = (const bf16*)d_in[2];
    const bf16* mem0 = (const bf16*)d_in[4];
    const bf16* Wq = (const bf16*)d_in[5];
    const bf16* Wk = (const bf16*)d_in[6];
    const bf16* Wv = (const bf16*)d_in[7];
    const bf16* Wo = (const bf16*)d_in[8];
    bf16* out = (bf16*)d_out;
    static int nhelp = 0;
    static bf16 *xa, *xb;
    static cudaStream_t s1;
    static cudaEvent_t ev_fork, ev_join;
    if (!nhelp) {
        cudaStreamCreateWithFlags(&s1, cudaStreamNonBlocking);
        cudaEventCreateWithFlags(&ev_fork, cudaEventDisableTiming);
        cudaEventCreateWithFlags(&ev_join, cudaEventDisableTiming);
        cudaFuncSetAttribute(k_setup, cudaFuncAttributeMaxDynamicSharedMemorySize, SU_SMEM);
        cudaFuncSetAttribute(k_rowf<0>, cudaFuncAttributeMaxDynamicSharedMemorySize, RF_SMEM);
        cudaFuncSetAttribute(k_rowf<1>, cudaFuncAttributeMaxDynamicSharedMemorySize, RF_SMEM);
        cudaFuncSetAttribute(k_col, cudaFuncAttributeMaxDynamicSharedMemorySize, COL_PAD);
        cudaFuncSetAttribute(k_chain<0>, cudaFuncAttributeMaxDynamicSharedMemorySize, CH_SMEM);
        cudaFuncSetAttribute(k_chain<1>, cudaFuncAttributeMaxDynamicSharedMemorySize, CH_SMEM);
        cudaFuncSetAttribute(k_setup, cudaFuncAttributePreferredSharedMemoryCarveout, 100);
        cudaFuncSetAttribute(k_rowf<0>, cudaFuncAttributePreferredSharedMemoryCarveout, 100);
        cudaFuncSetAttribute(k_rowf<1>, cudaFuncAttributePreferredSharedMemoryCarveout, 100);
        cudaFuncSetAttribute(k_col, cudaFuncAttributePreferredSharedMemoryCarveout, 100);
        cudaFuncSetAttribute(k_chain<0>, cudaFuncAttributePreferredSharedMemoryCarveout, 100);
        cudaFuncSetAttribute(k_chain<1>, cudaFuncAttributePreferredSharedMemoryCarveout, 100);
        cudaFuncSetAttribute(k_help, cudaFuncAttributeMaxDynamicSharedMemorySize, HP_SMEM);
        cudaFuncSetAttribute(k_help, cudaFuncAttributePreferredSharedMemoryCarveout, 100);
        int dev = 0, sms = 0;
        cudaGetDevice(&dev);
        cudaDeviceGetAttribute(&sms, cudaDevAttrMultiProcessorCount, dev);
        nhelp = sms - 96 < 12 ? 12 : sms - 96;
        cudaGetSymbolAddress((void**)&xa, g_xa);
        cudaGetSymbolAddress((void**)&xb, g_xb);
    }
    const int na = nhelp - (nhelp >= 36 ? 24 : nhelp >= 28 ? 16 : 8), nbh = 14;
    cudaStream_t s0 = cudaStreamPerThread;
    cudaEventRecord(ev_fork, s0);
    cudaStreamWaitEvent(s1, ev_fork, 0);
    k_rowf<1><<<(96 + nhelp) & ~1, 256, RF_SMEM, s0>>>(x);
    k_setup<<<NSETUP, 256, SU_SMEM, s1>>>(wr, wi, mem0);
    cudaEventRecord(ev_join, s1);
#define NLAYER 2
    for (int l = 0; l < NLAYER; l++) {
        const bf16* xin = l == 0 ? x : xb;
        if (l == 1) launch_pdl(k_rowf<0>, 128, 256, RF_SMEM, s0, xin);
        launch_pdl(k_col, 321, 128, l == 0 ? 0 : COL_PAD, s0, (int)(l == 0));
        launch_pdl(l == 0 ? k_chain<0> : k_chain<1>, 96, 384, CH_SMEM, s0, nhelp & ~3, 0u, Wq, Wk, Wv, Wo, (const bf16*)xa, l == 0 ? xb : out);
        launch_pdl(k_help, nhelp, 384, HP_SMEM, s0, xin, xa, l == 0 ? xb : out, l, na, nbh, 0, Wq, Wk, Wv, Wo);
    }
    cudaStreamWaitEvent(s0, ev_join, 0);
}
```

```cpp
#include <cuda_runtime.h>
#include <cuda_bf16.h>
#include <cuda_fp16.h>
#include <stdint.h>
#include <string.h>

namespace {

typedef __nv_bfloat16 bf16;
constexpr int S_ = 2048, D_ = 640, NSEG = 64;
constexpr int SPIN_LIM = 1 << 13;

__device__ float                  g_wmx[96];
__device__ __align__(1024) bf16   g_wot[4096 * 640];
__device__ __align__(16) float    g_co[1024];
__device__ __align__(256) uint2   g_stat[2 * 32 * 16 * 64];
__device__ float                  g_invM0;
__device__ __align__(16) float    g_wmax[128];
__device__ __align__(1024) char   g_redraw[65 * 32768];
constexpr int F_X = 2 * NSEG * 32, F_O = F_X + 2 * 128, NFLAG = F_O + 128, RING = 8;
constexpr int F_W = F_X + 66;
constexpr int F_R = F_O + 64;
constexpr int NSETUP = 131;
struct __align__(256) Flag { unsigned v; };
__device__ Flag                   g_flag[NFLAG];
__device__ Flag                   g_ready[1];
__device__ __align__(1024) char   g_item[RING * 32 * 32768];
__device__ __align__(1024) bf16   g_O[S_ * 4096];
__device__ __align__(1024) __half g_xn[S_ * D_];
__device__ __align__(1024) bf16   g_xa[S_ * D_];
__device__ __align__(1024) bf16   g_xb[S_ * D_];
__device__ __align__(1024) __half g_UT[D_ * S_];
__device__ __align__(1024) __half g_YT[D_ * S_];
__device__ __align__(1024) __half g_ctab[64 * 128 + 64 * 64];
__device__ __align__(1024) uint32_t g_Wf[321 * 2048];

#define TL(i)
#define TLN 0
#define TLL 1
#define CK(i)
__device__ __forceinline__ uint32_t smem_u32(const void* p) { return (uint32_t)__cvta_generic_to_shared(p); }
__device__ __forceinline__ uint32_t mapa(uint32_t a, uint32_t r) { uint32_t o; asm("mapa.shared::cluster.u32 %0,%1,%2;" : "=r"(o) : "r"(a), "r"(r)); return o; }
__device__ __forceinline__ void mbar_init(uint32_t a, int c) { asm volatile("mbarrier.init.shared::cta.b64 [%0],%1;" ::"r"(a), "r"(c) : "memory"); }
__device__ __forceinline__ void mbar_expect(uint32_t a, int bytes) { asm volatile("mbarrier.arrive.expect_tx.shared::cta.b64 _,[%0],%1;" ::"r"(a), "r"(bytes) : "memory"); }
__device__ __forceinline__ void mbar_arrive(uint32_t a) { asm volatile("mbarrier.arrive.shared::cta.b64 _,[%0];" ::"r"(a) : "memory"); }
__device__ __forceinline__ bool mbar_try(uint32_t a, uint32_t par) {
    uint32_t p;
    asm volatile("{.reg .pred q; mbarrier.try_wait.parity.shared::cta.b64 q,[%1],%2; selp.u32 %0,1,0,q;}" : "=r"(p) : "r"(a), "r"(par) : "memory");
    return p;
}
__device__ __forceinline__ void mbar_wait(uint32_t a, uint32_t par) {
    if (!mbar_try(a, par)) {
        int lim = 0;
        while (!mbar_try(a, par) && ++lim < SPIN_LIM) {}
    }
}
__device__ __forceinline__ void mbar_sleep(uint32_t a, uint32_t par) {
    asm volatile("{.reg .pred q; .reg .u32 n; mov.u32 n,0;\n"
                 "W_LOOP: mbarrier.try_wait.parity.shared::cta.b64 q,[%0],%1,%2; add.u32 n,n,1; setp.lt.and.u32 q,n,%3,!q; @q bra W_LOOP;}"
                 ::"r"(a), "r"(par), "n"(20000), "n"(SPIN_LIM) : "memory");
}
__device__ __forceinline__ void bar_arrive(int id, int n) { asm volatile("bar.arrive %0,%1;" ::"r"(id), "r"(n) : "memory"); }
__device__ __forceinline__ uint32_t clock32() { uint32_t c; asm volatile("mov.u32 %0,%%clock;" : "=r"(c)); return c; }
__device__ __forceinline__ uint32_t read_tid() { uint32_t v; asm volatile("mov.u32 %0,%%tid.x;" : "=r"(v)); return v; }
__device__ __forceinline__ void bar_sync(int id, int n) { asm volatile("bar.sync %0,%1;" ::"r"(id), "r"(n) : "memory"); }
__device__ __forceinline__ void fence_async_smem() { asm volatile("fence.proxy.async.shared::cta;" ::: "memory"); }
__device__ __forceinline__ void fence_async_glb() { asm volatile("fence.proxy.async.global;" ::: "memory"); }
__device__ __forceinline__ void cluster_sync_full() { asm volatile("barrier.cluster.arrive.aligned; barrier.cluster.wait.aligned;" ::: "memory"); }
__device__ __forceinline__ void bulk_g2s(uint32_t dst, const void* src, int bytes, uint32_t mb) {
    asm volatile("cp.async.bulk.shared::cluster.global.mbarrier::complete_tx::bytes [%0],[%1],%2,[%3];" ::"r"(dst), "l"(src), "r"(bytes), "r"(mb) : "memory");
}
__device__ __forceinline__ void bulk_g2s_last(uint32_t dst, const void* src, int bytes, uint32_t mb) {
    asm volatile("{.reg .b64 p; createpolicy.fractional.L2::evict_first.b64 p, 1.0;\n"
                 "cp.async.bulk.shared::cluster.global.mbarrier::complete_tx::bytes.L2::cache_hint [%0],[%1],%2,[%3],p;}"
                 ::"r"(dst), "l"(src), "r"(bytes), "r"(mb) : "memory");
}
__device__ __forceinline__ void bulk_s2s(uint32_t dst, uint32_t src, int bytes, uint32_t mb) {
    asm volatile("cp.async.bulk.shared::cluster.shared::cta.mbarrier::complete_tx::bytes [%0],[%1],%2,[%3];" ::"r"(dst), "r"(src), "r"(bytes), "r"(mb) : "memory");
}
__device__ __forceinline__ void bulk_s2g(void* dst, uint32_t src, int bytes) {
    asm volatile("cp.async.bulk.global.shared::cta.bulk_group [%0],[%1],%2;" ::"l"(dst), "r"(src), "r"(bytes) : "memory");
}
__device__ __forceinline__ void cp_async16(uint32_t dst, const void* src, uint32_t bytes = 16) {
    asm volatile("cp.async.cg.shared.global [%0],[%1],16,%2;" ::"r"(dst), "l"(src), "r"(bytes) : "memory");
}
__device__ __forceinline__ void cp_commit() { asm volatile("cp.async.commit_group;" ::: "memory"); }
template <int N> __device__ __forceinline__ void cp_wait() { asm volatile("cp.async.wait_group %0;" ::"n"(N) : "memory"); }
__device__ __forceinline__ void bulk_commit() { asm volatile("cp.async.bulk.commit_group;" ::: "memory"); }
__device__ __forceinline__ void bulk_wait0() { asm volatile("cp.async.bulk.wait_group 0;" ::: "memory"); }
__device__ __forceinline__ void ldsm4(uint32_t* r, uint32_t a) {
    asm volatile("ldmatrix.sync.aligned.m8n8.x4.shared.b16 {%0,%1,%2,%3},[%4];" : "=r"(r[0]), "=r"(r[1]), "=r"(r[2]), "=r"(r[3]) : "r"(a) : "memory");
}
__device__ __forceinline__ void ldsm4t(uint32_t* r, uint32_t a) {
    asm volatile("ldmatrix.sync.aligned.m8n8.x4.trans.shared.b16 {%0,%1,%2,%3},[%4];" : "=r"(r[0]), "=r"(r[1]), "=r"(r[2]), "=r"(r[3]) : "r"(a) : "memory");
}
__device__ __forceinline__ void stsm4(uint32_t a, uint32_t r0, uint32_t r1, uint32_t r2, uint32_t r3) {
    asm volatile("stmatrix.sync.aligned.m8n8.x4.shared.b16 [%0],{%1,%2,%3,%4};" ::"r"(a), "r"(r0), "r"(r1), "r"(r2), "r"(r3) : "memory");
}
__device__ __forceinline__ void stsm4t(uint32_t a, uint32_t r0, uint32_t r1, uint32_t r2, uint32_t r3) {
    asm volatile("stmatrix.sync.aligned.m8n8.x4.trans.shared.b16 [%0],{%1,%2,%3,%4};" ::"r"(a), "r"(r0), "r"(r1), "r"(r2), "r"(r3) : "memory");
}
__device__ __forceinline__ void lds128(uint32_t* r, uint32_t a) {
    asm volatile("ld.shared.v4.b32 {%0,%1,%2,%3},[%4];" : "=r"(r[0]), "=r"(r[1]), "=r"(r[2]), "=r"(r[3]) : "r"(a) : "memory");
}
__device__ __forceinline__ void lds64(uint32_t* r, uint32_t a) {
    asm volatile("ld.shared.v2.b32 {%0,%1},[%2];" : "=r"(r[0]), "=r"(r[1]) : "r"(a) : "memory");
}
__device__ __forceinline__ uint32_t lds32(uint32_t a) { uint32_t v; asm volatile("ld.shared.b32 %0,[%1];" : "=r"(v) : "r"(a) : "memory"); return v; }
__device__ __forceinline__ void sts128(uint32_t a, uint32_t r0, uint32_t r1, uint32_t r2, uint32_t r3) {
    asm volatile("st.shared.v4.b32 [%0],{%1,%2,%3,%4};" ::"r"(a), "r"(r0), "r"(r1), "r"(r2), "r"(r3) : "memory");
}
__device__ __forceinline__ void sts64(uint32_t a, uint32_t v0, uint32_t v1) { asm volatile("st.shared.v2.b32 [%0],{%1,%2};" ::"r"(a), "r"(v0), "r"(v1) : "memory"); }
[[maybe_unused]] __device__ __forceinline__ void sts32(uint32_t a, uint32_t v) { asm volatile("st.shared.b32 [%0],%1;" ::"r"(a), "r"(v) : "memory"); }
#define AU_(op) "{.reg .u32 t; add.u32 t,%4,%5; " op " {%0,%1,%2,%3},[t+%6];}"
template <int I> __device__ __forceinline__ void ldsm4_u(uint32_t* r, uint32_t a, uint32_t u) {
    asm volatile(AU_("ldmatrix.sync.aligned.m8n8.x4.shared.b16") : "=r"(r[0]), "=r"(r[1]), "=r"(r[2]), "=r"(r[3]) : "r"(a), "r"(u), "n"(I) : "memory");
}
template <int I> __device__ __forceinline__ void ldsm4t_u(uint32_t* r, uint32_t a, uint32_t u) {
    asm volatile(AU_("ldmatrix.sync.aligned.m8n8.x4.trans.shared.b16") : "=r"(r[0]), "=r"(r[1]), "=r"(r[2]), "=r"(r[3]) : "r"(a), "r"(u), "n"(I) : "memory");
}
template <int I> __device__ __forceinline__ void lds128_u(uint32_t* r, uint32_t a, uint32_t u) {
    asm volatile(AU_("ld.shared.v4.b32") : "=r"(r[0]), "=r"(r[1]), "=r"(r[2]), "=r"(r[3]) : "r"(a), "r"(u), "n"(I) : "memory");
}
template <int I> __device__ __forceinline__ void lds64_u(uint32_t* r, uint32_t a, uint32_t u) {
    asm volatile("{.reg .u32 t; add.u32 t,%2,%3; ld.shared.v2.b32 {%0,%1},[t+%4];}" : "=r"(r[0]), "=r"(r[1]) : "r"(a), "r"(u), "n"(I) : "memory");
}
template <int I> __device__ __forceinline__ uint32_t lds32_u(uint32_t a, uint32_t u) {
    uint32_t v;
    asm volatile("{.reg .u32 t; add.u32 t,%1,%2; ld.shared.b32 %0,[t+%3];}" : "=r"(v) : "r"(a), "r"(u), "n"(I) : "memory");
    return v;
}
template <int I> __device__ __forceinline__ void sts64_u(uint32_t a, uint32_t u, uint32_t v0, uint32_t v1) {
    asm volatile("{.reg .u32 t; add.u32 t,%0,%1; st.shared.v2.b32 [t+%2],{%3,%4};}" ::"r"(a), "r"(u), "n"(I), "r"(v0), "r"(v1) : "memory");
}
template <int I> __device__ __forceinline__ void sts32_u(uint32_t a, uint32_t u, uint32_t v) {
    asm volatile("{.reg .u32 t; add.u32 t,%0,%1; st.shared.b32 [t+%2],%3;}" ::"r"(a), "r"(u), "n"(I), "r"(v) : "memory");
}
template <int I> __device__ __forceinline__ void sts16_u(uint32_t a, uint32_t u, uint32_t v) {
    asm volatile("{.reg .u32 t; add.u32 t,%0,%1; st.shared.b16 [t+%2],%3;}" ::"r"(a), "r"(u), "n"(I), "h"((unsigned short)v) : "memory");
}
template <int I> __device__ __forceinline__ void sts128_u(uint32_t a, uint32_t u, uint32_t r0, uint32_t r1, uint32_t r2, uint32_t r3) {
    asm volatile("{.reg .u32 t; add.u32 t,%0,%1; st.shared.v4.b32 [t+%2],{%3,%4,%5,%6};}" ::"r"(a), "r"(u), "n"(I), "r"(r0), "r"(r1), "r"(r2), "r"(r3) : "memory");
}
template <int I> __device__ __forceinline__ void stsm4_u(uint32_t a, uint32_t u, uint32_t r0, uint32_t r1, uint32_t r2, uint32_t r3) {
    asm volatile("{.reg .u32 t; add.u32 t,%0,%1; stmatrix.sync.aligned.m8n8.x4.shared.b16 [t+%2],{%3,%4,%5,%6};}"
                 ::"r"(a), "r"(u), "n"(I), "r"(r0), "r"(r1), "r"(r2), "r"(r3) : "memory");
}
__device__ __forceinline__ void st_share2(uint32_t a, uint32_t u, uint32_t mb, uint32_t d0, uint32_t d1, uint32_t v0, uint32_t v1) {
    asm volatile("{.reg .pred p; .reg .u32 t,x,y; add.u32 t,%0,%1;\n"
                 "add.u32 x,t,%3; add.u32 y,%2,%3; st.async.shared::cluster.mbarrier::complete_tx::bytes.v2.b32 [x],{%5,%6},[y];\n"
                 "add.u32 x,t,%4; add.u32 y,%2,%4; st.async.shared::cluster.mbarrier::complete_tx::bytes.v2.b32 [x],{%5,%6},[y];\n"
                 "st.shared.v2.b32 [t],{%5,%6}; bar.warp.sync -1; setp.eq.u32 p,%0,0; @p mbarrier.arrive.shared::cta.b64 _,[%2];}"
                 ::"r"(a), "r"(u), "r"(mb), "r"(d0), "r"(d1), "r"(v0), "r"(v1) : "memory");
}
template <int V> struct IC { __host__ __device__ constexpr operator int() const { return V; } };
template <int N, class F> __device__ __forceinline__ void sfor(F f) {
    if constexpr (N > 0) { sfor<N - 1>(f); f(IC<N - 1>()); }
}
__device__ __forceinline__ void mma_f16(float* d, const uint32_t* a, uint32_t b0, uint32_t b1) {
    asm volatile("mma.sync.aligned.m16n8k16.row.col.f32.f16.f16.f32 {%0,%1,%2,%3},{%4,%5,%6,%7},{%8,%9},{%0,%1,%2,%3};"
                 : "+f"(d[0]), "+f"(d[1]), "+f"(d[2]), "+f"(d[3]) : "r"(a[0]), "r"(a[1]), "r"(a[2]), "r"(a[3]), "r"(b0), "r"(b1));
}
__device__ __forceinline__ void mma_bf(float* d, uint32_t a0, uint32_t a1, uint32_t a2, uint32_t a3, uint32_t b0, uint32_t b1) {
    asm volatile("mma.sync.aligned.m16n8k16.row.col.f32.bf16.bf16.f32 {%0,%1,%2,%3},{%4,%5,%6,%7},{%8,%9},{%0,%1,%2,%3};"
                 : "+f"(d[0]), "+f"(d[1]), "+f"(d[2]), "+f"(d[3]) : "r"(a0), "r"(a1), "r"(a2), "r"(a3), "r"(b0), "r"(b1));
}
__device__ __forceinline__ void mma_bf8(float* d, uint32_t a0, uint32_t a1, uint32_t b0) {
    asm volatile("mma.sync.aligned.m16n8k8.row.col.f32.bf16.bf16.f32 {%0,%1,%2,%3},{%4,%5},{%6},{%0,%1,%2,%3};"
                 : "+f"(d[0]), "+f"(d[1]), "+f"(d[2]), "+f"(d[3]) : "r"(a0), "r"(a1), "r"(b0));
}
__device__ __forceinline__ uint32_t pack_bf(float lo, float hi) { uint32_t r; asm("cvt.rn.bf16x2.f32 %0,%1,%2;" : "=r"(r) : "f"(hi), "f"(lo)); return r; }
__device__ __forceinline__ uint32_t pack_h(float lo, float hi) { uint32_t r; asm("cvt.rn.f16x2.f32 %0,%1,%2;" : "=r"(r) : "f"(hi), "f"(lo)); return r; }
__device__ __forceinline__ float bf_lo(uint32_t v) { return __uint_as_float(v << 16); }
__device__ __forceinline__ float bf_hi(uint32_t v) { return __uint_as_float(v & 0xffff0000u); }
__device__ __forceinline__ uint32_t bfma(uint32_t a, uint32_t b, uint32_t c) { uint32_t r; asm("fma.rn.bf16x2 %0,%1,%2,%3;" : "=r"(r) : "r"(a), "r"(b), "r"(c)); return r; }
__device__ __forceinline__ uint4 add_bf8(const uint4 x, const uint32_t* y, const uint32_t k = 0x3f803f80u) {
    return make_uint4(bfma(y[0], k, x.x), bfma(y[1], k, x.y), bfma(y[2], k, x.z), bfma(y[3], k, x.w));
}
__device__ __forceinline__ float ex2(float x) { float r; asm("ex2.approx.ftz.f32 %0,%1;" : "=f"(r) : "f"(x)); return r; }
__device__ __forceinline__ float rcp(float x) { float r; asm("rcp.approx.ftz.f32 %0,%1;" : "=f"(r) : "f"(x)); return r; }
__device__ __forceinline__ void wg_fence() { asm volatile("wgmma.fence.sync.aligned;" ::: "memory"); }
__device__ __forceinline__ void wg_commit() { asm volatile("wgmma.commit_group.sync.aligned;" ::: "memory"); }
template <int N> __device__ __forceinline__ void wg_wait() { asm volatile("wgmma.wait_group.sync.aligned %0;" ::"n"(N) : "memory"); }
__device__ __forceinline__ uint64_t mkdesc(uint32_t a, uint32_t lbo, uint32_t sbo, uint32_t sw) {
    return (uint64_t)((a & 0x3FFFF) >> 4) | ((uint64_t)(lbo >> 4) << 16) | ((uint64_t)(sbo >> 4) << 32) | ((uint64_t)sw << 62);
}
#define F4(d, i) "+f"(d[i]), "+f"(d[i + 1]), "+f"(d[i + 2]), "+f"(d[i + 3])
#define F8(d, i) F4(d, i), F4(d, i + 4)
#define F16(d, i) F8(d, i), F8(d, i + 8)
template <int OFF, int SC> __device__ __forceinline__ void wg_n32_x(float* d, const uint32_t* a, uint32_t lo) {
    asm volatile("{.reg .pred p; .reg .b32 l; .reg .b64 q; setp.ne.b32 p,%22,0; add.u32 l,%20,%21; mov.b64 q,{l,8};\n"
                 "wgmma.mma_async.sync.aligned.m64n32k16.f32.f16.f16 "
                 "{%0,%1,%2,%3,%4,%5,%6,%7,%8,%9,%10,%11,%12,%13,%14,%15},{%16,%17,%18,%19},q,p,1,1,0;}"
                 : F16(d, 0) : "r"(a[0]), "r"(a[1]), "r"(a[2]), "r"(a[3]), "r"(lo), "n"(OFF), "n"(SC));
}
__device__ __forceinline__ void wg_n128_rs(float* d, const uint32_t* a, uint64_t db, int sc) {
    asm volatile("{.reg .pred p; setp.ne.b32 p,%69,0; wgmma.mma_async.sync.aligned.m64n128k16.f32.f16.f16 "
                 "{%0,%1,%2,%3,%4,%5,%6,%7,%8,%9,%10,%11,%12,%13,%14,%15,%16,%17,%18,%19,%20,%21,%22,%23,%24,%25,%26,%27,%28,%29,%30,%31,"
                 "%32,%33,%34,%35,%36,%37,%38,%39,%40,%41,%42,%43,%44,%45,%46,%47,%48,%49,%50,%51,%52,%53,%54,%55,%56,%57,%58,%59,%60,%61,%62,%63},"
                 "{%64,%65,%66,%67},%68,p,1,1,0;}"
                 : F16(d, 0), F16(d, 16), F16(d, 32), F16(d, 48) : "r"(a[0]), "r"(a[1]), "r"(a[2]), "r"(a[3]), "l"(db), "r"(sc));
}
#define N80_REGS "{%0,%1,%2,%3,%4,%5,%6,%7,%8,%9,%10,%11,%12,%13,%14,%15,%16,%17,%18,%19,%20,%21,%22,%23,%24,%25,%26,%27,%28,%29,%30,%31,%32,%33,%34,%35,%36,%37,%38,%39}"
__device__ __forceinline__ void wg_n80_ss(float* d, uint64_t da, uint64_t db, int sc) {
    asm volatile("{.reg .pred p; setp.ne.b32 p,%42,0; wgmma.mma_async.sync.aligned.m64n80k16.f32.bf16.bf16 " N80_REGS ",%40,%41,p,1,1,0,0;}"
                 : F16(d, 0), F16(d, 16), F8(d, 32) : "l"(da), "l"(db), "r"(sc));
}
__device__ __forceinline__ void wg_n88_ss(float* d, uint64_t da, uint64_t db, int sc) {
    asm volatile("{.reg .pred p; setp.ne.b32 p,%46,0; wgmma.mma_async.sync.aligned.m64n88k16.f32.f16.f16 "
                 "{%0,%1,%2,%3,%4,%5,%6,%7,%8,%9,%10,%11,%12,%13,%14,%15,%16,%17,%18,%19,%20,%21,%22,%23,%24,%25,%26,%27,%28,%29,%30,%31,"
                 "%32,%33,%34,%35,%36,%37,%38,%39,%40,%41,%42,%43},%44,%45,p,1,1,0,0;}"
                 : F16(d, 0), F16(d, 16), F8(d, 32), F4(d, 40) : "l"(da), "l"(db), "r"(sc));
}
__device__ __forceinline__ void wg_n48_ss_ta(float* d, uint64_t da, uint64_t db, int sc) {
    asm volatile("{.reg .pred p; setp.ne.b32 p,%26,0; wgmma.mma_async.sync.aligned.m64n48k16.f32.f16.f16 "
                 "{%0,%1,%2,%3,%4,%5,%6,%7,%8,%9,%10,%11,%12,%13,%14,%15,%16,%17,%18,%19,%20,%21,%22,%23},%24,%25,p,1,1,1,0;}"
                 : F16(d, 0), F8(d, 16) : "l"(da), "l"(db), "r"(sc));
}
template <int TA> __device__ __forceinline__ void wg_n64_ss_tb(float* d, uint64_t da, uint64_t db, int sc) {
    asm volatile("{.reg .pred p; setp.ne.b32 p,%34,0; wgmma.mma_async.sync.aligned.m64n64k16.f32.f16.f16 "
                 "{%0,%1,%2,%3,%4,%5,%6,%7,%8,%9,%10,%11,%12,%13,%14,%15,%16,%17,%18,%19,%20,%21,%22,%23,%24,%25,%26,%27,%28,%29,%30,%31},"
                 "%32,%33,p,1,1,%35,1;}"
                 : F16(d, 0), F16(d, 16) : "l"(da), "l"(db), "r"(sc), "n"(TA));
}
__device__ __forceinline__ void pdl_wait() { asm volatile("griddepcontrol.wait;" ::: "memory"); }
__device__ __forceinline__ void pdl_go() { asm volatile("griddepcontrol.launch_dependents;" ::: "memory"); }
__device__ __forceinline__ float cos640(float p) {
    const float q = fmaf(p, 0.0015625f, 12582912.f) - 12582912.f;
    return __cosf(fmaf(q, -640.f, p) * 0.009817477042468103f);
}
__device__ __forceinline__ uint4 cos_row8(float p0, float step, float amp = 1.f) {
    float v[8];
    const float k = 2.f * cos640(step);
    v[0] = amp * cos640(p0); v[1] = amp * cos640(p0 + step);
#pragma unroll
    for (int i = 2; i < 8; i++) v[i] = fmaf(k, v[i - 1], -v[i - 2]);
    return make_uint4(pack_h(v[0], v[1]), pack_h(v[2], v[3]), pack_h(v[4], v[5]), pack_h(v[6], v[7]));
}
__device__ __forceinline__ float wfilter_max(int lane) {
    float m = fmaxf(fmaxf(g_wmax[lane], g_wmax[lane + 32]), fmaxf(g_wmax[lane + 64], g_wmax[lane + 96]));
    return __uint_as_float(__reduce_max_sync(~0u, __float_as_uint(m)));
}
__device__ __forceinline__ unsigned ld_acquire(const Flag* p) { unsigned v; asm volatile("ld.acquire.gpu.global.u32 %0,[%1];" : "=r"(v) : "l"(p) : "memory"); return v; }
#define POLL_NS 200
template <int NS = POLL_NS> __device__ __forceinline__ void wait_flag(const Flag* p, unsigned v) {
    if (ld_acquire(p) >= v) return;
    unsigned x;
    int lim = 0;
    do {
        __nanosleep(NS);
        asm volatile("ld.relaxed.gpu.global.u32 %0,[%1];" : "=r"(x) : "l"(p) : "memory");
    } while (x < v && ++lim < SPIN_LIM);
    ld_acquire(p);
}
__device__ __forceinline__ void prefetch_l2(const void* p, int bytes) { asm volatile("cp.async.bulk.prefetch.L2.global [%0],%1;" ::"l"(p), "r"(bytes) : "memory"); }
__device__ __forceinline__ void red_release(Flag* p) { asm volatile("red.release.gpu.global.add.u32 [%0],1;" ::"l"(p) : "memory"); }
__device__ __forceinline__ void red_relaxed(Flag* p) { asm volatile("red.relaxed.gpu.global.add.u32 [%0],1;" ::"l"(p) : "memory"); }
__device__ __forceinline__ void red_h8(void* p, uint32_t a, uint32_t b, uint32_t c, uint32_t d) {
    asm volatile("red.relaxed.gpu.global.add.noftz.v4.f16x2 [%0],{%1,%2,%3,%4};" ::"l"(p), "r"(a), "r"(b), "r"(c), "r"(d) : "memory");
}
__device__ __forceinline__ float pow2_scale(float bound, int top, float* inv) {
    int e = (int)((__float_as_uint(bound) >> 23) & 0xff) - 126;
    int k = top - e;
    k = max(-100, min(100, k));
    *inv = __uint_as_float((uint32_t)(127 - k) << 23);
    return __uint_as_float((uint32_t)(127 + k) << 23);
}
__device__ __forceinline__ char* red_base() { return (char*)(((uintptr_t)g_redraw + 32767) & ~(uintptr_t)32767); }

__device__ __forceinline__ void setup_a(char* sm, const int b, const bf16* __restrict__ wr, const bf16* __restrict__ wi) {
    const int tid = threadIdx.x, lane = tid & 31;
    const uint32_t sb = smem_u32(sm);
    auto row_byte = [&](int q) { return ((b >> 2) + 32 * ((q >> 1) * 8 + 2 * (b & 3) + (q & 1))) * 642; };
#pragma unroll 1
    for (int r = tid >> 5; r < 32; r += 8) {
        const char* src = (const char*)(r < 16 ? wr : wi) + (row_byte(r & 15) & ~15);
        cp_async16(sb + r * 672 + lane * 16, src + lane * 16);
        if (lane < 9) cp_async16(sb + r * 672 + 512 + lane * 16, src + 512 + lane * 16);
    }
    ((uint4*)g_stat)[b * 256 + tid] = make_uint4(0, 0, 0, 0);
    if (tid < 2 * (NFLAG / 128)) ((uint4*)(g_flag + b * (NFLAG / 128) + (tid >> 1)))[tid & 1] = make_uint4(0, 0, 0, 0);
    if (tid < 12) {
        const int i = b * 12 + tid;
        const int f = ((i >> 4) & 3) * 8 + (i & 7), im = (i >> 3) & 1, part = (i >> 8) & 1;
        ((uint4*)g_ctab)[i] = cos_row8((float)(i < 1024 ? (i >> 7) * 80 * (i & 63) + ((i & 64) ? 480 : 0) : ((i >> 6) & 3) * 160 * f + (im == part ? 0 : im ? 160 : 480)),
                                       (float)(i < 1024 ? 10 * (i & 63) : 20 * f), i < 1024 ? 0.125f : 0.17677669529663687f);
    }
    asm volatile("cp.async.wait_all;" ::: "memory");
    __syncthreads();
    const int q0 = (tid & 3) * 4;
    const char* rp[4];
#pragma unroll
    for (int u = 0; u < 4; u++) rp[u] = sm + (q0 + u) * 672 + (row_byte(q0 + u) & 15);
    uint32_t mx = 0;
#pragma unroll 2
    for (int c = tid >> 2; c < 321; c += 64) {
        uint32_t v[4];
#pragma unroll
        for (int u = 0; u < 4; u++) {
            v[u] = ((const unsigned short*)rp[u])[c] | ((uint32_t)((const unsigned short*)(rp[u] + 16 * 672))[c] << 16);
            mx = __vmaxu2(mx, v[u] & 0x7fff7fffu);
        }
        ((uint4*)g_Wf)[(size_t)c * 512 + b * 4 + ((tid ^ (b >> 1)) & 3)] = make_uint4(v[0], v[1], v[2], v[3]);
    }
    mx = __reduce_max_sync(~0u, max(mx & 0xffffu, mx >> 16));
    __syncthreads();
    if (lane == 0) ((uint32_t*)sm)[tid >> 5] = mx;
    __syncthreads();
    if (tid < 32) {
        mx = __reduce_max_sync(~0u, ((uint32_t*)sm)[lane & 7]);
        if (tid == 0) g_wmax[b] = __uint_as_float(mx << 16);
    }
}
__device__ __forceinline__ void setup_b(const int b, const bf16* __restrict__ mem0) {
    const int tid = threadIdx.x;
    uint4* z = (uint4*)red_base();
    if (b < 3) {
        const int w = tid >> 5, lane = tid & 31, p = b * 2 + ((w >> 1) & 1), odd = w & 1;
        uint32_t mx = 0;
#pragma unroll 4
        for (int i = lane; i < 640; i += 32) {
            const uint4 u = ((const uint4*)mem0)[i];
            mx = __vmaxu2(__vmaxu2(mx, u.x & 0x7fff7fffu), __vmaxu2(__vmaxu2(u.y & 0x7fff7fffu, u.z & 0x7fff7fffu), u.w & 0x7fff7fffu));
        }
        float inv, v[7];
        const float sc = pow2_scale(__uint_as_float(__reduce_max_sync(~0u, max(mx & 0xffffu, mx >> 16)) << 16), 14, &inv);
        if (tid == 0) g_invM0 = inv;
#pragma unroll
        for (int j = 0; j < 7; j++) {
            const int r = p * 56 + (j < 6 ? odd * 32 + (j >> 1) * 8 : 24) + (lane >> 2), mr = 2 * (lane & 3) + (j < 6 ? (j & 1) : odd);
            v[j] = r < 320 ? __bfloat162float(mem0[mr * 640 + (w >> 2) * 320 + r]) * sc : 0.f;
        }
        const int off = w * 2048 + (lane >> 4) * 1024 + ((lane >> 3) & 1) * 256 + (lane & 7) * 16 + (b == 2 ? (w >> 1) * 4096 + 128 : b * 16384);
        const uint4 u = make_uint4(pack_h(v[0], v[1]), pack_h(v[2], v[3]), pack_h(v[4], v[5]), pack_h(v[6], 32.f));
        z[off >> 4] = u; z[65536 + (off >> 4)] = u;
    }
}

#define SU_PAD 40960
constexpr int SU_SMEM = SU_PAD;
__global__ void __launch_bounds__(256, 4) k_setup(const bf16* __restrict__ wr, const bf16* __restrict__ wi, const bf16* __restrict__ mem0) {
    extern __shared__ __align__(1024) char sm[];
    TL(0);
    if (blockIdx.x >= 128) setup_b(blockIdx.x - 128, mem0);
    else setup_a(sm, blockIdx.x, wr, wi);
    __syncthreads();
    if (threadIdx.x == 0) red_release(g_ready);
    TL(1);
}
__device__ __forceinline__ float weight_scale(int h, int ty, float* inv) { return pow2_scale(__ldcg(g_wmx + h * 3 + ty), 6, inv); }

#define STR_(x) #x
#define STR(x) STR_(x)
#define RF_U 1
constexpr int RF_A = 22 * 2816, RF_X = RF_A + 22 * 1024, RF_BAR = RF_X + 64 * 1344, RF_SMEM = RF_BAR + 80;
__device__ __align__(1024) char g_rtab[4 * RF_A];
template <int first> __global__ void __cluster_dims__(2, 1, 1) __launch_bounds__(256, 2) k_rowf(const bf16* x) {
    extern __shared__ __align__(1024) char sm[];
    TL(first ? 2 : 16);
    const int tid = threadIdx.x, w = tid >> 5, lane = tid & 31, g = lane >> 2, t = lane & 3;
    if (blockIdx.x >= 128) { __nanosleep(2500); return; }
    const int a = first ? blockIdx.x >> 2 : 31 - (blockIdx.x >> 2), gq = blockIdx.x & 3;
    if (!first) pdl_go();
    const uint32_t sb = smem_u32(sm), mb = sb + RF_BAR + w * 8;
    if (lane == 0) {
        mbar_init(mb, 1);
        asm volatile("fence.mbarrier_init.release.cluster;" ::: "memory");
        if (!first && w == 0) {
            mbar_init(sb + RF_BAR + 64, 1);
            fence_async_smem();
            mbar_expect(sb + RF_BAR + 64, RF_A);
            bulk_g2s(sb, g_rtab + gq * RF_A, RF_A, sb + RF_BAR + 64);
        }
    }
    if (lane == 0) mbar_expect(mb, 8 * 1280);
    __syncwarp();
    asm volatile("barrier.cluster.arrive.relaxed.aligned; barrier.cluster.wait.aligned;" ::: "memory");
    if (!first) {
        if (lane == 0) wait_flag<100>(g_flag + F_R + a, a < 28 ? 32 : 192);
        __syncwarp();
        fence_async_glb();
    }
    TL(first ? 3 : 17);
    if (lane < 4)
        asm volatile("cp.async.bulk.shared::cluster.global.mbarrier::complete_tx::bytes.multicast::cluster [%0],[%1],1280,[%2],%3;"
                     ::"r"(sb + RF_X + (w * 8 + (gq & 1) * 4 + lane) * 1344), "l"(x + (size_t)(a * 64 + w * 8 + (gq & 1) * 4 + lane) * 640), "r"(mb),
                     "h"((unsigned short)3) : "memory");
    __syncwarp();
    if (first) pdl_go();
    if (first) {
#pragma unroll 3
        for (int id = tid; id < 22 * 176; id += 256) {
            const int kg = id / 176, n = id - kg * 176;
            const float c = (float)(2 * n + (gq & 1));
            *(uint4*)(sm + id * 16) = cos_row8(fmaf((float)(kg * 8), c, (float)((gq & 2) * 80)), c, 0.03952847075210474f);
        }
    }
    mbar_wait(mb, 0);
    const uint32_t row = sb + RF_X + (w * 8 + g) * 1344;
    float st[4][4] = {};
#pragma unroll 1
    for (int i = 0; i < 20; i += 4) {
        uint32_t u[4][4];
#pragma unroll
        for (int q = 0; q < 4; q++) lds128(u[q], row + (4 * (i + q) + t) * 16);
#pragma unroll
        for (int q = 0; q < 4; q++) {
            mma_bf(st[(q & 1) * 2], u[q][0], 0x3f803f80u, u[q][1], 0x3f803f80u, u[q][0], u[q][1]);
            mma_bf(st[(q & 1) * 2 + 1], u[q][2], 0x3f803f80u, u[q][3], 0x3f803f80u, u[q][2], u[q][3]);
        }
    }
#pragma unroll
    for (int q = 0; q < 4; q++) { st[0][q] += st[2][q]; st[1][q] += st[3][q]; }
    const float sq = __shfl_sync(~0u, (g & 1) ? st[0][1] + st[1][1] : st[0][0] + st[1][0], g * 4 + (g >> 1));
    const float mean = __shfl_sync(~0u, (g & 1) ? st[0][3] + st[1][3] : st[0][2] + st[1][2], g * 4 + (g >> 1)) * (1.f / 640.f);
    const float r = rsqrtf(fmaxf(fmaf(-mean, mean, sq * (1.f / 640.f)), 0.f) + 1e-5f), off = gq == 0 ? -4.f * mean * r : 0.f;
    const float r1 = (gq == 1 || gq == 2) ? -r : r, r2 = (gq & 1) ? -r : r, r3 = gq >= 2 ? -r : r;
    const uint32_t aa = sb + RF_A + w * 128 + g * 16;
    auto el = [&](int d) { unsigned short v; asm volatile("ld.shared.u16 %0,[%1];" : "=h"(v) : "r"(row + d * 2)); return __uint_as_float((uint32_t)v << 16); };
_Pragma(STR(unroll RF_U))
    for (int i = 0; i < 5; i++) {
        const int ch = t + 4 * i;
        uint32_t u[4][4];
        lds128(u[0], row + ch * 16); lds128(u[1], row + (39 - ch) * 16); lds128(u[2], row + (40 + ch) * 16); lds128(u[3], row + (79 - ch) * 16);
        const float nb0 = el(320 - 8 * ch), nb1 = el(ch ? 640 - 8 * ch : 0);
        float o[8];
#pragma unroll
        for (int q = 0; q < 8; q++) {
            const int m = (8 - q) >> 1;
            const float e0 = (q & 1) ? bf_hi(u[0][q >> 1]) : bf_lo(u[0][q >> 1]), e2 = (q & 1) ? bf_hi(u[2][q >> 1]) : bf_lo(u[2][q >> 1]);
            const float e1 = q == 0 ? nb0 : (q & 1) ? bf_hi(u[1][m & 3]) : bf_lo(u[1][m & 3]), e3 = q == 0 ? nb1 : (q & 1) ? bf_hi(u[3][m & 3]) : bf_lo(u[3][m & 3]);
            o[q] = fmaf(e3, r3, fmaf(e2, r2, fmaf(e1, r1, fmaf(e0, r, off))));
        }
        if (ch == 0) o[0] *= 0.5f;
        sts128(aa + ch * 1024, pack_h(o[0], o[1]), pack_h(o[2], o[3]), pack_h(o[4], o[5]), pack_h(o[6], o[7]));
    }
    if (t < 2) sts128(aa + (20 + t) * 1024, t == 0 ? pack_h(fmaf(el(480), r2, fmaf(el(160), r, 0.5f * off)), 0.f) : 0u, 0u, 0u, 0u);
    fence_async_smem();
    __syncthreads();
    if (!first) mbar_wait(sb + RF_BAR + 64, 0);
    else if (a == 0 && tid == 0) { bulk_s2g(g_rtab + gq * RF_A, sb, RF_A); bulk_commit(); }
    const int wg = w >> 2;
    float acc[44];
    uint64_t da = mkdesc(sb + RF_A, 1024, 128, 0), db = mkdesc(sb + wg * 1408, 2816, 128, 0);
    wg_fence();
#pragma unroll 1
    for (int k = 0; k < 11; k++) { wg_n88_ss(acc, da, db, k); da += 128; db += 352; }
    wg_commit(); wg_wait<0>();
    const uint32_t stg = sb + RF_X + wg * 96 * 144;
#pragma unroll
    for (int j = 0; j < 12; j += 2) {
        const int m = lane >> 3, j1 = j < 10 ? j + 1 : j;
        stsm4t(stg + ((j + (m >> 1)) * 8 + (lane & 7)) * 144 + ((w & 3) * 16 + (m & 1) * 8) * 2, pack_h(acc[j * 4], acc[j * 4 + 1]),
               pack_h(acc[j * 4 + 2], acc[j * 4 + 3]), pack_h(acc[j1 * 4], acc[j1 * 4 + 1]), pack_h(acc[j1 * 4 + 2], acc[j1 * 4 + 3]));
    }
    bar_sync(1 + wg, 128);
#pragma unroll 3
    for (int rr = (tid & 127) >> 3; rr < 88; rr += 16) {
        const int ch = tid & 7, c = 2 * (wg * 88 + rr) + (gq & 1);
        if (c <= 320 - (gq >> 1) && (c | (gq ^ 2))) {
            uint32_t u[4];
            lds128(u, stg + rr * 144 + ch * 16);
            ((uint4*)g_UT)[((size_t)(c == 320 ? 1 : 2 * c + (gq >> 1)) * 32 + a) * 8 + (ch ^ (a & 7))] = make_uint4(u[0], u[1], u[2], u[3]);
        }
    }
    if (first && blockIdx.x < 4 && tid == 0) asm volatile("cp.async.bulk.wait_group.read 0;" ::: "memory");
    TL(first ? 4 : 18);
}

constexpr int GST = 4, GSTB = 32768 + 20480, GNC = 32;
constexpr int G_BAR = GST * GSTB + 3072;
#define GPACE 1000
#define GPACE2 650
__device__ __forceinline__ void oproj_load(const uint32_t sb, const int op, const int mb, const int nb, const int c0, const uint32_t pace) {
    const int by = op == 2 ? 20480 : 16384;
    const char* src = op == 2 ? (const char*)g_wot + (size_t)nb * GNC * 20480 : (const char*)g_O + (size_t)(2 * mb + op) * GNC * 16384;
    uint32_t t0 = clock32() - pace + op * (pace / 3);
#pragma unroll 1
    for (int c = c0; c < c0 + GNC; c++, src += by) {
        const int st = c % GST;
        if (c >= GST) mbar_wait(sb + G_BAR + (GST + st) * 8, ((c / GST) - 1) & 1);
        while (clock32() - t0 < pace) {}
        t0 = clock32();
        const int by_ = by;
        mbar_expect(sb + G_BAR + st * 8, by_);
        if (op == 2) bulk_g2s(sb + st * GSTB + 32768, src, by_, sb + G_BAR + st * 8);
        else bulk_g2s_last(sb + st * GSTB + op * 16384, src, by_, sb + G_BAR + st * 8);
    }
}
__device__ __forceinline__ void oproj_mma(const uint32_t sb, const int mb, const int nb, const int c0, const bf16* res, bf16* out, const int layer) {
    const int w = threadIdx.x >> 5, lane = threadIdx.x & 31, wg = w >> 2;
    float acc[40];
    uint4 rv[5];
#pragma unroll 1
    for (int c = c0; c < c0 + GNC; c++) {
        const int st = c % GST;
        mbar_wait(sb + G_BAR + st * 8, (c / GST) & 1);
        const uint32_t d = sb + st * GSTB;
        wg_fence();
#pragma unroll
        for (int k = 0; k < 8; k++)
            wg_n80_ss(acc, mkdesc(d + wg * 16384 + k * 2048, 1024, 128, 0), mkdesc(d + 32768 + k * 2560, 1280, 128, 0), (c - c0) | k);
        wg_commit();
        if (c > c0) {
            wg_wait<1>();
            if (lane == 0) mbar_arrive(sb + G_BAR + (GST + (c - 1) % GST) * 8);
        }
    }
#pragma unroll
    for (int i = 0; i < 5; i++) {
        const int id = i * 32 + lane, r = id / 10;
        rv[i] = __ldcg((const uint4*)res + (size_t)(mb * 128 + w * 16 + r) * 80 + nb * 10 + id - r * 10);
    }
    wg_wait<0>();
    bar_sync(5, 256);
    const uint32_t stg = sb + (GST - 1) * GSTB + w * 16 * 176;
#pragma unroll
    for (int j = 0; j < 5; j++)
        stsm4(stg + (lane & 15) * 176 + (2 * j + (lane >> 4)) * 16, pack_bf(acc[j * 8], acc[j * 8 + 1]), pack_bf(acc[j * 8 + 2], acc[j * 8 + 3]),
              pack_bf(acc[j * 8 + 4], acc[j * 8 + 5]), pack_bf(acc[j * 8 + 6], acc[j * 8 + 7]));
    __syncwarp();
#pragma unroll
    for (int i = 0; i < 5; i++) {
        const int id = i * 32 + lane, r = id / 10, ch = id - r * 10;
        uint32_t y[4];
        lds128(y, stg + r * 176 + ch * 16);
        ((uint4*)out)[(size_t)(mb * 128 + w * 16 + r) * 80 + nb * 10 + ch] = add_bf8(rv[i], y);
    }
    fence_async_smem();
    __syncwarp();
    if (lane == 0) {
        mbar_arrive(sb + G_BAR + (2 * GST - 1) * 8);
        if (layer == 0) red_release(g_flag + F_R + 2 * mb + wg);
    }
}

__global__ void __launch_bounds__(128, 4) k_col(const int first) {
    __shared__ __align__(1024) char sz[8192];
    __shared__ __align__(1024) char stab[24576];
    __shared__ __align__(1024) char swf[8192];
    __shared__ __align__(8) uint64_t bar[2];
    const int tid = threadIdx.x, wl = tid >> 5, lane = tid & 31, g = lane >> 2, t = lane & 3;
    const int c = blockIdx.x;
    TL(first ? 5 : 19);
    const bool realc = c == 0 || c == 320;
    const uint32_t z = smem_u32(sz), b2 = smem_u32(stab), a1 = b2 + 16384, wf = smem_u32(swf), mb = smem_u32(bar);
    if (tid == 0) { mbar_init(mb, 1); mbar_init(mb + 8, 1); fence_async_smem(); }
    if (realc) {
        for (int i = tid; i < 256; i += 128) sts128(z + 4096 + i * 16, 0, 0, 0, 0);
        fence_async_smem();
    }
    const int k1 = wl * 8 + g;
    float tc[16], ts[16];
#pragma unroll
    for (int j = 0; j < 16; j++) {
        const int p = ((j >> 1) * 8 + 2 * t + (j & 1)) * k1;
        __sincosf((float)(p - 1024) * 0.003067961575771282f, &ts[j], &tc[j]);
        ts[j] = -ts[j]; tc[j] = -tc[j];
    }
    if (first && tid == 32) { wait_flag<400>(g_ready, NSETUP); fence_async_glb(); }
    __syncthreads();
    if (tid == 32) {
        mbar_expect(mb + 8, 24576 + 8192);
        bulk_g2s(b2, g_ctab, 24576, mb + 8);
        bulk_g2s(wf, g_Wf + (size_t)c * 2048, 8192, mb + 8);
    }
    float inv;
    const float wsc = pow2_scale(wfilter_max(lane), 0, &inv) * (realc ? 0.5f : 1.f);
    pdl_wait();
    TL(first ? 6 : 20);
    if (tid == 0) {
        const int by = realc ? 4096 : 8192;
        mbar_expect(mb, by);
        bulk_g2s_last(z, (const char*)g_UT + (size_t)(c == 320 ? 1 : 2 * c) * 4096, by, mb);
    }
    pdl_go();
    mbar_wait(mb + 8, 0);
    mbar_wait(mb, 0);
    float d[64];
    uint32_t a[4][4];
    wg_fence();
#pragma unroll
    for (int ks = 0; ks < 4; ks++) wg_n64_ss_tb<0>(d, mkdesc(a1 + ks * 2048, 1024, 128, 0), mkdesc(z + ks * 2048, 1024, 1024, 1), ks);
    wg_commit(); wg_wait<0>();
#pragma unroll
    for (int j = 0; j < 8; j++) {
        float yr[2], yi[2];
#pragma unroll
        for (int e = 0; e < 2; e++) {
            const float re = d[j * 4 + e], im = d[j * 4 + 2 + e], cc = tc[j * 2 + e], ss = ts[j * 2 + e];
            yr[e] = re * cc + im * ss; yi[e] = im * cc - re * ss;
        }
        a[j >> 1][(j & 1) * 2] = pack_h(yr[0], yr[1]); a[j >> 1][(j & 1) * 2 + 1] = pack_h(yi[0], yi[1]);
    }
    wg_fence();
#pragma unroll
    for (int ks = 0; ks < 4; ks++) wg_n128_rs(d, a[ks], mkdesc(b2 + ks * 4096, 2048, 128, 0), ks);
    wg_commit(); wg_wait<0>();
#pragma unroll
    for (int q = 0; q < 4; q++) {
        uint32_t wv[4];
        lds128(wv, wf + tid * 64 + ((q ^ (tid >> 1)) & 3) * 16);
#pragma unroll
        for (int jj = 0; jj < 2; jj++) {
            const int j = 2 * q + jj;
            float yr[2], yi[2];
#pragma unroll
            for (int e = 0; e < 2; e++) {
                const float xr = d[j * 4 + e] + d[32 + j * 4 + 2 + e], xi = d[j * 4 + 2 + e] - d[32 + j * 4 + e];
                const float fr = bf_lo(wv[jj * 2 + e]) * wsc, fi = bf_hi(wv[jj * 2 + e]) * wsc;
                yr[e] = xr * fr - xi * fi; yi[e] = xr * fi + xi * fr;
            }
            a[q][jj * 2] = pack_h(yr[0], yr[1]); a[q][jj * 2 + 1] = pack_h(yi[0], yi[1]);
        }
    }
    wg_fence();
#pragma unroll
    for (int ks = 0; ks < 4; ks++) wg_n128_rs(d, a[ks], mkdesc(b2 + ks * 4096, 2048, 128, 0), ks);
    wg_commit(); wg_wait<0>();
#pragma unroll
    for (int j = 0; j < 8; j++) {
        float yr[2], yi[2];
#pragma unroll
        for (int e = 0; e < 2; e++) {
            const float vr = d[j * 4 + e] - d[32 + j * 4 + 2 + e], vi = d[j * 4 + 2 + e] + d[32 + j * 4 + e];
            const float cc = tc[j * 2 + e], ss = ts[j * 2 + e];
            yr[e] = vr * cc - vi * ss; yi[e] = vi * cc + vr * ss;
        }
        a[j >> 1][(j & 1) * 2] = pack_h(yr[0], yr[1]); a[j >> 1][(j & 1) * 2 + 1] = pack_h(yi[0], yi[1]);
    }
    __syncthreads();
    const int mm = lane >> 3, rr = lane & 7;
    const uint32_t rowo = (wl * 16 + (mm & 1) * 8 + rr) * 128;
#pragma unroll
    for (int q = 0; q < 4; q++) stsm4(z + rowo + (((2 * q + (mm >> 1)) ^ rr) << 4), a[q][0], a[q][1], a[q][2], a[q][3]);
    fence_async_smem();
    __syncthreads();
    wg_fence();
#pragma unroll
    for (int ks = 0; ks < 4; ks++) wg_n64_ss_tb<1>(d, mkdesc(a1 + ks * 256, 128, 1024, 0), mkdesc(z + ks * 2048, 1024, 1024, 1), ks);
    wg_commit(); wg_wait<0>();
#pragma unroll
    for (int q = 0; q < 4; q++)
        stsm4(wf + rowo + (((2 * q + (mm >> 1)) ^ rr) << 4), pack_h(d[q * 8], d[q * 8 + 1]), pack_h(d[q * 8 + 2], d[q * 8 + 3]),
              pack_h(d[q * 8 + 4], d[q * 8 + 5]), pack_h(d[q * 8 + 6], d[q * 8 + 7]));
    __syncwarp();
    if (!(realc && wl >= 2)) {
        const int kk = c == 320 ? 320 : (c & 1) * 160 + (c >> 1) + (wl >> 1) * 320;
#pragma unroll
        for (int i = 0; i < 4; i++) {
            const int r = wl * 16 + i * 4 + (lane >> 3), ch = lane & 7;
            uint32_t v[4];
            lds128(v, wf + r * 128 + ((ch ^ (r & 7)) << 4));
            ((uint4*)g_YT)[((size_t)(r & 31) * 640 + kk) * 8 + (ch ^ (kk & 7))] = make_uint4(v[0], v[1], v[2], v[3]);
        }
    }
    TL(first ? 7 : 21);
}

constexpr int O_XS = 0;
constexpr int O_MS = 81920;
constexpr int O_QKP = O_MS + 10752;
constexpr int O_VM = O_QKP + 4096;
constexpr int O_SC = O_VM + 4096;
constexpr int O_OS = O_SC + 1536;
constexpr int O_XCH = O_OS + 2048;
constexpr int O_SUM = O_XCH + 8192;
constexpr int O_MX = O_SUM + 256;
constexpr int O_STG = O_MS + 65536 - 8192;
static_assert(O_STG - 16384 >= O_MX + 1024, "shared-memory map");
constexpr int O_WO = O_STG + 16384;
constexpr int O_SCL = O_WO + 65536;
constexpr int O_BAR = O_SCL + 64;
constexpr int B_XF = O_BAR, B_S = O_BAR + 16, B_GO = O_BAR + 24, B_VH = O_BAR + 88, B_VX = O_BAR + 32, B_STG = O_BAR + 48, B_FREE = O_BAR + 72;
constexpr int T_FA = O_BAR + 96, T_EA = T_FA + 32, T_FB = T_EA + 32, T_EB = T_FB + 56, T_RED = T_EB + 32;
constexpr int O_WMX = O_BAR + 512, B_W = O_BAR + 64;
constexpr int O_LAST = (O_WMX + 192 + 1023) / 1024 * 1024;
constexpr int CH_SMEM = O_LAST + 8192;
static_assert(O_WO == 19 * 8192, "weight staging");
__device__ __forceinline__ uint32_t tail_b(int c) { return c % 7 < 4 ? O_XS + (c % 7) * 20480 : O_WO + (c % 7 - 4) * 20480; }
__device__ __forceinline__ int s_tx(int c) { return c == 2 ? 2 * 768 : 768 + 2048; }

#define NPERM 1
#define NWO0 1
#define NWO0B 6
#define NWO1 6
#define AUNR 2
#define TDELAY 300
#define WDEPTH 6
#define RDELAY 550

#define STAMP(i)

#define NTA 20
#define NTB 28
template <int LO, int HI>
__device__ __forceinline__ void tok_issue(const uint32_t (&A0)[20][4], const uint32_t (&A1)[20][4], float (&b0)[16], float (&b1)[16], uint32_t xd,
                                          const uint32_t zero) {
    if (LO == 0) wg_fence();
    sfor<HI - LO>([&](auto I) {
        constexpr int i = LO + I;
        if constexpr (i < 20) wg_n32_x<i * 64, i>(b0, A0[i], xd); else wg_n32_x<(i - 20) * 64, i - 20>(b1, A1[i - 20], xd + zero);
        if constexpr (i == 19 || i == NTB - 1 || i == 39) wg_commit();
    });
}
__device__ __forceinline__ void tok_give(const float (&b0)[16], const uint32_t L16, const uint32_t xch0) {
    wg_wait<1>();
    sfor<2>([&](auto I) {
        constexpr int i = I;
        sts128_u<i * 512>(L16, xch0, pack_h(b0[8 * i], b0[8 * i + 1]), pack_h(b0[8 * i + 2], b0[8 * i + 3]), pack_h(b0[8 * i + 4], b0[8 * i + 5]),
                          pack_h(b0[8 * i + 6], b0[8 * i + 7]));
    });
}
__device__ __forceinline__ void tok_finish(float (&b1)[16], const uint32_t (&e)[2][4], const uint32_t L16, const uint32_t dst, const uint32_t idn) {
#pragma unroll
    for (int j = 0; j < 4; j++)
        asm volatile("mma.sync.aligned.m16n8k8.row.col.f32.f16.f16.f32 {%0,%1,%2,%3},{%4,%5},{%6},{%0,%1,%2,%3};"
                     : F4(b1, 4 * j) : "r"(e[j >> 1][(j & 1) * 2]), "r"(e[j >> 1][(j & 1) * 2 + 1]), "r"(idn));
    stsm4_u<0>(L16, dst, pack_bf(b1[0], b1[1]), pack_bf(b1[2], b1[3]), pack_bf(b1[4], b1[5]), pack_bf(b1[6], b1[7]));
    stsm4_u<512>(L16, dst, pack_bf(b1[8], b1[9]), pack_bf(b1[10], b1[11]), pack_bf(b1[12], b1[13]), pack_bf(b1[14], b1[15]));
}
__device__ __forceinline__ uint32_t uni(uint32_t v) { return __shfl_sync(~0u, v, 0); }
__device__ __forceinline__ uint32_t badd(uint32_t a, uint32_t b) { uint32_t r; asm("add.rn.bf16x2 %0,%1,%2;" : "=r"(r) : "r"(a), "r"(b)); return r; }
__device__ __forceinline__ uint32_t bmax(uint32_t a, uint32_t b) { uint32_t r; asm("max.bf16x2 %0,%1,%2;" : "=r"(r) : "r"(a), "r"(b)); return r; }
__device__ __forceinline__ uint32_t babsmax(uint32_t a, uint32_t b) { uint32_t r; asm("max.xorsign.abs.bf16x2 %0,%1,%2;" : "=r"(r) : "r"(a), "r"(b)); return r; }
__device__ __forceinline__ uint32_t habsmax(uint32_t a, uint32_t b) { uint32_t r; asm("max.xorsign.abs.f16x2 %0,%1,%2;" : "=r"(r) : "r"(a), "r"(b)); return r; }

template <int NPF>
__device__ __forceinline__ float mem_out(const uint32_t sb, const uint32_t L16, const uint32_t L8, uint32_t (&wo)[16][4], const uint32_t woa,
                                         char* dst, const bool odd) {
    bar_sync(2, 352);
    float a[4][4];
#pragma unroll
    for (int i = 0; i < 4; i++) a[i][0] = a[i][1] = a[i][2] = a[i][3] = 0.f;
    uint32_t ob[4][4], sm_[2], sc[2];
    sfor<8>([&](auto I) {
        constexpr int i = I;
        if constexpr (!(i & 1)) ldsm4t_u<O_OS + (i >> 1) * 512>(ob[i >> 1], L16, sb);
        if constexpr (i >= NPF) { ldsm4t(wo[i], woa + i * 1024); ldsm4t(wo[8 + i], (woa ^ 32) + i * 1024); }
    });
    lds64_u<O_SUM>(sm_, L8 & 24, sb); lds64(sc, sb + O_SCL);
#pragma unroll
    for (int i = 0; i < 8; i++) {
        mma_bf(a[i & 1], wo[i][0], wo[i][1], wo[i][2], wo[i][3], ob[i >> 1][(i & 1) * 2], ob[i >> 1][(i & 1) * 2 + 1]);
        mma_bf(a[2 + (i & 1)], wo[8 + i][0], wo[8 + i][1], wo[8 + i][2], wo[8 + i][3], ob[i >> 1][(i & 1) * 2], ob[i >> 1][(i & 1) * 2 + 1]);
    }
    const float f0 = rcp(__uint_as_float(sm_[0])) * __uint_as_float(sc[0]), f1 = rcp(__uint_as_float(sm_[1])) * __uint_as_float(sc[0]);
    red_h8(dst, pack_h((a[0][0] + a[1][0]) * f0, (a[0][1] + a[1][1]) * f1), pack_h((a[0][2] + a[1][2]) * f0, (a[0][3] + a[1][3]) * f1),
           pack_h((a[2][0] + a[3][0]) * f0, (a[2][1] + a[3][1]) * f1), pack_h(odd ? (a[2][3] + a[3][3]) * f1 : (a[2][2] + a[3][2]) * f0, 1.f));
    return __uint_as_float(sc[1]);
}

template <int NE, int UNR>
__device__ __forceinline__ void tok_attention(const uint32_t qk, const uint32_t dq, const uint32_t km, const uint32_t dk, const uint32_t vt, const uint32_t vm,
                                              const int e0, const int mi, const int lane, const int seg, const int h, const float iqk, const float iv) {
    const int g = lane >> 2, t = lane & 3;
    float s[6][4];
#pragma unroll
    for (int i = 0; i < 6; i++) s[i][0] = s[i][1] = s[i][2] = s[i][3] = 0.f;
#pragma unroll UNR
    for (int e = 0; e < 8; e++) {
        uint32_t q[4], k[4];
        ldsm4t(q, qk + (e >> 2) * dq + (e & 3) * 1024 + mi * 512);
        ldsm4t(k, km + (e >> 2) * dk + (e & 3) * 512);
        mma_bf(s[4], q[0], q[2], q[1], q[3], k[0], k[1]);
        mma_bf(s[5], q[0], q[2], q[1], q[3], k[2], k[3]);
        ldsm4t(k, qk + (e >> 2) * dq + 4096 + (e & 3) * 1024);
        mma_bf(s[0], q[0], q[2], q[1], q[3], k[0], k[1]);
        mma_bf(s[1], q[0], q[2], q[1], q[3], k[2], k[3]);
        if (mi) {
            ldsm4t(k, qk + (e >> 2) * dq + 4096 + (e & 3) * 1024 + 512);
            mma_bf(s[2], q[0], q[2], q[1], q[3], k[0], k[1]);
            mma_bf(s[3], q[0], q[2], q[1], q[3], k[2], k[3]);
        }
    }
#pragma unroll
    for (int q = 0; q < 4; q++) s[4][q] += s[5][q];
    const float sl = iqk * (0.08838834764831845f * 1.4426950408889634f);
    float mx[2] = {-3.0e38f, -3.0e38f};
#pragma unroll
    for (int i = 0; i < 5; i++)
#pragma unroll
        for (int q = 0; q < 4; q++) {
            const bool ok = i == 4 || (i * 8 + 2 * t + (q & 1)) <= (mi * 16 + g + (q >> 1) * 8);
            s[i][q] = ok ? s[i][q] * sl : -1.0e9f * 1.4426950408889634f;
            mx[q >> 1] = fmaxf(mx[q >> 1], s[i][q]);
        }
    float sum[2] = {0.f, 0.f};
#pragma unroll
    for (int r = 0; r < 2; r++) {
        mx[r] = fmaxf(mx[r], __shfl_xor_sync(~0u, mx[r], 1));
        mx[r] = fmaxf(mx[r], __shfl_xor_sync(~0u, mx[r], 2));
    }
#pragma unroll
    for (int i = 0; i < 5; i++)
#pragma unroll
        for (int q = 0; q < 4; q++) { s[i][q] = ex2(s[i][q] - mx[q >> 1]); sum[q >> 1] += s[i][q]; }
#pragma unroll
    for (int r = 0; r < 2; r++) {
        sum[r] += __shfl_xor_sync(~0u, sum[r], 1);
        sum[r] += __shfl_xor_sync(~0u, sum[r], 2);
        sum[r] = iv * rcp(sum[r]);
    }
    uint32_t pp[5][2];
#pragma unroll
    for (int i = 0; i < 5; i++) { pp[i][0] = pack_bf(s[i][0] * sum[0], s[i][1] * sum[0]); pp[i][1] = pack_bf(s[i][2] * sum[1], s[i][3] * sum[1]); }
    uint32_t* o = (uint32_t*)g_O + (((size_t)(seg >> 1) * 512 + h * 16) * 8 + (seg & 1) * 4 + mi * 2) * 32 + lane;
#pragma unroll(UNR == 8 ? NE : 1)
    for (int u = 0; u < NE; u++) {
        const int e = e0 + u;
        float o0[4] = {0.f, 0.f, 0.f, 0.f}, o1[4] = {0.f, 0.f, 0.f, 0.f};
        uint32_t v[4];
        lds64(v, vm + e * 256);
        mma_bf8(o0, pp[4][0], pp[4][1], v[0]);
        mma_bf8(o1, pp[4][0], pp[4][1], v[1]);
        ldsm4(v, vt + e * 1024);
        mma_bf(o0, pp[0][0], pp[0][1], pp[1][0], pp[1][1], v[0], v[2]);
        mma_bf(o1, pp[0][0], pp[0][1], pp[1][0], pp[1][1], v[1], v[3]);
        ldsm4(v, vt + e * 1024 + 512);
        mma_bf(o0, pp[2][0], pp[2][1], pp[3][0], pp[3][1], v[0], v[2]);
        mma_bf(o1, pp[2][0], pp[2][1], pp[3][0], pp[3][1], v[1], v[3]);
        o[(2 * e) * 256] = pack_bf(o0[0], o0[1]); o[(2 * e) * 256 + 32] = pack_bf(o0[2], o0[3]);
        o[(2 * e + 1) * 256] = pack_bf(o1[0], o1[1]); o[(2 * e + 1) * 256 + 32] = pack_bf(o1[2], o1[3]);
    }
}

__device__ __forceinline__
void attend_last(const uint32_t sb, const int layer) {
    const int tid = read_tid(), ln = tid & 31, w = tid >> 5;
    int h;
    asm volatile("mov.u32 %0,%%clusterid.x;" : "=r"(h));
    uint32_t inv[2];
    lds64(inv, sb + O_SCL + 16);
    mbar_wait(sb + B_S, (NSEG - 1) & 1);
    mbar_wait(sb + B_VX + 8, 0);
    if (layer == TLL) TL(54);
    if (w == 0 && ln < 2)
        asm volatile("mbarrier.arrive.relaxed.cluster.shared::cluster.b64 _,[%0];" ::"r"(mapa(sb + B_STG + 8, ln)) : "memory");
    tok_attention<2, AUNR>(sb + O_STG - 16384 + ln * 16, 16384, sb + O_LAST + ln * 16, 2048, sb + O_STG + 8192 - 16384 + ln * 16, sb + O_VM + 2048 + ln * 8,
                     (w >> 1) * 2, w & 1, ln, NSEG - 1, h, __uint_as_float(inv[0]), __uint_as_float(inv[1]));
    if (layer == TLL) TL(55);
    __syncwarp();
    if (ln == 0) red_release(g_flag + F_O + layer * 32 + 31);
    if (layer == TLL) TL(43);
}

template <int layer> __device__ __forceinline__ void chain_mma(const uint32_t sb, const int c, const int h, const uint32_t zero, const bf16* __restrict__ Wq,
                                          const bf16* __restrict__ Wk, const bf16* __restrict__ Wv, const bf16* __restrict__ Wo,
                                          const bf16* res, bf16* out) {
    int tid = read_tid(), lane = tid & 31;
    const int w = __shfl_sync(~0u, tid >> 5, 0), wg = w >> 2;
    [[maybe_unused]] const int cta = h * 3 + c;
    uint32_t A0[20][4], A1[20][4];
    const int t0 = (w & 3) + wg * 4, t1 = t0 ^ 4;
    float sl;
    {
        const int tl = tid & 127, r = tl >> 3, ch = tl & 7;
        const size_t so = (size_t)(wg * 320 + r) * 4096 + h * 128 + ch * 8;
        const bf16 *wa = (c == 2 ? Wv : Wq + c * 64) + so, *wb = (c == 2 ? Wv + 64 : Wk + c * 64) + so;
        const uint32_t ring = sb + wg * 4096;
        const uint32_t dst = ring + r * 128 + ((ch ^ r) & 7) * 16;
        const uint32_t src = ring + ((lane & 7) + (lane >> 4) * 8) * 128 + ((((w & 3) * 2 + ((lane >> 3) & 1)) ^ lane) & 7) * 16;
        const int q4 = lane & 3, gr = (c * 2 + ((w >> 1) & 1)) * 56 + (q4 == 3 ? 24 : (w & 1) * 32 + q4 * 8);
        const bf16* wo_ = Wo + (size_t)(h * 128 + (lane >> 2)) * 640 + wg * 320 + min(gr, 312);
        const uint32_t wdst = sb + O_WO + w * 8192 + (lane >> 2) * 64 + ((q4 ^ (lane >> 3)) & 3) * 16;
        auto issue = [&](int i) {
            if (i < 20) {
                const uint32_t d = dst + (i < 19 ? i * 8192 : O_LAST);
                cp_async16(d, wa + (size_t)i * 65536); cp_async16(d + 2048, wb + (size_t)i * 65536);
                if (i < 16) cp_async16(wdst + i * 512, wo_ + i * 5120, gr < 320 ? 16 : 0);
            }
            cp_commit();
        };
#pragma unroll 1
        for (int i = 0; i < WDEPTH; i++) issue(i);
        asm volatile("barrier.cluster.arrive.relaxed.aligned;" ::: "memory");
        float fa, fb;
        if (layer == 0) {
            uint32_t ma = 0, mb = 0;
#pragma unroll 1
            for (int i = 0; i < 20; i++) {
                issue(i + WDEPTH);
                cp_wait<WDEPTH>();
                const uint32_t d = dst + (i < 19 ? i * 8192 : O_LAST);
                uint32_t u[8];
                lds128(u, d); lds128(u + 4, d + 2048);
                ma = babsmax(babsmax(ma, babsmax(u[0], u[1])), babsmax(u[2], u[3])); mb = babsmax(babsmax(mb, babsmax(u[4], u[5])), babsmax(u[6], u[7]));
            }
            ma = __reduce_max_sync(~0u, max(ma & 0x7fffu, (ma >> 16) & 0x7fffu)); mb = __reduce_max_sync(~0u, max(mb & 0x7fffu, (mb >> 16) & 0x7fffu));
            asm volatile("barrier.cluster.wait.aligned;" ::: "memory");
            if (lane < 3)
                asm volatile("st.async.shared::cluster.mbarrier::complete_tx::bytes.v2.b32 [%0],{%1,%2},[%3];"
                             ::"r"(mapa(sb + O_WMX + (c * 8 + w) * 8, lane)), "r"(ma), "r"(mb), "r"(mapa(sb + B_W, lane)) : "memory");
            __syncwarp();
            {
                uint32_t off[4];
                float cs[4] = {0.f, 0.f, 0.f, 0.f};
#pragma unroll
                for (int q = 0; q < 4; q++) {
                    const int g_ = (c * 2 + ((w >> 1) & 1)) * 56 + (q == 3 ? 24 : (w & 1) * 32 + q * 8), col = wg * 320 + g_, nb = col / 80;
                    off[q] = g_ < 320 && !(q == 3 && (w & 1)) ? ((nb * 512 + h * 16) * 10 + (col - nb * 80) / 8) * 32 + lane : ~0u;
                }
                const uint32_t ta = sb + O_WO + w * 8192 + (lane & 7) * 64 + (((lane >> 3) ^ (lane >> 1)) & 3) * 16;
#pragma unroll 2
                for (int i = 0; i < 16; i++) {
                    uint32_t r[4];
                    ldsm4t(r, ta + i * 512);
#pragma unroll
                    for (int q = 0; q < 4; q++) {
                        if (off[q] != ~0u) ((uint32_t*)g_wot)[off[q] + i * 320] = r[q];
                        cs[q] += fabsf(bf_lo(r[q])) + fabsf(bf_hi(r[q]));
                    }
                }
                float cm = 0.f;
#pragma unroll
                for (int q = 0; q < 4; q++) {
                    cs[q] += __shfl_xor_sync(~0u, cs[q], 1); cs[q] += __shfl_xor_sync(~0u, cs[q], 2);
                    cm = fmaxf(cm, cs[q]);
                }
                const uint32_t n1 = __reduce_max_sync(~0u, __float_as_uint(cm));
                if (lane == 0) g_co[h * 32 + c * 8 + w] = __uint_as_float(n1);
            }
            mbar_wait(sb + B_W, 0);
            uint32_t v[2];
            lds64(v, sb + O_WMX + (lane < 24 ? lane : 0) * 8);
            const bool mine = (lane >> 3) < 3 && ((lane >> 4) == 1) == (c == 2);
            ma = __reduce_max_sync(~0u, mine ? v[0] : 0u); mb = __reduce_max_sync(~0u, mine ? v[1] : 0u);
            if (c == 2) ma = mb = max(ma, mb);
            fa = __uint_as_float(ma << 16); fb = __uint_as_float(mb << 16);
            if (tid == 0) {
                if (c != 1) g_wmx[h * 3 + c] = fa;
                if (c == 0) g_wmx[h * 3 + 1] = fb;
            }
        } else {
            fa = __ldcg(g_wmx + h * 3 + (c == 2 ? 2 : 0)); fb = __ldcg(g_wmx + h * 3 + (c == 2 ? 2 : 1));
            asm volatile("barrier.cluster.wait.aligned;" ::: "memory");
        }
        if (layer == TLL) TL(49);
        float ia, ib;
        const float sa = pow2_scale(fa, 6, &ia), sc_b = pow2_scale(fb, 6, &ib);
        sl = __uint_as_float(uni(__float_as_uint(ia * ib * (0.08838834764831845f * 1.4426950408889634f))));
        const uint32_t pa = pack_bf(sa, sa), pb = pack_bf(sc_b, sc_b);
        const int ahead = layer == 0 ? 20 : WDEPTH;
        auto convert = [&](int lo) {
#pragma unroll 1
            for (int i = lo; i < lo + 10; i++) {
                issue(i + ahead);
                cp_wait<WDEPTH>();
                const uint32_t d = dst + (i < 19 ? i * 8192 : O_LAST);
                uint32_t u[8];
                lds128(u, d); lds128(u + 4, d + 2048);
#pragma unroll
                for (int q = 0; q < 8; q++)
                    asm("{.reg .b32 m,l,u; mul.rn.bf16x2 m,%0,%1; shl.b32 l,m,16; and.b32 u,m,0xffff0000; cvt.rn.f16x2.f32 %0,u,l;}" : "+r"(u[q]) : "r"(q < 4 ? pa : pb));
                sts128(d, u[0], u[1], u[2], u[3]); sts128(d + 2048, u[4], u[5], u[6], u[7]);
            }
            bar_sync(6 + wg, 128);
        };
        const uint32_t s0 = src + wg * 2048, s1 = src + 2048 - wg * 2048;
        convert(0);
#pragma unroll
        for (int i = 0; i < 10; i++) { ldsm4t(A0[i], s0 + i * 8192); ldsm4t(A1[i], s1 + i * 8192); }
        if (layer == TLL) TL(50);
        convert(10);
#pragma unroll
        for (int i = 10; i < 20; i++) { ldsm4t(A0[i], s0 + (i < 19 ? i * 8192 : O_LAST)); ldsm4t(A1[i], s1 + (i < 19 ? i * 8192 : O_LAST)); }
        if (layer == TLL) TL(53);
        bar_arrive(9, 288);
        bar_sync(4, 288);
        asm volatile("barrier.cluster.arrive.relaxed.aligned;" ::: "memory");
    }
    const uint32_t idn = (lane >> 3) == (lane & 3) ? ((lane & 4) ? 0x3c000000u : 0x3c00u) : 0u;
    float invM = g_invM0;
    char* redp = red_base() + (size_t)layer * 32 * 32768 + w * 2048 + (lane >> 4) * 1024 + ((lane >> 3) & 1) * 256 + (lane & 7) * 16;
    const uint32_t ro2 = uni((w >> 1) * 4096 + 128), rown = uni(c == 2 ? ro2 : c * 16384);
    const uint32_t L16 = lane * 16, L8 = lane * 8, L4 = lane * 4;
    const uint32_t xch0 = uni(sb + O_XCH + t0 * 1024), xch1 = uni(sb + O_XCH + t1 * 1024);
    const uint32_t qo0 = uni(sb + O_QKP + (w & 3) * 1024 + (wg ? 768 : 0)), qp0 = uni(qo0 + (wg ? 128 : 256));
    const uint32_t qo1 = uni(sb + O_QKP + (w & 3) * 1024 + (wg ? 128 : 512)), qp1 = uni(qo1 + (wg ? 256 : 128));
    const uint32_t vo1 = uni(qo1 + (wg ? -128 : 256)), vp1 = uni(qp1 + (wg ? -128 : 256));
    const uint32_t msr = uni(sb + O_MS + wg * 5376);
    const uint32_t msw = uni(msr + ((w >> 1) & 1) * 896 + (w & 1) * 512), msh = uni(msr + ((w >> 1) & 1) * 896 + 384 + (w & 1) * 2);
    const uint32_t sco = uni(sb + O_SC + c * 768 + (w & 3) * 256);
    const uint32_t woa = sb + O_WO + w * 8192 + (lane >> 4) * 512 + (lane & 7) * 64 + (((lane >> 3) ^ (lane >> 1)) & 1) * 16 + ((lane >> 2) & 1) * 32;
    const uint32_t w512 = uni(sb + w * 512), w128 = uni(sb + w * 128);
    const uint32_t pd0 = uni(mapa(sb, c == 2 ? 0 : 2) - sb), pd1 = uni(mapa(sb, c == 1 ? 0 : 1) - sb);
    const bool scw = c < 2 && w >= 4 && w <= 6;
    uint32_t sn = uni(sb + O_STG + (c == 2 ? 8192 : 0) + t1 * 1024);
    uint32_t ka = uni(sb + (w == 6 ? O_QKP + 512 : O_STG + 4096 + (w & 1) * 512));
    uint32_t vs = uni(sb + O_VM + t1 * 256);
    uint32_t va = uni(sb + O_STG + 8192 + w * 2048), vr = uni(sb + O_VM + w * 512);
    const uint32_t sn2 = uni(2 * sn - 16384), ka2 = uni(2 * ka - (w == 6 ? 0 : 16384)), vs2 = uni(2 * vs + 2048), va2 = uni(2 * va - 16384),
                   vr2 = uni(2 * vr + 2048);
    uint32_t xd = uni((uint32_t)mkdesc(sb + O_XS + wg * 20480, 512, 128, 0));
    const uint32_t xd2 = uni(2 * xd + 2560);

    uint32_t wp[2 * NPERM + 1][4];
    sfor<NPERM>([&](auto I) { constexpr int i = I; ldsm4t(wp[2 * i], woa + i * 1024); ldsm4t(wp[2 * i + 1], (woa ^ 32) + i * 1024); });
    auto wo_fetch = [&](uint32_t (&wo)[16][4], auto I) {
        constexpr int i = I;
        if constexpr (i < NPERM) {
#pragma unroll
            for (int q = 0; q < 4; q++) { wo[i][q] = wp[2 * i][q]; wo[8 + i][q] = wp[2 * i + 1][q]; }
        } else { ldsm4t(wo[i], woa + i * 1024); ldsm4t(wo[8 + i], (woa ^ 32) + i * 1024); }
    };
    if (layer == TLL) TL(32);
    float b0[16], b1[16];
    mbar_wait(sb + B_XF, 0);
    if (layer == TLL) TL(33);
    tok_issue<0, NTB>(A0, A1, b0, b1, xd, zero);
    tok_give(b0, L16, xch0);
    tok_issue<NTB, 40>(A0, A1, b0, b1, xd, zero);
    bar_sync(4, 256);
    wg_wait<0>();
    {
        uint32_t e[2][4];
        lds128_u<0>(e[0], L16, xch1); lds128_u<512>(e[1], L16, xch1);
        tok_finish(b1, e, L16, sn, idn);
    }
    sn = sn2 - sn; xd = xd2 - xd;
    bar_sync(5, 288);
    asm volatile("barrier.cluster.wait.aligned;" ::: "memory");
    if (layer == TLL) TL(34);
    mbar_wait(sb + B_XF + 8, 0);
    if (layer == TLL) TL(35);
    tok_issue<0, NTA>(A0, A1, b0, b1, xd, zero);
    uint32_t tr = clock32() - RDELAY;

#pragma unroll 1
    for (int st = 0;; st++) {
        uint4 mv[3];
        asm volatile("{.reg .pred p; .reg .b32 t;\n"
                     "mov.b32 %0,0; mov.b32 %1,0; mov.b32 %2,0; mov.b32 %3,0; mov.b32 %4,0; mov.b32 %5,0; mov.b32 %6,0; mov.b32 %7,0;\n"
                     "mov.b32 %8,0; mov.b32 %9,0; mov.b32 %10,0; mov.b32 %11,0;\n"
                     "T_LOOP: mov.u32 t,%%clock; sub.u32 t,t,%14; setp.ge.u32 p,t,%15;\n"
                     "@p ld.relaxed.gpu.global.v4.u32 {%0,%1,%2,%3},[%12]; @p ld.relaxed.gpu.global.v4.u32 {%4,%5,%6,%7},[%12+16384];\n"
                     "@p ld.relaxed.gpu.global.v4.u32 {%8,%9,%10,%11},[%13];\n"
                     "@!p bra T_LOOP;}"
                     : "=r"(mv[0].x), "=r"(mv[0].y), "=r"(mv[0].z), "=r"(mv[0].w), "=r"(mv[1].x), "=r"(mv[1].y), "=r"(mv[1].z), "=r"(mv[1].w),
                       "=r"(mv[2].x), "=r"(mv[2].y), "=r"(mv[2].z), "=r"(mv[2].w)
                     : "l"(redp), "l"(redp + ro2), "r"(tr), "n"(RDELAY) : "memory");
        STAMP(10);
        tok_issue<NTA, NTB>(A0, A1, b0, b1, xd, zero);
        tok_give(b0, L16, xch0);
        tok_issue<NTB, 40>(A0, A1, b0, b1, xd, zero);
        xd = xd2 - xd;
        STAMP(9);
        if (zero >> 30) break;
        asm volatile("{.reg .pred p; .reg .b32 a,h,t,n; .reg .b16 l,u; .reg .b64 q;\n"
                     "add.u32 a,%12,%13; add.u32 h,%12,%14; mov.u32 n,0;\n"
                     "M_LOOP:\n .pragma \"nounroll\";\n"
                     "st.shared.b32 [a],%0; st.shared.b32 [a+128],%1; st.shared.b32 [a+256],%2; mov.b32 {l,u},%3; st.shared.b16 [h],l;\n"
                     "st.shared.b32 [a+1792],%4; st.shared.b32 [a+1920],%5; st.shared.b32 [a+2048],%6; mov.b32 {l,u},%7; st.shared.b16 [h+1792],l;\n"
                     "st.shared.b32 [a+3584],%8; st.shared.b32 [a+3712],%9; st.shared.b32 [a+3840],%10; mov.b32 {l,u},%11; st.shared.b16 [h+3584],l;\n"
                     "lop3.b32 t,%3,%7,0x50000000,0x7e; lop3.b32 t,t,%11,0x50000000,0xf6; setp.gt.u32 p,t,0xffff;\n"
                     "vote.sync.any.pred p,p,-1; add.u32 n,n,1; setp.lt.and.u32 p,n,%17,p; @!p bra M_DONE;\n"
                     "ld.relaxed.gpu.global.v4.u32 {%0,%1,%2,%3},[%15]; ld.relaxed.gpu.global.v4.u32 {%4,%5,%6,%7},[%15+16384];\n"
                     "cvt.u64.u32 q,%16; add.u64 q,q,%15; ld.relaxed.gpu.global.v4.u32 {%8,%9,%10,%11},[q];\n"
                     "bra M_LOOP;\n"
                     "M_DONE:}"
                     : "+r"(mv[0].x), "+r"(mv[0].y), "+r"(mv[0].z), "+r"(mv[0].w), "+r"(mv[1].x), "+r"(mv[1].y), "+r"(mv[1].z), "+r"(mv[1].w),
                       "+r"(mv[2].x), "+r"(mv[2].y), "+r"(mv[2].z), "+r"(mv[2].w)
                     : "r"(L4), "r"(msw), "r"(msh), "l"(redp), "r"(ro2), "n"(SPIN_LIM) : "memory");
        bar_sync(3, 288);
        STAMP(0);
        uint32_t e[2][4];
        float f1[4];
        {
            uint32_t b[10][4];
            float acc[4][4];
#pragma unroll
            for (int i = 0; i < 4; i++) acc[i][0] = acc[i][1] = acc[i][2] = acc[i][3] = 0.f;
            auto ld = [&](auto I) { constexpr int i = I; ldsm4t_u<i * 512>(b[i], L16, msr); };
            auto mm = [&](auto I) {
                constexpr int i = I;
                mma_f16(acc[0], A0[2 * i], b[i][0], b[i][1]); mma_f16(acc[2], A1[2 * i], b[i][0], b[i][1]);
                mma_f16(acc[1], A0[2 * i + 1], b[i][2], b[i][3]); mma_f16(acc[3], A1[2 * i + 1], b[i][2], b[i][3]);
            };
            ld(IC<0>()); ld(IC<1>()); ld(IC<2>()); ld(IC<3>());
            sts32_u<O_MX>(L4, w128,
                          habsmax(habsmax(habsmax(habsmax(mv[0].x, mv[0].y), habsmax(mv[0].z, mv[1].x)), habsmax(habsmax(mv[1].y, mv[1].z), mv[2].x)),
                                  habsmax(habsmax(mv[2].y, mv[2].z), habsmax(habsmax(mv[0].w, mv[1].w), mv[2].w) & 0xffffu)));
            wg_wait<0>();
            ld(IC<4>()); mm(IC<0>()); ld(IC<5>()); mm(IC<1>()); ld(IC<6>()); mm(IC<2>());
            ld(IC<7>()); mm(IC<3>()); ld(IC<8>()); mm(IC<4>()); ld(IC<9>()); mm(IC<5>());
            lds128_u<0>(e[0], L16, xch1); lds128_u<512>(e[1], L16, xch1);
            mm(IC<6>()); mm(IC<7>()); mm(IC<8>()); mm(IC<9>());
            const uint32_t u0 = pack_bf((acc[0][0] + acc[1][0]) * invM, (acc[0][1] + acc[1][1]) * invM);
            const uint32_t u1 = pack_bf((acc[0][2] + acc[1][2]) * invM, (acc[0][3] + acc[1][3]) * invM);
#pragma unroll
            for (int i = 0; i < 4; i++) f1[i] = (acc[2][i] + acc[3][i]) * invM;
            sts32_u<0>(L4, qo0, u0); sts32_u<0>(L4, qp0, u1); sts32_u<0>(L4, qo1, pack_bf(f1[0], f1[1])); sts32_u<0>(L4, qp1, pack_bf(f1[2], f1[3]));
        }
        STAMP(1);
        bar_sync(1, 320);
        if (__builtin_expect(scw, 1)) {
            float a[4][4];
#pragma unroll
            for (int i = 0; i < 4; i++) a[i][0] = a[i][1] = a[i][2] = a[i][3] = 0.f;
            uint32_t q[4][4], k[4][4];
            sfor<4>([&](auto I) {
                constexpr int i = I;
                ldsm4t_u<O_QKP + i * 1024>(q[i], L16, sb); ldsm4t_u<i * 1024>(k[i], L16, ka);
            });
#pragma unroll
            for (int i = 0; i < 4; i++) {
                mma_bf(a[i & 1], q[i][0], q[i][1], q[i][2], q[i][3], k[i][0], k[i][1]);
                mma_bf(a[2 + (i & 1)], q[i][0], q[i][1], q[i][2], q[i][3], k[i][2], k[i][3]);
            }
            const float mk = w == 6 ? 1.f : 0.f;
            const float x0 = (a[0][0] + a[0][2]) + (a[1][0] + a[1][2]), x1 = (a[0][1] + a[0][3]) + (a[1][1] + a[1][3]);
            const float y0 = (a[2][0] + a[2][2]) + (a[3][0] + a[3][2]), y1 = (a[2][1] + a[2][3]) + (a[3][1] + a[3][3]);
            st_share2(L8, sco, sb + B_S, pd0, pd1, pack_bf(fmaf(y0, mk, x0) * sl, fmaf(y1, mk, x1) * sl), pack_bf(y0 * sl, y1 * sl));
        }
        if (c == 2) {
            const uint32_t x = lds32_u<0>(L4, vo1), y = lds32_u<0>(L4, vp1);
            st_share2(L8, vs, sb + B_S, pd0, pd1, pack_bf(f1[0] + bf_lo(x), f1[1] + bf_hi(x)), pack_bf(f1[2] + bf_lo(y), f1[3] + bf_hi(y)));
        }
        STAMP(3);
        if (st == NSEG - 1) break;
        tok_finish(b1, e, L16, sn, idn);
        asm volatile("{.reg .pred p; setp.eq.u32 p,%1,0; @p mbarrier.arrive.shared::cta.b64 _,[%0];}" ::"r"(sb + B_GO), "r"(L4 + (c != 2)) : "memory");
        redp += (st & 1) ? 32768 - 512 : 512;
        if (wg == 0) {
            uint32_t wo[16][4], vx[2][2][4], vm[2][2];
            ldsm4_u<0>(vx[0][0], L16, va); ldsm4_u<512>(vx[0][1], L16, va); ldsm4_u<1024>(vx[1][0], L16, va); ldsm4_u<1536>(vx[1][1], L16, va);
            sfor<NWO0>([&](auto I) { wo_fetch(wo, I); });
            mbar_wait(sb + B_S, st & 1);
            STAMP(4);
            uint32_t s[5];
            {
                uint32_t p[2][5];
                sfor<2>([&](auto R) {
                    constexpr int r = R;
                    lds64_u<O_SC + r * 768>(p[r], L8, sb); lds64_u<O_SC + r * 768 + 256>(p[r] + 2, L8, sb); p[r][4] = lds32_u<O_SC + r * 768 + 512>(L8, sb);
                });
#pragma unroll
                for (int j = 0; j < 5; j++) s[j] = badd(p[0][j], p[1][j]);
            }
            lds64_u<0>(vm[0], L8, vr); lds64_u<256>(vm[1], L8, vr);
            uint32_t mm = bmax(bmax(bmax(s[0], s[1]), bmax(s[2], s[3])), s[4]);
            mm = bmax(bmax(mm, __shfl_xor_sync(~0u, mm, 1)), bmax(__shfl_xor_sync(~0u, mm, 2), __shfl_xor_sync(~0u, mm, 3)));
            const float m = fmaxf(bf_lo(mm), bf_hi(mm));
            float o0[4] = {0.f, 0.f, 0.f, 0.f}, o1[4] = {0.f, 0.f, 0.f, 0.f}, d[10];
#pragma unroll
            for (int j = 0; j < 5; j++) { d[2 * j] = bf_lo(s[j]) - m; d[2 * j + 1] = bf_hi(s[j]) - m; }
#pragma unroll
            for (int j = 0; j < 10; j++) d[(j + 8) % 10] = ex2(d[(j + 8) % 10]);
            float sum = ((d[8] + d[9]) + (d[0] + d[1])) + ((d[2] + d[3]) + (d[4] + d[5])) + (d[6] + d[7]);
            const uint32_t p4 = pack_bf(d[8], d[9]), p0 = pack_bf(d[0], d[1]), p1 = pack_bf(d[2], d[3]), p2 = pack_bf(d[4], d[5]), p3 = pack_bf(d[6], d[7]);
            mma_bf8(o0, vm[0][0], vm[0][1], p4);
            mma_bf8(o1, vm[1][0], vm[1][1], p4);
            mma_bf(o0, vx[0][0][0], vx[0][0][1], vx[0][0][2], vx[0][0][3], p0, p1);
            mma_bf(o1, vx[1][0][0], vx[1][0][1], vx[1][0][2], vx[1][0][3], p0, p1);
            mma_bf(o0, vx[0][1][0], vx[0][1][1], vx[0][1][2], vx[0][1][3], p2, p3);
            mma_bf(o1, vx[1][1][0], vx[1][1][1], vx[1][1][2], vx[1][1][3], p2, p3);
            sfor<NWO0B - NWO0>([&](auto I) { constexpr int i = I; wo_fetch(wo, IC<NWO0 + i>()); });
            sum += __shfl_xor_sync(~0u, sum, 1);
            sum += __shfl_xor_sync(~0u, sum, 2);
            sts32_u<O_OS>(L4, w512, pack_bf(o0[0], o0[1])); sts32_u<O_OS + 128>(L4, w512, pack_bf(o0[2], o0[3]));
            sts32_u<O_OS + 256>(L4, w512, pack_bf(o1[0], o1[1])); sts32_u<O_OS + 384>(L4, w512, pack_bf(o1[2], o1[3]));
            sts32_u<O_SUM>(lane & 28, sb, __float_as_uint(sum));
            STAMP(5);
            invM = mem_out<NWO0B>(sb, L16, L8, wo, woa, redp + rown, w & 1);
            tr = clock32();

        } else {
            uint32_t wo[16][4];
            sfor<NWO1>([&](auto I) { wo_fetch(wo, I); });
            invM = mem_out<NWO1>(sb, L16, L8, wo, woa, redp + rown, w & 1);
            tr = clock32();

        }
        STAMP(7);
        tok_issue<0, NTA>(A0, A1, b0, b1, xd, zero);
        sn = sn2 - sn; ka = ka2 - ka; vs = vs2 - vs; va = va2 - va; vr = vr2 - vr;
        STAMP(8);
    }
    if (layer == TLL) TL(40);
    if (c == 2) attend_last(sb, layer);
    bar_arrive(8, 320);
    tid = read_tid(); lane = tid & 31;
    float acc[40];
    const int nc = c == 2 ? 10 : 11;
    const int mb = 28 + (h >> 3), nj = c == 2 ? 1 : 2;
    uint32_t rv[2][2];
    const size_t go = ((size_t)(mb * 64 + (w & 3) * 16 + (lane >> 2)) * 640 + (h & 7) * 80 + (wg * 5 + c * 2) * 8 + (lane & 3) * 2) >> 1;
#pragma unroll
    for (int u = 0; u < 4; u++) rv[u >> 1][u & 1] = (u >> 1) < nj ? __ldcg((const uint32_t*)res + go + (u >> 1) * 4 + (u & 1) * 2560) : 0u;
#pragma unroll 1
    for (int k = 0; k < nc; k++) {
        mbar_wait(sb + T_FB + (k % 7) * 8, k >= 7);
        mbar_wait(sb + T_FA + (k & 3) * 8, (k >> 2) & 1);
        if (layer == TLL && k == 0) TL(41);
        const uint64_t da = mkdesc(sb + O_MS + (k & 3) * 16384 + wg * 8192, 1024, 128, 0), db = mkdesc(sb + tail_b(k) + wg * 10240, 1280, 128, 0);
        wg_fence();
#pragma unroll
        for (int q = 0; q < 4; q++) wg_n80_ss(acc, da + q * 128, db + q * 160, k | q);
        wg_commit();
        if (k > 0) {
            wg_wait<1>();
            if (lane == 0) { mbar_arrive(sb + T_EA + ((k - 1) & 3) * 8); if (k <= 4) mbar_arrive(sb + T_EB + (k - 1) * 8); }
        }
    }
    if (layer == TLL) TL(52);
    wg_wait<0>();
    asm volatile("barrier.cluster.arrive.relaxed.aligned; barrier.cluster.wait.aligned;" ::: "memory");
    const uint32_t ra = sb + O_XS + tid * 16, rb = sb + O_MS + tid * 16;
#pragma unroll
    for (int j = 0; j < 5; j++) {
        const float* q = acc + 4 * j;
        sts128(rb + j * 4096, __float_as_uint(wg ? q[0] : q[20]), __float_as_uint(wg ? q[1] : q[21]), __float_as_uint(wg ? q[2] : q[22]), __float_as_uint(wg ? q[3] : q[23]));
    }
    bar_sync(4, 256);
    sfor<5>([&](auto J) {
        constexpr int j = J;
        const float* q = acc + 4 * j;
        uint32_t p[4];
        lds128(p, sb + O_MS + (tid ^ 128) * 16 + j * 4096);
        const uint32_t d = ra + c * 8192 + (j & 1) * 4096;
        asm volatile("{.reg .pred p; setp.eq.u32 p,%7,%8;\n"
                     "@!p st.async.shared::cluster.mbarrier::complete_tx::bytes.v4.f32 [%0],{%1,%2,%3,%4},[%5]; @p st.shared.v4.f32 [%6],{%1,%2,%3,%4};}"
                     ::"r"(mapa(d, j >> 1)), "f"((wg ? q[20] : q[0]) + __uint_as_float(p[0])), "f"((wg ? q[21] : q[1]) + __uint_as_float(p[1])),
                     "f"((wg ? q[22] : q[2]) + __uint_as_float(p[2])), "f"((wg ? q[23] : q[3]) + __uint_as_float(p[3])), "r"(mapa(sb + T_RED, j >> 1)),
                     "r"(d), "r"(c), "n"(j >> 1) : "memory");
    });
    mbar_wait(sb + T_RED, 0);
#pragma unroll 1
    for (int u = 0; u < nj; u++) {
        uint32_t p[3][4];
#pragma unroll
        for (int q = 0; q < 3; q++) lds128(p[q], ra + q * 8192 + u * 4096);
        float y[4];
#pragma unroll
        for (int i = 0; i < 4; i++) y[i] = __uint_as_float(p[0][i]) + __uint_as_float(p[1][i]) + __uint_as_float(p[2][i]);
        ((uint32_t*)out)[go + u * 4] = bfma(pack_bf(y[0], y[1]), 0x3f803f80u, u ? rv[1][0] : rv[0][0]);
        ((uint32_t*)out)[go + u * 4 + 2560] = bfma(pack_bf(y[2], y[3]), 0x3f803f80u, u ? rv[1][1] : rv[0][1]);
    }
    __syncwarp();
    if (layer == 0 && lane == 0) red_release(g_flag + F_R + mb);
    TL(layer == 0 ? 15 : 29);
    asm volatile("barrier.cluster.arrive.relaxed.aligned; barrier.cluster.wait.aligned;" ::: "memory");
}

__device__ __forceinline__ void tail_load_b(const uint32_t sb, const int h, const int c, const int k) {
    mbar_expect(sb + T_FB + (k % 7) * 8, 20480);
    bulk_g2s(sb + tail_b(k), (const char*)g_wot + (size_t)((h & 7) * GNC + c * 11 + k) * 20480, 20480, sb + T_FB + (k % 7) * 8);
}
template <int layer> __device__ __forceinline__ void chain_aux(const uint32_t sb, const int c, const int h, const int nact) {
    const int tid = read_tid(), w = __shfl_sync(~0u, tid >> 5, 0), lane = tid & 31;
    if (w == 8) {
        mbar_init(sb + O_BAR + lane * 8, lane == 2 ? (c == 2 ? 9 : 4) : lane == 3 || (lane >= 16 && lane < 20) || (lane >= 27 && lane < 31) ? 8 : 1);
        asm volatile("fence.mbarrier_init.release.cluster;" ::: "memory");
        fence_async_smem();
        __syncwarp();
    }
    {
        uint4* z = (uint4*)red_base() + layer * 65536;
#pragma unroll 1
        for (int i = blockIdx.x * 128 + tid - 256; i < 65536; i += 96 * 128)
            if (i >= 2048 || (i & 32)) z[i] = make_uint4(0, 0, 0, 0);
    }
    if (w == 8 && lane == 0) {
        mbar_expect(sb + B_S, s_tx(c));
        mbar_expect(sb + B_W, 192);
        mbar_expect(sb + T_RED, (c == 2 ? 1 : 2) * 2 * 4096);
        if (layer == 1) prefetch_l2(red_base() + 32 * 32768 + blockIdx.x * 1024, 1024);
        if (layer == 0) wait_flag<400>(g_ready, NSETUP);
    }
    __syncwarp();
    cluster_sync_full();
    asm volatile("barrier.cluster.arrive.relaxed.aligned;" ::: "memory");
    pdl_wait();
    if (w == 11 && lane == 0) red_relaxed(g_flag + F_X + layer * 128 + 65);
    Flag* flag = g_flag + layer * NSEG * 32 + h;
    const Flag* xflag = g_flag + F_X + layer * 128;
    char* const it0 = g_item + (size_t)h * 32768;
    if (w == 8) {
#pragma unroll 1
        for (int n = 0; n < 3; n++) {
            wait_flag<100>(xflag + (n >> 1), 4);
            fence_async_glb();
            if (n == 0) { bar_sync(4, 288); fence_async_smem(); }
            if (lane == 0 && n < 2) {
                mbar_expect(sb + B_XF + n * 8, 40960);
                bulk_g2s(sb + O_XS + n * 40960, (const char*)g_xn + n * 40960, 40960, sb + B_XF + n * 8);
            }
            __syncwarp();
        }
#pragma unroll 1
        for (int n = 0; n < NSEG - 1; n++) {
            const int np = n & 1;
            char* const vit = it0 + (size_t)(n % RING) * 32 * 32768 + 16384;
            if (c == 2 && n > 0) {
                if (lane == 0) {
                    if (n >= RING) wait_flag(flag + (n - RING) * 32, 7);
                    mbar_sleep(sb + B_GO, (n - 1) & 1);
                    fence_async_smem();
                    bulk_s2g(vit, sb + O_STG + 8192 - np * 16384, 8192);
                    bulk_commit();
                }
                __syncwarp();
            }
            if (n == 0) { wait_flag<100>(g_flag + F_W + layer * 128, 96); bar_sync(5, 288); } else bar_sync(2, 352);
            if (n == 1) TL(12 + layer * 14);
            if (n == 63) TL(13 + layer * 14);
            if (lane == 0) {
                const uint32_t vs = sb + O_STG + 8192 - np * 16384, vb = sb + B_VX + np * 8;
                if (n == 0) { mbar_expect(sb + B_XF, 40960); bulk_g2s(sb + O_XS, (const char*)g_xn + 2 * 40960, 40960, sb + B_XF); }
                if (c == 2) {
                    if (n == 0) { fence_async_smem(); bulk_s2g(vit, vs, 8192); bulk_commit(); }
                    bulk_wait0();
                    fence_async_glb();
                    asm volatile("mbarrier.arrive.relaxed.cluster.shared::cluster.b64 _,[%0];" ::"r"(mapa(sb + B_VH, 0)) : "memory");
                    asm volatile("mbarrier.arrive.relaxed.cluster.shared::cluster.b64 _,[%0];" ::"r"(mapa(sb + B_VH, 1)) : "memory");
                    red_relaxed(flag + n * 32);
                } else {
                    mbar_sleep(sb + B_VH, np);
                    fence_async_glb();
                    mbar_expect(vb, 8192);
                    bulk_g2s(vs, vit, 8192, vb);
                }
                if (n == h * 3 + c && !np && n + 6 < NSEG) prefetch_l2(red_base() + (size_t)(layer * 32 + (n >> 1) + 3) * 32768, 32768);
            }
            __syncwarp();
        }
        {
            bar_sync(2, 352);
            TL(13 + layer * 14);
            if (lane == 0) {
                if (c == 2) mbar_expect(sb + B_VX + 8, 2 * 8192 + 2 * 2048);
                else {
                    fence_async_smem();
                    bulk_s2s(mapa(sb + O_STG - (c == 0 ? 16384 : 0), 2), sb + O_STG - 16384, 8192, mapa(sb + B_VX + 8, 2));
                }
            }
            __syncwarp();
        }
    } else if (w == 11) {
        float cvo;
        {
            auto max8 = [&](const float* p) {
                const float4 u = ((const float4*)p)[0], v = ((const float4*)p)[1];
                return fmaxf(fmaxf(fmaxf(u.x, u.y), fmaxf(u.z, u.w)), fmaxf(fmaxf(v.x, v.y), fmaxf(v.z, v.w)));
            };
            wait_flag<300>(g_flag + F_W + layer * 128, 96);
            const float* pc = g_co + lane * 32;
            float a = 640.f * __ldcg(g_wmx + lane * 3 + 2), o = fmaxf(fmaxf(max8(pc), max8(pc + 8)), max8(pc + 16));
#pragma unroll 1
            for (int s = 16; s; s >>= 1) { a = fmaxf(a, __shfl_xor_sync(~0u, a, s)); o += __shfl_xor_sync(~0u, o, s); }
            cvo = a * o * 2.f;
        }
        float invM = g_invM0;
        float iq, ik, iv;
        weight_scale(h, 0, &iq); weight_scale(h, 1, &ik); weight_scale(h, 2, &iv);
        if (lane == 0) sts64(sb + O_SCL + 16, __float_as_uint(iq * ik), __float_as_uint(iv));
        const uint32_t L16 = sb + lane * 16 + O_MX;
#pragma unroll 1
        for (int st = 0; st < NSEG; st++) {
            bar_sync(1, 320);
            if (st == NSEG - 1) break;
            if (lane == 0) mbar_arrive(sb + B_STG + (st & 1) * 8);
            uint32_t u[2][4];
            lds128(u[0], L16); lds128(u[1], L16 + 512);
            uint32_t mx = habsmax(habsmax(habsmax(u[0][0], u[0][1]), habsmax(u[0][2], u[0][3])), habsmax(habsmax(u[1][0], u[1][1]), habsmax(u[1][2], u[1][3])));
            mx = __reduce_max_sync(~0u, max(mx & 0x7fffu, (mx >> 16) & 0x7fffu));
            const float bound = fmaxf(__half2float(__ushort_as_half((unsigned short)mx)) * invM, 25.5f) * cvo;
            const float sc = pow2_scale(bound, 15, &invM);
            sts64(sb + O_SCL, __float_as_uint(sc * iv), __float_as_uint(invM));
            bar_arrive(2, 352);
        }
    } else if (w == 10) {
        bar_sync(9, 288);
        if (lane == 0) red_release(g_flag + F_W + layer * 128);
#pragma unroll 1
        for (int n = 0; n < NSEG; n++) {
            bar_sync(3, 288);
            if (lane == 0 && n < NSEG - 1) {
                fence_async_smem();
                const uint32_t stg = sb + O_STG - (n & 1) * 16384;
                char* it = it0 + (size_t)(n % RING) * 32 * 32768;
                if (c < 2) bulk_s2g(it + c * 8192, stg, 8192);
                bulk_commit();
                if (n + 1 >= RING && n + 1 < NSEG) wait_flag(flag - (RING - 1) * 32, 7);
                bulk_wait0();
                mbar_arrive(sb + B_FREE + (n & 1) * 8);
                fence_async_glb();
                if (c < 2) red_relaxed(flag);
                flag += 32;
            }
            __syncwarp();
        }
    } else {
        bool allx = false;
#pragma unroll 1
        for (int st = 0; st < NSEG - 1; st++) {
            const int par = st & 1;
            char* const it = it0 + (size_t)(st % RING) * 32 * 32768;
            if (lane == 0 && !allx && st + 3 < NSEG) {
                allx = ld_acquire(xflag + 64) >= nact;
                if (!allx) wait_flag(st + 4 < NSEG ? xflag + ((st + 3) >> 1) : xflag + 64, st + 4 < NSEG ? 4 : nact);
                fence_async_glb();
            }
            __syncwarp();
            if (c < 2) mbar_sleep(sb + B_VX + par * 8, (st >> 1) & 1);
            if (st < NSEG - 2) mbar_sleep(sb + B_XF + par * 8, ((st >> 1) + 1) & 1);
            bar_sync(1, 320);
            if (lane == 0 && st + 3 < NSEG) {
                mbar_expect(sb + B_XF + (par ^ 1) * 8, 40960);
                bulk_g2s_last(sb + O_XS + (par ^ 1) * 40960, (const char*)g_xn + (size_t)(st + 3) * 40960, 40960, sb + B_XF + (par ^ 1) * 8);
            } else if (lane == 0) {
                tail_load_b(sb, h, c, (par ^ 1) * 2); tail_load_b(sb, h, c, (par ^ 1) * 2 + 1);
            }
            __syncwarp();
            if (lane == 0 && c < 2) {
                fence_async_smem();
#pragma unroll 1
                for (int i = 0; i < 4; i++) bulk_s2g(it + 24576 + (c * 4 + i) * 512, sb + O_QKP + i * 1024 + 512, 512);
                bulk_commit();
                asm volatile("cp.async.bulk.wait_group.read 0;" ::: "memory");
            }
            __syncwarp();
            bar_arrive(2, 352);
            mbar_sleep(sb + B_S, par);
            __syncwarp();
            if (lane == 0) {
                mbar_expect(sb + B_S, s_tx(c));
                if (c == 2) { fence_async_smem(); bulk_s2g(it + 28672, sb + O_VM + par * 2048, 2048); bulk_commit(); }
            }
            __syncwarp();
            if (lane == 0) { bulk_wait0(); fence_async_glb(); red_relaxed(flag); }
            __syncwarp();
            mbar_sleep(sb + B_FREE + par * 8, (st >> 1) & 1);
            flag += 32;
        }
        {
            bar_sync(1, 320);
            if (lane == 0 && c < 2) {
                fence_async_smem();
#pragma unroll 1
                for (int i = 0; i < 4; i++)
                    bulk_s2s(mapa(sb + O_LAST + (c * 4 + i) * 512, 2), sb + O_QKP + i * 1024 + 512, 512, mapa(sb + B_VX + 8, 2));
            }
            __syncwarp();
            bar_arrive(8, 320);
        }
    }
    __syncwarp();
    const int nc = c == 2 ? 10 : 11;
    if (w == 10) {
        bar_sync(8, 320);
        if (lane == 0) {
            if (layer == 1 && blockIdx.x == 0) g_ready[0].v = 0;
            if (c < 2) mbar_sleep(sb + B_STG + 8, 1);
            fence_async_smem();
            __nanosleep(TDELAY);
            wait_flag(xflag + 64, nact);
            wait_flag<50>(g_flag + F_O + layer * 32 + 28 + (h >> 3), (h >> 3) == 3 ? 32 + 8 * 32 : 64);
            fence_async_glb();
#pragma unroll 1
            for (int k = 0; k < nc; k++) {
                if (k >= 4) mbar_sleep(sb + T_EA + (k & 3) * 8, ((k >> 2) - 1) & 1);
                mbar_expect(sb + T_FA + (k & 3) * 8, 16384);
                bulk_g2s_last(sb + O_MS + (k & 3) * 16384, (const char*)g_O + (size_t)((28 + (h >> 3)) * GNC + c * 11 + k) * 16384, 16384, sb + T_FA + (k & 3) * 8);
            }
        }
    } else if (w == 9 && lane == 0) {
        __nanosleep(TDELAY);
#pragma unroll 1
        for (int k = 4; k < nc; k++) {
            if (k >= 7) mbar_sleep(sb + T_EB + (k - 7) * 8, 0);
            tail_load_b(sb, h, c, k);
        }
    }
    __syncwarp();
    asm volatile("barrier.cluster.wait.aligned;" ::: "memory");
    asm volatile("barrier.cluster.arrive.relaxed.aligned; barrier.cluster.wait.aligned;" ::: "memory");
    asm volatile("barrier.cluster.arrive.relaxed.aligned; barrier.cluster.wait.aligned;" ::: "memory");
}

constexpr int RI_A = 0, RI_TAB = 81920, RI_STG = RI_TAB + 82 * 768;
constexpr int RI_RES = RI_STG + 25600, RI_ST = RI_RES + 2 * 64 * 336;
constexpr int HB_A = G_BAR + 64, HB_AFREE = HB_A + 32, HB_LN = HB_A + 40, HB_FULL = HB_A + 64, HB_DONE = HB_FULL + 48, HB_FREE = HB_DONE + 48;
constexpr int HP_SMEM = HB_FREE + 48;
static_assert(G_BAR >= RI_ST + 2048, "helper shared-memory map");
#define IDL 280
#define ITEM_NS 60
#define PFW_AT 28
#define PFW_NS 150
__device__ __forceinline__ void helper_aux(const uint32_t sb, const int j, const int nh, const int na, const int nbh, const int layer, const bf16* Wq,
                                           const bf16* Wk, const bf16* Wv, const bf16* Wo) {
    const int w = threadIdx.x >> 5, lane = threadIdx.x & 31, p = w - 8;
    if (lane == 0 && j < (nh & ~3)) {
        int n = 0;
        for (int a = j >> 2; a < 32; a += nh >> 2, n++) {
            if (n == 0) continue;
            mbar_wait(sb + HB_AFREE, (n - 1) & 1);
            mbar_expect(sb + HB_A + p * 8, 20480);
            bulk_g2s_last(sb + RI_A + p * 20480, (const char*)g_YT + (size_t)a * 81920 + p * 20480, 20480, sb + HB_A + p * 8);
            if (p == 0) { mbar_wait(sb + HB_LN, (n - 1) & 1); red_release(g_flag + F_X + layer * 128 + a - (nh >> 2)); }
        }
        if (p == 0) { mbar_wait(sb + HB_LN, (n - 1) & 1); red_release(g_flag + F_X + layer * 128 + (j >> 2) + (n - 1) * (nh >> 2)); }
    }
    __syncwarp();
    if (layer == 0 && w == 8 && lane == 0) wait_flag<400>(g_flag + F_W, 96);
    __syncwarp();
    bar_sync(3, 384);
    if (p == 3 && lane == 0 && j < (nh & ~3)) red_release(g_flag + F_X + layer * 128 + 64);
    fence_async_smem();
    Flag* oflag = g_flag + F_O + layer * 32;
    if (j < na) {
        int sl = p & 1, ph = 1;
        for (int idx = j + (p & 1) * na; idx < (NSEG - 1) * 32 && p >= 2 && lane == 0; idx += 2 * na) {
            mbar_wait(sb + HB_DONE + sl * 8, ph ^ 1);
            mbar_arrive(sb + HB_FREE + sl * 8);
            red_release(oflag + (idx >> 6));
            atomicAdd(&g_flag[layer * NSEG * 32 + idx].v, 1u);
            sl += 2;
            if (sl >= 6) { sl -= 6; ph ^= 1; }
        }
        for (int idx = j + p * na; idx < (NSEG - 1) * 32 && p < 2 && lane == 0; idx += 2 * na) {
            mbar_wait(sb + HB_FREE + sl * 8, ph);
            wait_flag<ITEM_NS>(g_flag + layer * NSEG * 32 + idx, 6);
            fence_async_glb();
            if (idx < (NSEG - 2) * 32) __nanosleep(IDL);
            mbar_expect(sb + HB_FULL + sl * 8, 30720);
            bulk_g2s(sb + sl * 30720, g_item + (size_t)(idx % (RING * 32)) * 32768, 30720, sb + HB_FULL + sl * 8);
            sl += 2;
            if (sl >= 6) { sl -= 6; ph ^= 1; }
        }
    } else if (lane == 0 && p == 3) {
        if (layer == 0) {
            wait_flag<1000>(oflag + PFW_AT, 64);
            const int np = nh - na;
#pragma unroll 1
            for (int i = j - na; i < 1280; i += np) {
                const bf16* W = i < 320 ? Wq : i < 640 ? Wk : i < 960 ? Wv : Wo;
                prefetch_l2((const char*)W + (size_t)(i % 320) * 16384, 16384);
                __nanosleep(PFW_NS);
            }
#pragma unroll 1
            for (int i = j - na; i < 205; i += np) {
                const char* p_ = i < 160 ? (const char*)g_Wf + i * 16384 : i < 165 ? (const char*)g_stat + (i - 144) * 16384
                               : i < 167 ? (const char*)g_ctab + (i - 165) * 8192 : (const char*)(g_flag + NFLAG) - (i - 166) * 16384;
                prefetch_l2(p_, 16384);
                __nanosleep(PFW_NS);
            }
            if (j - na < 16) prefetch_l2(g_rtab + (j - na) * (RF_A / 4), RF_A / 4);
#pragma unroll 1
            for (int i = j - na; i < 130; i += np) { prefetch_l2((const char*)g_xb + i * 16384, 16384); __nanosleep(PFW_NS); }
        }
    } else if (lane == 0) {
        if (p == 2) wait_flag<500>(g_flag + F_X + layer * 128 + 64, nh & ~3);
        int c0 = 0;
        for (int mb = (j - na) >> 3; mb < nbh; mb += (nh - na) >> 3, c0 += GNC) {
            if (p < 2) wait_flag<300>(oflag + 2 * mb + p, 64);
            fence_async_glb();
            oproj_load(sb, p, mb, (j - na) & 7, c0, nh - na < 24 ? 0 : mb == nbh - 1 ? GPACE2 : GPACE);
        }
    }
}
__device__ __forceinline__ void helper_mma(char* sm, const int jh, const int nh, const int na, const int nbh, const int layer, const bf16* res, bf16* x,
                                           bf16* out) {
    const uint32_t sb = smem_u32(sm);
    const int tid = threadIdx.x, w = tid >> 5, lane = tid & 31;
    const bool act = jh < (nh & ~3);
    const int j4 = jh & 3;
    const int fr = tid & 63, rg = w >> 1;
    auto chunk0 = [&](int u) { return u == 0 ? 5 * j4 : u == 1 ? 75 - 5 * j4 : u == 2 ? 40 + 5 * j4 : 35 - 5 * j4; };
    const int gr = tid / 20, gq_ = tid - gr * 20, go = gr * 80 + chunk0(gq_ / 5) + gq_ % 5;
    const uint32_t gs = sb + RI_RES + gr * 336 + gq_ * 16;
    auto residual = [&](int a, int n) {
#pragma unroll 1
        for (int r = 0; r < 64 - gr && tid < 240 && a < 32; r += 12) cp_async16(gs + (n & 1) * 21504 + r * 336, (const uint4*)res + (a * 64 + r) * 80 + go);
        cp_commit();
    };
    if (act) {
        if (tid < 240) {
            const int k0 = tid / 48, n = tid - k0 * 48;
            const float d = (float)(40 * j4 + n), amp = 2.f * 0.03952847075210474f;
#pragma unroll 4
            for (int u = 0; u < 16; u++)
                *(uint4*)(sm + RI_TAB + (tid + u * 240) * 16) = cos_row8(fmaf((float)((k0 + (u & 3) * 5) * 16 + ((u >> 2) & 1)), d, (float)((u & 8) * 20)), 2.f * d, amp);
            if (tid < 96) *(uint4*)(sm + RI_TAB + (3840 + tid) * 16) = make_uint4(k0 == 0 ? pack_h((n & 1) ? -amp : amp, 0.f) : 0u, 0, 0, 0);
        }
        fence_async_smem();
        residual(jh >> 2, 0);
    }
    bar_sync(1, 384);
    if (layer == TLL) TL(36);
    if (act) {
        const float4 wm = ((const float4*)g_wmax)[lane];
        const int wg = w >> 2;
        int n = 0;
#pragma unroll 1
        for (int a = jh >> 2; a < 32; a += nh >> 2, n++) {
            float acc[2][24];
            uint64_t da = mkdesc(sb + RI_A + wg * 40960, 1024, 1024, 1), db = mkdesc(sb + RI_TAB + wg * 30720, 768, 128, 0);
#pragma unroll
            for (int gq = 0; gq < 2; gq++) {
                mbar_wait(sb + HB_A + (wg * 2 + gq) * 8, n & 1);
                if (layer == TLL && n == TLN && gq == 0) TL(45);
                wg_fence();
#pragma unroll 5
                for (int k = 0; k < 10; k++) { wg_n48_ss_ta(acc[gq], da, db, k); da += 128; db += 96; }
                wg_commit();
            }
            if (wg == 0) {
                mbar_wait(sb + HB_A + 16, n & 1);
                wg_fence();
                wg_n48_ss_ta(acc[0], da, db + 20 * 96, 1);
                wg_commit();
            }
            float inv;
            pow2_scale(__uint_as_float(__reduce_max_sync(~0u, __float_as_uint(fmaxf(fmaxf(wm.x, wm.y), fmaxf(wm.z, wm.w))))), 0, &inv);
            const uint32_t ysc = pack_bf(inv, inv);
            wg_wait<0>();
            if (layer == TLL && n == TLN) TL(46);
            if (lane == 0) mbar_arrive(sb + HB_AFREE);
            const uint32_t ad = sb + RI_STG + ((w & 3) * 16 + (lane & 15)) * 400 + (lane >> 4) * 96 + wg * 192;
#pragma unroll
            for (int q = 0; q < 6; q++) {
                const float *e = acc[0] + q * 4, *o = acc[1] + q * 4;
                stsm4(ad + q * 16, pack_h(e[0] + o[0], e[1] + o[1]), pack_h(e[2] + o[2], e[3] + o[3]), pack_h(e[0] - o[0], e[1] - o[1]), pack_h(e[2] - o[2], e[3] - o[3]));
            }
            cp_wait<0>();
            bar_sync(4, 256);
            const uint32_t xa = sb + RI_RES + (n & 1) * 21504 + fr * 336 + rg * 80, sg = (rg & 1) ? 0xbc00bc00u : 0x3c003c00u;
            float sum = 0.f, sq = 0.f;
            uint32_t ya = sb + RI_STG + fr * 400 + (rg >> 1) * 96 + ((rg & 1) ? 64 : 0), carry;
            asm("fma.rn.f16x2 %0,%1,%2,%3;" : "=r"(carry) : "r"(lds32(ya + 208)), "r"(sg), "r"(lds32(ya + 16)));
#pragma unroll 1
            for (int ch = 0; ch < 5; ch++, ya += (rg & 1) ? -16 : 16) {
                uint32_t y[4], z[4], xr[4];
                lds128(y, ya); lds128(z, ya + 192); lds128(xr, xa + ch * 16);
#pragma unroll
                for (int q = 0; q < 4; q++) asm("fma.rn.f16x2 %0,%1,%2,%0;" : "+r"(y[q]) : "r"(z[q]), "r"(sg));
                if (rg & 1) {
                    const uint32_t y0 = y[0], y1 = y[1];
                    y[0] = __byte_perm(carry, y[3], 0x7610); y[1] = __byte_perm(y[3], y[2], 0x7610);
                    y[3] = __byte_perm(y1, y0, 0x7610); y[2] = __byte_perm(y[2], y1, 0x7610);
                    carry = y0;
                }
#pragma unroll
                for (int q = 0; q < 4; q++) {
                    const float2 yf = __half22float2(*(const __half2*)&y[q]);
                    xr[q] = bfma(pack_bf(yf.x, yf.y), ysc, xr[q]);
                    const float e = bf_lo(xr[q]), f = bf_hi(xr[q]);
                    sum += e + f; sq = fmaf(e, e, fmaf(f, f, sq));
                }
                sts128(xa + ch * 16, xr[0], xr[1], xr[2], xr[3]);
            }
            uint2* stat = g_stat + (size_t)(layer * 32 + a) * 1024 + rg * 64 + fr;
            asm volatile("st.relaxed.gpu.global.v2.u32 [%0],{%1,%2};" ::"l"(stat + j4 * 256), "r"(__float_as_uint(sum)), "r"(__float_as_uint(sq) | 0x80000000u) : "memory");
            if (layer == TLL && n == TLN) TL(47);
            uint32_t s0[3], s1[3];
            int lim = 0;
            do {
#pragma unroll
                for (int q = 0; q < 3; q++)
                    asm volatile("ld.relaxed.gpu.global.v2.u32 {%0,%1},[%2];" : "=r"(s0[q]), "=r"(s1[q]) : "l"(stat + ((j4 + 1 + q) & 3) * 256) : "memory");
            } while (__any_sync(~0u, (int)(s1[0] & s1[1] & s1[2]) >= 0) && ++lim < SPIN_LIM);
#pragma unroll
            for (int q = 0; q < 3; q++) { sum += __uint_as_float(s0[q]); sq -= __uint_as_float(s1[q]); }
            sts64(sb + RI_ST + tid * 8, __float_as_uint(sum), __float_as_uint(sq));
            bar_sync(4, 256);
            if (layer == TLL && n == TLN) TL(48);
#pragma unroll
            for (int q = 1; q < 4; q++) {
                uint32_t st2[2];
                lds64(st2, sb + RI_ST + ((tid + q * 64) & 255) * 8);
                sum += __uint_as_float(st2[0]); sq += __uint_as_float(st2[1]);
            }
            const float mean = sum * (1.f / 640.f), r = rsqrtf(fmaxf(fmaf(-mean, mean, sq * (1.f / 640.f)), 0.f) + 1e-5f), off = -mean * r;
            uint4* dst = (uint4*)g_xn + ((size_t)(2 * a + (w & 1)) * 80 + chunk0(rg)) * 32 + lane;
#pragma unroll
            for (int i = 0; i < 5; i++) {
                uint32_t u[4];
                lds128(u, xa + i * 16);
                dst[i * 32] = make_uint4(pack_h(fmaf(bf_lo(u[0]), r, off), fmaf(bf_hi(u[0]), r, off)), pack_h(fmaf(bf_lo(u[1]), r, off), fmaf(bf_hi(u[1]), r, off)),
                                         pack_h(fmaf(bf_lo(u[2]), r, off), fmaf(bf_hi(u[2]), r, off)), pack_h(fmaf(bf_lo(u[3]), r, off), fmaf(bf_hi(u[3]), r, off)));
            }
            __syncwarp();
            if (lane == 0) mbar_arrive(sb + HB_LN);
            if (layer == TLL) TL(37);
            if (layer == TLL && n == TLN) TL(44);
            residual(a + (nh >> 2), n + 1);
#pragma unroll 2
            for (int rr = 0; rr < 64 - gr && tid < 240; rr += 12) {
                uint32_t v[4];
                lds128(v, gs + (n & 1) * 21504 + rr * 336);
                ((uint4*)x)[(a * 64 + rr) * 80 + go] = make_uint4(v[0], v[1], v[2], v[3]);
            }
        }
    }
    bar_sync(3, 384);
    if (layer == TLL) TL(38);
    if (jh >= na) {
        int c0 = 0;
#pragma unroll 1
        for (int mb = (jh - na) >> 3; mb < nbh; mb += (nh - na) >> 3, c0 += GNC) oproj_mma(sb, mb, (jh - na) & 7, c0, x, out, layer);
        if (layer == TLL) TL(42);
        return;
    }
    const int p = w >> 1, mi = w & 1;
    int slot = p, ph = 0;
    for (int idx = jh + p * na; idx < (NSEG - 1) * 32; idx += 4 * na) {
        const uint32_t it = sb + slot * 30720 + lane * 16;
        float iq, ik, iv;
        weight_scale(idx & 31, 0, &iq); weight_scale(idx & 31, 1, &ik); weight_scale(idx & 31, 2, &iv);
        bar_sync(6 + p, 64);
        mbar_wait(sb + HB_DONE + slot * 8, ph ^ 1);
        mbar_wait(sb + HB_FULL + slot * 8, ph);
        tok_attention<8, 8>(it, 8192, it + 24576, 2048, it + 16384, it - lane * 8 + 28672, 0, mi, lane, idx >> 5, idx & 31, iq * ik, iv);
        __syncwarp();
        if (lane == 0) mbar_arrive(sb + HB_DONE + slot * 8);
        slot += 4;
        if (slot >= 6) { slot -= 6; ph ^= 1; }
    }
    if (layer == TLL) TL(39);
}

template <int layer> __global__ void __cluster_dims__(3, 1, 1) __launch_bounds__(384, 1)
k_chain(const int nact, const uint32_t zero, const bf16* __restrict__ Wq, const bf16* __restrict__ Wk, const bf16* __restrict__ Wv,
        const bf16* __restrict__ Wo, const bf16* res, bf16* out) {
    extern __shared__ __align__(1024) char sm[];
    const uint32_t sb = smem_u32(sm);
    const int b = blockIdx.x, h = b / 3, c = b - h * 3;
    pdl_go();
    if (threadIdx.x >= 256) {
        asm volatile("setmaxnreg.dec.sync.aligned.u32 24;");
        TL(11 + layer * 14);
        chain_aux<layer>(sb, c, h, nact);
    } else {
        asm volatile("setmaxnreg.inc.sync.aligned.u32 240;");
        chain_mma<layer>(sb, c, h, zero, Wq, Wk, Wv, Wo, res, out);
    }
}
__global__ void __launch_bounds__(384, 1) k_help(const bf16* res, bf16* x, bf16* out, const int layer, const int na, const int nbh, const int zero, const bf16* Wq,
                                                  const bf16* Wk, const bf16* Wv, const bf16* Wo) {
    extern __shared__ __align__(1024) char sm[];
    if (layer == TLL) TL(51);
    pdl_go();
    if (threadIdx.x >= 256) {
        const uint32_t sb = smem_u32(sm);
        const int p = (threadIdx.x >> 5) - 8, i = (threadIdx.x & 31) * 4 + p;
        if (i < 34) mbar_init(sb + G_BAR + i * 8, i < 4 ? 3 : i < 8 || i == 12 || i == 13 ? 8 : i >= 22 && i < 28 ? 2 : 1);
        fence_async_smem();
        wait_flag<100>(g_flag + F_X + layer * 128 + 65, 1);
        fence_async_glb();
        if (i == 8 + p && blockIdx.x < (gridDim.x & ~3)) {
            mbar_expect(sb + HB_A + p * 8, 20480);
            bulk_g2s(sb + RI_A + p * 20480, (const char*)g_YT + (size_t)(blockIdx.x >> 2) * 81920 + p * 20480, 20480, sb + HB_A + p * 8);
        }
        __syncwarp();
        bar_sync(2, 128);
        bar_arrive(1, 384);
    }
    if (threadIdx.x + zero >= 256) helper_aux(smem_u32(sm), blockIdx.x, gridDim.x, na, nbh, layer, Wq, Wk, Wv, Wo);
    else helper_mma(sm, blockIdx.x, gridDim.x, na, nbh, layer, res, x, out);
    __syncwarp();
    if (blockIdx.x == 0) pdl_wait();
}

#define COL_PAD 15872
template <class... P, class... A>
void launch_pdl(void (*k)(P...), int grid, int block, int smem, cudaStream_t st, A... args) {
    cudaLaunchConfig_t cfg = {};
    cfg.gridDim = dim3(grid); cfg.blockDim = dim3(block); cfg.dynamicSmemBytes = smem; cfg.stream = st;
    cudaLaunchAttribute at[1];
    at[0].id = cudaLaunchAttributeProgrammaticStreamSerialization; at[0].val.programmaticStreamSerializationAllowed = 1;
    cfg.attrs = at;
    cfg.numAttrs = 1;
    cudaLaunchKernelEx(&cfg, k, args...);
}

}

extern "C" void kernel_launch(void* const* d_in, const int* in_sizes, int n_in, void* d_out, int out_size) {
    const bf16* x = (const bf16*)d_in[0];
    const bf16* wr = (const bf16*)d_in[1];
    const bf16* wi = (const bf16*)d_in[2];
    const bf16* mem0 = (const bf16*)d_in[4];
    const bf16* Wq = (const bf16*)d_in[5];
    const bf16* Wk = (const bf16*)d_in[6];
    const bf16* Wv = (const bf16*)d_in[7];
    const bf16* Wo = (const bf16*)d_in[8];
    bf16* out = (bf16*)d_out;
    static int nhelp = 0;
    static bf16 *xa, *xb;
    static cudaStream_t s1;
    static cudaEvent_t ev_fork, ev_join;
    if (!nhelp) {
        cudaStreamCreateWithFlags(&s1, cudaStreamNonBlocking);
        cudaEventCreateWithFlags(&ev_fork, cudaEventDisableTiming);
        cudaEventCreateWithFlags(&ev_join, cudaEventDisableTiming);
        cudaFuncSetAttribute(k_setup, cudaFuncAttributeMaxDynamicSharedMemorySize, SU_SMEM);
        cudaFuncSetAttribute(k_rowf<0>, cudaFuncAttributeMaxDynamicSharedMemorySize, RF_SMEM);
        cudaFuncSetAttribute(k_rowf<1>, cudaFuncAttributeMaxDynamicSharedMemorySize, RF_SMEM);
        cudaFuncSetAttribute(k_col, cudaFuncAttributeMaxDynamicSharedMemorySize, COL_PAD);
        cudaFuncSetAttribute(k_chain<0>, cudaFuncAttributeMaxDynamicSharedMemorySize, CH_SMEM);
        cudaFuncSetAttribute(k_chain<1>, cudaFuncAttributeMaxDynamicSharedMemorySize, CH_SMEM);
        cudaFuncSetAttribute(k_setup, cudaFuncAttributePreferredSharedMemoryCarveout, 100);
        cudaFuncSetAttribute(k_rowf<0>, cudaFuncAttributePreferredSharedMemoryCarveout, 100);
        cudaFuncSetAttribute(k_rowf<1>, cudaFuncAttributePreferredSharedMemoryCarveout, 100);
        cudaFuncSetAttribute(k_col, cudaFuncAttributePreferredSharedMemoryCarveout, 100);
        cudaFuncSetAttribute(k_chain<0>, cudaFuncAttributePreferredSharedMemoryCarveout, 100);
        cudaFuncSetAttribute(k_chain<1>, cudaFuncAttributePreferredSharedMemoryCarveout, 100);
        cudaFuncSetAttribute(k_help, cudaFuncAttributeMaxDynamicSharedMemorySize, HP_SMEM);
        cudaFuncSetAttribute(k_help, cudaFuncAttributePreferredSharedMemoryCarveout, 100);
        int dev = 0, sms = 0;
        cudaGetDevice(&dev);
        cudaDeviceGetAttribute(&sms, cudaDevAttrMultiProcessorCount, dev);
        nhelp = sms - 96 < 12 ? 12 : sms - 96;
        cudaGetSymbolAddress((void**)&xa, g_xa);
        cudaGetSymbolAddress((void**)&xb, g_xb);
    }
    const int na = nhelp - (nhelp >= 36 ? 24 : nhelp >= 28 ? 16 : 8), nbh = 14;
    cudaStream_t s0 = cudaStreamPerThread;
    cudaEventRecord(ev_fork, s0);
    cudaStreamWaitEvent(s1, ev_fork, 0);
    k_rowf<1><<<(96 + nhelp) & ~1, 256, RF_SMEM, s0>>>(x);
    k_setup<<<NSETUP, 256, SU_SMEM, s1>>>(wr, wi, mem0);
    cudaEventRecord(ev_join, s1);
#define NLAYER 2
    for (int l = 0; l < NLAYER; l++) {
        const bf16* xin = l == 0 ? x : xb;
        if (l == 1) launch_pdl(k_rowf<0>, 128, 256, RF_SMEM, s0, xin);
        launch_pdl(k_col, 321, 128, l == 0 ? 0 : COL_PAD, s0, (int)(l == 0));
        launch_pdl(l == 0 ? k_chain<0> : k_chain<1>, 96, 384, CH_SMEM, s0, nhelp & ~3, 0u, Wq, Wk, Wv, Wo, (const bf16*)xa, l == 0 ? xb : out);
        launch_pdl(k_help, nhelp, 384, HP_SMEM, s0, xin, xa, l == 0 ? xb : out, l, na, nbh, 0, Wq, Wk, Wv, Wo);
    }
    cudaStreamWaitEvent(s0, ev_join, 0);
}
```

```cpp
#include <cuda_runtime.h>
#include <cuda_bf16.h>
#include <cuda_fp16.h>
#include <stdint.h>
#include <string.h>

namespace {

typedef __nv_bfloat16 bf16;
constexpr int S_ = 2048, D_ = 640, NSEG = 64;
constexpr int SPIN_LIM = 1 << 13;

__device__ float                  g_wmx[96];
__device__ __align__(1024) bf16   g_wot[4096 * 640];
__device__ __align__(16) float    g_co[1024];
__device__ __align__(256) uint2   g_stat[2 * 32 * 16 * 64];
__device__ float                  g_invM0;
__device__ __align__(16) float    g_wmax[128];
__device__ __align__(1024) char   g_redraw[65 * 32768];
constexpr int F_X = 2 * NSEG * 32, F_O = F_X + 2 * 128, NFLAG = F_O + 128, RING = 8;
constexpr int F_W = F_X + 66;
constexpr int F_R = F_O + 64;
constexpr int NSETUP = 131;
struct __align__(256) Flag { unsigned v; };
__device__ Flag                   g_flag[NFLAG];
__device__ Flag                   g_ready[1];
__device__ __align__(1024) char   g_item[RING * 32 * 32768];
__device__ __align__(1024) bf16   g_O[S_ * 4096];
__device__ __align__(1024) __half g_xn[S_ * D_];
__device__ __align__(1024) bf16   g_xa[S_ * D_];
__device__ __align__(1024) bf16   g_xb[S_ * D_];
__device__ __align__(1024) __half g_UT[D_ * S_];
__device__ __align__(1024) __half g_YT[D_ * S_];
__device__ __align__(1024) __half g_ctab[64 * 128 + 64 * 64];
__device__ __align__(1024) uint32_t g_Wf[321 * 2048];

#define TL(i)
#define TLN 0
#define TLL 1
#define CK(i)
__device__ __forceinline__ uint32_t smem_u32(const void* p) { return (uint32_t)__cvta_generic_to_shared(p); }
__device__ __forceinline__ uint32_t mapa(uint32_t a, uint32_t r) { uint32_t o; asm("mapa.shared::cluster.u32 %0,%1,%2;" : "=r"(o) : "r"(a), "r"(r)); return o; }
__device__ __forceinline__ void mbar_init(uint32_t a, int c) { asm volatile("mbarrier.init.shared::cta.b64 [%0],%1;" ::"r"(a), "r"(c) : "memory"); }
__device__ __forceinline__ void mbar_expect(uint32_t a, int bytes) { asm volatile("mbarrier.arrive.expect_tx.shared::cta.b64 _,[%0],%1;" ::"r"(a), "r"(bytes) : "memory"); }
__device__ __forceinline__ void mbar_arrive(uint32_t a) { asm volatile("mbarrier.arrive.shared::cta.b64 _,[%0];" ::"r"(a) : "memory"); }
__device__ __forceinline__ bool mbar_try(uint32_t a, uint32_t par) {
    uint32_t p;
    asm volatile("{.reg .pred q; mbarrier.try_wait.parity.shared::cta.b64 q,[%1],%2; selp.u32 %0,1,0,q;}" : "=r"(p) : "r"(a), "r"(par) : "memory");
    return p;
}
__device__ __forceinline__ void mbar_wait(uint32_t a, uint32_t par) {
    if (!mbar_try(a, par)) {
        int lim = 0;
        while (!mbar_try(a, par) && ++lim < SPIN_LIM) {}
    }
}
__device__ __forceinline__ void mbar_sleep(uint32_t a, uint32_t par) {
    asm volatile("{.reg .pred q; .reg .u32 n; mov.u32 n,0;\n"
                 "W_LOOP: mbarrier.try_wait.parity.shared::cta.b64 q,[%0],%1,%2; add.u32 n,n,1; setp.lt.and.u32 q,n,%3,!q; @q bra W_LOOP;}"
                 ::"r"(a), "r"(par), "n"(20000), "n"(SPIN_LIM) : "memory");
}
__device__ __forceinline__ void bar_arrive(int id, int n) { asm volatile("bar.arrive %0,%1;" ::"r"(id), "r"(n) : "memory"); }
__device__ __forceinline__ uint32_t clock32() { uint32_t c; asm volatile("mov.u32 %0,%%clock;" : "=r"(c)); return c; }
__device__ __forceinline__ uint32_t read_tid() { uint32_t v; asm volatile("mov.u32 %0,%%tid.x;" : "=r"(v)); return v; }
__device__ __forceinline__ void bar_sync(int id, int n) { asm volatile("bar.sync %0,%1;" ::"r"(id), "r"(n) : "memory"); }
__device__ __forceinline__ void fence_async_smem() { asm volatile("fence.proxy.async.shared::cta;" ::: "memory"); }
__device__ __forceinline__ void fence_async_glb() { asm volatile("fence.proxy.async.global;" ::: "memory"); }
__device__ __forceinline__ void cluster_sync_full() { asm volatile("barrier.cluster.arrive.aligned; barrier.cluster.wait.aligned;" ::: "memory"); }
__device__ __forceinline__ void bulk_g2s(uint32_t dst, const void* src, int bytes, uint32_t mb) {
    asm volatile("cp.async.bulk.shared::cluster.global.mbarrier::complete_tx::bytes [%0],[%1],%2,[%3];" ::"r"(dst), "l"(src), "r"(bytes), "r"(mb) : "memory");
}
__device__ __forceinline__ void bulk_g2s_last(uint32_t dst, const void* src, int bytes, uint32_t mb) {
    asm volatile("{.reg .b64 p; createpolicy.fractional.L2::evict_first.b64 p, 1.0;\n"
                 "cp.async.bulk.shared::cluster.global.mbarrier::complete_tx::bytes.L2::cache_hint [%0],[%1],%2,[%3],p;}"
                 ::"r"(dst), "l"(src), "r"(bytes), "r"(mb) : "memory");
}
__device__ __forceinline__ void bulk_s2s(uint32_t dst, uint32_t src, int bytes, uint32_t mb) {
    asm volatile("cp.async.bulk.shared::cluster.shared::cta.mbarrier::complete_tx::bytes [%0],[%1],%2,[%3];" ::"r"(dst), "r"(src), "r"(bytes), "r"(mb) : "memory");
}
__device__ __forceinline__ void bulk_s2g(void* dst, uint32_t src, int bytes) {
    asm volatile("cp.async.bulk.global.shared::cta.bulk_group [%0],[%1],%2;" ::"l"(dst), "r"(src), "r"(bytes) : "memory");
}
__device__ __forceinline__ void cp_async16(uint32_t dst, const void* src, uint32_t bytes = 16) {
    asm volatile("cp.async.cg.shared.global [%0],[%1],16,%2;" ::"r"(dst), "l"(src), "r"(bytes) : "memory");
}
__device__ __forceinline__ void cp_commit() { asm volatile("cp.async.commit_group;" ::: "memory"); }
template <int N> __device__ __forceinline__ void cp_wait() { asm volatile("cp.async.wait_group %0;" ::"n"(N) : "memory"); }
__device__ __forceinline__ void bulk_commit() { asm volatile("cp.async.bulk.commit_group;" ::: "memory"); }
__device__ __forceinline__ void bulk_wait0() { asm volatile("cp.async.bulk.wait_group 0;" ::: "memory"); }
__device__ __forceinline__ void ldsm4(uint32_t* r, uint32_t a) {
    asm volatile("ldmatrix.sync.aligned.m8n8.x4.shared.b16 {%0,%1,%2,%3},[%4];" : "=r"(r[0]), "=r"(r[1]), "=r"(r[2]), "=r"(r[3]) : "r"(a) : "memory");
}
__device__ __forceinline__ void ldsm4t(uint32_t* r, uint32_t a) {
    asm volatile("ldmatrix.sync.aligned.m8n8.x4.trans.shared.b16 {%0,%1,%2,%3},[%4];" : "=r"(r[0]), "=r"(r[1]), "=r"(r[2]), "=r"(r[3]) : "r"(a) : "memory");
}
__device__ __forceinline__ void stsm4(uint32_t a, uint32_t r0, uint32_t r1, uint32_t r2, uint32_t r3) {
    asm volatile("stmatrix.sync.aligned.m8n8.x4.shared.b16 [%0],{%1,%2,%3,%4};" ::"r"(a), "r"(r0), "r"(r1), "r"(r2), "r"(r3) : "memory");
}
__device__ __forceinline__ void stsm4t(uint32_t a, uint32_t r0, uint32_t r1, uint32_t r2, uint32_t r3) {
    asm volatile("stmatrix.sync.aligned.m8n8.x4.trans.shared.b16 [%0],{%1,%2,%3,%4};" ::"r"(a), "r"(r0), "r"(r1), "r"(r2), "r"(r3) : "memory");
}
__device__ __forceinline__ void lds128(uint32_t* r, uint32_t a) {
    asm volatile("ld.shared.v4.b32 {%0,%1,%2,%3},[%4];" : "=r"(r[0]), "=r"(r[1]), "=r"(r[2]), "=r"(r[3]) : "r"(a) : "memory");
}
__device__ __forceinline__ void lds64(uint32_t* r, uint32_t a) {
    asm volatile("ld.shared.v2.b32 {%0,%1},[%2];" : "=r"(r[0]), "=r"(r[1]) : "r"(a) : "memory");
}
__device__ __forceinline__ uint32_t lds32(uint32_t a) { uint32_t v; asm volatile("ld.shared.b32 %0,[%1];" : "=r"(v) : "r"(a) : "memory"); return v; }
__device__ __forceinline__ void sts128(uint32_t a, uint32_t r0, uint32_t r1, uint32_t r2, uint32_t r3) {
    asm volatile("st.shared.v4.b32 [%0],{%1,%2,%3,%4};" ::"r"(a), "r"(r0), "r"(r1), "r"(r2), "r"(r3) : "memory");
}
__device__ __forceinline__ void sts64(uint32_t a, uint32_t v0, uint32_t v1) { asm volatile("st.shared.v2.b32 [%0],{%1,%2};" ::"r"(a), "r"(v0), "r"(v1) : "memory"); }
[[maybe_unused]] __device__ __forceinline__ void sts32(uint32_t a, uint32_t v) { asm volatile("st.shared.b32 [%0],%1;" ::"r"(a), "r"(v) : "memory"); }
#define AU_(op) "{.reg .u32 t; add.u32 t,%4,%5; " op " {%0,%1,%2,%3},[t+%6];}"
template <int I> __device__ __forceinline__ void ldsm4_u(uint32_t* r, uint32_t a, uint32_t u) {
    asm volatile(AU_("ldmatrix.sync.aligned.m8n8.x4.shared.b16") : "=r"(r[0]), "=r"(r[1]), "=r"(r[2]), "=r"(r[3]) : "r"(a), "r"(u), "n"(I) : "memory");
}
template <int I> __device__ __forceinline__ void ldsm4t_u(uint32_t* r, uint32_t a, uint32_t u) {
    asm volatile(AU_("ldmatrix.sync.aligned.m8n8.x4.trans.shared.b16") : "=r"(r[0]), "=r"(r[1]), "=r"(r[2]), "=r"(r[3]) : "r"(a), "r"(u), "n"(I) : "memory");
}
template <int I> __device__ __forceinline__ void lds128_u(uint32_t* r, uint32_t a, uint32_t u) {
    asm volatile(AU_("ld.shared.v4.b32") : "=r"(r[0]), "=r"(r[1]), "=r"(r[2]), "=r"(r[3]) : "r"(a), "r"(u), "n"(I) : "memory");
}
template <int I> __device__ __forceinline__ void lds64_u(uint32_t* r, uint32_t a, uint32_t u) {
    asm volatile("{.reg .u32 t; add.u32 t,%2,%3; ld.shared.v2.b32 {%0,%1},[t+%4];}" : "=r"(r[0]), "=r"(r[1]) : "r"(a), "r"(u), "n"(I) : "memory");
}
template <int I> __device__ __forceinline__ uint32_t lds32_u(uint32_t a, uint32_t u) {
    uint32_t v;
    asm volatile("{.reg .u32 t; add.u32 t,%1,%2; ld.shared.b32 %0,[t+%3];}" : "=r"(v) : "r"(a), "r"(u), "n"(I) : "memory");
    return v;
}
template <int I> __device__ __forceinline__ void sts64_u(uint32_t a, uint32_t u, uint32_t v0, uint32_t v1) {
    asm volatile("{.reg .u32 t; add.u32 t,%0,%1; st.shared.v2.b32 [t+%2],{%3,%4};}" ::"r"(a), "r"(u), "n"(I), "r"(v0), "r"(v1) : "memory");
}
template <int I> __device__ __forceinline__ void sts32_u(uint32_t a, uint32_t u, uint32_t v) {
    asm volatile("{.reg .u32 t; add.u32 t,%0,%1; st.shared.b32 [t+%2],%3;}" ::"r"(a), "r"(u), "n"(I), "r"(v) : "memory");
}
template <int I> __device__ __forceinline__ void sts16_u(uint32_t a, uint32_t u, uint32_t v) {
    asm volatile("{.reg .u32 t; add.u32 t,%0,%1; st.shared.b16 [t+%2],%3;}" ::"r"(a), "r"(u), "n"(I), "h"((unsigned short)v) : "memory");
}
template <int I> __device__ __forceinline__ void sts128_u(uint32_t a, uint32_t u, uint32_t r0, uint32_t r1, uint32_t r2, uint32_t r3) {
    asm volatile("{.reg .u32 t; add.u32 t,%0,%1; st.shared.v4.b32 [t+%2],{%3,%4,%5,%6};}" ::"r"(a), "r"(u), "n"(I), "r"(r0), "r"(r1), "r"(r2), "r"(r3) : "memory");
}
template <int I> __device__ __forceinline__ void stsm4_u(uint32_t a, uint32_t u, uint32_t r0, uint32_t r1, uint32_t r2, uint32_t r3) {
    asm volatile("{.reg .u32 t; add.u32 t,%0,%1; stmatrix.sync.aligned.m8n8.x4.shared.b16 [t+%2],{%3,%4,%5,%6};}"
                 ::"r"(a), "r"(u), "n"(I), "r"(r0), "r"(r1), "r"(r2), "r"(r3) : "memory");
}
__device__ __forceinline__ void st_share2(uint32_t a, uint32_t u, uint32_t mb, uint32_t d0, uint32_t d1, uint32_t v0, uint32_t v1) {
    asm volatile("{.reg .pred p; .reg .u32 t,x,y; add.u32 t,%0,%1;\n"
                 "add.u32 x,t,%3; add.u32 y,%2,%3; st.async.shared::cluster.mbarrier::complete_tx::bytes.v2.b32 [x],{%5,%6},[y];\n"
                 "add.u32 x,t,%4; add.u32 y,%2,%4; st.async.shared::cluster.mbarrier::complete_tx::bytes.v2.b32 [x],{%5,%6},[y];\n"
                 "st.shared.v2.b32 [t],{%5,%6}; bar.warp.sync -1; setp.eq.u32 p,%0,0; @p mbarrier.arrive.shared::cta.b64 _,[%2];}"
                 ::"r"(a), "r"(u), "r"(mb), "r"(d0), "r"(d1), "r"(v0), "r"(v1) : "memory");
}
template <int V> struct IC { __host__ __device__ constexpr operator int() const { return V; } };
template <int N, class F> __device__ __forceinline__ void sfor(F f) {
    if constexpr (N > 0) { sfor<N - 1>(f); f(IC<N - 1>()); }
}
__device__ __forceinline__ void mma_f16(float* d, const uint32_t* a, uint32_t b0, uint32_t b1) {
    asm volatile("mma.sync.aligned.m16n8k16.row.col.f32.f16.f16.f32 {%0,%1,%2,%3},{%4,%5,%6,%7},{%8,%9},{%0,%1,%2,%3};"
                 : "+f"(d[0]), "+f"(d[1]), "+f"(d[2]), "+f"(d[3]) : "r"(a[0]), "r"(a[1]), "r"(a[2]), "r"(a[3]), "r"(b0), "r"(b1));
}
__device__ __forceinline__ void mma_bf(float* d, uint32_t a0, uint32_t a1, uint32_t a2, uint32_t a3, uint32_t b0, uint32_t b1) {
    asm volatile("mma.sync.aligned.m16n8k16.row.col.f32.bf16.bf16.f32 {%0,%1,%2,%3},{%4,%5,%6,%7},{%8,%9},{%0,%1,%2,%3};"
                 : "+f"(d[0]), "+f"(d[1]), "+f"(d[2]), "+f"(d[3]) : "r"(a0), "r"(a1), "r"(a2), "r"(a3), "r"(b0), "r"(b1));
}
__device__ __forceinline__ void mma_bf8(float* d, uint32_t a0, uint32_t a1, uint32_t b0) {
    asm volatile("mma.sync.aligned.m16n8k8.row.col.f32.bf16.bf16.f32 {%0,%1,%2,%3},{%4,%5},{%6},{%0,%1,%2,%3};"
                 : "+f"(d[0]), "+f"(d[1]), "+f"(d[2]), "+f"(d[3]) : "r"(a0), "r"(a1), "r"(b0));
}
__device__ __forceinline__ uint32_t pack_bf(float lo, float hi) { uint32_t r; asm("cvt.rn.bf16x2.f32 %0,%1,%2;" : "=r"(r) : "f"(hi), "f"(lo)); return r; }
__device__ __forceinline__ uint32_t pack_h(float lo, float hi) { uint32_t r; asm("cvt.rn.f16x2.f32 %0,%1,%2;" : "=r"(r) : "f"(hi), "f"(lo)); return r; }
__device__ __forceinline__ float bf_lo(uint32_t v) { return __uint_as_float(v << 16); }
__device__ __forceinline__ float bf_hi(uint32_t v) { return __uint_as_float(v & 0xffff0000u); }
__device__ __forceinline__ uint32_t bfma(uint32_t a, uint32_t b, uint32_t c) { uint32_t r; asm("fma.rn.bf16x2 %0,%1,%2,%3;" : "=r"(r) : "r"(a), "r"(b), "r"(c)); return r; }
__device__ __forceinline__ uint4 add_bf8(const uint4 x, const uint32_t* y, const uint32_t k = 0x3f803f80u) {
    return make_uint4(bfma(y[0], k, x.x), bfma(y[1], k, x.y), bfma(y[2], k, x.z), bfma(y[3], k, x.w));
}
__device__ __forceinline__ float ex2(float x) { float r; asm("ex2.approx.ftz.f32 %0,%1;" : "=f"(r) : "f"(x)); return r; }
__device__ __forceinline__ float rcp(float x) { float r; asm("rcp.approx.ftz.f32 %0,%1;" : "=f"(r) : "f"(x)); return r; }
__device__ __forceinline__ void wg_fence() { asm volatile("wgmma.fence.sync.aligned;" ::: "memory"); }
__device__ __forceinline__ void wg_commit() { asm volatile("wgmma.commit_group.sync.aligned;" ::: "memory"); }
template <int N> __device__ __forceinline__ void wg_wait() { asm volatile("wgmma.wait_group.sync.aligned %0;" ::"n"(N) : "memory"); }
__device__ __forceinline__ uint64_t mkdesc(uint32_t a, uint32_t lbo, uint32_t sbo, uint32_t sw) {
    return (uint64_t)((a & 0x3FFFF) >> 4) | ((uint64_t)(lbo >> 4) << 16) | ((uint64_t)(sbo >> 4) << 32) | ((uint64_t)sw << 62);
}
#define F4(d, i) "+f"(d[i]), "+f"(d[i + 1]), "+f"(d[i + 2]), "+f"(d[i + 3])
#define F8(d, i) F4(d, i), F4(d, i + 4)
#define F16(d, i) F8(d, i), F8(d, i + 8)
template <int OFF, int SC> __device__ __forceinline__ void wg_n32_x(float* d, const uint32_t* a, uint32_t lo) {
    asm volatile("{.reg .pred p; .reg .b32 l; .reg .b64 q; setp.ne.b32 p,%22,0; add.u32 l,%20,%21; mov.b64 q,{l,8};\n"
                 "wgmma.mma_async.sync.aligned.m64n32k16.f32.f16.f16 "
                 "{%0,%1,%2,%3,%4,%5,%6,%7,%8,%9,%10,%11,%12,%13,%14,%15},{%16,%17,%18,%19},q,p,1,1,0;}"
                 : F16(d, 0) : "r"(a[0]), "r"(a[1]), "r"(a[2]), "r"(a[3]), "r"(lo), "n"(OFF), "n"(SC));
}
__device__ __forceinline__ void wg_n128_rs(float* d, const uint32_t* a, uint64_t db, int sc) {
    asm volatile("{.reg .pred p; setp.ne.b32 p,%69,0; wgmma.mma_async.sync.aligned.m64n128k16.f32.f16.f16 "
                 "{%0,%1,%2,%3,%4,%5,%6,%7,%8,%9,%10,%11,%12,%13,%14,%15,%16,%17,%18,%19,%20,%21,%22,%23,%24,%25,%26,%27,%28,%29,%30,%31,"
                 "%32,%33,%34,%35,%36,%37,%38,%39,%40,%41,%42,%43,%44,%45,%46,%47,%48,%49,%50,%51,%52,%53,%54,%55,%56,%57,%58,%59,%60,%61,%62,%63},"
                 "{%64,%65,%66,%67},%68,p,1,1,0;}"
                 : F16(d, 0), F16(d, 16), F16(d, 32), F16(d, 48) : "r"(a[0]), "r"(a[1]), "r"(a[2]), "r"(a[3]), "l"(db), "r"(sc));
}
#define N80_REGS "{%0,%1,%2,%3,%4,%5,%6,%7,%8,%9,%10,%11,%12,%13,%14,%15,%16,%17,%18,%19,%20,%21,%22,%23,%24,%25,%26,%27,%28,%29,%30,%31,%32,%33,%34,%35,%36,%37,%38,%39}"
__device__ __forceinline__ void wg_n80_ss(float* d, uint64_t da, uint64_t db, int sc) {
    asm volatile("{.reg .pred p; setp.ne.b32 p,%42,0; wgmma.mma_async.sync.aligned.m64n80k16.f32.bf16.bf16 " N80_REGS ",%40,%41,p,1,1,0,0;}"
                 : F16(d, 0), F16(d, 16), F8(d, 32) : "l"(da), "l"(db), "r"(sc));
}
__device__ __forceinline__ void wg_n88_ss(float* d, uint64_t da, uint64_t db, int sc) {
    asm volatile("{.reg .pred p; setp.ne.b32 p,%46,0; wgmma.mma_async.sync.aligned.m64n88k16.f32.f16.f16 "
                 "{%0,%1,%2,%3,%4,%5,%6,%7,%8,%9,%10,%11,%12,%13,%14,%15,%16,%17,%18,%19,%20,%21,%22,%23,%24,%25,%26,%27,%28,%29,%30,%31,"
                 "%32,%33,%34,%35,%36,%37,%38,%39,%40,%41,%42,%43},%44,%45,p,1,1,0,0;}"
                 : F16(d, 0), F16(d, 16), F8(d, 32), F4(d, 40) : "l"(da), "l"(db), "r"(sc));
}
__device__ __forceinline__ void wg_n48_ss_ta(float* d, uint64_t da, uint64_t db, int sc) {
    asm volatile("{.reg .pred p; setp.ne.b32 p,%26,0; wgmma.mma_async.sync.aligned.m64n48k16.f32.f16.f16 "
                 "{%0,%1,%2,%3,%4,%5,%6,%7,%8,%9,%10,%11,%12,%13,%14,%15,%16,%17,%18,%19,%20,%21,%22,%23},%24,%25,p,1,1,1,0;}"
                 : F16(d, 0), F8(d, 16) : "l"(da), "l"(db), "r"(sc));
}
template <int TA> __device__ __forceinline__ void wg_n64_ss_tb(float* d, uint64_t da, uint64_t db, int sc) {
    asm volatile("{.reg .pred p; setp.ne.b32 p,%34,0; wgmma.mma_async.sync.aligned.m64n64k16.f32.f16.f16 "
                 "{%0,%1,%2,%3,%4,%5,%6,%7,%8,%9,%10,%11,%12,%13,%14,%15,%16,%17,%18,%19,%20,%21,%22,%23,%24,%25,%26,%27,%28,%29,%30,%31},"
                 "%32,%33,p,1,1,%35,1;}"
                 : F16(d, 0), F16(d, 16) : "l"(da), "l"(db), "r"(sc), "n"(TA));
}
__device__ __forceinline__ void pdl_wait() { asm volatile("griddepcontrol.wait;" ::: "memory"); }
__device__ __forceinline__ void pdl_go() { asm volatile("griddepcontrol.launch_dependents;" ::: "memory"); }
__device__ __forceinline__ float cos640(float p) {
    const float q = fmaf(p, 0.0015625f, 12582912.f) - 12582912.f;
    return __cosf(fmaf(q, -640.f, p) * 0.009817477042468103f);
}
__device__ __forceinline__ uint4 cos_row8(float p0, float step, float amp = 1.f) {
    float v[8];
    const float k = 2.f * cos640(step);
    v[0] = amp * cos640(p0); v[1] = amp * cos640(p0 + step);
#pragma unroll
    for (int i = 2; i < 8; i++) v[i] = fmaf(k, v[i - 1], -v[i - 2]);
    return make_uint4(pack_h(v[0], v[1]), pack_h(v[2], v[3]), pack_h(v[4], v[5]), pack_h(v[6], v[7]));
}
__device__ __forceinline__ float wfilter_max(int lane) {
    float m = fmaxf(fmaxf(g_wmax[lane], g_wmax[lane + 32]), fmaxf(g_wmax[lane + 64], g_wmax[lane + 96]));
    return __uint_as_float(__reduce_max_sync(~0u, __float_as_uint(m)));
}
__device__ __forceinline__ unsigned ld_acquire(const Flag* p) { unsigned v; asm volatile("ld.acquire.gpu.global.u32 %0,[%1];" : "=r"(v) : "l"(p) : "memory"); return v; }
#define POLL_NS 200
template <int NS = POLL_NS> __device__ __forceinline__ void wait_flag(const Flag* p, unsigned v) {
    if (ld_acquire(p) >= v) return;
    unsigned x;
    int lim = 0;
    do {
        __nanosleep(NS);
        asm volatile("ld.relaxed.gpu.global.u32 %0,[%1];" : "=r"(x) : "l"(p) : "memory");
    } while (x < v && ++lim < SPIN_LIM);
    ld_acquire(p);
}
__device__ __forceinline__ void prefetch_l2(const void* p, int bytes) { asm volatile("cp.async.bulk.prefetch.L2.global [%0],%1;" ::"l"(p), "r"(bytes) : "memory"); }
__device__ __forceinline__ void red_release(Flag* p) { asm volatile("red.release.gpu.global.add.u32 [%0],1;" ::"l"(p) : "memory"); }
__device__ __forceinline__ void red_relaxed(Flag* p) { asm volatile("red.relaxed.gpu.global.add.u32 [%0],1;" ::"l"(p) : "memory"); }
__device__ __forceinline__ void red_h8(void* p, uint32_t a, uint32_t b, uint32_t c, uint32_t d) {
    asm volatile("red.relaxed.gpu.global.add.noftz.v4.f16x2 [%0],{%1,%2,%3,%4};" ::"l"(p), "r"(a), "r"(b), "r"(c), "r"(d) : "memory");
}
__device__ __forceinline__ float pow2_scale(float bound, int top, float* inv) {
    int e = (int)((__float_as_uint(bound) >> 23) & 0xff) - 126;
    int k = top - e;
    k = max(-100, min(100, k));
    *inv = __uint_as_float((uint32_t)(127 - k) << 23);
    return __uint_as_float((uint32_t)(127 + k) << 23);
}
__device__ __forceinline__ char* red_base() { return (char*)(((uintptr_t)g_redraw + 32767) & ~(uintptr_t)32767); }

__device__ __forceinline__ void setup_a(char* sm, const int b, const bf16* __restrict__ wr, const bf16* __restrict__ wi) {
    const int tid = threadIdx.x, lane = tid & 31;
    const uint32_t sb = smem_u32(sm);
    auto row_byte = [&](int q) { return ((b >> 2) + 32 * ((q >> 1) * 8 + 2 * (b & 3) + (q & 1))) * 642; };
#pragma unroll 1
    for (int r = tid >> 5; r < 32; r += 8) {
        const char* src = (const char*)(r < 16 ? wr : wi) + (row_byte(r & 15) & ~15);
        cp_async16(sb + r * 672 + lane * 16, src + lane * 16);
        if (lane < 9) cp_async16(sb + r * 672 + 512 + lane * 16, src + 512 + lane * 16);
    }
    ((uint4*)g_stat)[b * 256 + tid] = make_uint4(0, 0, 0, 0);
    if (tid < 2 * (NFLAG / 128)) ((uint4*)(g_flag + b * (NFLAG / 128) + (tid >> 1)))[tid & 1] = make_uint4(0, 0, 0, 0);
    if (tid < 12) {
        const int i = b * 12 + tid;
        const int f = ((i >> 4) & 3) * 8 + (i & 7), im = (i >> 3) & 1, part = (i >> 8) & 1;
        ((uint4*)g_ctab)[i] = cos_row8((float)(i < 1024 ? (i >> 7) * 80 * (i & 63) + ((i & 64) ? 480 : 0) : ((i >> 6) & 3) * 160 * f + (im == part ? 0 : im ? 160 : 480)),
                                       (float)(i < 1024 ? 10 * (i & 63) : 20 * f), i < 1024 ? 0.125f : 0.17677669529663687f);
    }
    asm volatile("cp.async.wait_all;" ::: "memory");
    __syncthreads();
    const int q0 = (tid & 3) * 4;
    const char* rp[4];
#pragma unroll
    for (int u = 0; u < 4; u++) rp[u] = sm + (q0 + u) * 672 + (row_byte(q0 + u) & 15);
    uint32_t mx = 0;
#pragma unroll 2
    for (int c = tid >> 2; c < 321; c += 64) {
        uint32_t v[4];
#pragma unroll
        for (int u = 0; u < 4; u++) {
            v[u] = ((const unsigned short*)rp[u])[c] | ((uint32_t)((const unsigned short*)(rp[u] + 16 * 672))[c] << 16);
            mx = __vmaxu2(mx, v[u] & 0x7fff7fffu);
        }
        ((uint4*)g_Wf)[(size_t)c * 512 + b * 4 + ((tid ^ (b >> 1)) & 3)] = make_uint4(v[0], v[1], v[2], v[3]);
    }
    mx = __reduce_max_sync(~0u, max(mx & 0xffffu, mx >> 16));
    __syncthreads();
    if (lane == 0) ((uint32_t*)sm)[tid >> 5] = mx;
    __syncthreads();
    if (tid < 32) {
        mx = __reduce_max_sync(~0u, ((uint32_t*)sm)[lane & 7]);
        if (tid == 0) g_wmax[b] = __uint_as_float(mx << 16);
    }
}
__device__ __forceinline__ void setup_b(const int b, const bf16* __restrict__ mem0) {
    const int tid = threadIdx.x;
    uint4* z = (uint4*)red_base();
    if (b < 3) {
        const int w = tid >> 5, lane = tid & 31, p = b * 2 + ((w >> 1) & 1), odd = w & 1;
        uint32_t mx = 0;
#pragma unroll 4
        for (int i = lane; i < 640; i += 32) {
            const uint4 u = ((const uint4*)mem0)[i];
            mx = __vmaxu2(__vmaxu2(mx, u.x & 0x7fff7fffu), __vmaxu2(__vmaxu2(u.y & 0x7fff7fffu, u.z & 0x7fff7fffu), u.w & 0x7fff7fffu));
        }
        float inv, v[7];
        const float sc = pow2_scale(__uint_as_float(__reduce_max_sync(~0u, max(mx & 0xffffu, mx >> 16)) << 16), 14, &inv);
        if (tid == 0) g_invM0 = inv;
#pragma unroll
        for (int j = 0; j < 7; j++) {
            const int r = p * 56 + (j < 6 ? odd * 32 + (j >> 1) * 8 : 24) + (lane >> 2), mr = 2 * (lane & 3) + (j < 6 ? (j & 1) : odd);
            v[j] = r < 320 ? __bfloat162float(mem0[mr * 640 + (w >> 2) * 320 + r]) * sc : 0.f;
        }
        const int off = w * 2048 + (lane >> 4) * 1024 + ((lane >> 3) & 1) * 256 + (lane & 7) * 16 + (b == 2 ? (w >> 1) * 4096 + 128 : b * 16384);
        const uint4 u = make_uint4(pack_h(v[0], v[1]), pack_h(v[2], v[3]), pack_h(v[4], v[5]), pack_h(v[6], 32.f));
        z[off >> 4] = u; z[65536 + (off >> 4)] = u;
    }
}

#define SU_PAD 40960
constexpr int SU_SMEM = SU_PAD;
__global__ void __launch_bounds__(256, 4) k_setup(const bf16* __restrict__ wr, const bf16* __restrict__ wi, const bf16* __restrict__ mem0) {
    extern __shared__ __align__(1024) char sm[];
    TL(0);
    if (blockIdx.x >= 128) setup_b(blockIdx.x - 128, mem0);
    else setup_a(sm, blockIdx.x, wr, wi);
    __syncthreads();
    if (threadIdx.x == 0) red_release(g_ready);
    TL(1);
}
__device__ __forceinline__ float weight_scale(int h, int ty, float* inv) { return pow2_scale(__ldcg(g_wmx + h * 3 + ty), 6, inv); }

#define STR_(x) #x
#define STR(x) STR_(x)
#define RF_U 1
constexpr int RF_A = 22 * 2816, RF_X = RF_A + 22 * 1024, RF_BAR = RF_X + 64 * 1344, RF_SMEM = RF_BAR + 80;
__device__ __align__(1024) char g_rtab[4 * RF_A];
template <int first> __global__ void __cluster_dims__(2, 1, 1) __launch_bounds__(256, 2) k_rowf(const bf16* x) {
    extern __shared__ __align__(1024) char sm[];
    TL(first ? 2 : 16);
    const int tid = threadIdx.x, w = tid >> 5, lane = tid & 31, g = lane >> 2, t = lane & 3;
    if (blockIdx.x >= 128) { __nanosleep(2500); return; }
    const int a = first ? blockIdx.x >> 2 : 31 - (blockIdx.x >> 2), gq = blockIdx.x & 3;
    if (!first) pdl_go();
    const uint32_t sb = smem_u32(sm), mb = sb + RF_BAR + w * 8;
    if (lane == 0) {
        mbar_init(mb, 1);
        asm volatile("fence.mbarrier_init.release.cluster;" ::: "memory");
        if (!first && w == 0) {
            mbar_init(sb + RF_BAR + 64, 1);
            fence_async_smem();
            mbar_expect(sb + RF_BAR + 64, RF_A);
            bulk_g2s(sb, g_rtab + gq * RF_A, RF_A, sb + RF_BAR + 64);
        }
    }
    if (lane == 0) mbar_expect(mb, 8 * 1280);
    __syncwarp();
    asm volatile("barrier.cluster.arrive.relaxed.aligned; barrier.cluster.wait.aligned;" ::: "memory");
    if (!first) {
        if (lane == 0) wait_flag<100>(g_flag + F_R + a, a < 28 ? 32 : 192);
        __syncwarp();
        fence_async_glb();
    }
    TL(first ? 3 : 17);
    if (lane < 4)
        asm volatile("cp.async.bulk.shared::cluster.global.mbarrier::complete_tx::bytes.multicast::cluster [%0],[%1],1280,[%2],%3;"
                     ::"r"(sb + RF_X + (w * 8 + (gq & 1) * 4 + lane) * 1344), "l"(x + (size_t)(a * 64 + w * 8 + (gq & 1) * 4 + lane) * 640), "r"(mb),
                     "h"((unsigned short)3) : "memory");
    __syncwarp();
    if (first) pdl_go();
    if (first) {
#pragma unroll 3
        for (int id = tid; id < 22 * 176; id += 256) {
            const int kg = id / 176, n = id - kg * 176;
            const float c = (float)(2 * n + (gq & 1));
            *(uint4*)(sm + id * 16) = cos_row8(fmaf((float)(kg * 8), c, (float)((gq & 2) * 80)), c, 0.03952847075210474f);
        }
    }
    mbar_wait(mb, 0);
    const uint32_t row = sb + RF_X + (w * 8 + g) * 1344;
    float st[4][4] = {};
#pragma unroll 1
    for (int i = 0; i < 20; i += 4) {
        uint32_t u[4][4];
#pragma unroll
        for (int q = 0; q < 4; q++) lds128(u[q], row + (4 * (i + q) + t) * 16);
#pragma unroll
        for (int q = 0; q < 4; q++) {
            mma_bf(st[(q & 1) * 2], u[q][0], 0x3f803f80u, u[q][1], 0x3f803f80u, u[q][0], u[q][1]);
            mma_bf(st[(q & 1) * 2 + 1], u[q][2], 0x3f803f80u, u[q][3], 0x3f803f80u, u[q][2], u[q][3]);
        }
    }
#pragma unroll
    for (int q = 0; q < 4; q++) { st[0][q] += st[2][q]; st[1][q] += st[3][q]; }
    const float sq = __shfl_sync(~0u, (g & 1) ? st[0][1] + st[1][1] : st[0][0] + st[1][0], g * 4 + (g >> 1));
    const float mean = __shfl_sync(~0u, (g & 1) ? st[0][3] + st[1][3] : st[0][2] + st[1][2], g * 4 + (g >> 1)) * (1.f / 640.f);
    const float r = rsqrtf(fmaxf(fmaf(-mean, mean, sq * (1.f / 640.f)), 0.f) + 1e-5f), off = gq == 0 ? -4.f * mean * r : 0.f;
    const float r1 = (gq == 1 || gq == 2) ? -r : r, r2 = (gq & 1) ? -r : r, r3 = gq >= 2 ? -r : r;
    const uint32_t aa = sb + RF_A + w * 128 + g * 16;
    auto el = [&](int d) { unsigned short v; asm volatile("ld.shared.u16 %0,[%1];" : "=h"(v) : "r"(row + d * 2)); return __uint_as_float((uint32_t)v << 16); };
_Pragma(STR(unroll RF_U))
    for (int i = 0; i < 5; i++) {
        const int ch = t + 4 * i;
        uint32_t u[4][4];
        lds128(u[0], row + ch * 16); lds128(u[1], row + (39 - ch) * 16); lds128(u[2], row + (40 + ch) * 16); lds128(u[3], row + (79 - ch) * 16);
        const float nb0 = el(320 - 8 * ch), nb1 = el(ch ? 640 - 8 * ch : 0);
        float o[8];
#pragma unroll
        for (int q = 0; q < 8; q++) {
            const int m = (8 - q) >> 1;
            const float e0 = (q & 1) ? bf_hi(u[0][q >> 1]) : bf_lo(u[0][q >> 1]), e2 = (q & 1) ? bf_hi(u[2][q >> 1]) : bf_lo(u[2][q >> 1]);
            const float e1 = q == 0 ? nb0 : (q & 1) ? bf_hi(u[1][m & 3]) : bf_lo(u[1][m & 3]), e3 = q == 0 ? nb1 : (q & 1) ? bf_hi(u[3][m & 3]) : bf_lo(u[3][m & 3]);
            o[q] = fmaf(e3, r3, fmaf(e2, r2, fmaf(e1, r1, fmaf(e0, r, off))));
        }
        if (ch == 0) o[0] *= 0.5f;
        sts128(aa + ch * 1024, pack_h(o[0], o[1]), pack_h(o[2], o[3]), pack_h(o[4], o[5]), pack_h(o[6], o[7]));
    }
    if (t < 2) sts128(aa + (20 + t) * 1024, t == 0 ? pack_h(fmaf(el(480), r2, fmaf(el(160), r, 0.5f * off)), 0.f) : 0u, 0u, 0u, 0u);
    fence_async_smem();
    __syncthreads();
    if (!first) mbar_wait(sb + RF_BAR + 64, 0);
    else if (a == 0 && tid == 0) { bulk_s2g(g_rtab + gq * RF_A, sb, RF_A); bulk_commit(); }
    const int wg = w >> 2;
    float acc[44];
    uint64_t da = mkdesc(sb + RF_A, 1024, 128, 0), db = mkdesc(sb + wg * 1408, 2816, 128, 0);
    wg_fence();
#pragma unroll 1
    for (int k = 0; k < 11; k++) { wg_n88_ss(acc, da, db, k); da += 128; db += 352; }
    wg_commit(); wg_wait<0>();
    const uint32_t stg = sb + RF_X + wg * 96 * 144;
#pragma unroll
    for (int j = 0; j < 12; j += 2) {
        const int m = lane >> 3, j1 = j < 10 ? j + 1 : j;
        stsm4t(stg + ((j + (m >> 1)) * 8 + (lane & 7)) * 144 + ((w & 3) * 16 + (m & 1) * 8) * 2, pack_h(acc[j * 4], acc[j * 4 + 1]),
               pack_h(acc[j * 4 + 2], acc[j * 4 + 3]), pack_h(acc[j1 * 4], acc[j1 * 4 + 1]), pack_h(acc[j1 * 4 + 2], acc[j1 * 4 + 3]));
    }
    bar_sync(1 + wg, 128);
#pragma unroll 3
    for (int rr = (tid & 127) >> 3; rr < 88; rr += 16) {
        const int ch = tid & 7, c = 2 * (wg * 88 + rr) + (gq & 1);
        if (c <= 320 - (gq >> 1) && (c | (gq ^ 2))) {
            uint32_t u[4];
            lds128(u, stg + rr * 144 + ch * 16);
            ((uint4*)g_UT)[((size_t)(c == 320 ? 1 : 2 * c + (gq >> 1)) * 32 + a) * 8 + (ch ^ (a & 7))] = make_uint4(u[0], u[1], u[2], u[3]);
        }
    }
    if (first && blockIdx.x < 4 && tid == 0) asm volatile("cp.async.bulk.wait_group.read 0;" ::: "memory");
    TL(first ? 4 : 18);
}

constexpr int GST = 4, GSTB = 32768 + 20480, GNC = 32;
constexpr int G_BAR = GST * GSTB + 3072;
#define GPACE 1000
#define GPACE2 650
__device__ __forceinline__ void oproj_load(const uint32_t sb, const int op, const int mb, const int nb, const int c0, const uint32_t pace) {
    const int by = op == 2 ? 20480 : 16384;
    const char* src = op == 2 ? (const char*)g_wot + (size_t)nb * GNC * 20480 : (const char*)g_O + (size_t)(2 * mb + op) * GNC * 16384;
    uint32_t t0 = clock32() - pace + op * (pace / 3);
#pragma unroll 1
    for (int c = c0; c < c0 + GNC; c++, src += by) {
        const int st = c % GST;
        if (c >= GST) mbar_wait(sb + G_BAR + (GST + st) * 8, ((c / GST) - 1) & 1);
        while (clock32() - t0 < pace) {}
        t0 = clock32();
        const int by_ = by;
        mbar_expect(sb + G_BAR + st * 8, by_);
        if (op == 2) bulk_g2s(sb + st * GSTB + 32768, src, by_, sb + G_BAR + st * 8);
        else bulk_g2s_last(sb + st * GSTB + op * 16384, src, by_, sb + G_BAR + st * 8);
    }
}
__device__ __forceinline__ void oproj_mma(const uint32_t sb, const int mb, const int nb, const int c0, const bf16* res, bf16* out, const int layer) {
    const int w = threadIdx.x >> 5, lane = threadIdx.x & 31, wg = w >> 2;
    float acc[40];
    uint4 rv[5];
#pragma unroll 1
    for (int c = c0; c < c0 + GNC; c++) {
        const int st = c % GST;
        mbar_wait(sb + G_BAR + st * 8, (c / GST) & 1);
        const uint32_t d = sb + st * GSTB;
        wg_fence();
#pragma unroll
        for (int k = 0; k < 8; k++)
            wg_n80_ss(acc, mkdesc(d + wg * 16384 + k * 2048, 1024, 128, 0), mkdesc(d + 32768 + k * 2560, 1280, 128, 0), (c - c0) | k);
        wg_commit();
        if (c > c0) {
            wg_wait<1>();
            if (lane == 0) mbar_arrive(sb + G_BAR + (GST + (c - 1) % GST) * 8);
        }
    }
#pragma unroll
    for (int i = 0; i < 5; i++) {
        const int id = i * 32 + lane, r = id / 10;
        rv[i] = __ldcg((const uint4*)res + (size_t)(mb * 128 + w * 16 + r) * 80 + nb * 10 + id - r * 10);
    }
    wg_wait<0>();
    bar_sync(5, 256);
    const uint32_t stg = sb + (GST - 1) * GSTB + w * 16 * 176;
#pragma unroll
    for (int j = 0; j < 5; j++)
        stsm4(stg + (lane & 15) * 176 + (2 * j + (lane >> 4)) * 16, pack_bf(acc[j * 8], acc[j * 8 + 1]), pack_bf(acc[j * 8 + 2], acc[j * 8 + 3]),
              pack_bf(acc[j * 8 + 4], acc[j * 8 + 5]), pack_bf(acc[j * 8 + 6], acc[j * 8 + 7]));
    __syncwarp();
#pragma unroll
    for (int i = 0; i < 5; i++) {
        const int id = i * 32 + lane, r = id / 10, ch = id - r * 10;
        uint32_t y[4];
        lds128(y, stg + r * 176 + ch * 16);
        ((uint4*)out)[(size_t)(mb * 128 + w * 16 + r) * 80 + nb * 10 + ch] = add_bf8(rv[i], y);
    }
    fence_async_smem();
    __syncwarp();
    if (lane == 0) {
        mbar_arrive(sb + G_BAR + (2 * GST - 1) * 8);
        if (layer == 0) red_release(g_flag + F_R + 2 * mb + wg);
    }
}

__global__ void __launch_bounds__(128, 4) k_col(const int first) {
    __shared__ __align__(1024) char sz[8192];
    __shared__ __align__(1024) char stab[24576];
    __shared__ __align__(1024) char swf[8192];
    __shared__ __align__(8) uint64_t bar[2];
    const int tid = threadIdx.x, wl = tid >> 5, lane = tid & 31, g = lane >> 2, t = lane & 3;
    const int c = blockIdx.x;
    TL(first ? 5 : 19);
    const bool realc = c == 0 || c == 320;
    const uint32_t z = smem_u32(sz), b2 = smem_u32(stab), a1 = b2 + 16384, wf = smem_u32(swf), mb = smem_u32(bar);
    if (tid == 0) { mbar_init(mb, 1); mbar_init(mb + 8, 1); fence_async_smem(); }
    if (realc) {
        for (int i = tid; i < 256; i += 128) sts128(z + 4096 + i * 16, 0, 0, 0, 0);
        fence_async_smem();
    }
    const int k1 = wl * 8 + g;
    float tc[16], ts[16];
#pragma unroll
    for (int j = 0; j < 16; j++) {
        const int p = ((j >> 1) * 8 + 2 * t + (j & 1)) * k1;
        __sincosf((float)(p - 1024) * 0.003067961575771282f, &ts[j], &tc[j]);
        ts[j] = -ts[j]; tc[j] = -tc[j];
    }
    if (first && tid == 32) { wait_flag<400>(g_ready, NSETUP); fence_async_glb(); }
    __syncthreads();
    if (tid == 32) {
        mbar_expect(mb + 8, 24576 + 8192);
        bulk_g2s(b2, g_ctab, 24576, mb + 8);
        bulk_g2s(wf, g_Wf + (size_t)c * 2048, 8192, mb + 8);
    }
    float inv;
    const float wsc = pow2_scale(wfilter_max(lane), 0, &inv) * (realc ? 0.5f : 1.f);
    pdl_wait();
    TL(first ? 6 : 20);
    if (tid == 0) {
        const int by = realc ? 4096 : 8192;
        mbar_expect(mb, by);
        bulk_g2s_last(z, (const char*)g_UT + (size_t)(c == 320 ? 1 : 2 * c) * 4096, by, mb);
    }
    pdl_go();
    mbar_wait(mb + 8, 0);
    mbar_wait(mb, 0);
    float d[64];
    uint32_t a[4][4];
    wg_fence();
#pragma unroll
    for (int ks = 0; ks < 4; ks++) wg_n64_ss_tb<0>(d, mkdesc(a1 + ks * 2048, 1024, 128, 0), mkdesc(z + ks * 2048, 1024, 1024, 1), ks);
    wg_commit(); wg_wait<0>();
#pragma unroll
    for (int j = 0; j < 8; j++) {
        float yr[2], yi[2];
#pragma unroll
        for (int e = 0; e < 2; e++) {
            const float re = d[j * 4 + e], im = d[j * 4 + 2 + e], cc = tc[j * 2 + e], ss = ts[j * 2 + e];
            yr[e] = re * cc + im * ss; yi[e] = im * cc - re * ss;
        }
        a[j >> 1][(j & 1) * 2] = pack_h(yr[0], yr[1]); a[j >> 1][(j & 1) * 2 + 1] = pack_h(yi[0], yi[1]);
    }
    wg_fence();
#pragma unroll
    for (int ks = 0; ks < 4; ks++) wg_n128_rs(d, a[ks], mkdesc(b2 + ks * 4096, 2048, 128, 0), ks);
    wg_commit(); wg_wait<0>();
#pragma unroll
    for (int q = 0; q < 4; q++) {
        uint32_t wv[4];
        lds128(wv, wf + tid * 64 + ((q ^ (tid >> 1)) & 3) * 16);
#pragma unroll
        for (int jj = 0; jj < 2; jj++) {
            const int j = 2 * q + jj;
            float yr[2], yi[2];
#pragma unroll
            for (int e = 0; e < 2; e++) {
                const float xr = d[j * 4 + e] + d[32 + j * 4 + 2 + e], xi = d[j * 4 + 2 + e] - d[32 + j * 4 + e];
                const float fr = bf_lo(wv[jj * 2 + e]) * wsc, fi = bf_hi(wv[jj * 2 + e]) * wsc;
                yr[e] = xr * fr - xi * fi; yi[e] = xr * fi + xi * fr;
            }
            a[q][jj * 2] = pack_h(yr[0], yr[1]); a[q][jj * 2 + 1] = pack_h(yi[0], yi[1]);
        }
    }
    wg_fence();
#pragma unroll
    for (int ks = 0; ks < 4; ks++) wg_n128_rs(d, a[ks], mkdesc(b2 + ks * 4096, 2048, 128, 0), ks);
    wg_commit(); wg_wait<0>();
#pragma unroll
    for (int j = 0; j < 8; j++) {
        float yr[2], yi[2];
#pragma unroll
        for (int e = 0; e < 2; e++) {
            const float vr = d[j * 4 + e] - d[32 + j * 4 + 2 + e], vi = d[j * 4 + 2 + e] + d[32 + j * 4 + e];
            const float cc = tc[j * 2 + e], ss = ts[j * 2 + e];
            yr[e] = vr * cc - vi * ss; yi[e] = vi * cc + vr * ss;
        }
        a[j >> 1][(j & 1) * 2] = pack_h(yr[0], yr[1]); a[j >> 1][(j & 1) * 2 + 1] = pack_h(yi[0], yi[1]);
    }
    __syncthreads();
    const int mm = lane >> 3, rr = lane & 7;
    const uint32_t rowo = (wl * 16 + (mm & 1) * 8 + rr) * 128;
#pragma unroll
    for (int q = 0; q < 4; q++) stsm4(z + rowo + (((2 * q + (mm >> 1)) ^ rr) << 4), a[q][0], a[q][1], a[q][2], a[q][3]);
    fence_async_smem();
    __syncthreads();
    wg_fence();
#pragma unroll
    for (int ks = 0; ks < 4; ks++) wg_n64_ss_tb<1>(d, mkdesc(a1 + ks * 256, 128, 1024, 0), mkdesc(z + ks * 2048, 1024, 1024, 1), ks);
    wg_commit(); wg_wait<0>();
#pragma unroll
    for (int q = 0; q < 4; q++)
        stsm4(wf + rowo + (((2 * q + (mm >> 1)) ^ rr) << 4), pack_h(d[q * 8], d[q * 8 + 1]), pack_h(d[q * 8 + 2], d[q * 8 + 3]),
              pack_h(d[q * 8 + 4], d[q * 8 + 5]), pack_h(d[q * 8 + 6], d[q * 8 + 7]));
    __syncwarp();
    if (!(realc && wl >= 2)) {
        const int kk = c == 320 ? 320 : (c & 1) * 160 + (c >> 1) + (wl >> 1) * 320;
#pragma unroll
        for (int i = 0; i < 4; i++) {
            const int r = wl * 16 + i * 4 + (lane >> 3), ch = lane & 7;
            uint32_t v[4];
            lds128(v, wf + r * 128 + ((ch ^ (r & 7)) << 4));
            ((uint4*)g_YT)[((size_t)(r & 31) * 640 + kk) * 8 + (ch ^ (kk & 7))] = make_uint4(v[0], v[1], v[2], v[3]);
        }
    }
    TL(first ? 7 : 21);
}

constexpr int O_XS = 0;
constexpr int O_MS = 81920;
constexpr int O_QKP = O_MS + 10752;
constexpr int O_VM = O_QKP + 4096;
constexpr int O_SC = O_VM + 4096;
constexpr int O_OS = O_SC + 1536;
constexpr int O_XCH = O_OS + 2048;
constexpr int O_SUM = O_XCH + 8192;
constexpr int O_MX = O_SUM + 256;
constexpr int O_STG = O_MS + 65536 - 8192;
static_assert(O_STG - 16384 >= O_MX + 1024, "shared-memory map");
constexpr int O_WO = O_STG + 16384;
constexpr int O_SCL = O_WO + 65536;
constexpr int O_BAR = O_SCL + 64;
constexpr int B_XF = O_BAR, B_S = O_BAR + 16, B_GO = O_BAR + 24, B_VH = O_BAR + 88, B_VX = O_BAR + 32, B_STG = O_BAR + 48, B_FREE = O_BAR + 72;
constexpr int T_FA = O_BAR + 96, T_EA = T_FA + 32, T_FB = T_EA + 32, T_EB = T_FB + 56, T_RED = T_EB + 32;
constexpr int O_WMX = O_BAR + 512, B_W = O_BAR + 64;
constexpr int O_LAST = (O_WMX + 192 + 1023) / 1024 * 1024;
constexpr int CH_SMEM = O_LAST + 8192;
static_assert(O_WO == 19 * 8192, "weight staging");
__device__ __forceinline__ uint32_t tail_b(int c) { return c % 7 < 4 ? O_XS + (c % 7) * 20480 : O_WO + (c % 7 - 4) * 20480; }
__device__ __forceinline__ int s_tx(int c) { return c == 2 ? 2 * 768 : 768 + 2048; }

#define NPERM 1
#define NWO0 1
#define NWO0B 6
#define NWO1 6
#define AUNR 2
#define TDELAY 300
#define WDEPTH 6
#define RDELAY 550
#define RB2 25

#define STAMP(i)

#define NTA 20
#define NTB 28
template <int LO, int HI>
__device__ __forceinline__ void tok_issue(const uint32_t (&A0)[20][4], const uint32_t (&A1)[20][4], float (&b0)[16], float (&b1)[16], uint32_t xd,
                                          const uint32_t zero) {
    if (LO == 0) wg_fence();
    sfor<HI - LO>([&](auto I) {
        constexpr int i = LO + I;
        if constexpr (i < 20) wg_n32_x<i * 64, i>(b0, A0[i], xd); else wg_n32_x<(i - 20) * 64, i - 20>(b1, A1[i - 20], xd + zero);
        if constexpr (i == 19 || i == NTB - 1 || i == 39) wg_commit();
    });
}
__device__ __forceinline__ void tok_give(const float (&b0)[16], const uint32_t L16, const uint32_t xch0) {
    wg_wait<1>();
    sfor<2>([&](auto I) {
        constexpr int i = I;
        sts128_u<i * 512>(L16, xch0, pack_h(b0[8 * i], b0[8 * i + 1]), pack_h(b0[8 * i + 2], b0[8 * i + 3]), pack_h(b0[8 * i + 4], b0[8 * i + 5]),
                          pack_h(b0[8 * i + 6], b0[8 * i + 7]));
    });
}
__device__ __forceinline__ void tok_finish(float (&b1)[16], const uint32_t (&e)[2][4], const uint32_t L16, const uint32_t dst, const uint32_t idn) {
#pragma unroll
    for (int j = 0; j < 4; j++)
        asm volatile("mma.sync.aligned.m16n8k8.row.col.f32.f16.f16.f32 {%0,%1,%2,%3},{%4,%5},{%6},{%0,%1,%2,%3};"
                     : F4(b1, 4 * j) : "r"(e[j >> 1][(j & 1) * 2]), "r"(e[j >> 1][(j & 1) * 2 + 1]), "r"(idn));
    stsm4_u<0>(L16, dst, pack_bf(b1[0], b1[1]), pack_bf(b1[2], b1[3]), pack_bf(b1[4], b1[5]), pack_bf(b1[6], b1[7]));
    stsm4_u<512>(L16, dst, pack_bf(b1[8], b1[9]), pack_bf(b1[10], b1[11]), pack_bf(b1[12], b1[13]), pack_bf(b1[14], b1[15]));
}
__device__ __forceinline__ uint32_t uni(uint32_t v) { return __shfl_sync(~0u, v, 0); }
__device__ __forceinline__ uint32_t badd(uint32_t a, uint32_t b) { uint32_t r; asm("add.rn.bf16x2 %0,%1,%2;" : "=r"(r) : "r"(a), "r"(b)); return r; }
__device__ __forceinline__ uint32_t bmax(uint32_t a, uint32_t b) { uint32_t r; asm("max.bf16x2 %0,%1,%2;" : "=r"(r) : "r"(a), "r"(b)); return r; }
__device__ __forceinline__ uint32_t babsmax(uint32_t a, uint32_t b) { uint32_t r; asm("max.xorsign.abs.bf16x2 %0,%1,%2;" : "=r"(r) : "r"(a), "r"(b)); return r; }
__device__ __forceinline__ uint32_t habsmax(uint32_t a, uint32_t b) { uint32_t r; asm("max.xorsign.abs.f16x2 %0,%1,%2;" : "=r"(r) : "r"(a), "r"(b)); return r; }

template <int NPF>
__device__ __forceinline__ float mem_out(const uint32_t sb, const uint32_t L16, const uint32_t L8, uint32_t (&wo)[16][4], const uint32_t woa,
                                         char* dst, const bool odd) {
    bar_sync(2, 352);
    float a[4][4];
#pragma unroll
    for (int i = 0; i < 4; i++) a[i][0] = a[i][1] = a[i][2] = a[i][3] = 0.f;
    uint32_t ob[4][4], sm_[2], sc[2];
    sfor<8>([&](auto I) {
        constexpr int i = I;
        if constexpr (!(i & 1)) ldsm4t_u<O_OS + (i >> 1) * 512>(ob[i >> 1], L16, sb);
        if constexpr (i >= NPF) { ldsm4t(wo[i], woa + i * 1024); ldsm4t(wo[8 + i], (woa ^ 32) + i * 1024); }
    });
    lds64_u<O_SUM>(sm_, L8 & 24, sb); lds64(sc, sb + O_SCL);
#pragma unroll
    for (int i = 0; i < 8; i++) {
        mma_bf(a[i & 1], wo[i][0], wo[i][1], wo[i][2], wo[i][3], ob[i >> 1][(i & 1) * 2], ob[i >> 1][(i & 1) * 2 + 1]);
        mma_bf(a[2 + (i & 1)], wo[8 + i][0], wo[8 + i][1], wo[8 + i][2], wo[8 + i][3], ob[i >> 1][(i & 1) * 2], ob[i >> 1][(i & 1) * 2 + 1]);
    }
    const float f0 = rcp(__uint_as_float(sm_[0])) * __uint_as_float(sc[0]), f1 = rcp(__uint_as_float(sm_[1])) * __uint_as_float(sc[0]);
    red_h8(dst, pack_h((a[0][0] + a[1][0]) * f0, (a[0][1] + a[1][1]) * f1), pack_h((a[0][2] + a[1][2]) * f0, (a[0][3] + a[1][3]) * f1),
           pack_h((a[2][0] + a[3][0]) * f0, (a[2][1] + a[3][1]) * f1), pack_h(odd ? (a[2][3] + a[3][3]) * f1 : (a[2][2] + a[3][2]) * f0, 1.f));
    return __uint_as_float(sc[1]);
}

template <int NE, int UNR>
__device__ __forceinline__ void tok_attention(const uint32_t qk, const uint32_t dq, const uint32_t km, const uint32_t dk, const uint32_t vt, const uint32_t vm,
                                              const int e0, const int mi, const int lane, const int seg, const int h, const float iqk, const float iv) {
    const int g = lane >> 2, t = lane & 3;
    float s[6][4];
#pragma unroll
    for (int i = 0; i < 6; i++) s[i][0] = s[i][1] = s[i][2] = s[i][3] = 0.f;
#pragma unroll UNR
    for (int e = 0; e < 8; e++) {
        uint32_t q[4], k[4];
        ldsm4t(q, qk + (e >> 2) * dq + (e & 3) * 1024 + mi * 512);
        ldsm4t(k, km + (e >> 2) * dk + (e & 3) * 512);
        mma_bf(s[4], q[0], q[2], q[1], q[3], k[0], k[1]);
        mma_bf(s[5], q[0], q[2], q[1], q[3], k[2], k[3]);
        ldsm4t(k, qk + (e >> 2) * dq + 4096 + (e & 3) * 1024);
        mma_bf(s[0], q[0], q[2], q[1], q[3], k[0], k[1]);
        mma_bf(s[1], q[0], q[2], q[1], q[3], k[2], k[3]);
        if (mi) {
            ldsm4t(k, qk + (e >> 2) * dq + 4096 + (e & 3) * 1024 + 512);
            mma_bf(s[2], q[0], q[2], q[1], q[3], k[0], k[1]);
            mma_bf(s[3], q[0], q[2], q[1], q[3], k[2], k[3]);
        }
    }
#pragma unroll
    for (int q = 0; q < 4; q++) s[4][q] += s[5][q];
    const float sl = iqk * (0.08838834764831845f * 1.4426950408889634f);
    float mx[2] = {-3.0e38f, -3.0e38f};
#pragma unroll
    for (int i = 0; i < 5; i++)
#pragma unroll
        for (int q = 0; q < 4; q++) {
            const bool ok = i == 4 || (i * 8 + 2 * t + (q & 1)) <= (mi * 16 + g + (q >> 1) * 8);
            s[i][q] = ok ? s[i][q] * sl : -1.0e9f * 1.4426950408889634f;
            mx[q >> 1] = fmaxf(mx[q >> 1], s[i][q]);
        }
    float sum[2] = {0.f, 0.f};
#pragma unroll
    for (int r = 0; r < 2; r++) {
        mx[r] = fmaxf(mx[r], __shfl_xor_sync(~0u, mx[r], 1));
        mx[r] = fmaxf(mx[r], __shfl_xor_sync(~0u, mx[r], 2));
    }
#pragma unroll
    for (int i = 0; i < 5; i++)
#pragma unroll
        for (int q = 0; q < 4; q++) { s[i][q] = ex2(s[i][q] - mx[q >> 1]); sum[q >> 1] += s[i][q]; }
#pragma unroll
    for (int r = 0; r < 2; r++) {
        sum[r] += __shfl_xor_sync(~0u, sum[r], 1);
        sum[r] += __shfl_xor_sync(~0u, sum[r], 2);
        sum[r] = iv * rcp(sum[r]);
    }
    uint32_t pp[5][2];
#pragma unroll
    for (int i = 0; i < 5; i++) { pp[i][0] = pack_bf(s[i][0] * sum[0], s[i][1] * sum[0]); pp[i][1] = pack_bf(s[i][2] * sum[1], s[i][3] * sum[1]); }
    uint32_t* o = (uint32_t*)g_O + (((size_t)(seg >> 1) * 512 + h * 16) * 8 + (seg & 1) * 4 + mi * 2) * 32 + lane;
#pragma unroll(UNR == 8 ? NE : 1)
    for (int u = 0; u < NE; u++) {
        const int e = e0 + u;
        float o0[4] = {0.f, 0.f, 0.f, 0.f}, o1[4] = {0.f, 0.f, 0.f, 0.f};
        uint32_t v[4];
        lds64(v, vm + e * 256);
        mma_bf8(o0, pp[4][0], pp[4][1], v[0]);
        mma_bf8(o1, pp[4][0], pp[4][1], v[1]);
        ldsm4(v, vt + e * 1024);
        mma_bf(o0, pp[0][0], pp[0][1], pp[1][0], pp[1][1], v[0], v[2]);
        mma_bf(o1, pp[0][0], pp[0][1], pp[1][0], pp[1][1], v[1], v[3]);
        ldsm4(v, vt + e * 1024 + 512);
        mma_bf(o0, pp[2][0], pp[2][1], pp[3][0], pp[3][1], v[0], v[2]);
        mma_bf(o1, pp[2][0], pp[2][1], pp[3][0], pp[3][1], v[1], v[3]);
        o[(2 * e) * 256] = pack_bf(o0[0], o0[1]); o[(2 * e) * 256 + 32] = pack_bf(o0[2], o0[3]);
        o[(2 * e + 1) * 256] = pack_bf(o1[0], o1[1]); o[(2 * e + 1) * 256 + 32] = pack_bf(o1[2], o1[3]);
    }
}

__device__ __forceinline__
void attend_last(const uint32_t sb, const int layer) {
    const int tid = read_tid(), ln = tid & 31, w = tid >> 5;
    int h;
    asm volatile("mov.u32 %0,%%clusterid.x;" : "=r"(h));
    uint32_t inv[2];
    lds64(inv, sb + O_SCL + 16);
    mbar_wait(sb + B_S, (NSEG - 1) & 1);
    mbar_wait(sb + B_VX + 8, 0);
    if (layer == TLL) TL(54);
    if (w == 0 && ln < 2)
        asm volatile("mbarrier.arrive.relaxed.cluster.shared::cluster.b64 _,[%0];" ::"r"(mapa(sb + B_STG + 8, ln)) : "memory");
    tok_attention<2, AUNR>(sb + O_STG - 16384 + ln * 16, 16384, sb + O_LAST + ln * 16, 2048, sb + O_STG + 8192 - 16384 + ln * 16, sb + O_VM + 2048 + ln * 8,
                     (w >> 1) * 2, w & 1, ln, NSEG - 1, h, __uint_as_float(inv[0]), __uint_as_float(inv[1]));
    if (layer == TLL) TL(55);
    __syncwarp();
    if (ln == 0) red_release(g_flag + F_O + layer * 32 + 31);
    if (layer == TLL) TL(43);
}

template <int layer> __device__ __forceinline__ void chain_mma(const uint32_t sb, const int c, const int h, const uint32_t zero, const bf16* __restrict__ Wq,
                                          const bf16* __restrict__ Wk, const bf16* __restrict__ Wv, const bf16* __restrict__ Wo,
                                          const bf16* res, bf16* out) {
    int tid = read_tid(), lane = tid & 31;
    const int w = __shfl_sync(~0u, tid >> 5, 0), wg = w >> 2;
    [[maybe_unused]] const int cta = h * 3 + c;
    uint32_t A0[20][4], A1[20][4];
    const int t0 = (w & 3) + wg * 4, t1 = t0 ^ 4;
    float sl;
    {
        const int tl = tid & 127, r = tl >> 3, ch = tl & 7;
        const size_t so = (size_t)(wg * 320 + r) * 4096 + h * 128 + ch * 8;
        const bf16 *wa = (c == 2 ? Wv : Wq + c * 64) + so, *wb = (c == 2 ? Wv + 64 : Wk + c * 64) + so;
        const uint32_t ring = sb + wg * 4096;
        const uint32_t dst = ring + r * 128 + ((ch ^ r) & 7) * 16;
        const uint32_t src = ring + ((lane & 7) + (lane >> 4) * 8) * 128 + ((((w & 3) * 2 + ((lane >> 3) & 1)) ^ lane) & 7) * 16;
        const int q4 = lane & 3, gr = (c * 2 + ((w >> 1) & 1)) * 56 + (q4 == 3 ? 24 : (w & 1) * 32 + q4 * 8);
        const bf16* wo_ = Wo + (size_t)(h * 128 + (lane >> 2)) * 640 + wg * 320 + min(gr, 312);
        const uint32_t wdst = sb + O_WO + w * 8192 + (lane >> 2) * 64 + ((q4 ^ (lane >> 3)) & 3) * 16;
        auto issue = [&](int i) {
            if (i < 20) {
                const uint32_t d = dst + (i < 19 ? i * 8192 : O_LAST);
                cp_async16(d, wa + (size_t)i * 65536); cp_async16(d + 2048, wb + (size_t)i * 65536);
                if (i < 16) cp_async16(wdst + i * 512, wo_ + i * 5120, gr < 320 ? 16 : 0);
            }
            cp_commit();
        };
#pragma unroll 1
        for (int i = 0; i < WDEPTH; i++) issue(i);
        asm volatile("barrier.cluster.arrive.relaxed.aligned;" ::: "memory");
        float fa, fb;
        if (layer == 0) {
            uint32_t ma = 0, mb = 0;
#pragma unroll 1
            for (int i = 0; i < 20; i++) {
                issue(i + WDEPTH);
                cp_wait<WDEPTH>();
                const uint32_t d = dst + (i < 19 ? i * 8192 : O_LAST);
                uint32_t u[8];
                lds128(u, d); lds128(u + 4, d + 2048);
                ma = babsmax(babsmax(ma, babsmax(u[0], u[1])), babsmax(u[2], u[3])); mb = babsmax(babsmax(mb, babsmax(u[4], u[5])), babsmax(u[6], u[7]));
            }
            ma = __reduce_max_sync(~0u, max(ma & 0x7fffu, (ma >> 16) & 0x7fffu)); mb = __reduce_max_sync(~0u, max(mb & 0x7fffu, (mb >> 16) & 0x7fffu));
            asm volatile("barrier.cluster.wait.aligned;" ::: "memory");
            if (lane < 3)
                asm volatile("st.async.shared::cluster.mbarrier::complete_tx::bytes.v2.b32 [%0],{%1,%2},[%3];"
                             ::"r"(mapa(sb + O_WMX + (c * 8 + w) * 8, lane)), "r"(ma), "r"(mb), "r"(mapa(sb + B_W, lane)) : "memory");
            __syncwarp();
            {
                uint32_t off[4];
                float cs[4] = {0.f, 0.f, 0.f, 0.f};
#pragma unroll
                for (int q = 0; q < 4; q++) {
                    const int g_ = (c * 2 + ((w >> 1) & 1)) * 56 + (q == 3 ? 24 : (w & 1) * 32 + q * 8), col = wg * 320 + g_, nb = col / 80;
                    off[q] = g_ < 320 && !(q == 3 && (w & 1)) ? ((nb * 512 + h * 16) * 10 + (col - nb * 80) / 8) * 32 + lane : ~0u;
                }
                const uint32_t ta = sb + O_WO + w * 8192 + (lane & 7) * 64 + (((lane >> 3) ^ (lane >> 1)) & 3) * 16;
#pragma unroll 2
                for (int i = 0; i < 16; i++) {
                    uint32_t r[4];
                    ldsm4t(r, ta + i * 512);
#pragma unroll
                    for (int q = 0; q < 4; q++) {
                        if (off[q] != ~0u) ((uint32_t*)g_wot)[off[q] + i * 320] = r[q];
                        cs[q] += fabsf(bf_lo(r[q])) + fabsf(bf_hi(r[q]));
                    }
                }
                float cm = 0.f;
#pragma unroll
                for (int q = 0; q < 4; q++) {
                    cs[q] += __shfl_xor_sync(~0u, cs[q], 1); cs[q] += __shfl_xor_sync(~0u, cs[q], 2);
                    cm = fmaxf(cm, cs[q]);
                }
                const uint32_t n1 = __reduce_max_sync(~0u, __float_as_uint(cm));
                if (lane == 0) g_co[h * 32 + c * 8 + w] = __uint_as_float(n1);
            }
            mbar_wait(sb + B_W, 0);
            uint32_t v[2];
            lds64(v, sb + O_WMX + (lane < 24 ? lane : 0) * 8);
            const bool mine = (lane >> 3) < 3 && ((lane >> 4) == 1) == (c == 2);
            ma = __reduce_max_sync(~0u, mine ? v[0] : 0u); mb = __reduce_max_sync(~0u, mine ? v[1] : 0u);
            if (c == 2) ma = mb = max(ma, mb);
            fa = __uint_as_float(ma << 16); fb = __uint_as_float(mb << 16);
            if (tid == 0) {
                if (c != 1) g_wmx[h * 3 + c] = fa;
                if (c == 0) g_wmx[h * 3 + 1] = fb;
            }
        } else {
            fa = __ldcg(g_wmx + h * 3 + (c == 2 ? 2 : 0)); fb = __ldcg(g_wmx + h * 3 + (c == 2 ? 2 : 1));
            asm volatile("barrier.cluster.wait.aligned;" ::: "memory");
        }
        if (layer == TLL) TL(49);
        float ia, ib;
        const float sa = pow2_scale(fa, 6, &ia), sc_b = pow2_scale(fb, 6, &ib);
        sl = __uint_as_float(uni(__float_as_uint(ia * ib * (0.08838834764831845f * 1.4426950408889634f))));
        const uint32_t pa = pack_bf(sa, sa), pb = pack_bf(sc_b, sc_b);
        const int ahead = layer == 0 ? 20 : WDEPTH;
        auto convert = [&](int lo) {
#pragma unroll 1
            for (int i = lo; i < lo + 10; i++) {
                issue(i + ahead);
                cp_wait<WDEPTH>();
                const uint32_t d = dst + (i < 19 ? i * 8192 : O_LAST);
                uint32_t u[8];
                lds128(u, d); lds128(u + 4, d + 2048);
#pragma unroll
                for (int q = 0; q < 8; q++)
                    asm("{.reg .b32 m,l,u; mul.rn.bf16x2 m,%0,%1; shl.b32 l,m,16; and.b32 u,m,0xffff0000; cvt.rn.f16x2.f32 %0,u,l;}" : "+r"(u[q]) : "r"(q < 4 ? pa : pb));
                sts128(d, u[0], u[1], u[2], u[3]); sts128(d + 2048, u[4], u[5], u[6], u[7]);
            }
            bar_sync(6 + wg, 128);
        };
        const uint32_t s0 = src + wg * 2048, s1 = src + 2048 - wg * 2048;
        convert(0);
#pragma unroll
        for (int i = 0; i < 10; i++) { ldsm4t(A0[i], s0 + i * 8192); ldsm4t(A1[i], s1 + i * 8192); }
        if (layer == TLL) TL(50);
        convert(10);
#pragma unroll
        for (int i = 10; i < 20; i++) { ldsm4t(A0[i], s0 + (i < 19 ? i * 8192 : O_LAST)); ldsm4t(A1[i], s1 + (i < 19 ? i * 8192 : O_LAST)); }
        if (layer == TLL) TL(53);
        bar_arrive(9, 288);
        bar_sync(4, 288);
        asm volatile("barrier.cluster.arrive.relaxed.aligned;" ::: "memory");
    }
    const uint32_t idn = (lane >> 3) == (lane & 3) ? ((lane & 4) ? 0x3c000000u : 0x3c00u) : 0u;
    float invM = g_invM0;
    char* redp = red_base() + (size_t)layer * 32 * 32768 + w * 2048 + (lane >> 4) * 1024 + ((lane >> 3) & 1) * 256 + (lane & 7) * 16;
    const uint32_t ro2 = uni((w >> 1) * 4096 + 128), rown = uni(c == 2 ? ro2 : c * 16384);
    const uint32_t L16 = lane * 16, L8 = lane * 8, L4 = lane * 4;
    const uint32_t xch0 = uni(sb + O_XCH + t0 * 1024), xch1 = uni(sb + O_XCH + t1 * 1024);
    const uint32_t qo0 = uni(sb + O_QKP + (w & 3) * 1024 + (wg ? 768 : 0)), qp0 = uni(qo0 + (wg ? 128 : 256));
    const uint32_t qo1 = uni(sb + O_QKP + (w & 3) * 1024 + (wg ? 128 : 512)), qp1 = uni(qo1 + (wg ? 256 : 128));
    const uint32_t vo1 = uni(qo1 + (wg ? -128 : 256)), vp1 = uni(qp1 + (wg ? -128 : 256));
    const uint32_t msr = uni(sb + O_MS + wg * 5376);
    const uint32_t msw = uni(msr + ((w >> 1) & 1) * 896 + (w & 1) * 512), msh = uni(msr + ((w >> 1) & 1) * 896 + 384 + (w & 1) * 2);
    const uint32_t sco = uni(sb + O_SC + c * 768 + (w & 3) * 256);
    const uint32_t woa = sb + O_WO + w * 8192 + (lane >> 4) * 512 + (lane & 7) * 64 + (((lane >> 3) ^ (lane >> 1)) & 1) * 16 + ((lane >> 2) & 1) * 32;
    const uint32_t w512 = uni(sb + w * 512), w128 = uni(sb + w * 128);
    const uint32_t pd0 = uni(mapa(sb, c == 2 ? 0 : 2) - sb), pd1 = uni(mapa(sb, c == 1 ? 0 : 1) - sb);
    const bool scw = c < 2 && w >= 4 && w <= 6;
    uint32_t sn = uni(sb + O_STG + (c == 2 ? 8192 : 0) + t1 * 1024);
    uint32_t ka = uni(sb + (w == 6 ? O_QKP + 512 : O_STG + 4096 + (w & 1) * 512));
    uint32_t vs = uni(sb + O_VM + t1 * 256);
    uint32_t va = uni(sb + O_STG + 8192 + w * 2048), vr = uni(sb + O_VM + w * 512);
    const uint32_t sn2 = uni(2 * sn - 16384), ka2 = uni(2 * ka - (w == 6 ? 0 : 16384)), vs2 = uni(2 * vs + 2048), va2 = uni(2 * va - 16384),
                   vr2 = uni(2 * vr + 2048);
    uint32_t xd = uni((uint32_t)mkdesc(sb + O_XS + wg * 20480, 512, 128, 0));
    const uint32_t xd2 = uni(2 * xd + 2560);

    uint32_t wp[2 * NPERM + 1][4];
    sfor<NPERM>([&](auto I) { constexpr int i = I; ldsm4t(wp[2 * i], woa + i * 1024); ldsm4t(wp[2 * i + 1], (woa ^ 32) + i * 1024); });
    auto wo_fetch = [&](uint32_t (&wo)[16][4], auto I) {
        constexpr int i = I;
        if constexpr (i < NPERM) {
#pragma unroll
            for (int q = 0; q < 4; q++) { wo[i][q] = wp[2 * i][q]; wo[8 + i][q] = wp[2 * i + 1][q]; }
        } else { ldsm4t(wo[i], woa + i * 1024); ldsm4t(wo[8 + i], (woa ^ 32) + i * 1024); }
    };
    if (layer == TLL) TL(32);
    float b0[16], b1[16];
    mbar_wait(sb + B_XF, 0);
    if (layer == TLL) TL(33);
    tok_issue<0, NTB>(A0, A1, b0, b1, xd, zero);
    tok_give(b0, L16, xch0);
    tok_issue<NTB, 40>(A0, A1, b0, b1, xd, zero);
    bar_sync(4, 256);
    wg_wait<0>();
    {
        uint32_t e[2][4];
        lds128_u<0>(e[0], L16, xch1); lds128_u<512>(e[1], L16, xch1);
        tok_finish(b1, e, L16, sn, idn);
    }
    sn = sn2 - sn; xd = xd2 - xd;
    bar_sync(5, 288);
    asm volatile("barrier.cluster.wait.aligned;" ::: "memory");
    if (layer == TLL) TL(34);
    mbar_wait(sb + B_XF + 8, 0);
    if (layer == TLL) TL(35);
    tok_issue<0, NTA>(A0, A1, b0, b1, xd, zero);
    const uint32_t rbias = uni(c == 2 ? RB2 : 0);
    uint32_t tr = clock32() - RDELAY;

#pragma unroll 1
    for (int st = 0;; st++) {
        uint4 mv[3];
        asm volatile("{.reg .pred p; .reg .b32 t;\n"
                     "mov.b32 %0,0; mov.b32 %1,0; mov.b32 %2,0; mov.b32 %3,0; mov.b32 %4,0; mov.b32 %5,0; mov.b32 %6,0; mov.b32 %7,0;\n"
                     "mov.b32 %8,0; mov.b32 %9,0; mov.b32 %10,0; mov.b32 %11,0;\n"
                     "T_LOOP: mov.u32 t,%%clock; sub.u32 t,t,%14; setp.ge.u32 p,t,%15;\n"
                     "@p ld.relaxed.gpu.global.v4.u32 {%0,%1,%2,%3},[%12]; @p ld.relaxed.gpu.global.v4.u32 {%4,%5,%6,%7},[%12+16384];\n"
                     "@p ld.relaxed.gpu.global.v4.u32 {%8,%9,%10,%11},[%13];\n"
                     "@!p bra T_LOOP;}"
                     : "=r"(mv[0].x), "=r"(mv[0].y), "=r"(mv[0].z), "=r"(mv[0].w), "=r"(mv[1].x), "=r"(mv[1].y), "=r"(mv[1].z), "=r"(mv[1].w),
                       "=r"(mv[2].x), "=r"(mv[2].y), "=r"(mv[2].z), "=r"(mv[2].w)
                     : "l"(redp), "l"(redp + ro2), "r"(tr), "n"(RDELAY) : "memory");
        STAMP(10);
        tok_issue<NTA, NTB>(A0, A1, b0, b1, xd, zero);
        tok_give(b0, L16, xch0);
        tok_issue<NTB, 40>(A0, A1, b0, b1, xd, zero);
        xd = xd2 - xd;
        STAMP(9);
        if (zero >> 30) break;
        asm volatile("{.reg .pred p; .reg .b32 a,h,t,n; .reg .b16 l,u; .reg .b64 q;\n"
                     "add.u32 a,%12,%13; add.u32 h,%12,%14; mov.u32 n,0;\n"
                     "M_LOOP:\n .pragma \"nounroll\";\n"
                     "st.shared.b32 [a],%0; st.shared.b32 [a+128],%1; st.shared.b32 [a+256],%2; mov.b32 {l,u},%3; st.shared.b16 [h],l;\n"
                     "st.shared.b32 [a+1792],%4; st.shared.b32 [a+1920],%5; st.shared.b32 [a+2048],%6; mov.b32 {l,u},%7; st.shared.b16 [h+1792],l;\n"
                     "st.shared.b32 [a+3584],%8; st.shared.b32 [a+3712],%9; st.shared.b32 [a+3840],%10; mov.b32 {l,u},%11; st.shared.b16 [h+3584],l;\n"
                     "lop3.b32 t,%3,%7,0x50000000,0x7e; lop3.b32 t,t,%11,0x50000000,0xf6; setp.gt.u32 p,t,0xffff;\n"
                     "vote.sync.any.pred p,p,-1; add.u32 n,n,1; setp.lt.and.u32 p,n,%17,p; @!p bra M_DONE;\n"
                     "ld.relaxed.gpu.global.v4.u32 {%0,%1,%2,%3},[%15]; ld.relaxed.gpu.global.v4.u32 {%4,%5,%6,%7},[%15+16384];\n"
                     "cvt.u64.u32 q,%16; add.u64 q,q,%15; ld.relaxed.gpu.global.v4.u32 {%8,%9,%10,%11},[q];\n"
                     "bra M_LOOP;\n"
                     "M_DONE:}"
                     : "+r"(mv[0].x), "+r"(mv[0].y), "+r"(mv[0].z), "+r"(mv[0].w), "+r"(mv[1].x), "+r"(mv[1].y), "+r"(mv[1].z), "+r"(mv[1].w),
                       "+r"(mv[2].x), "+r"(mv[2].y), "+r"(mv[2].z), "+r"(mv[2].w)
                     : "r"(L4), "r"(msw), "r"(msh), "l"(redp), "r"(ro2), "n"(SPIN_LIM) : "memory");
        bar_sync(3, 288);
        STAMP(0);
        uint32_t e[2][4];
        float f1[4];
        {
            uint32_t b[10][4];
            float acc[4][4];
#pragma unroll
            for (int i = 0; i < 4; i++) acc[i][0] = acc[i][1] = acc[i][2] = acc[i][3] = 0.f;
            auto ld = [&](auto I) { constexpr int i = I; ldsm4t_u<i * 512>(b[i], L16, msr); };
            auto mm = [&](auto I) {
                constexpr int i = I;
                mma_f16(acc[0], A0[2 * i], b[i][0], b[i][1]); mma_f16(acc[2], A1[2 * i], b[i][0], b[i][1]);
                mma_f16(acc[1], A0[2 * i + 1], b[i][2], b[i][3]); mma_f16(acc[3], A1[2 * i + 1], b[i][2], b[i][3]);
            };
            ld(IC<0>()); ld(IC<1>()); ld(IC<2>()); ld(IC<3>());
            sts32_u<O_MX>(L4, w128,
                          habsmax(habsmax(habsmax(habsmax(mv[0].x, mv[0].y), habsmax(mv[0].z, mv[1].x)), habsmax(habsmax(mv[1].y, mv[1].z), mv[2].x)),
                                  habsmax(habsmax(mv[2].y, mv[2].z), habsmax(habsmax(mv[0].w, mv[1].w), mv[2].w) & 0xffffu)));
            wg_wait<0>();
            ld(IC<4>()); mm(IC<0>()); ld(IC<5>()); mm(IC<1>()); ld(IC<6>()); mm(IC<2>());
            ld(IC<7>()); mm(IC<3>()); ld(IC<8>()); mm(IC<4>()); ld(IC<9>()); mm(IC<5>());
            lds128_u<0>(e[0], L16, xch1); lds128_u<512>(e[1], L16, xch1);
            mm(IC<6>()); mm(IC<7>()); mm(IC<8>()); mm(IC<9>());
            const uint32_t u0 = pack_bf((acc[0][0] + acc[1][0]) * invM, (acc[0][1] + acc[1][1]) * invM);
            const uint32_t u1 = pack_bf((acc[0][2] + acc[1][2]) * invM, (acc[0][3] + acc[1][3]) * invM);
#pragma unroll
            for (int i = 0; i < 4; i++) f1[i] = (acc[2][i] + acc[3][i]) * invM;
            sts32_u<0>(L4, qo0, u0); sts32_u<0>(L4, qp0, u1); sts32_u<0>(L4, qo1, pack_bf(f1[0], f1[1])); sts32_u<0>(L4, qp1, pack_bf(f1[2], f1[3]));
        }
        STAMP(1);
        bar_sync(1, 320);
        if (__builtin_expect(scw, 1)) {
            float a[4][4];
#pragma unroll
            for (int i = 0; i < 4; i++) a[i][0] = a[i][1] = a[i][2] = a[i][3] = 0.f;
            uint32_t q[4][4], k[4][4];
            sfor<4>([&](auto I) {
                constexpr int i = I;
                ldsm4t_u<O_QKP + i * 1024>(q[i], L16, sb); ldsm4t_u<i * 1024>(k[i], L16, ka);
            });
#pragma unroll
            for (int i = 0; i < 4; i++) {
                mma_bf(a[i & 1], q[i][0], q[i][1], q[i][2], q[i][3], k[i][0], k[i][1]);
                mma_bf(a[2 + (i & 1)], q[i][0], q[i][1], q[i][2], q[i][3], k[i][2], k[i][3]);
            }
            const float mk = w == 6 ? 1.f : 0.f;
            const float x0 = (a[0][0] + a[0][2]) + (a[1][0] + a[1][2]), x1 = (a[0][1] + a[0][3]) + (a[1][1] + a[1][3]);
            const float y0 = (a[2][0] + a[2][2]) + (a[3][0] + a[3][2]), y1 = (a[2][1] + a[2][3]) + (a[3][1] + a[3][3]);
            st_share2(L8, sco, sb + B_S, pd0, pd1, pack_bf(fmaf(y0, mk, x0) * sl, fmaf(y1, mk, x1) * sl), pack_bf(y0 * sl, y1 * sl));
        }
        if (c == 2) {
            const uint32_t x = lds32_u<0>(L4, vo1), y = lds32_u<0>(L4, vp1);
            st_share2(L8, vs, sb + B_S, pd0, pd1, pack_bf(f1[0] + bf_lo(x), f1[1] + bf_hi(x)), pack_bf(f1[2] + bf_lo(y), f1[3] + bf_hi(y)));
        }
        STAMP(3);
        if (st == NSEG - 1) break;
        tok_finish(b1, e, L16, sn, idn);
        asm volatile("{.reg .pred p; setp.eq.u32 p,%1,0; @p mbarrier.arrive.shared::cta.b64 _,[%0];}" ::"r"(sb + B_GO), "r"(L4 + (c != 2)) : "memory");
        redp += (st & 1) ? 32768 - 512 : 512;
        if (wg == 0) {
            uint32_t wo[16][4], vx[2][2][4], vm[2][2];
            ldsm4_u<0>(vx[0][0], L16, va); ldsm4_u<512>(vx[0][1], L16, va); ldsm4_u<1024>(vx[1][0], L16, va); ldsm4_u<1536>(vx[1][1], L16, va);
            sfor<NWO0>([&](auto I) { wo_fetch(wo, I); });
            mbar_wait(sb + B_S, st & 1);
            STAMP(4);
            uint32_t s[5];
            {
                uint32_t p[2][5];
                sfor<2>([&](auto R) {
                    constexpr int r = R;
                    lds64_u<O_SC + r * 768>(p[r], L8, sb); lds64_u<O_SC + r * 768 + 256>(p[r] + 2, L8, sb); p[r][4] = lds32_u<O_SC + r * 768 + 512>(L8, sb);
                });
#pragma unroll
                for (int j = 0; j < 5; j++) s[j] = badd(p[0][j], p[1][j]);
            }
            lds64_u<0>(vm[0], L8, vr); lds64_u<256>(vm[1], L8, vr);
            uint32_t mm = bmax(bmax(bmax(s[0], s[1]), bmax(s[2], s[3])), s[4]);
            mm = bmax(bmax(mm, __shfl_xor_sync(~0u, mm, 1)), bmax(__shfl_xor_sync(~0u, mm, 2), __shfl_xor_sync(~0u, mm, 3)));
            const float m = fmaxf(bf_lo(mm), bf_hi(mm));
            float o0[4] = {0.f, 0.f, 0.f, 0.f}, o1[4] = {0.f, 0.f, 0.f, 0.f}, d[10];
#pragma unroll
            for (int j = 0; j < 5; j++) { d[2 * j] = bf_lo(s[j]) - m; d[2 * j + 1] = bf_hi(s[j]) - m; }
#pragma unroll
            for (int j = 0; j < 10; j++) d[(j + 8) % 10] = ex2(d[(j + 8) % 10]);
            float sum = ((d[8] + d[9]) + (d[0] + d[1])) + ((d[2] + d[3]) + (d[4] + d[5])) + (d[6] + d[7]);
            const uint32_t p4 = pack_bf(d[8], d[9]), p0 = pack_bf(d[0], d[1]), p1 = pack_bf(d[2], d[3]), p2 = pack_bf(d[4], d[5]), p3 = pack_bf(d[6], d[7]);
            mma_bf8(o0, vm[0][0], vm[0][1], p4);
            mma_bf8(o1, vm[1][0], vm[1][1], p4);
            mma_bf(o0, vx[0][0][0], vx[0][0][1], vx[0][0][2], vx[0][0][3], p0, p1);
            mma_bf(o1, vx[1][0][0], vx[1][0][1], vx[1][0][2], vx[1][0][3], p0, p1);
            mma_bf(o0, vx[0][1][0], vx[0][1][1], vx[0][1][2], vx[0][1][3], p2, p3);
            mma_bf(o1, vx[1][1][0], vx[1][1][1], vx[1][1][2], vx[1][1][3], p2, p3);
            sfor<NWO0B - NWO0>([&](auto I) { constexpr int i = I; wo_fetch(wo, IC<NWO0 + i>()); });
            sum += __shfl_xor_sync(~0u, sum, 1);
            sum += __shfl_xor_sync(~0u, sum, 2);
            sts32_u<O_OS>(L4, w512, pack_bf(o0[0], o0[1])); sts32_u<O_OS + 128>(L4, w512, pack_bf(o0[2], o0[3]));
            sts32_u<O_OS + 256>(L4, w512, pack_bf(o1[0], o1[1])); sts32_u<O_OS + 384>(L4, w512, pack_bf(o1[2], o1[3]));
            sts32_u<O_SUM>(lane & 28, sb, __float_as_uint(sum));
            STAMP(5);
            invM = mem_out<NWO0B>(sb, L16, L8, wo, woa, redp + rown, w & 1);
            tr = clock32() - rbias;

        } else {
            uint32_t wo[16][4];
            sfor<NWO1>([&](auto I) { wo_fetch(wo, I); });
            invM = mem_out<NWO1>(sb, L16, L8, wo, woa, redp + rown, w & 1);
            tr = clock32() - rbias;

        }
        STAMP(7);
        tok_issue<0, NTA>(A0, A1, b0, b1, xd, zero);
        sn = sn2 - sn; ka = ka2 - ka; vs = vs2 - vs; va = va2 - va; vr = vr2 - vr;
        STAMP(8);
    }
    if (layer == TLL) TL(40);
    if (c == 2) attend_last(sb, layer);
    bar_arrive(8, 320);
    tid = read_tid(); lane = tid & 31;
    float acc[40];
    const int nc = c == 2 ? 10 : 11;
    const int mb = 28 + (h >> 3), nj = c == 2 ? 1 : 2;
    uint32_t rv[2][2];
    const size_t go = ((size_t)(mb * 64 + (w & 3) * 16 + (lane >> 2)) * 640 + (h & 7) * 80 + (wg * 5 + c * 2) * 8 + (lane & 3) * 2) >> 1;
#pragma unroll
    for (int u = 0; u < 4; u++) rv[u >> 1][u & 1] = (u >> 1) < nj ? __ldcg((const uint32_t*)res + go + (u >> 1) * 4 + (u & 1) * 2560) : 0u;
#pragma unroll 1
    for (int k = 0; k < nc; k++) {
        mbar_wait(sb + T_FB + (k % 7) * 8, k >= 7);
        mbar_wait(sb + T_FA + (k & 3) * 8, (k >> 2) & 1);
        if (layer == TLL && k == 0) TL(41);
        const uint64_t da = mkdesc(sb + O_MS + (k & 3) * 16384 + wg * 8192, 1024, 128, 0), db = mkdesc(sb + tail_b(k) + wg * 10240, 1280, 128, 0);
        wg_fence();
#pragma unroll
        for (int q = 0; q < 4; q++) wg_n80_ss(acc, da + q * 128, db + q * 160, k | q);
        wg_commit();
        if (k > 0) {
            wg_wait<1>();
            if (lane == 0) { mbar_arrive(sb + T_EA + ((k - 1) & 3) * 8); if (k <= 4) mbar_arrive(sb + T_EB + (k - 1) * 8); }
        }
    }
    if (layer == TLL) TL(52);
    wg_wait<0>();
    asm volatile("barrier.cluster.arrive.relaxed.aligned; barrier.cluster.wait.aligned;" ::: "memory");
    const uint32_t ra = sb + O_XS + tid * 16, rb = sb + O_MS + tid * 16;
#pragma unroll
    for (int j = 0; j < 5; j++) {
        const float* q = acc + 4 * j;
        sts128(rb + j * 4096, __float_as_uint(wg ? q[0] : q[20]), __float_as_uint(wg ? q[1] : q[21]), __float_as_uint(wg ? q[2] : q[22]), __float_as_uint(wg ? q[3] : q[23]));
    }
    bar_sync(4, 256);
    sfor<5>([&](auto J) {
        constexpr int j = J;
        const float* q = acc + 4 * j;
        uint32_t p[4];
        lds128(p, sb + O_MS + (tid ^ 128) * 16 + j * 4096);
        const uint32_t d = ra + c * 8192 + (j & 1) * 4096;
        asm volatile("{.reg .pred p; setp.eq.u32 p,%7,%8;\n"
                     "@!p st.async.shared::cluster.mbarrier::complete_tx::bytes.v4.f32 [%0],{%1,%2,%3,%4},[%5]; @p st.shared.v4.f32 [%6],{%1,%2,%3,%4};}"
                     ::"r"(mapa(d, j >> 1)), "f"((wg ? q[20] : q[0]) + __uint_as_float(p[0])), "f"((wg ? q[21] : q[1]) + __uint_as_float(p[1])),
                     "f"((wg ? q[22] : q[2]) + __uint_as_float(p[2])), "f"((wg ? q[23] : q[3]) + __uint_as_float(p[3])), "r"(mapa(sb + T_RED, j >> 1)),
                     "r"(d), "r"(c), "n"(j >> 1) : "memory");
    });
    mbar_wait(sb + T_RED, 0);
#pragma unroll 1
    for (int u = 0; u < nj; u++) {
        uint32_t p[3][4];
#pragma unroll
        for (int q = 0; q < 3; q++) lds128(p[q], ra + q * 8192 + u * 4096);
        float y[4];
#pragma unroll
        for (int i = 0; i < 4; i++) y[i] = __uint_as_float(p[0][i]) + __uint_as_float(p[1][i]) + __uint_as_float(p[2][i]);
        ((uint32_t*)out)[go + u * 4] = bfma(pack_bf(y[0], y[1]), 0x3f803f80u, u ? rv[1][0] : rv[0][0]);
        ((uint32_t*)out)[go + u * 4 + 2560] = bfma(pack_bf(y[2], y[3]), 0x3f803f80u, u ? rv[1][1] : rv[0][1]);
    }
    __syncwarp();
    if (layer == 0 && lane == 0) red_release(g_flag + F_R + mb);
    TL(layer == 0 ? 15 : 29);
    asm volatile("barrier.cluster.arrive.relaxed.aligned; barrier.cluster.wait.aligned;" ::: "memory");
}

__device__ __forceinline__ void tail_load_b(const uint32_t sb, const int h, const int c, const int k) {
    mbar_expect(sb + T_FB + (k % 7) * 8, 20480);
    bulk_g2s(sb + tail_b(k), (const char*)g_wot + (size_t)((h & 7) * GNC + c * 11 + k) * 20480, 20480, sb + T_FB + (k % 7) * 8);
}
template <int layer> __device__ __forceinline__ void chain_aux(const uint32_t sb, const int c, const int h, const int nact) {
    const int tid = read_tid(), w = __shfl_sync(~0u, tid >> 5, 0), lane = tid & 31;
    if (w == 8) {
        mbar_init(sb + O_BAR + lane * 8, lane == 2 ? (c == 2 ? 9 : 4) : lane == 3 || (lane >= 16 && lane < 20) || (lane >= 27 && lane < 31) ? 8 : 1);
        asm volatile("fence.mbarrier_init.release.cluster;" ::: "memory");
        fence_async_smem();
        __syncwarp();
    }
    {
        uint4* z = (uint4*)red_base() + layer * 65536;
#pragma unroll 1
        for (int i = blockIdx.x * 128 + tid - 256; i < 65536; i += 96 * 128)
            if (i >= 2048 || (i & 32)) z[i] = make_uint4(0, 0, 0, 0);
    }
    if (w == 8 && lane == 0) {
        mbar_expect(sb + B_S, s_tx(c));
        mbar_expect(sb + B_W, 192);
        mbar_expect(sb + T_RED, (c == 2 ? 1 : 2) * 2 * 4096);
        if (layer == 1) prefetch_l2(red_base() + 32 * 32768 + blockIdx.x * 1024, 1024);
        if (layer == 0) wait_flag<400>(g_ready, NSETUP);
    }
    __syncwarp();
    cluster_sync_full();
    asm volatile("barrier.cluster.arrive.relaxed.aligned;" ::: "memory");
    pdl_wait();
    if (w == 11 && lane == 0) red_relaxed(g_flag + F_X + layer * 128 + 65);
    Flag* flag = g_flag + layer * NSEG * 32 + h;
    const Flag* xflag = g_flag + F_X + layer * 128;
    char* const it0 = g_item + (size_t)h * 32768;
    if (w == 8) {
#pragma unroll 1
        for (int n = 0; n < 3; n++) {
            wait_flag<100>(xflag + (n >> 1), 4);
            fence_async_glb();
            if (n == 0) { bar_sync(4, 288); fence_async_smem(); }
            if (lane == 0 && n < 2) {
                mbar_expect(sb + B_XF + n * 8, 40960);
                bulk_g2s(sb + O_XS + n * 40960, (const char*)g_xn + n * 40960, 40960, sb + B_XF + n * 8);
            }
            __syncwarp();
        }
#pragma unroll 1
        for (int n = 0; n < NSEG - 1; n++) {
            const int np = n & 1;
            char* const vit = it0 + (size_t)(n % RING) * 32 * 32768 + 16384;
            if (c == 2 && n > 0) {
                if (lane == 0) {
                    if (n >= RING) wait_flag(flag + (n - RING) * 32, 7);
                    mbar_sleep(sb + B_GO, (n - 1) & 1);
                    fence_async_smem();
                    bulk_s2g(vit, sb + O_STG + 8192 - np * 16384, 8192);
                    bulk_commit();
                }
                __syncwarp();
            }
            if (n == 0) { wait_flag<100>(g_flag + F_W + layer * 128, 96); bar_sync(5, 288); } else bar_sync(2, 352);
            if (n == 1) TL(12 + layer * 14);
            if (n == 63) TL(13 + layer * 14);
            if (lane == 0) {
                const uint32_t vs = sb + O_STG + 8192 - np * 16384, vb = sb + B_VX + np * 8;
                if (n == 0) { mbar_expect(sb + B_XF, 40960); bulk_g2s(sb + O_XS, (const char*)g_xn + 2 * 40960, 40960, sb + B_XF); }
                if (c == 2) {
                    if (n == 0) { fence_async_smem(); bulk_s2g(vit, vs, 8192); bulk_commit(); }
                    bulk_wait0();
                    fence_async_glb();
                    asm volatile("mbarrier.arrive.relaxed.cluster.shared::cluster.b64 _,[%0];" ::"r"(mapa(sb + B_VH, 0)) : "memory");
                    asm volatile("mbarrier.arrive.relaxed.cluster.shared::cluster.b64 _,[%0];" ::"r"(mapa(sb + B_VH, 1)) : "memory");
                    red_relaxed(flag + n * 32);
                } else {
                    mbar_sleep(sb + B_VH, np);
                    fence_async_glb();
                    mbar_expect(vb, 8192);
                    bulk_g2s(vs, vit, 8192, vb);
                }
                if (n == h * 3 + c && !np && n + 6 < NSEG) prefetch_l2(red_base() + (size_t)(layer * 32 + (n >> 1) + 3) * 32768, 32768);
            }
            __syncwarp();
        }
        {
            bar_sync(2, 352);
            TL(13 + layer * 14);
            if (lane == 0) {
                if (c == 2) mbar_expect(sb + B_VX + 8, 2 * 8192 + 2 * 2048);
                else {
                    fence_async_smem();
                    bulk_s2s(mapa(sb + O_STG - (c == 0 ? 16384 : 0), 2), sb + O_STG - 16384, 8192, mapa(sb + B_VX + 8, 2));
                }
            }
            __syncwarp();
        }
    } else if (w == 9) {
        float cvo;
        {
            auto max8 = [&](const float* p) {
                const float4 u = ((const float4*)p)[0], v = ((const float4*)p)[1];
                return fmaxf(fmaxf(fmaxf(u.x, u.y), fmaxf(u.z, u.w)), fmaxf(fmaxf(v.x, v.y), fmaxf(v.z, v.w)));
            };
            wait_flag<300>(g_flag + F_W + layer * 128, 96);
            const float* pc = g_co + lane * 32;
            float a = 640.f * __ldcg(g_wmx + lane * 3 + 2), o = fmaxf(fmaxf(max8(pc), max8(pc + 8)), max8(pc + 16));
#pragma unroll 1
            for (int s = 16; s; s >>= 1) { a = fmaxf(a, __shfl_xor_sync(~0u, a, s)); o += __shfl_xor_sync(~0u, o, s); }
            cvo = a * o * 2.f;
        }
        float invM = g_invM0;
        float iq, ik, iv;
        weight_scale(h, 0, &iq); weight_scale(h, 1, &ik); weight_scale(h, 2, &iv);
        if (lane == 0) sts64(sb + O_SCL + 16, __float_as_uint(iq * ik), __float_as_uint(iv));
        const uint32_t L16 = sb + lane * 16 + O_MX;
#pragma unroll 1
        for (int st = 0; st < NSEG; st++) {
            bar_sync(1, 320);
            if (st == NSEG - 1) break;
            if (lane == 0) mbar_arrive(sb + B_STG + (st & 1) * 8);
            uint32_t u[2][4];
            lds128(u[0], L16); lds128(u[1], L16 + 512);
            uint32_t mx = habsmax(habsmax(habsmax(u[0][0], u[0][1]), habsmax(u[0][2], u[0][3])), habsmax(habsmax(u[1][0], u[1][1]), habsmax(u[1][2], u[1][3])));
            mx = __reduce_max_sync(~0u, max(mx & 0x7fffu, (mx >> 16) & 0x7fffu));
            const float bound = fmaxf(__half2float(__ushort_as_half((unsigned short)mx)) * invM, 25.5f) * cvo;
            const float sc = pow2_scale(bound, 15, &invM);
            sts64(sb + O_SCL, __float_as_uint(sc * iv), __float_as_uint(invM));
            bar_arrive(2, 352);
        }
    } else if (w == 10) {
        bar_sync(9, 288);
        if (lane == 0) red_release(g_flag + F_W + layer * 128);
#pragma unroll 1
        for (int n = 0; n < NSEG; n++) {
            bar_sync(3, 288);
            if (lane == 0 && n < NSEG - 1) {
                fence_async_smem();
                const uint32_t stg = sb + O_STG - (n & 1) * 16384;
                char* it = it0 + (size_t)(n % RING) * 32 * 32768;
                if (c < 2) bulk_s2g(it + c * 8192, stg, 8192);
                bulk_commit();
                if (n + 1 >= RING && n + 1 < NSEG) wait_flag(flag - (RING - 1) * 32, 7);
                bulk_wait0();
                mbar_arrive(sb + B_FREE + (n & 1) * 8);
                fence_async_glb();
                if (c < 2) red_relaxed(flag);
                flag += 32;
            }
            __syncwarp();
        }
    } else {
        bool allx = false;
#pragma unroll 1
        for (int st = 0; st < NSEG - 1; st++) {
            const int par = st & 1;
            char* const it = it0 + (size_t)(st % RING) * 32 * 32768;
            if (lane == 0 && !allx && st + 3 < NSEG) {
                allx = ld_acquire(xflag + 64) >= nact;
                if (!allx) wait_flag(st + 4 < NSEG ? xflag + ((st + 3) >> 1) : xflag + 64, st + 4 < NSEG ? 4 : nact);
                fence_async_glb();
            }
            __syncwarp();
            if (c < 2) mbar_sleep(sb + B_VX + par * 8, (st >> 1) & 1);
            if (st < NSEG - 2) mbar_sleep(sb + B_XF + par * 8, ((st >> 1) + 1) & 1);
            bar_sync(1, 320);
            if (lane == 0 && st + 3 < NSEG) {
                mbar_expect(sb + B_XF + (par ^ 1) * 8, 40960);
                bulk_g2s_last(sb + O_XS + (par ^ 1) * 40960, (const char*)g_xn + (size_t)(st + 3) * 40960, 40960, sb + B_XF + (par ^ 1) * 8);
            } else if (lane == 0) {
                tail_load_b(sb, h, c, (par ^ 1) * 2); tail_load_b(sb, h, c, (par ^ 1) * 2 + 1);
            }
            __syncwarp();
            if (lane == 0 && c < 2) {
                fence_async_smem();
#pragma unroll 1
                for (int i = 0; i < 4; i++) bulk_s2g(it + 24576 + (c * 4 + i) * 512, sb + O_QKP + i * 1024 + 512, 512);
                bulk_commit();
                asm volatile("cp.async.bulk.wait_group.read 0;" ::: "memory");
            }
            __syncwarp();
            bar_arrive(2, 352);
            mbar_sleep(sb + B_S, par);
            __syncwarp();
            if (lane == 0) {
                mbar_expect(sb + B_S, s_tx(c));
                if (c == 0) { fence_async_smem(); bulk_s2g(it + 28672, sb + O_VM + par * 2048, 2048); bulk_commit(); }
            }
            __syncwarp();
            if (lane == 0) { bulk_wait0(); fence_async_glb(); red_relaxed(flag); }
            __syncwarp();
            mbar_sleep(sb + B_FREE + par * 8, (st >> 1) & 1);
            flag += 32;
        }
        {
            bar_sync(1, 320);
            if (lane == 0 && c < 2) {
                fence_async_smem();
#pragma unroll 1
                for (int i = 0; i < 4; i++)
                    bulk_s2s(mapa(sb + O_LAST + (c * 4 + i) * 512, 2), sb + O_QKP + i * 1024 + 512, 512, mapa(sb + B_VX + 8, 2));
            }
            __syncwarp();
            bar_arrive(8, 320);
        }
    }
    __syncwarp();
    const int nc = c == 2 ? 10 : 11;
    if (w == 10) {
        bar_sync(8, 320);
        if (lane == 0) {
            if (layer == 1 && blockIdx.x == 0) g_ready[0].v = 0;
            if (c < 2) mbar_sleep(sb + B_STG + 8, 1);
            fence_async_smem();
            __nanosleep(TDELAY);
            wait_flag(xflag + 64, nact);
            wait_flag<50>(g_flag + F_O + layer * 32 + 28 + (h >> 3), (h >> 3) == 3 ? 32 + 8 * 32 : 64);
            fence_async_glb();
#pragma unroll 1
            for (int k = 0; k < nc; k++) {
                if (k >= 4) mbar_sleep(sb + T_EA + (k & 3) * 8, ((k >> 2) - 1) & 1);
                mbar_expect(sb + T_FA + (k & 3) * 8, 16384);
                bulk_g2s_last(sb + O_MS + (k & 3) * 16384, (const char*)g_O + (size_t)((28 + (h >> 3)) * GNC + c * 11 + k) * 16384, 16384, sb + T_FA + (k & 3) * 8);
            }
        }
    } else if (w == 9 && lane == 0) {
        __nanosleep(TDELAY);
#pragma unroll 1
        for (int k = 4; k < nc; k++) {
            if (k >= 7) mbar_sleep(sb + T_EB + (k - 7) * 8, 0);
            tail_load_b(sb, h, c, k);
        }
    }
    __syncwarp();
    asm volatile("barrier.cluster.wait.aligned;" ::: "memory");
    asm volatile("barrier.cluster.arrive.relaxed.aligned; barrier.cluster.wait.aligned;" ::: "memory");
    asm volatile("barrier.cluster.arrive.relaxed.aligned; barrier.cluster.wait.aligned;" ::: "memory");
}

constexpr int RI_A = 0, RI_TAB = 81920, RI_STG = RI_TAB + 82 * 768;
constexpr int RI_RES = RI_STG + 25600, RI_ST = RI_RES + 2 * 64 * 336;
constexpr int HB_A = G_BAR + 64, HB_AFREE = HB_A + 32, HB_LN = HB_A + 40, HB_FULL = HB_A + 64, HB_DONE = HB_FULL + 48, HB_FREE = HB_DONE + 48;
constexpr int HP_SMEM = HB_FREE + 48;
static_assert(G_BAR >= RI_ST + 2048, "helper shared-memory map");
#define IDL 280
#define ITEM_NS 60
#define PFW_AT 28
#define PFW_NS 150
__device__ __forceinline__ void helper_aux(const uint32_t sb, const int j, const int nh, const int na, const int nbh, const int layer, const bf16* Wq,
                                           const bf16* Wk, const bf16* Wv, const bf16* Wo) {
    const int w = threadIdx.x >> 5, lane = threadIdx.x & 31, p = w - 8;
    if (lane == 0 && j < (nh & ~3)) {
        int n = 0;
        for (int a = j >> 2; a < 32; a += nh >> 2, n++) {
            if (n == 0) continue;
            mbar_wait(sb + HB_AFREE, (n - 1) & 1);
            mbar_expect(sb + HB_A + p * 8, 20480);
            bulk_g2s_last(sb + RI_A + p * 20480, (const char*)g_YT + (size_t)a * 81920 + p * 20480, 20480, sb + HB_A + p * 8);
            if (p == 0) { mbar_wait(sb + HB_LN, (n - 1) & 1); red_release(g_flag + F_X + layer * 128 + a - (nh >> 2)); }
        }
        if (p == 0) { mbar_wait(sb + HB_LN, (n - 1) & 1); red_release(g_flag + F_X + layer * 128 + (j >> 2) + (n - 1) * (nh >> 2)); }
    }
    __syncwarp();
    if (layer == 0 && w == 8 && lane == 0) wait_flag<400>(g_flag + F_W, 96);
    __syncwarp();
    bar_sync(3, 384);
    if (p == 3 && lane == 0 && j < (nh & ~3)) red_release(g_flag + F_X + layer * 128 + 64);
    fence_async_smem();
    Flag* oflag = g_flag + F_O + layer * 32;
    if (j < na) {
        int sl = p & 1, ph = 1;
        for (int idx = j + (p & 1) * na; idx < (NSEG - 1) * 32 && p >= 2 && lane == 0; idx += 2 * na) {
            mbar_wait(sb + HB_DONE + sl * 8, ph ^ 1);
            mbar_arrive(sb + HB_FREE + sl * 8);
            red_release(oflag + (idx >> 6));
            atomicAdd(&g_flag[layer * NSEG * 32 + idx].v, 1u);
            sl += 2;
            if (sl >= 6) { sl -= 6; ph ^= 1; }
        }
        for (int idx = j + p * na; idx < (NSEG - 1) * 32 && p < 2 && lane == 0; idx += 2 * na) {
            mbar_wait(sb + HB_FREE + sl * 8, ph);
            wait_flag<ITEM_NS>(g_flag + layer * NSEG * 32 + idx, 6);
            fence_async_glb();
            if (idx < (NSEG - 2) * 32) __nanosleep(IDL);
            mbar_expect(sb + HB_FULL + sl * 8, 30720);
            bulk_g2s(sb + sl * 30720, g_item + (size_t)(idx % (RING * 32)) * 32768, 30720, sb + HB_FULL + sl * 8);
            sl += 2;
            if (sl >= 6) { sl -= 6; ph ^= 1; }
        }
    } else if (lane == 0 && p == 3) {
        if (layer == 0) {
            wait_flag<1000>(oflag + PFW_AT, 64);
            const int np = nh - na;
#pragma unroll 1
            for (int i = j - na; i < 1280; i += np) {
                const bf16* W = i < 320 ? Wq : i < 640 ? Wk : i < 960 ? Wv : Wo;
                prefetch_l2((const char*)W + (size_t)(i % 320) * 16384, 16384);
                __nanosleep(PFW_NS);
            }
#pragma unroll 1
            for (int i = j - na; i < 205; i += np) {
                const char* p_ = i < 160 ? (const char*)g_Wf + i * 16384 : i < 165 ? (const char*)g_stat + (i - 144) * 16384
                               : i < 167 ? (const char*)g_ctab + (i - 165) * 8192 : (const char*)(g_flag + NFLAG) - (i - 166) * 16384;
                prefetch_l2(p_, 16384);
                __nanosleep(PFW_NS);
            }
            if (j - na < 16) prefetch_l2(g_rtab + (j - na) * (RF_A / 4), RF_A / 4);
#pragma unroll 1
            for (int i = j - na; i < 130; i += np) { prefetch_l2((const char*)g_xb + i * 16384, 16384); __nanosleep(PFW_NS); }
        }
    } else if (lane == 0) {
        if (p == 2) wait_flag<500>(g_flag + F_X + layer * 128 + 64, nh & ~3);
        int c0 = 0;
        for (int mb = (j - na) >> 3; mb < nbh; mb += (nh - na) >> 3, c0 += GNC) {
            if (p < 2) wait_flag<300>(oflag + 2 * mb + p, 64);
            fence_async_glb();
            oproj_load(sb, p, mb, (j - na) & 7, c0, nh - na < 24 ? 0 : mb == nbh - 1 ? GPACE2 : GPACE);
        }
    }
}
__device__ __forceinline__ void helper_mma(char* sm, const int jh, const int nh, const int na, const int nbh, const int layer, const bf16* res, bf16* x,
                                           bf16* out) {
    const uint32_t sb = smem_u32(sm);
    const int tid = threadIdx.x, w = tid >> 5, lane = tid & 31;
    const bool act = jh < (nh & ~3);
    const int j4 = jh & 3;
    const int fr = tid & 63, rg = w >> 1;
    auto chunk0 = [&](int u) { return u == 0 ? 5 * j4 : u == 1 ? 75 - 5 * j4 : u == 2 ? 40 + 5 * j4 : 35 - 5 * j4; };
    const int gr = tid / 20, gq_ = tid - gr * 20, go = gr * 80 + chunk0(gq_ / 5) + gq_ % 5;
    const uint32_t gs = sb + RI_RES + gr * 336 + gq_ * 16;
    auto residual = [&](int a, int n) {
#pragma unroll 1
        for (int r = 0; r < 64 - gr && tid < 240 && a < 32; r += 12) cp_async16(gs + (n & 1) * 21504 + r * 336, (const uint4*)res + (a * 64 + r) * 80 + go);
        cp_commit();
    };
    if (act) {
        if (tid < 240) {
            const int k0 = tid / 48, n = tid - k0 * 48;
            const float d = (float)(40 * j4 + n), amp = 2.f * 0.03952847075210474f;
#pragma unroll 4
            for (int u = 0; u < 16; u++)
                *(uint4*)(sm + RI_TAB + (tid + u * 240) * 16) = cos_row8(fmaf((float)((k0 + (u & 3) * 5) * 16 + ((u >> 2) & 1)), d, (float)((u & 8) * 20)), 2.f * d, amp);
            if (tid < 96) *(uint4*)(sm + RI_TAB + (3840 + tid) * 16) = make_uint4(k0 == 0 ? pack_h((n & 1) ? -amp : amp, 0.f) : 0u, 0, 0, 0);
        }
        fence_async_smem();
        residual(jh >> 2, 0);
    }
    bar_sync(1, 384);
    if (layer == TLL) TL(36);
    if (act) {
        const float4 wm = ((const float4*)g_wmax)[lane];
        const int wg = w >> 2;
        int n = 0;
#pragma unroll 1
        for (int a = jh >> 2; a < 32; a += nh >> 2, n++) {
            float acc[2][24];
            uint64_t da = mkdesc(sb + RI_A + wg * 40960, 1024, 1024, 1), db = mkdesc(sb + RI_TAB + wg * 30720, 768, 128, 0);
#pragma unroll
            for (int gq = 0; gq < 2; gq++) {
                mbar_wait(sb + HB_A + (wg * 2 + gq) * 8, n & 1);
                if (layer == TLL && n == TLN && gq == 0) TL(45);
                wg_fence();
#pragma unroll 5
                for (int k = 0; k < 10; k++) { wg_n48_ss_ta(acc[gq], da, db, k); da += 128; db += 96; }
                wg_commit();
            }
            if (wg == 0) {
                mbar_wait(sb + HB_A + 16, n & 1);
                wg_fence();
                wg_n48_ss_ta(acc[0], da, db + 20 * 96, 1);
                wg_commit();
            }
            float inv;
            pow2_scale(__uint_as_float(__reduce_max_sync(~0u, __float_as_uint(fmaxf(fmaxf(wm.x, wm.y), fmaxf(wm.z, wm.w))))), 0, &inv);
            const uint32_t ysc = pack_bf(inv, inv);
            wg_wait<0>();
            if (layer == TLL && n == TLN) TL(46);
            if (lane == 0) mbar_arrive(sb + HB_AFREE);
            const uint32_t ad = sb + RI_STG + ((w & 3) * 16 + (lane & 15)) * 400 + (lane >> 4) * 96 + wg * 192;
#pragma unroll
            for (int q = 0; q < 6; q++) {
                const float *e = acc[0] + q * 4, *o = acc[1] + q * 4;
                stsm4(ad + q * 16, pack_h(e[0] + o[0], e[1] + o[1]), pack_h(e[2] + o[2], e[3] + o[3]), pack_h(e[0] - o[0], e[1] - o[1]), pack_h(e[2] - o[2], e[3] - o[3]));
            }
            cp_wait<0>();
            bar_sync(4, 256);
            const uint32_t xa = sb + RI_RES + (n & 1) * 21504 + fr * 336 + rg * 80, sg = (rg & 1) ? 0xbc00bc00u : 0x3c003c00u;
            float sum = 0.f, sq = 0.f;
            uint32_t ya = sb + RI_STG + fr * 400 + (rg >> 1) * 96 + ((rg & 1) ? 64 : 0), carry;
            asm("fma.rn.f16x2 %0,%1,%2,%3;" : "=r"(carry) : "r"(lds32(ya + 208)), "r"(sg), "r"(lds32(ya + 16)));
#pragma unroll 1
            for (int ch = 0; ch < 5; ch++, ya += (rg & 1) ? -16 : 16) {
                uint32_t y[4], z[4], xr[4];
                lds128(y, ya); lds128(z, ya + 192); lds128(xr, xa + ch * 16);
#pragma unroll
                for (int q = 0; q < 4; q++) asm("fma.rn.f16x2 %0,%1,%2,%0;" : "+r"(y[q]) : "r"(z[q]), "r"(sg));
                if (rg & 1) {
                    const uint32_t y0 = y[0], y1 = y[1];
                    y[0] = __byte_perm(carry, y[3], 0x7610); y[1] = __byte_perm(y[3], y[2], 0x7610);
                    y[3] = __byte_perm(y1, y0, 0x7610); y[2] = __byte_perm(y[2], y1, 0x7610);
                    carry = y0;
                }
#pragma unroll
                for (int q = 0; q < 4; q++) {
                    const float2 yf = __half22float2(*(const __half2*)&y[q]);
                    xr[q] = bfma(pack_bf(yf.x, yf.y), ysc, xr[q]);
                    const float e = bf_lo(xr[q]), f = bf_hi(xr[q]);
                    sum += e + f; sq = fmaf(e, e, fmaf(f, f, sq));
                }
                sts128(xa + ch * 16, xr[0], xr[1], xr[2], xr[3]);
            }
            uint2* stat = g_stat + (size_t)(layer * 32 + a) * 1024 + rg * 64 + fr;
            asm volatile("st.relaxed.gpu.global.v2.u32 [%0],{%1,%2};" ::"l"(stat + j4 * 256), "r"(__float_as_uint(sum)), "r"(__float_as_uint(sq) | 0x80000000u) : "memory");
            if (layer == TLL && n == TLN) TL(47);
            uint32_t s0[3], s1[3];
            int lim = 0;
            do {
#pragma unroll
                for (int q = 0; q < 3; q++)
                    asm volatile("ld.relaxed.gpu.global.v2.u32 {%0,%1},[%2];" : "=r"(s0[q]), "=r"(s1[q]) : "l"(stat + ((j4 + 1 + q) & 3) * 256) : "memory");
            } while (__any_sync(~0u, (int)(s1[0] & s1[1] & s1[2]) >= 0) && ++lim < SPIN_LIM);
#pragma unroll
            for (int q = 0; q < 3; q++) { sum += __uint_as_float(s0[q]); sq -= __uint_as_float(s1[q]); }
            sts64(sb + RI_ST + tid * 8, __float_as_uint(sum), __float_as_uint(sq));
            bar_sync(4, 256);
            if (layer == TLL && n == TLN) TL(48);
#pragma unroll
            for (int q = 1; q < 4; q++) {
                uint32_t st2[2];
                lds64(st2, sb + RI_ST + ((tid + q * 64) & 255) * 8);
                sum += __uint_as_float(st2[0]); sq += __uint_as_float(st2[1]);
            }
            const float mean = sum * (1.f / 640.f), r = rsqrtf(fmaxf(fmaf(-mean, mean, sq * (1.f / 640.f)), 0.f) + 1e-5f), off = -mean * r;
            uint4* dst = (uint4*)g_xn + ((size_t)(2 * a + (w & 1)) * 80 + chunk0(rg)) * 32 + lane;
#pragma unroll
            for (int i = 0; i < 5; i++) {
                uint32_t u[4];
                lds128(u, xa + i * 16);
                dst[i * 32] = make_uint4(pack_h(fmaf(bf_lo(u[0]), r, off), fmaf(bf_hi(u[0]), r, off)), pack_h(fmaf(bf_lo(u[1]), r, off), fmaf(bf_hi(u[1]), r, off)),
                                         pack_h(fmaf(bf_lo(u[2]), r, off), fmaf(bf_hi(u[2]), r, off)), pack_h(fmaf(bf_lo(u[3]), r, off), fmaf(bf_hi(u[3]), r, off)));
            }
            __syncwarp();
            if (lane == 0) mbar_arrive(sb + HB_LN);
            if (layer == TLL) TL(37);
            if (layer == TLL && n == TLN) TL(44);
            residual(a + (nh >> 2), n + 1);
#pragma unroll 2
            for (int rr = 0; rr < 64 - gr && tid < 240; rr += 12) {
                uint32_t v[4];
                lds128(v, gs + (n & 1) * 21504 + rr * 336);
                ((uint4*)x)[(a * 64 + rr) * 80 + go] = make_uint4(v[0], v[1], v[2], v[3]);
            }
        }
    }
    bar_sync(3, 384);
    if (layer == TLL) TL(38);
    if (jh >= na) {
        int c0 = 0;
#pragma unroll 1
        for (int mb = (jh - na) >> 3; mb < nbh; mb += (nh - na) >> 3, c0 += GNC) oproj_mma(sb, mb, (jh - na) & 7, c0, x, out, layer);
        if (layer == TLL) TL(42);
        return;
    }
    const int p = w >> 1, mi = w & 1;
    int slot = p, ph = 0;
    for (int idx = jh + p * na; idx < (NSEG - 1) * 32; idx += 4 * na) {
        const uint32_t it = sb + slot * 30720 + lane * 16;
        float iq, ik, iv;
        weight_scale(idx & 31, 0, &iq); weight_scale(idx & 31, 1, &ik); weight_scale(idx & 31, 2, &iv);
        bar_sync(6 + p, 64);
        mbar_wait(sb + HB_DONE + slot * 8, ph ^ 1);
        mbar_wait(sb + HB_FULL + slot * 8, ph);
        tok_attention<8, 8>(it, 8192, it + 24576, 2048, it + 16384, it - lane * 8 + 28672, 0, mi, lane, idx >> 5, idx & 31, iq * ik, iv);
        __syncwarp();
        if (lane == 0) mbar_arrive(sb + HB_DONE + slot * 8);
        slot += 4;
        if (slot >= 6) { slot -= 6; ph ^= 1; }
    }
    if (layer == TLL) TL(39);
}

template <int layer> __global__ void __cluster_dims__(3, 1, 1) __launch_bounds__(384, 1)
k_chain(const int nact, const uint32_t zero, const bf16* __restrict__ Wq, const bf16* __restrict__ Wk, const bf16* __restrict__ Wv,
        const bf16* __restrict__ Wo, const bf16* res, bf16* out) {
    extern __shared__ __align__(1024) char sm[];
    const uint32_t sb = smem_u32(sm);
    const int b = blockIdx.x, h = b / 3, c = b - h * 3;
    pdl_go();
    if (threadIdx.x >= 256) {
        asm volatile("setmaxnreg.dec.sync.aligned.u32 24;");
        TL(11 + layer * 14);
        chain_aux<layer>(sb, c, h, nact);
    } else {
        asm volatile("setmaxnreg.inc.sync.aligned.u32 240;");
        chain_mma<layer>(sb, c, h, zero, Wq, Wk, Wv, Wo, res, out);
    }
}
__global__ void __launch_bounds__(384, 1) k_help(const bf16* res, bf16* x, bf16* out, const int layer, const int na, const int nbh, const int zero, const bf16* Wq,
                                                  const bf16* Wk, const bf16* Wv, const bf16* Wo) {
    extern __shared__ __align__(1024) char sm[];
    if (layer == TLL) TL(51);
    pdl_go();
    if (threadIdx.x >= 256) {
        const uint32_t sb = smem_u32(sm);
        const int p = (threadIdx.x >> 5) - 8, i = (threadIdx.x & 31) * 4 + p;
        if (i < 34) mbar_init(sb + G_BAR + i * 8, i < 4 ? 3 : i < 8 || i == 12 || i == 13 ? 8 : i >= 22 && i < 28 ? 2 : 1);
        fence_async_smem();
        wait_flag<100>(g_flag + F_X + layer * 128 + 65, 1);
        fence_async_glb();
        if (i == 8 + p && blockIdx.x < (gridDim.x & ~3)) {
            mbar_expect(sb + HB_A + p * 8, 20480);
            bulk_g2s(sb + RI_A + p * 20480, (const char*)g_YT + (size_t)(blockIdx.x >> 2) * 81920 + p * 20480, 20480, sb + HB_A + p * 8);
        }
        __syncwarp();
        bar_sync(2, 128);
        bar_arrive(1, 384);
    }
    if (threadIdx.x + zero >= 256) helper_aux(smem_u32(sm), blockIdx.x, gridDim.x, na, nbh, layer, Wq, Wk, Wv, Wo);
    else helper_mma(sm, blockIdx.x, gridDim.x, na, nbh, layer, res, x, out);
    __syncwarp();
    if (blockIdx.x == 0) pdl_wait();
}

#define COL_PAD 15872
template <class... P, class... A>
void launch_pdl(void (*k)(P...), int grid, int block, int smem, cudaStream_t st, A... args) {
    cudaLaunchConfig_t cfg = {};
    cfg.gridDim = dim3(grid); cfg.blockDim = dim3(block); cfg.dynamicSmemBytes = smem; cfg.stream = st;
    cudaLaunchAttribute at[1];
    at[0].id = cudaLaunchAttributeProgrammaticStreamSerialization; at[0].val.programmaticStreamSerializationAllowed = 1;
    cfg.attrs = at;
    cfg.numAttrs = 1;
    cudaLaunchKernelEx(&cfg, k, args...);
}

}

extern "C" void kernel_launch(void* const* d_in, const int* in_sizes, int n_in, void* d_out, int out_size) {
    const bf16* x = (const bf16*)d_in[0];
    const bf16* wr = (const bf16*)d_in[1];
    const bf16* wi = (const bf16*)d_in[2];
    const bf16* mem0 = (const bf16*)d_in[4];
    const bf16* Wq = (const bf16*)d_in[5];
    const bf16* Wk = (const bf16*)d_in[6];
    const bf16* Wv = (const bf16*)d_in[7];
    const bf16* Wo = (const bf16*)d_in[8];
    bf16* out = (bf16*)d_out;
    static int nhelp = 0;
    static bf16 *xa, *xb;
    static cudaStream_t s1;
    static cudaEvent_t ev_fork, ev_join;
    if (!nhelp) {
        cudaStreamCreateWithFlags(&s1, cudaStreamNonBlocking);
        cudaEventCreateWithFlags(&ev_fork, cudaEventDisableTiming);
        cudaEventCreateWithFlags(&ev_join, cudaEventDisableTiming);
        cudaFuncSetAttribute(k_setup, cudaFuncAttributeMaxDynamicSharedMemorySize, SU_SMEM);
        cudaFuncSetAttribute(k_rowf<0>, cudaFuncAttributeMaxDynamicSharedMemorySize, RF_SMEM);
        cudaFuncSetAttribute(k_rowf<1>, cudaFuncAttributeMaxDynamicSharedMemorySize, RF_SMEM);
        cudaFuncSetAttribute(k_col, cudaFuncAttributeMaxDynamicSharedMemorySize, COL_PAD);
        cudaFuncSetAttribute(k_chain<0>, cudaFuncAttributeMaxDynamicSharedMemorySize, CH_SMEM);
        cudaFuncSetAttribute(k_chain<1>, cudaFuncAttributeMaxDynamicSharedMemorySize, CH_SMEM);
        cudaFuncSetAttribute(k_setup, cudaFuncAttributePreferredSharedMemoryCarveout, 100);
        cudaFuncSetAttribute(k_rowf<0>, cudaFuncAttributePreferredSharedMemoryCarveout, 100);
        cudaFuncSetAttribute(k_rowf<1>, cudaFuncAttributePreferredSharedMemoryCarveout, 100);
        cudaFuncSetAttribute(k_col, cudaFuncAttributePreferredSharedMemoryCarveout, 100);
        cudaFuncSetAttribute(k_chain<0>, cudaFuncAttributePreferredSharedMemoryCarveout, 100);
        cudaFuncSetAttribute(k_chain<1>, cudaFuncAttributePreferredSharedMemoryCarveout, 100);
        cudaFuncSetAttribute(k_help, cudaFuncAttributeMaxDynamicSharedMemorySize, HP_SMEM);
        cudaFuncSetAttribute(k_help, cudaFuncAttributePreferredSharedMemoryCarveout, 100);
        int dev = 0, sms = 0;
        cudaGetDevice(&dev);
        cudaDeviceGetAttribute(&sms, cudaDevAttrMultiProcessorCount, dev);
        nhelp = sms - 96 < 12 ? 12 : sms - 96;
        cudaGetSymbolAddress((void**)&xa, g_xa);
        cudaGetSymbolAddress((void**)&xb, g_xb);
    }
    const int na = nhelp - (nhelp >= 36 ? 24 : nhelp >= 28 ? 16 : 8), nbh = 14;
    cudaStream_t s0 = cudaStreamPerThread;
    cudaEventRecord(ev_fork, s0);
    cudaStreamWaitEvent(s1, ev_fork, 0);
    k_rowf<1><<<(96 + nhelp) & ~1, 256, RF_SMEM, s0>>>(x);
    k_setup<<<NSETUP, 256, SU_SMEM, s1>>>(wr, wi, mem0);
    cudaEventRecord(ev_join, s1);
#define NLAYER 2
    for (int l = 0; l < NLAYER; l++) {
        const bf16* xin = l == 0 ? x : xb;
        if (l == 1) launch_pdl(k_rowf<0>, 128, 256, RF_SMEM, s0, xin);
        launch_pdl(k_col, 321, 128, l == 0 ? 0 : COL_PAD, s0, (int)(l == 0));
        launch_pdl(l == 0 ? k_chain<0> : k_chain<1>, 96, 384, CH_SMEM, s0, nhelp & ~3, 0u, Wq, Wk, Wv, Wo, (const bf16*)xa, l == 0 ? xb : out);
        launch_pdl(k_help, nhelp, 384, HP_SMEM, s0, xin, xa, l == 0 ? xb : out, l, na, nbh, 0, Wq, Wk, Wv, Wo);
    }
    cudaStreamWaitEvent(s0, ev_join, 0);
}
```
